```python
import torch

def _softmax(x, axis=-1):
    return torch.softmax(x, dim=axis)
def _gelu(x):
    return torch.nn.functional.gelu(x, approximate="tanh")
def _silu(x):
    return torch.nn.functional.silu(x)
def _sigmoid(x):
    return torch.sigmoid(x)
def _layernorm(x, axis=-1, eps=1e-5):
    m = x.mean(dim=axis, keepdim=True)
    v = x.var(dim=axis, keepdim=True, unbiased=False)
    return (x - m) / torch.sqrt(v + eps)
def _scatter_add(tgt, idx, src, axis=0):
    return tgt.clone().index_add_(axis, idx, src)
def _segment_sum(src, seg, n):
    out = torch.zeros((n,) + src.shape[1:], dtype=src.dtype)
    return out.index_add_(0, seg, src)
def _pad(x, pw):
    flat = tuple(v for pair in reversed(pw) for v in pair)
    return torch.nn.functional.pad(x, flat)

kernel_name = 'interleave_layers__grouped_kv_mqa__dense_activation_silu__prompt'

def setup_inputs():

    _w = (lambda a: (lambda t: t.to(torch.bfloat16) if t.is_floating_point() else t)(torch.as_tensor(a)))
    def _A_setup():
        B, S, D, H = 1, 2048, 512, 32
        Dh = D // H
        return {
            "x": _w((lambda *s: torch.randn(*s, dtype=torch.bfloat16) * 0.05)(B, S, D)),
            "wq": _w((lambda *s: torch.randn(*s, dtype=torch.bfloat16) * 0.05)(D, H * Dh)),
            "wk": _w((lambda *s: torch.randn(*s, dtype=torch.bfloat16) * 0.05)(D, Dh)),
            "wv": _w((lambda *s: torch.randn(*s, dtype=torch.bfloat16) * 0.05)(D, Dh)),
            "wo": _w((lambda *s: torch.randn(*s, dtype=torch.bfloat16) * 0.05)(H * Dh, D)),
        }
    _A_in = _A_setup()

    def _B_setup():
        B, S, D, F = 1, 2048, 512, 1792
        return {
            "x": _w((lambda *s: torch.randn(*s, dtype=torch.bfloat16) * 0.05)(B, S, D)),
            "w1": _w((lambda *s: torch.randn(*s, dtype=torch.bfloat16) * 0.8)(D, F) * (D ** -0.5)),
            "w2": _w((lambda *s: torch.randn(*s, dtype=torch.bfloat16) * 0.8)(F, D) * (F ** -0.5)),
        }
    _B_in = _B_setup()

    return {
        "A_x": _A_in["x"],
        "A_wq": _A_in["wq"],
        "A_wk": _A_in["wk"],
        "A_wv": _A_in["wv"],
        "A_wo": _A_in["wo"],
        "B_x": _B_in["x"],
        "B_w1": _B_in["w1"],
        "B_w2": _B_in["w2"],
    }

def reference(A_x, A_wq, A_wk, A_wv, A_wo, B_x, B_w1, B_w2):
    def _A_ref(x, wq, wk, wv, wo):
        B, S, D = x.shape
        H = 32
        Dh = D // H
        q = (lambda x, *d: x.permute(*d))((x @ wq).reshape(B, S, H, Dh), 0, 2, 1, 3)
        k = x @ wk
        v = x @ wv
        scores = torch.einsum("bhqd,bkd->bhqk", q, k) * (Dh ** -0.5)
        p = _softmax(scores, axis=-1)
        o = torch.einsum("bhqk,bkd->bhqd", p, v)
        return (lambda x, *d: x.permute(*d))(o, 0, 2, 1, 3).reshape(B, S, H * Dh) @ wo

    def _B_ref(x, w1, w2):
        h = torch.einsum("bsd,df->bsf", x, w1)
        h = _silu(h)
        out = torch.einsum("bsf,fd->bsd", h, w2)
        return out

    x = A_x
    x = x + _A_ref(_layernorm(x, axis=-1), A_wq, A_wk, A_wv, A_wo)
    x = x + _B_ref(_layernorm(x, axis=-1), B_w1, B_w2)
    x = x + _A_ref(_layernorm(x, axis=-1), A_wq, A_wk, A_wv, A_wo)
    x = x + _B_ref(_layernorm(x, axis=-1), B_w1, B_w2)
    return x
```

```cpp
#include <cuda_runtime.h>
#include <cuda_bf16.h>
#include <cuda.h>
#include <stdint.h>

namespace {

constexpr int S_ = 2048, D_ = 512, H_ = 32, F_ = 1792;

__device__ __align__(1024) __nv_bfloat16 g_q[S_ * D_];
__device__ __align__(1024) __nv_bfloat16 g_o[S_ * D_];
__device__ __align__(1024) __nv_bfloat16 g_x1[S_ * D_];
__device__ __align__(1024) __nv_bfloat16 g_x2[S_ * D_];
__device__ __align__(1024) __nv_bfloat16 g_x3[S_ * D_];
__device__ __align__(1024) __nv_bfloat16 g_h[S_ * F_];
__device__ __align__(1024) uint8_t g_kimg[S_ * 32];
__device__ __align__(1024) uint8_t g_vimg[(S_ / 16) * 768];
__device__ __align__(1024) float2 g_stats[4][8 * S_];
__device__ __align__(16) float g_cs_q[D_];
__device__ __align__(16) float g_cs_kv[32];
__device__ __align__(16) float g_cs_1[F_];
__device__ __align__(16) float2 g_kvmax[16];

__device__ __forceinline__ uint32_t smem_u32(const void* p) { return (uint32_t)__cvta_generic_to_shared(p); }
__device__ __forceinline__ void mbar_init(uint32_t bar, uint32_t cnt) {
    asm volatile("mbarrier.init.shared::cta.b64 [%0], %1;" ::"r"(bar), "r"(cnt));
}
__device__ __forceinline__ void mbar_expect_tx(uint32_t bar, uint32_t bytes) {
    asm volatile("mbarrier.arrive.expect_tx.shared::cta.b64 _, [%0], %1;" ::"r"(bar), "r"(bytes) : "memory");
}
__device__ __forceinline__ void mbar_arrive(uint32_t bar) {
    asm volatile("mbarrier.arrive.shared::cta.b64 _, [%0];" ::"r"(bar) : "memory");
}
__device__ __forceinline__ void mbar_arrive_remote(uint32_t bar, uint32_t cta) {
    asm volatile("{\n.reg .b32 ra;\nmapa.shared::cluster.u32 ra, %0, %1;\nmbarrier.arrive.shared::cluster.b64 _, [ra];\n}" ::"r"(bar), "r"(cta) : "memory");
}
__device__ __forceinline__ void mbar_wait(uint32_t bar, uint32_t parity) {
    asm volatile("{\n.reg .pred p;\nWAIT_%=:\nmbarrier.try_wait.parity.shared::cta.b64 p, [%0], %1;\n@p bra DONE_%=;\nbra WAIT_%=;\nDONE_%=:\n}" ::"r"(bar), "r"(parity) : "memory");
}
__device__ __forceinline__ void bulk_load(uint32_t dst, const void* src, uint32_t bytes, uint32_t bar) {
    asm volatile("cp.async.bulk.shared::cluster.global.mbarrier::complete_tx::bytes [%0], [%1], %2, [%3];" ::"r"(dst), "l"(src), "r"(bytes), "r"(bar) : "memory");
}
__device__ __forceinline__ void tma2d(uint32_t dst, const CUtensorMap* m, int c0, int c1, uint32_t bar) {
    asm volatile("cp.async.bulk.tensor.2d.shared::cluster.global.mbarrier::complete_tx::bytes [%0], [%1, {%3, %4}], [%2];" ::"r"(dst), "l"(m), "r"(bar), "r"(c0), "r"(c1) : "memory");
}
__device__ __forceinline__ void tma2d_mc(uint32_t dst, const CUtensorMap* m, int c0, int c1, uint32_t bar, uint16_t mask) {
    asm volatile("cp.async.bulk.tensor.2d.shared::cluster.global.mbarrier::complete_tx::bytes.multicast::cluster [%0], [%1, {%3, %4}], [%2], %5;" ::"r"(dst), "l"(m), "r"(bar), "r"(c0), "r"(c1), "h"(mask) : "memory");
}
__device__ __forceinline__ void tma3d(uint32_t dst, const CUtensorMap* m, int c0, int c1, int c2, uint32_t bar) {
    asm volatile("cp.async.bulk.tensor.3d.shared::cluster.global.mbarrier::complete_tx::bytes [%0], [%1, {%3, %4, %5}], [%2];" ::"r"(dst), "l"(m), "r"(bar), "r"(c0), "r"(c1), "r"(c2) : "memory");
}
__device__ __forceinline__ void tma3d_mc(uint32_t dst, const CUtensorMap* m, int c0, int c1, int c2, uint32_t bar, uint16_t mask) {
    asm volatile("cp.async.bulk.tensor.3d.shared::cluster.global.mbarrier::complete_tx::bytes.multicast::cluster [%0], [%1, {%3, %4, %5}], [%2], %6;" ::"r"(dst), "l"(m), "r"(bar), "r"(c0), "r"(c1), "r"(c2), "h"(mask) : "memory");
}
__device__ __forceinline__ void tma2d_store(const CUtensorMap* m, uint32_t src, int c0, int c1) {
    asm volatile("cp.async.bulk.tensor.2d.global.shared::cta.bulk_group [%0, {%2, %3}], [%1];" ::"l"(m), "r"(src), "r"(c0), "r"(c1) : "memory");
}
__device__ __forceinline__ void tma3d_store(const CUtensorMap* m, uint32_t src, int c0, int c1, int c2) {
    asm volatile("cp.async.bulk.tensor.3d.global.shared::cta.bulk_group [%0, {%2, %3, %4}], [%1];" ::"l"(m), "r"(src), "r"(c0), "r"(c1), "r"(c2) : "memory");
}
__device__ __forceinline__ void bulk_commit() { asm volatile("cp.async.bulk.commit_group;" ::: "memory"); }
__device__ __forceinline__ void bulk_wait_read() { asm volatile("cp.async.bulk.wait_group.read 0;" ::: "memory"); }
__device__ __forceinline__ void prefetch_tmap(const CUtensorMap* m) { asm volatile("prefetch.tensormap [%0];" ::"l"(m) : "memory"); }
__device__ __forceinline__ void fence_async_smem() { asm volatile("fence.proxy.async.shared::cta;" ::: "memory"); }
__device__ __forceinline__ void fence_mbar_init() { asm volatile("fence.mbarrier_init.release.cluster;" ::: "memory"); }
__device__ __forceinline__ void cluster_sync() { asm volatile("barrier.cluster.arrive.release.aligned;\nbarrier.cluster.wait.acquire.aligned;" ::: "memory"); }
__device__ __forceinline__ uint32_t cluster_rank() { uint32_t r; asm volatile("mov.u32 %0, %%cluster_ctarank;" : "=r"(r)); return r; }
__device__ __forceinline__ void pdl_wait() { asm volatile("griddepcontrol.wait;" ::: "memory"); }
__device__ __forceinline__ void pdl_launch() { asm volatile("griddepcontrol.launch_dependents;" ::: "memory"); }
__device__ __forceinline__ void named_bar(int id, int n) { asm volatile("bar.sync %0, %1;" ::"r"(id), "r"(n) : "memory"); }

__device__ __forceinline__ void wg_fence() { asm volatile("wgmma.fence.sync.aligned;" ::: "memory"); }
__device__ __forceinline__ void wg_commit() { asm volatile("wgmma.commit_group.sync.aligned;" ::: "memory"); }
template <int N> __device__ __forceinline__ void wg_wait() { asm volatile("wgmma.wait_group.sync.aligned %0;" ::"n"(N) : "memory"); }
template <int N> __device__ __forceinline__ void fence_regs(float (&d)[N]) {
#pragma unroll
    for (int i = 0; i < N; i++) asm volatile("" : "+f"(d[i])::"memory");
}
__device__ __forceinline__ uint64_t mkdesc(uint32_t addr, uint32_t lbo, uint32_t sbo, uint32_t swz) {
    uint64_t d = 0;
    d |= (uint64_t)((addr & 0x3FFFF) >> 4);
    d |= (uint64_t)((lbo & 0x3FFFF) >> 4) << 16;
    d |= (uint64_t)((sbo & 0x3FFFF) >> 4) << 32;
    d |= (uint64_t)swz << 62;
    return d;
}
__device__ __forceinline__ void ldsm_x4(uint32_t& r0, uint32_t& r1, uint32_t& r2, uint32_t& r3, uint32_t addr) {
    asm volatile("ldmatrix.sync.aligned.m8n8.x4.shared.b16 {%0,%1,%2,%3}, [%4];" : "=r"(r0), "=r"(r1), "=r"(r2), "=r"(r3) : "r"(addr) : "memory");
}
__device__ __forceinline__ void stsm_x4(uint32_t addr, uint32_t r0, uint32_t r1, uint32_t r2, uint32_t r3) {
    asm volatile("stmatrix.sync.aligned.m8n8.x4.shared.b16 [%0], {%1,%2,%3,%4};" ::"r"(addr), "r"(r0), "r"(r1), "r"(r2), "r"(r3) : "memory");
}
__device__ __forceinline__ uint32_t pack_bf16(float lo, float hi) {
    uint32_t r;
    asm("cvt.rn.bf16x2.f32 %0, %1, %2;" : "=r"(r) : "f"(hi), "f"(lo));
    return r;
}
__device__ __forceinline__ float bf_lo(uint32_t v) { return __uint_as_float(v << 16); }
__device__ __forceinline__ float bf_hi(uint32_t v) { return __uint_as_float(v & 0xFFFF0000u); }

#define WG_REGS_4(o) "+f"(d[o]), "+f"(d[o + 1]), "+f"(d[o + 2]), "+f"(d[o + 3])
#define WG_REGS_8(o) WG_REGS_4(o), WG_REGS_4(o + 4)
#define WG_REGS_16(o) WG_REGS_8(o), WG_REGS_8(o + 8)
#define WG_REGS_32(o) WG_REGS_16(o), WG_REGS_16(o + 16)

__device__ __forceinline__ void wgmma_ss_n32_tb(float (&d)[16], uint64_t dA, uint64_t dB, int sc) {
    asm volatile("{\n.reg .pred p;\nsetp.ne.b32 p, %18, 0;\n"
                 "wgmma.mma_async.sync.aligned.m64n32k16.f32.bf16.bf16 "
                 "{%0,%1,%2,%3,%4,%5,%6,%7,%8,%9,%10,%11,%12,%13,%14,%15}, %16, %17, p, 1, 1, 0, 1;\n}\n"
                 : WG_REGS_16(0) : "l"(dA), "l"(dB), "r"(sc));
}
__device__ __forceinline__ void wgmma_ss_n64_tb(float (&d)[32], uint64_t dA, uint64_t dB, int sc) {
    asm volatile("{\n.reg .pred p;\nsetp.ne.b32 p, %34, 0;\n"
                 "wgmma.mma_async.sync.aligned.m64n64k16.f32.bf16.bf16 "
                 "{%0,%1,%2,%3,%4,%5,%6,%7,%8,%9,%10,%11,%12,%13,%14,%15,%16,%17,%18,%19,%20,%21,%22,%23,%24,%25,%26,%27,%28,%29,%30,%31}, "
                 "%32, %33, p, 1, 1, 0, 1;\n}\n"
                 : WG_REGS_32(0) : "l"(dA), "l"(dB), "r"(sc));
}
__device__ __forceinline__ void wgmma_ss_n224_tb(float (&d)[112], uint64_t dA, uint64_t dB, int sc) {
    asm volatile("{\n.reg .pred p;\nsetp.ne.b32 p, %114, 0;\n"
                 "wgmma.mma_async.sync.aligned.m64n224k16.f32.bf16.bf16 "
                 "{%0,%1,%2,%3,%4,%5,%6,%7,%8,%9,%10,%11,%12,%13,%14,%15,%16,%17,%18,%19,%20,%21,%22,%23,%24,%25,%26,%27,%28,%29,%30,%31,"
                 "%32,%33,%34,%35,%36,%37,%38,%39,%40,%41,%42,%43,%44,%45,%46,%47,%48,%49,%50,%51,%52,%53,%54,%55,%56,%57,%58,%59,%60,%61,%62,%63,"
                 "%64,%65,%66,%67,%68,%69,%70,%71,%72,%73,%74,%75,%76,%77,%78,%79,%80,%81,%82,%83,%84,%85,%86,%87,%88,%89,%90,%91,%92,%93,%94,%95,"
                 "%96,%97,%98,%99,%100,%101,%102,%103,%104,%105,%106,%107,%108,%109,%110,%111}, "
                 "%112, %113, p, 1, 1, 0, 1;\n}\n"
                 : WG_REGS_32(0), WG_REGS_32(32), WG_REGS_32(64), WG_REGS_16(96) : "l"(dA), "l"(dB), "r"(sc));
}
template <int BN> __device__ __forceinline__ void wgmma_ss_tb(float (&d)[BN / 2], uint64_t dA, uint64_t dB, int sc) {
    if constexpr (BN == 32) wgmma_ss_n32_tb(d, dA, dB, sc);
    else if constexpr (BN == 64) wgmma_ss_n64_tb(d, dA, dB, sc);
    else wgmma_ss_n224_tb(d, dA, dB, sc);
}
__device__ __forceinline__ void wgmma_rs_n64_z(float (&d)[32], uint32_t a0, uint32_t a1, uint32_t a2, uint32_t a3, uint64_t dB) {
    asm volatile("{\n.reg .pred p;\nsetp.ne.b32 p, 0, 0;\n"
                 "wgmma.mma_async.sync.aligned.m64n64k16.f32.bf16.bf16 "
                 "{%0,%1,%2,%3,%4,%5,%6,%7,%8,%9,%10,%11,%12,%13,%14,%15,%16,%17,%18,%19,%20,%21,%22,%23,%24,%25,%26,%27,%28,%29,%30,%31}, "
                 "{%32,%33,%34,%35}, %36, p, 1, 1, 0;\n}\n"
                 : "=f"(d[0]), "=f"(d[1]), "=f"(d[2]), "=f"(d[3]), "=f"(d[4]), "=f"(d[5]), "=f"(d[6]), "=f"(d[7]),
                   "=f"(d[8]), "=f"(d[9]), "=f"(d[10]), "=f"(d[11]), "=f"(d[12]), "=f"(d[13]), "=f"(d[14]), "=f"(d[15]),
                   "=f"(d[16]), "=f"(d[17]), "=f"(d[18]), "=f"(d[19]), "=f"(d[20]), "=f"(d[21]), "=f"(d[22]), "=f"(d[23]),
                   "=f"(d[24]), "=f"(d[25]), "=f"(d[26]), "=f"(d[27]), "=f"(d[28]), "=f"(d[29]), "=f"(d[30]), "=f"(d[31])
                 : "r"(a0), "r"(a1), "r"(a2), "r"(a3), "l"(dB));
}
__device__ __forceinline__ void wgmma_rs_n24_tb(float (&d)[12], uint32_t a0, uint32_t a1, uint32_t a2, uint32_t a3, uint64_t dB) {
    asm volatile("{\n.reg .pred p;\nsetp.eq.b32 p, 0, 0;\n"
                 "wgmma.mma_async.sync.aligned.m64n24k16.f32.bf16.bf16 "
                 "{%0,%1,%2,%3,%4,%5,%6,%7,%8,%9,%10,%11}, {%12,%13,%14,%15}, %16, p, 1, 1, 1;\n}\n"
                 : WG_REGS_8(0), WG_REGS_4(8) : "r"(a0), "r"(a1), "r"(a2), "r"(a3), "l"(dB));
}

constexpr int PREP_STAT_CTAS = S_ / 8;
constexpr int PREP_CS_CTAS = 8 + 1 + F_ / 64;

__global__ void __launch_bounds__(256) prep_kernel(const __nv_bfloat16* __restrict__ x, const __nv_bfloat16* __restrict__ wq,
                                                   const __nv_bfloat16* __restrict__ wk, const __nv_bfloat16* __restrict__ wv,
                                                   const __nv_bfloat16* __restrict__ wo, const __nv_bfloat16* __restrict__ w1,
                                                   const __nv_bfloat16* __restrict__ w2) {
    pdl_launch();
    const int tid = threadIdx.x;
    if (blockIdx.x < PREP_CS_CTAS) {
        __shared__ float red[32][65];
        const int b = blockIdx.x;
        const int rg = tid >> 3, c8 = tid & 7;
        float acc[8];
#pragma unroll
        for (int i = 0; i < 8; i++) acc[i] = 0.f;
        const __nv_bfloat16* base;
        int ld;
        bool active = true;
        if (b < 8) { base = wq + b * 64 + c8 * 8; ld = D_; }
        else if (b == 8) { base = (c8 < 2 ? wk + c8 * 8 : wv + (c8 - 2) * 8); ld = 16; active = c8 < 4; }
        else { base = w1 + (b - 9) * 64 + c8 * 8; ld = F_; }
        if (active) {
            uint4 v[16];
#pragma unroll
            for (int i = 0; i < 16; i++) v[i] = __ldg((const uint4*)(base + (size_t)(rg + 32 * i) * ld));
#pragma unroll
            for (int i = 0; i < 16; i++) {
                acc[0] += bf_lo(v[i].x); acc[1] += bf_hi(v[i].x); acc[2] += bf_lo(v[i].y); acc[3] += bf_hi(v[i].y);
                acc[4] += bf_lo(v[i].z); acc[5] += bf_hi(v[i].z); acc[6] += bf_lo(v[i].w); acc[7] += bf_hi(v[i].w);
            }
        }
#pragma unroll
        for (int i = 0; i < 8; i++) red[rg][c8 * 8 + i] = acc[i];
        __syncthreads();
        if (tid < 64) {
            float s = 0.f;
#pragma unroll
            for (int i = 0; i < 32; i++) s += red[i][tid];
            if (b < 8) g_cs_q[b * 64 + tid] = s;
            else if (b == 8) { if (tid < 32) g_cs_kv[tid] = s; }
            else g_cs_1[(b - 9) * 64 + tid] = s;
        }
    } else {
        const int cb = blockIdx.x - PREP_CS_CTAS;
        if (tid < 72) {
            const int line = cb * 72 + tid;
            const char* p = line < 4096 ? (const char*)wo + (size_t)line * 128 : (const char*)w2 + (size_t)(line - 4096) * 128;
            asm volatile("prefetch.global.L2 [%0];" ::"l"(p));
        }
        const int warp = tid >> 5, lane = tid & 31;
        const int row = cb * 8 + warp;
        const uint4* p = (const uint4*)(x + (size_t)row * D_ + lane * 16);
        const uint4 a = __ldg(p), b = __ldg(p + 1);
        float v[16] = {bf_lo(a.x), bf_hi(a.x), bf_lo(a.y), bf_hi(a.y), bf_lo(a.z), bf_hi(a.z), bf_lo(a.w), bf_hi(a.w),
                       bf_lo(b.x), bf_hi(b.x), bf_lo(b.y), bf_hi(b.y), bf_lo(b.z), bf_hi(b.z), bf_lo(b.w), bf_hi(b.w)};
        float s = 0.f;
#pragma unroll
        for (int i = 0; i < 16; i++) s += v[i];
        s += __shfl_xor_sync(0xffffffffu, s, 1);
        s += __shfl_xor_sync(0xffffffffu, s, 2);
        const float mean = s * (1.f / 64.f);
        float m2 = 0.f;
#pragma unroll
        for (int i = 0; i < 16; i++) { const float d = v[i] - mean; m2 += d * d; }
        m2 += __shfl_xor_sync(0xffffffffu, m2, 1);
        m2 += __shfl_xor_sync(0xffffffffu, m2, 2);
        if ((lane & 3) == 0) g_stats[0][(lane >> 2) * S_ + row] = make_float2(mean, m2);
    }
}

enum { EPI_QKV = 0, EPI_RES = 1, EPI_FFN1 = 2 };

struct GemmParams {
    const float2* stats_in;
    float2* stats_out;
    int wait_in_epilogue;
};

template <int BN> struct BTile;
template <> struct BTile<64>  { static constexpr int BYTES = 64 * 128;     static constexpr int SWZ = 1, LBO = 8192, SBO = 1024, KSTEP = 2048; };
template <> struct BTile<224> { static constexpr int BYTES = 7 * 64 * 64;  static constexpr int SWZ = 2, LBO = 4096, SBO = 512,  KSTEP = 1024; };
template <> struct BTile<32>  { static constexpr int BYTES = 2 * 64 * 32;  static constexpr int SWZ = 3, LBO = 2048, SBO = 256,  KSTEP = 512; };

constexpr int A_BYTES = 128 * 128;

template <int BN, int STAGES, int EPI> struct GemmSmem {
    static constexpr int STAGE = A_BYTES + ((BTile<BN>::BYTES + 1023) / 1024) * 1024;
    static constexpr int RES_OFF = STAGES * STAGE;
    static constexpr int AUX_OFF = RES_OFF + (EPI == EPI_RES ? 16384 : 0);
    static constexpr int AUX_BYTES = 2048;
    static constexpr int TOTAL = AUX_OFF + AUX_BYTES + 1024;
};

__device__ __forceinline__ void load_row_stats(const float2* __restrict__ st, int row0, int c, float& mean0, float& rstd0, float& mean1, float& rstd1) {
    const float2 a0 = st[(2 * c) * S_ + row0], a1 = st[(2 * c + 1) * S_ + row0];
    const float2 b0 = st[(2 * c) * S_ + row0 + 8], b1 = st[(2 * c + 1) * S_ + row0 + 8];
    float sa = a0.x + a1.x, sb = b0.x + b1.x;
    sa += __shfl_xor_sync(0xffffffffu, sa, 1); sa += __shfl_xor_sync(0xffffffffu, sa, 2);
    sb += __shfl_xor_sync(0xffffffffu, sb, 1); sb += __shfl_xor_sync(0xffffffffu, sb, 2);
    mean0 = sa * 0.125f; mean1 = sb * 0.125f;
    float ma = a0.y + a1.y + 64.f * ((a0.x - mean0) * (a0.x - mean0) + (a1.x - mean0) * (a1.x - mean0));
    float mb = b0.y + b1.y + 64.f * ((b0.x - mean1) * (b0.x - mean1) + (b1.x - mean1) * (b1.x - mean1));
    ma += __shfl_xor_sync(0xffffffffu, ma, 1); ma += __shfl_xor_sync(0xffffffffu, ma, 2);
    mb += __shfl_xor_sync(0xffffffffu, mb, 1); mb += __shfl_xor_sync(0xffffffffu, mb, 2);
    rstd0 = 1.0f / sqrtf(ma * (1.f / 512.f) + 1e-5f);
    rstd1 = 1.0f / sqrtf(mb * (1.f / 512.f) + 1e-5f);
}

template <int BN, int KB, int STAGES, int EPI, int MC>
__device__ __forceinline__ void gemm_body(const CUtensorMap* mapA, const CUtensorMap* mapB, const CUtensorMap* mapB2, const CUtensorMap* mapR,
                                          const CUtensorMap* mapC, const GemmParams& prm, int tile_m, int tile_n, uint8_t* smem_raw) {
    using SM = GemmSmem<BN, STAGES, EPI>;
    using BT = BTile<BN>;
    const uint32_t sbase = (smem_u32(smem_raw) + 1023) & ~1023u;
    uint8_t* sgen = smem_raw + (sbase - smem_u32(smem_raw));
    const uint32_t bar_full = sbase + SM::AUX_OFF, bar_empty = bar_full + 8 * STAGES, bar_res = bar_empty + 8 * STAGES;
    float* s_cs = (float*)(sgen + SM::AUX_OFF + 256);
    float* s_red = (float*)(sgen + SM::AUX_OFF + 256 + 1024);
    const int tid = threadIdx.x, warp = tid >> 5, lane = tid & 31;
    const uint32_t rank = MC ? cluster_rank() : 0;

    if (tid == 0) {
        for (int s = 0; s < STAGES; s++) { mbar_init(bar_full + 8 * s, 1); mbar_init(bar_empty + 8 * s, MC ? 4 : 2); }
        mbar_init(bar_res, 1);
        fence_mbar_init();
    }
    if (warp == 8 && lane == 0) { prefetch_tmap(mapA); prefetch_tmap(mapB); prefetch_tmap(mapC); }
    __syncthreads();
    if (MC) cluster_sync();
    pdl_launch();

    const int m0 = tile_m * 128, n0 = tile_n * BN;
    if (warp == 8) {
        if (lane == 0) {
            constexpr uint32_t STAGE_TX = A_BYTES + BT::BYTES;
            auto loadB = [&](int kb, int s) {
                const uint32_t dst = sbase + s * SM::STAGE + A_BYTES, bar = bar_full + 8 * s;
                if constexpr (BN == 64) {
                    if constexpr (MC == 2) tma2d_mc(dst + rank * 4096, mapB, n0, kb * 64 + rank * 32, bar, 3);
                    else tma2d(dst, mapB, n0, kb * 64, bar);
                } else if constexpr (BN == 224) {
                    if constexpr (MC == 2) {
                        if (rank == 0) tma3d_mc(dst, mapB, 0, kb * 64, tile_n * 7, bar, 3);
                        else tma3d_mc(dst + 4 * 4096, mapB2, 0, kb * 64, tile_n * 7 + 4, bar, 3);
                    } else tma3d(dst, mapB, 0, kb * 64, tile_n * 7, bar);
                } else {
                    tma2d(dst, mapB, 0, kb * 64, bar);
                    tma2d(dst + 2048, mapB2, 0, kb * 64, bar);
                }
            };
            auto loadA = [&](int kb, int s) {
                const uint32_t dst = sbase + s * SM::STAGE, bar = bar_full + 8 * s;
                if constexpr (MC == 1) tma2d_mc(dst + rank * 8192, mapA, kb * 64, m0 + rank * 64, bar, 3);
                else { tma2d(dst, mapA, kb * 64, m0, bar); tma2d(dst + 8192, mapA, kb * 64, m0 + 64, bar); }
            };
            constexpr int PRE = STAGES < KB ? STAGES : KB;
            for (int kb = 0; kb < PRE; kb++) { mbar_expect_tx(bar_full + 8 * kb, STAGE_TX); loadB(kb, kb); }
            if (!prm.wait_in_epilogue) pdl_wait();
            for (int kb = 0; kb < PRE; kb++) loadA(kb, kb);
            if constexpr (EPI == EPI_RES) {
                mbar_expect_tx(bar_res, 16384);
                tma2d(sbase + SM::RES_OFF, mapR, n0, m0, bar_res);
                tma2d(sbase + SM::RES_OFF + 8192, mapR, n0, m0 + 64, bar_res);
            }
            int s = PRE % STAGES, ph = (PRE / STAGES) & 1;
            for (int kb = PRE; kb < KB; kb++) {
                mbar_wait(bar_empty + 8 * s, ph ^ 1);
                mbar_expect_tx(bar_full + 8 * s, STAGE_TX);
                loadB(kb, s);
                loadA(kb, s);
                if (++s == STAGES) { s = 0; ph ^= 1; }
            }
        }
    } else {
        const int wg = warp >> 2, g = lane >> 2, c = lane & 3;
        float acc[BN / 2];
        const uint64_t dA0 = mkdesc(sbase + wg * 8192, 16, 1024, 1);
        const uint64_t dB0 = mkdesc(sbase + A_BYTES, BT::LBO, BT::SBO, BT::SWZ);
        int s = 0, ph = 0;
#pragma unroll 1
        for (int kb = 0; kb < KB; kb++) {
            mbar_wait(bar_full + 8 * s, ph);
            const uint64_t dA = dA0 + (uint64_t)(s * (SM::STAGE >> 4)), dB = dB0 + (uint64_t)(s * (SM::STAGE >> 4));
            wg_fence();
#pragma unroll
            for (int k = 0; k < 4; k++) wgmma_ss_tb<BN>(acc, dA + (uint64_t)(k * 2), dB + (uint64_t)(k * (BT::KSTEP >> 4)), (kb | k) != 0);
            wg_commit();
            if (kb > 0) {
                wg_wait<1>();
                const int sp = s == 0 ? STAGES - 1 : s - 1;
                if ((tid & 127) == 0) {
                    if (MC) { mbar_arrive_remote(bar_empty + 8 * sp, 0); mbar_arrive_remote(bar_empty + 8 * sp, 1); }
                    else mbar_arrive(bar_empty + 8 * sp);
                }
            }
            if (++s == STAGES) { s = 0; ph ^= 1; }
        }
        pdl_wait();
        const int rloc = wg * 64 + (warp & 3) * 16 + g;
        const int row0 = m0 + rloc;
        float mean0 = 0.f, rstd0 = 1.f, mean1 = 0.f, rstd1 = 1.f;
        if constexpr (EPI != EPI_RES) {
            load_row_stats(prm.stats_in, row0, c, mean0, rstd0, mean1, rstd1);
            const float* cs = EPI == EPI_FFN1 ? g_cs_1 + n0 : (BN == 64 ? g_cs_q + n0 : g_cs_kv);
            for (int i = tid; i < BN; i += 256) s_cs[i] = cs[i];
            named_bar(1, 256);
        }
        wg_wait<0>();
        fence_regs(acc);

        if constexpr (EPI == EPI_QKV && BN == 32) {
            const float rm0 = rstd0 * mean0, rm1 = rstd1 * mean1;
            float kn0 = 0.f, kn1 = 0.f, vmax = 0.f;
#pragma unroll
            for (int j = 0; j < 4; j++) {
                const float2 cs2 = *(const float2*)(s_cs + 8 * j + 2 * c);
                const uint32_t u0 = pack_bf16(acc[4 * j] * rstd0 - rm0 * cs2.x, acc[4 * j + 1] * rstd0 - rm0 * cs2.y);
                const uint32_t u1 = pack_bf16(acc[4 * j + 2] * rstd1 - rm1 * cs2.x, acc[4 * j + 3] * rstd1 - rm1 * cs2.y);
                if (j < 2) {
                    kn0 += bf_lo(u0) * bf_lo(u0) + bf_hi(u0) * bf_hi(u0);
                    kn1 += bf_lo(u1) * bf_lo(u1) + bf_hi(u1) * bf_hi(u1);
                    *(uint32_t*)(g_kimg + (row0 >> 3) * 256 + j * 128 + g * 16 + c * 4) = u0;
                    *(uint32_t*)(g_kimg + ((row0 + 8) >> 3) * 256 + j * 128 + g * 16 + c * 4) = u1;
                } else {
                    vmax = fmaxf(vmax, fmaxf(fmaxf(fabsf(bf_lo(u0)), fabsf(bf_hi(u0))), fmaxf(fabsf(bf_lo(u1)), fabsf(bf_hi(u1)))));
                    uint8_t* vb = g_vimg + (row0 >> 4) * 768 + (j - 2) * 256 + g * 16 + c * 4;
                    *(uint32_t*)(vb) = u0;
                    *(uint32_t*)(vb + 128) = u1;
                }
            }
            {
                uint8_t* vb = g_vimg + (row0 >> 4) * 768 + 512 + g * 16 + c * 4;
                const uint32_t one = c == 0 ? 0x00003F80u : 0u;
                *(uint32_t*)(vb) = one;
                *(uint32_t*)(vb + 128) = one;
            }
            kn0 += __shfl_xor_sync(0xffffffffu, kn0, 1); kn0 += __shfl_xor_sync(0xffffffffu, kn0, 2);
            kn1 += __shfl_xor_sync(0xffffffffu, kn1, 1); kn1 += __shfl_xor_sync(0xffffffffu, kn1, 2);
            float km = fmaxf(kn0, kn1);
            if (!(kn0 == kn0) || !(kn1 == kn1)) km = __int_as_float(0x7f800000);
#pragma unroll
            for (int o = 4; o < 32; o <<= 1) km = fmaxf(km, __shfl_xor_sync(0xffffffffu, km, o));
#pragma unroll
            for (int o = 1; o < 32; o <<= 1) vmax = fmaxf(vmax, __shfl_xor_sync(0xffffffffu, vmax, o));
            if (lane == 0) { s_red[warp * 2] = km; s_red[warp * 2 + 1] = vmax; }
            named_bar(1, 256);
            if (tid == 0) {
                float a = 0.f, b = 0.f;
                for (int i = 0; i < 8; i++) { a = fmaxf(a, s_red[2 * i]); b = fmaxf(b, s_red[2 * i + 1]); }
                g_kvmax[tile_m] = make_float2(a, b);
            }
        } else if constexpr (BN == 64) {
            if constexpr (EPI != EPI_RES) named_bar(1, 256);
            const uint32_t stile = sbase + (EPI == EPI_RES ? SM::RES_OFF : 0);
            const int mrow = wg * 64 + (warp & 3) * 16 + (lane & 7) + ((lane >> 3) & 1) * 8;
            const uint32_t rbase = stile + mrow * 128;
            if constexpr (EPI == EPI_RES) {
                mbar_wait(bar_res, 0);
                float s0 = 0.f, s1 = 0.f;
#pragma unroll
                for (int jj = 0; jj < 4; jj++) {
                    uint32_t r0, r1, r2, r3;
                    const uint32_t addr = rbase + (((2 * jj + (lane >> 4)) ^ (mrow & 7)) << 4);
                    ldsm_x4(r0, r1, r2, r3, addr);
                    const uint32_t u0 = pack_bf16(acc[8 * jj] + bf_lo(r0), acc[8 * jj + 1] + bf_hi(r0));
                    const uint32_t u1 = pack_bf16(acc[8 * jj + 2] + bf_lo(r1), acc[8 * jj + 3] + bf_hi(r1));
                    const uint32_t u2 = pack_bf16(acc[8 * jj + 4] + bf_lo(r2), acc[8 * jj + 5] + bf_hi(r2));
                    const uint32_t u3 = pack_bf16(acc[8 * jj + 6] + bf_lo(r3), acc[8 * jj + 7] + bf_hi(r3));
                    stsm_x4(addr, u0, u1, u2, u3);
                    acc[8 * jj] = bf_lo(u0); acc[8 * jj + 1] = bf_hi(u0); acc[8 * jj + 4] = bf_lo(u2); acc[8 * jj + 5] = bf_hi(u2);
                    acc[8 * jj + 2] = bf_lo(u1); acc[8 * jj + 3] = bf_hi(u1); acc[8 * jj + 6] = bf_lo(u3); acc[8 * jj + 7] = bf_hi(u3);
                    s0 += (acc[8 * jj] + acc[8 * jj + 1]) + (acc[8 * jj + 4] + acc[8 * jj + 5]);
                    s1 += (acc[8 * jj + 2] + acc[8 * jj + 3]) + (acc[8 * jj + 6] + acc[8 * jj + 7]);
                }
                fence_async_smem();
                named_bar(2 + wg, 128);
                if ((tid & 127) == 0) { tma2d_store(mapC, stile + wg * 8192, n0, m0 + wg * 64); bulk_commit(); }
                s0 += __shfl_xor_sync(0xffffffffu, s0, 1); s0 += __shfl_xor_sync(0xffffffffu, s0, 2);
                s1 += __shfl_xor_sync(0xffffffffu, s1, 1); s1 += __shfl_xor_sync(0xffffffffu, s1, 2);
                const float mu0 = s0 * (1.f / 64.f), mu1 = s1 * (1.f / 64.f);
                float q0 = 0.f, q1 = 0.f;
#pragma unroll
                for (int j = 0; j < 8; j++) {
                    float d;
                    d = acc[4 * j] - mu0; q0 += d * d; d = acc[4 * j + 1] - mu0; q0 += d * d;
                    d = acc[4 * j + 2] - mu1; q1 += d * d; d = acc[4 * j + 3] - mu1; q1 += d * d;
                }
                q0 += __shfl_xor_sync(0xffffffffu, q0, 1); q0 += __shfl_xor_sync(0xffffffffu, q0, 2);
                q1 += __shfl_xor_sync(0xffffffffu, q1, 1); q1 += __shfl_xor_sync(0xffffffffu, q1, 2);
                if (c == 0 && prm.stats_out) {
                    prm.stats_out[tile_n * S_ + row0] = make_float2(mu0, q0);
                    prm.stats_out[tile_n * S_ + row0 + 8] = make_float2(mu1, q1);
                }
            } else {
                const float sc = 0.25f * 1.4426950408889634f;
                const float a0 = rstd0 * sc, a1 = rstd1 * sc, rm0 = a0 * mean0, rm1 = a1 * mean1;
#pragma unroll
                for (int jj = 0; jj < 4; jj++) {
                    const float2 ca = *(const float2*)(s_cs + 16 * jj + 2 * c), cb = *(const float2*)(s_cs + 16 * jj + 8 + 2 * c);
                    const uint32_t u0 = pack_bf16(acc[8 * jj] * a0 - rm0 * ca.x, acc[8 * jj + 1] * a0 - rm0 * ca.y);
                    const uint32_t u1 = pack_bf16(acc[8 * jj + 2] * a1 - rm1 * ca.x, acc[8 * jj + 3] * a1 - rm1 * ca.y);
                    const uint32_t u2 = pack_bf16(acc[8 * jj + 4] * a0 - rm0 * cb.x, acc[8 * jj + 5] * a0 - rm0 * cb.y);
                    const uint32_t u3 = pack_bf16(acc[8 * jj + 6] * a1 - rm1 * cb.x, acc[8 * jj + 7] * a1 - rm1 * cb.y);
                    stsm_x4(rbase + (((2 * jj + (lane >> 4)) ^ (mrow & 7)) << 4), u0, u1, u2, u3);
                }
                fence_async_smem();
                named_bar(2 + wg, 128);
                if ((tid & 127) == 0) { tma2d_store(mapC, stile + wg * 8192, n0, m0 + wg * 64); bulk_commit(); }
            }
            if ((tid & 127) == 0) bulk_wait_read();
        } else {
            named_bar(1, 256);
            const uint32_t stile = sbase + wg * (7 * 4096);
            const int mrow = (warp & 3) * 16 + (lane & 7) + ((lane >> 3) & 1) * 8;
            const float rm0 = rstd0 * mean0, rm1 = rstd1 * mean1;
#pragma unroll
            for (int jj = 0; jj < 14; jj++) {
                const float2 ca = *(const float2*)(s_cs + 16 * jj + 2 * c), cb = *(const float2*)(s_cs + 16 * jj + 8 + 2 * c);
                float y[8] = {acc[8 * jj] * rstd0 - rm0 * ca.x,     acc[8 * jj + 1] * rstd0 - rm0 * ca.y,
                              acc[8 * jj + 2] * rstd1 - rm1 * ca.x, acc[8 * jj + 3] * rstd1 - rm1 * ca.y,
                              acc[8 * jj + 4] * rstd0 - rm0 * cb.x, acc[8 * jj + 5] * rstd0 - rm0 * cb.y,
                              acc[8 * jj + 6] * rstd1 - rm1 * cb.x, acc[8 * jj + 7] * rstd1 - rm1 * cb.y};
#pragma unroll
                for (int i = 0; i < 8; i++) {
                    float e, r;
                    asm("ex2.approx.ftz.f32 %0, %1;" : "=f"(e) : "f"(y[i] * -1.4426950408889634f));
                    asm("rcp.approx.ftz.f32 %0, %1;" : "=f"(r) : "f"(1.0f + e));
                    y[i] *= r;
                }
                const int chunk = (2 * jj + (lane >> 4)) & 3, blk = jj >> 1;
                stsm_x4(stile + blk * 4096 + mrow * 64 + ((chunk ^ ((mrow >> 1) & 3)) << 4),
                        pack_bf16(y[0], y[1]), pack_bf16(y[2], y[3]), pack_bf16(y[4], y[5]), pack_bf16(y[6], y[7]));
            }
            fence_async_smem();
            named_bar(2 + wg, 128);
            if ((tid & 127) == 0) { tma3d_store(mapC, stile, 0, m0 + wg * 64, tile_n * 7); bulk_commit(); bulk_wait_read(); }
        }
    }
    if (MC) cluster_sync();
}

constexpr int QKV_STAGES = 4;
__global__ void __launch_bounds__(288) qkv_kernel(const __grid_constant__ CUtensorMap mapA, const __grid_constant__ CUtensorMap mapWq,
                                                  const __grid_constant__ CUtensorMap mapWk, const __grid_constant__ CUtensorMap mapWv,
                                                  const __grid_constant__ CUtensorMap mapQ, const GemmParams prm) {
    extern __shared__ uint8_t smem_raw[];
    if (blockIdx.x < 128) gemm_body<64, 8, QKV_STAGES, EPI_QKV, 0>(&mapA, &mapWq, &mapWq, &mapA, &mapQ, prm, blockIdx.x >> 3, blockIdx.x & 7, smem_raw);
    else gemm_body<32, 8, QKV_STAGES, EPI_QKV, 0>(&mapA, &mapWk, &mapWv, &mapA, &mapQ, prm, blockIdx.x - 128, 0, smem_raw);
}
constexpr int WO_STAGES = 6, FFN2_STAGES = 8, FFN1_STAGES = 4;
template <int KB, int STAGES>
__global__ void __launch_bounds__(288) res_gemm_kernel(const __grid_constant__ CUtensorMap mapA, const __grid_constant__ CUtensorMap mapW,
                                                       const __grid_constant__ CUtensorMap mapR, const __grid_constant__ CUtensorMap mapC, const GemmParams prm) {
    extern __shared__ uint8_t smem_raw[];
    gemm_body<64, KB, STAGES, EPI_RES, 1>(&mapA, &mapW, &mapW, &mapR, &mapC, prm, blockIdx.x >> 3, blockIdx.x & 7, smem_raw);
}
__global__ void __launch_bounds__(288) ffn1_kernel(const __grid_constant__ CUtensorMap mapA, const __grid_constant__ CUtensorMap mapW4,
                                                   const __grid_constant__ CUtensorMap mapW3, const __grid_constant__ CUtensorMap mapH, const GemmParams prm) {
    extern __shared__ uint8_t smem_raw[];
    const int pair = blockIdx.x >> 1, tile_n = pair & 7, tile_m = (pair >> 3) * 2 + (blockIdx.x & 1);
    gemm_body<224, 8, FFN1_STAGES, EPI_FFN1, 2>(&mapA, &mapW4, &mapW3, &mapA, &mapH, prm, tile_m, tile_n, smem_raw);
}

constexpr int NPOLY = 10;
__host__ __device__ constexpr bool is_mufu(int i) { return ((i + 1) * (16 - NPOLY)) / 16 != (i * (16 - NPOLY)) / 16; }

__device__ __forceinline__ float ex2(float x) { float r; asm("ex2.approx.ftz.f32 %0, %1;" : "=f"(r) : "f"(x)); return r; }
__device__ __forceinline__ uint32_t exp_pair_mufu(float a, float b) { return pack_bf16(ex2(a), ex2(b)); }
__device__ __forceinline__ uint32_t exp_pair_fma(float a, float b, uint32_t c3f) {
    constexpr float MAGIC = 98430.4140625f;
    const float ta = a + MAGIC, tb = b + (MAGIC - 143.5f);
    uint32_t y, m, r;
    asm("mad.lo.u32 %0, %1, 65536, %2;" : "=r"(y) : "r"(__float_as_uint(tb)), "r"(__float_as_uint(ta)));
    asm("lop3.b32 %0, %1, 0x007F007F, %2, 0xEA;" : "=r"(m) : "r"(y), "r"(c3f));
    const uint32_t e = y & 0xFF80FF80u;
    asm("fma.rn.bf16x2 %0, %1, %2, %3;" : "=r"(r) : "r"(y), "r"(m), "r"(e));
    return r;
}

constexpr int KCH = 256, NCH = S_ / KCH;
constexpr int K_BYTES = S_ * 32, V_BYTES = (S_ / 16) * 768;
constexpr int ATT_SMEM = K_BYTES + V_BYTES;

__global__ void __launch_bounds__(512, 1) attn_kernel() {
    extern __shared__ __align__(1024) uint8_t smem[];
    __shared__ uint64_t bars[NCH];
    __shared__ int s_slow;
    const int tid = threadIdx.x, wg = tid >> 7, warp = (tid >> 5) & 3, lane = tid & 31;
    const uint32_t sK = smem_u32(smem), sV = sK + K_BYTES;
    if (tid == 0) {
        for (int i = 0; i < NCH; i++) mbar_init(smem_u32(&bars[i]), 1);
        s_slow = 0;
        fence_mbar_init();
    }
    __syncthreads();
    pdl_launch();
    pdl_wait();
    if (tid == 0) {
        for (int i = 0; i < NCH; i++) {
            mbar_expect_tx(smem_u32(&bars[i]), KCH * 32 + (KCH / 16) * 768);
            bulk_load(sK + i * KCH * 32, g_kimg + i * KCH * 32, KCH * 32, smem_u32(&bars[i]));
            bulk_load(sV + i * (KCH / 16) * 768, g_vimg + i * (KCH / 16) * 768, (KCH / 16) * 768, smem_u32(&bars[i]));
        }
    }
    const int tb = blockIdx.x >> 3, hg = blockIdx.x & 7;
    const int head = hg * 4 + wg;
    const int g = lane >> 2, c = lane & 3;
    uint32_t qa[2][4];
    float qn = 0.f;
#pragma unroll
    for (int m = 0; m < 2; m++) {
        const int row = tb * 128 + m * 64 + warp * 16 + g;
        const uint32_t* p0 = (const uint32_t*)(g_q + (size_t)row * D_ + head * 16);
        const uint32_t* p1 = (const uint32_t*)(g_q + (size_t)(row + 8) * D_ + head * 16);
        qa[m][0] = p0[c]; qa[m][1] = p1[c]; qa[m][2] = p0[c + 4]; qa[m][3] = p1[c + 4];
        float n0 = bf_lo(qa[m][0]) * bf_lo(qa[m][0]) + bf_hi(qa[m][0]) * bf_hi(qa[m][0]) + bf_lo(qa[m][2]) * bf_lo(qa[m][2]) + bf_hi(qa[m][2]) * bf_hi(qa[m][2]);
        float n1 = bf_lo(qa[m][1]) * bf_lo(qa[m][1]) + bf_hi(qa[m][1]) * bf_hi(qa[m][1]) + bf_lo(qa[m][3]) * bf_lo(qa[m][3]) + bf_hi(qa[m][3]) * bf_hi(qa[m][3]);
        n0 += __shfl_xor_sync(0xffffffffu, n0, 1); n0 += __shfl_xor_sync(0xffffffffu, n0, 2);
        n1 += __shfl_xor_sync(0xffffffffu, n1, 1); n1 += __shfl_xor_sync(0xffffffffu, n1, 2);
        if (!(n0 == n0) || !(n1 == n1)) n0 = __int_as_float(0x7f800000);
        qn = fmaxf(qn, fmaxf(n0, n1));
    }
    {
        float km = 0.f, vm = 0.f;
#pragma unroll
        for (int i = 0; i < 16; i++) { const float2 t = g_kvmax[i]; km = fmaxf(km, t.x); vm = fmaxf(vm, t.y); }
        const bool ok = (qn * km <= 10000.f) && (vm <= 16384.f);
        if (!ok) s_slow = 1;
    }
    float oacc[2][12];
#pragma unroll
    for (int m = 0; m < 2; m++)
#pragma unroll
        for (int i = 0; i < 12; i++) oacc[m][i] = 0.f;
    __syncthreads();
    const bool slow = s_slow != 0;

    const uint64_t dK0 = mkdesc(sK, 128, 256, 0);
    const uint64_t dV0 = mkdesc(sV, 128, 256, 0);
    uint32_t c3f;
    asm volatile("mov.b32 %0, 0x3F003F00;" : "=r"(c3f));
    if (!slow) {
#pragma unroll 1
        for (int t = 0; t < S_ / 64; t++) {
            if ((t & 3) == 0) mbar_wait(smem_u32(&bars[t >> 2]), 0);
            const uint64_t dK = dK0 + (uint64_t)(t * 64 * 32 / 16);
            const uint64_t dV = dV0 + (uint64_t)(t * 4 * 768 / 16);
#pragma unroll
            for (int m = 0; m < 2; m++) {
                float s[32];
                wg_fence();
                wgmma_rs_n64_z(s, qa[m][0], qa[m][1], qa[m][2], qa[m][3], dK);
                wg_commit();
                wg_wait<0>();
                fence_regs(s);
                uint32_t p[16];
#pragma unroll
                for (int i = 0; i < 16; i++) p[i] = is_mufu(i) ? exp_pair_mufu(s[2 * i], s[2 * i + 1]) : exp_pair_fma(s[2 * i], s[2 * i + 1], c3f);
                wg_fence();
#pragma unroll
                for (int kk = 0; kk < 4; kk++)
                    wgmma_rs_n24_tb(oacc[m], p[4 * kk], p[4 * kk + 1], p[4 * kk + 2], p[4 * kk + 3], dV + (uint64_t)(kk * 768 / 16));
                wg_commit();
            }
        }
        wg_wait<0>();
    } else {
        float mx[2][2] = {{-INFINITY, -INFINITY}, {-INFINITY, -INFINITY}};
#pragma unroll 1
        for (int t = 0; t < S_ / 64; t++) {
            if ((t & 3) == 0) mbar_wait(smem_u32(&bars[t >> 2]), 0);
            const uint64_t dK = dK0 + (uint64_t)(t * 64 * 32 / 16);
            const uint64_t dV = dV0 + (uint64_t)(t * 4 * 768 / 16);
#pragma unroll
            for (int m = 0; m < 2; m++) {
                float s[32];
                wg_fence();
                wgmma_rs_n64_z(s, qa[m][0], qa[m][1], qa[m][2], qa[m][3], dK);
                wg_commit();
                wg_wait<0>();
                fence_regs(s);
                fence_regs(oacc[m]);
                float r0 = mx[m][0], r1 = mx[m][1];
#pragma unroll
                for (int j = 0; j < 8; j++) {
                    r0 = fmaxf(r0, fmaxf(s[4 * j], s[4 * j + 1]));
                    r1 = fmaxf(r1, fmaxf(s[4 * j + 2], s[4 * j + 3]));
                }
                r0 = fmaxf(r0, __shfl_xor_sync(0xffffffffu, r0, 1)); r0 = fmaxf(r0, __shfl_xor_sync(0xffffffffu, r0, 2));
                r1 = fmaxf(r1, __shfl_xor_sync(0xffffffffu, r1, 1)); r1 = fmaxf(r1, __shfl_xor_sync(0xffffffffu, r1, 2));
                const float al0 = ex2(mx[m][0] - r0), al1 = ex2(mx[m][1] - r1);
                mx[m][0] = r0; mx[m][1] = r1;
#pragma unroll
                for (int j = 0; j < 3; j++) {
                    oacc[m][4 * j] *= al0; oacc[m][4 * j + 1] *= al0;
                    oacc[m][4 * j + 2] *= al1; oacc[m][4 * j + 3] *= al1;
                }
                uint32_t p[16];
#pragma unroll
                for (int j = 0; j < 8; j++) {
                    p[2 * j] = pack_bf16(ex2(s[4 * j] - r0), ex2(s[4 * j + 1] - r0));
                    p[2 * j + 1] = pack_bf16(ex2(s[4 * j + 2] - r1), ex2(s[4 * j + 3] - r1));
                }
                fence_regs(oacc[m]);
                wg_fence();
#pragma unroll
                for (int kk = 0; kk < 4; kk++)
                    wgmma_rs_n24_tb(oacc[m], p[4 * kk], p[4 * kk + 1], p[4 * kk + 2], p[4 * kk + 3], dV + (uint64_t)(kk * 768 / 16));
                wg_commit();
                wg_wait<0>();
            }
        }
    }
    fence_regs(oacc[0]); fence_regs(oacc[1]);
#pragma unroll
    for (int m = 0; m < 2; m++) {
        const float l0 = __shfl_sync(0xffffffffu, oacc[m][8], lane & ~3);
        const float l1 = __shfl_sync(0xffffffffu, oacc[m][10], lane & ~3);
        const float r0 = 1.0f / l0, r1 = 1.0f / l1;
        const int row = tb * 128 + m * 64 + warp * 16 + g;
        uint32_t* p0 = (uint32_t*)(g_o + (size_t)row * D_ + head * 16);
        uint32_t* p1 = (uint32_t*)(g_o + (size_t)(row + 8) * D_ + head * 16);
        p0[c] = pack_bf16(oacc[m][0] * r0, oacc[m][1] * r0);
        p1[c] = pack_bf16(oacc[m][2] * r1, oacc[m][3] * r1);
        p0[c + 4] = pack_bf16(oacc[m][4] * r0, oacc[m][5] * r0);
        p1[c + 4] = pack_bf16(oacc[m][6] * r1, oacc[m][7] * r1);
    }
}

typedef CUresult (*EncodeFn)(CUtensorMap*, CUtensorMapDataType, cuuint32_t, void*, const cuuint64_t*, const cuuint64_t*, const cuuint32_t*,
                             const cuuint32_t*, CUtensorMapInterleave, CUtensorMapSwizzle, CUtensorMapL2promotion, CUtensorMapFloatOOBfill);

EncodeFn get_encode() {
    static EncodeFn fn = nullptr;
    if (!fn) {
        void* p = nullptr;
        cudaDriverEntryPointQueryResult qr;
        cudaGetDriverEntryPoint("cuTensorMapEncodeTiled", &p, cudaEnableDefault, &qr);
        fn = (EncodeFn)p;
    }
    return fn;
}
CUtensorMap map2d(const void* ptr, uint64_t cols, uint64_t rows, uint32_t bc, uint32_t br, CUtensorMapSwizzle sw) {
    CUtensorMap m;
    cuuint64_t gd[2] = {cols, rows}, gs[1] = {cols * 2};
    cuuint32_t bx[2] = {bc, br}, es[2] = {1, 1};
    get_encode()(&m, CU_TENSOR_MAP_DATA_TYPE_BFLOAT16, 2, (void*)ptr, gd, gs, bx, es, CU_TENSOR_MAP_INTERLEAVE_NONE, sw,
                 CU_TENSOR_MAP_L2_PROMOTION_L2_128B, CU_TENSOR_MAP_FLOAT_OOB_FILL_NONE);
    return m;
}
CUtensorMap map3d32(const void* ptr, uint64_t cols, uint64_t rows, uint32_t br, uint32_t nb) {
    CUtensorMap m;
    cuuint64_t gd[3] = {32, rows, cols / 32}, gs[2] = {cols * 2, 64};
    cuuint32_t bx[3] = {32, br, nb}, es[3] = {1, 1, 1};
    get_encode()(&m, CU_TENSOR_MAP_DATA_TYPE_BFLOAT16, 3, (void*)ptr, gd, gs, bx, es, CU_TENSOR_MAP_INTERLEAVE_NONE, CU_TENSOR_MAP_SWIZZLE_64B,
                 CU_TENSOR_MAP_L2_PROMOTION_L2_128B, CU_TENSOR_MAP_FLOAT_OOB_FILL_NONE);
    return m;
}

template <typename... KArgs, typename... Args>
void launch(void (*kern)(KArgs...), int grid, int block, int smem, int cluster, bool pdl, Args... args) {
    cudaLaunchConfig_t cfg = {};
    cfg.gridDim = dim3(grid);
    cfg.blockDim = dim3(block);
    cfg.dynamicSmemBytes = smem;
    cfg.stream = cudaStreamPerThread;
    cudaLaunchAttribute at[2];
    int n = 0;
    if (cluster > 1) { at[n].id = cudaLaunchAttributeClusterDimension; at[n].val.clusterDim.x = cluster; at[n].val.clusterDim.y = 1; at[n].val.clusterDim.z = 1; n++; }
    if (pdl) { at[n].id = cudaLaunchAttributeProgrammaticStreamSerialization; at[n].val.programmaticStreamSerializationAllowed = 1; n++; }
    cfg.attrs = at;
    cfg.numAttrs = n;
    cudaLaunchKernelEx(&cfg, kern, KArgs(args)...);
}

template <typename T> void* sym(const T& s) { void* p = nullptr; cudaGetSymbolAddress(&p, s); return p; }

}

extern "C" void kernel_launch(void* const* d_in, const int* in_sizes, int n_in, void* d_out, int out_size) {
    const __nv_bfloat16* x = (const __nv_bfloat16*)d_in[0];
    const __nv_bfloat16* wq = (const __nv_bfloat16*)d_in[1];
    const __nv_bfloat16* wk = (const __nv_bfloat16*)d_in[2];
    const __nv_bfloat16* wv = (const __nv_bfloat16*)d_in[3];
    const __nv_bfloat16* wo = (const __nv_bfloat16*)d_in[4];
    const __nv_bfloat16* w1 = (const __nv_bfloat16*)d_in[6];
    const __nv_bfloat16* w2 = (const __nv_bfloat16*)d_in[7];

    constexpr int SM_QKV = GemmSmem<64, QKV_STAGES, EPI_QKV>::TOTAL;
    constexpr int SM_WO = GemmSmem<64, WO_STAGES, EPI_RES>::TOTAL;
    constexpr int SM_FFN1 = GemmSmem<224, FFN1_STAGES, EPI_FFN1>::TOTAL;
    constexpr int SM_FFN2 = GemmSmem<64, FFN2_STAGES, EPI_RES>::TOTAL;
    cudaFuncSetAttribute(qkv_kernel, cudaFuncAttributeMaxDynamicSharedMemorySize, SM_QKV);
    cudaFuncSetAttribute(res_gemm_kernel<8, WO_STAGES>, cudaFuncAttributeMaxDynamicSharedMemorySize, SM_WO);
    cudaFuncSetAttribute(ffn1_kernel, cudaFuncAttributeMaxDynamicSharedMemorySize, SM_FFN1);
    cudaFuncSetAttribute(res_gemm_kernel<28, FFN2_STAGES>, cudaFuncAttributeMaxDynamicSharedMemorySize, SM_FFN2);
    cudaFuncSetAttribute(attn_kernel, cudaFuncAttributeMaxDynamicSharedMemorySize, ATT_SMEM);

    void *q = sym(g_q), *o = sym(g_o), *x1 = sym(g_x1), *x2 = sym(g_x2), *x3 = sym(g_x3), *h = sym(g_h);
    float2* stats = (float2*)sym(g_stats);
    const void* xs[5] = {x, x1, x2, x3, d_out};

    const CUtensorMapSwizzle SW128 = CU_TENSOR_MAP_SWIZZLE_128B;
    const CUtensorMap mWq = map2d(wq, D_, D_, 64, 64, SW128);
    const CUtensorMap mWk = map2d(wk, 16, D_, 16, 64, CU_TENSOR_MAP_SWIZZLE_32B);
    const CUtensorMap mWv = map2d(wv, 16, D_, 16, 64, CU_TENSOR_MAP_SWIZZLE_32B);
    const CUtensorMap mWo = map2d(wo, D_, D_, 64, 64, SW128);
    const CUtensorMap mW1a = map3d32(w1, F_, D_, 64, 4), mW1b = map3d32(w1, F_, D_, 64, 3);
    const CUtensorMap mW2 = map2d(w2, D_, F_, 64, 64, SW128);
    const CUtensorMap mQ = map2d(q, D_, S_, 64, 64, SW128);
    const CUtensorMap mO = map2d(o, D_, S_, 64, 64, SW128);
    const CUtensorMap mHst = map3d32(h, F_, S_, 64, 7);
    const CUtensorMap mHld = map2d(h, F_, S_, 64, 64, SW128);
    CUtensorMap mX[5];
    for (int i = 0; i < 5; i++) mX[i] = map2d(xs[i], D_, S_, 64, 64, SW128);

    launch(prep_kernel, PREP_CS_CTAS + PREP_STAT_CTAS, 256, 0, 1, false, x, wq, wk, wv, wo, w1, w2);
    for (int layer = 0; layer < 2; layer++) {
        const int xi = layer * 2;
        GemmParams p;
        p.stats_in = stats + (size_t)xi * 8 * S_; p.stats_out = nullptr; p.wait_in_epilogue = layer == 0;
        launch(qkv_kernel, 144, 288, SM_QKV, 1, true, mX[xi], mWq, mWk, mWv, mQ, p);
        launch(attn_kernel, 128, 512, ATT_SMEM, 1, true);
        p.stats_in = nullptr; p.stats_out = stats + (size_t)(xi + 1) * 8 * S_; p.wait_in_epilogue = 0;
        launch(res_gemm_kernel<8, WO_STAGES>, 128, 288, SM_WO, 2, true, mO, mWo, mX[xi], mX[xi + 1], p);
        p.stats_in = stats + (size_t)(xi + 1) * 8 * S_; p.stats_out = nullptr;
        launch(ffn1_kernel, 128, 288, SM_FFN1, 2, true, mX[xi + 1], mW1a, mW1b, mHst, p);
        p.stats_in = nullptr; p.stats_out = layer == 0 ? stats + (size_t)2 * 8 * S_ : nullptr;
        launch(res_gemm_kernel<28, FFN2_STAGES>, 128, 288, SM_FFN2, 2, true, mHld, mW2, mX[xi + 1], mX[xi + 2], p);
    }
}
```

```cpp
#include <cuda_runtime.h>
#include <cuda_bf16.h>
#include <cuda.h>
#include <stdint.h>

namespace {

constexpr int S_ = 2048, D_ = 512, H_ = 32, F_ = 1792;

__device__ __align__(1024) __nv_bfloat16 g_q[S_ * D_];
__device__ __align__(1024) __nv_bfloat16 g_o[S_ * D_];
__device__ __align__(1024) __nv_bfloat16 g_x1[S_ * D_];
__device__ __align__(1024) __nv_bfloat16 g_x2[S_ * D_];
__device__ __align__(1024) __nv_bfloat16 g_x3[S_ * D_];
__device__ __align__(1024) __nv_bfloat16 g_h[S_ * F_];
__device__ __align__(1024) uint8_t g_kimg[S_ * 32];
__device__ __align__(1024) uint8_t g_vimg[(S_ / 16) * 768];
__device__ __align__(1024) float2 g_stats[4][8 * S_];
__device__ __align__(16) float g_cs_q[D_];
__device__ __align__(16) float g_cs_kv[32];
__device__ __align__(16) float g_cs_1[F_];
__device__ __align__(16) float2 g_kvmax[16];

#define TL(k, slot)

__device__ __forceinline__ uint32_t smem_u32(const void* p) { return (uint32_t)__cvta_generic_to_shared(p); }
__device__ __forceinline__ void mbar_init(uint32_t bar, uint32_t cnt) {
    asm volatile("mbarrier.init.shared::cta.b64 [%0], %1;" ::"r"(bar), "r"(cnt));
}
__device__ __forceinline__ void mbar_expect_tx(uint32_t bar, uint32_t bytes) {
    asm volatile("mbarrier.arrive.expect_tx.shared::cta.b64 _, [%0], %1;" ::"r"(bar), "r"(bytes) : "memory");
}
__device__ __forceinline__ void mbar_arrive(uint32_t bar) {
    asm volatile("mbarrier.arrive.shared::cta.b64 _, [%0];" ::"r"(bar) : "memory");
}
__device__ __forceinline__ void mbar_arrive_remote(uint32_t bar, uint32_t cta) {
    asm volatile("{\n.reg .b32 ra;\nmapa.shared::cluster.u32 ra, %0, %1;\nmbarrier.arrive.shared::cluster.b64 _, [ra];\n}" ::"r"(bar), "r"(cta) : "memory");
}
__device__ __forceinline__ void mbar_wait(uint32_t bar, uint32_t parity) {
    asm volatile("{\n.reg .pred p;\nWAIT_%=:\nmbarrier.try_wait.parity.shared::cta.b64 p, [%0], %1;\n@p bra DONE_%=;\nbra WAIT_%=;\nDONE_%=:\n}" ::"r"(bar), "r"(parity) : "memory");
}
__device__ __forceinline__ void bulk_load(uint32_t dst, const void* src, uint32_t bytes, uint32_t bar) {
    asm volatile("cp.async.bulk.shared::cluster.global.mbarrier::complete_tx::bytes [%0], [%1], %2, [%3];" ::"r"(dst), "l"(src), "r"(bytes), "r"(bar) : "memory");
}
__device__ __forceinline__ void tma2d(uint32_t dst, const CUtensorMap* m, int c0, int c1, uint32_t bar) {
    asm volatile("cp.async.bulk.tensor.2d.shared::cluster.global.mbarrier::complete_tx::bytes [%0], [%1, {%3, %4}], [%2];" ::"r"(dst), "l"(m), "r"(bar), "r"(c0), "r"(c1) : "memory");
}
__device__ __forceinline__ void tma2d_mc(uint32_t dst, const CUtensorMap* m, int c0, int c1, uint32_t bar, uint16_t mask) {
    asm volatile("cp.async.bulk.tensor.2d.shared::cluster.global.mbarrier::complete_tx::bytes.multicast::cluster [%0], [%1, {%3, %4}], [%2], %5;" ::"r"(dst), "l"(m), "r"(bar), "r"(c0), "r"(c1), "h"(mask) : "memory");
}
__device__ __forceinline__ void tma3d(uint32_t dst, const CUtensorMap* m, int c0, int c1, int c2, uint32_t bar) {
    asm volatile("cp.async.bulk.tensor.3d.shared::cluster.global.mbarrier::complete_tx::bytes [%0], [%1, {%3, %4, %5}], [%2];" ::"r"(dst), "l"(m), "r"(bar), "r"(c0), "r"(c1), "r"(c2) : "memory");
}
__device__ __forceinline__ void tma3d_mc(uint32_t dst, const CUtensorMap* m, int c0, int c1, int c2, uint32_t bar, uint16_t mask) {
    asm volatile("cp.async.bulk.tensor.3d.shared::cluster.global.mbarrier::complete_tx::bytes.multicast::cluster [%0], [%1, {%3, %4, %5}], [%2], %6;" ::"r"(dst), "l"(m), "r"(bar), "r"(c0), "r"(c1), "r"(c2), "h"(mask) : "memory");
}
__device__ __forceinline__ void tma2d_store(const CUtensorMap* m, uint32_t src, int c0, int c1) {
    asm volatile("cp.async.bulk.tensor.2d.global.shared::cta.bulk_group [%0, {%2, %3}], [%1];" ::"l"(m), "r"(src), "r"(c0), "r"(c1) : "memory");
}
__device__ __forceinline__ void tma3d_store(const CUtensorMap* m, uint32_t src, int c0, int c1, int c2) {
    asm volatile("cp.async.bulk.tensor.3d.global.shared::cta.bulk_group [%0, {%2, %3, %4}], [%1];" ::"l"(m), "r"(src), "r"(c0), "r"(c1), "r"(c2) : "memory");
}
__device__ __forceinline__ void bulk_commit() { asm volatile("cp.async.bulk.commit_group;" ::: "memory"); }
__device__ __forceinline__ void bulk_wait_read() { asm volatile("cp.async.bulk.wait_group.read 0;" ::: "memory"); }
__device__ __forceinline__ void prefetch_tmap(const CUtensorMap* m) { asm volatile("prefetch.tensormap [%0];" ::"l"(m) : "memory"); }
__device__ __forceinline__ void fence_async_smem() { asm volatile("fence.proxy.async.shared::cta;" ::: "memory"); }
__device__ __forceinline__ void fence_mbar_init() { asm volatile("fence.mbarrier_init.release.cluster;" ::: "memory"); }
__device__ __forceinline__ void cluster_sync() { asm volatile("barrier.cluster.arrive.release.aligned;\nbarrier.cluster.wait.acquire.aligned;" ::: "memory"); }
__device__ __forceinline__ uint32_t cluster_rank() { uint32_t r; asm volatile("mov.u32 %0, %%cluster_ctarank;" : "=r"(r)); return r; }
__device__ __forceinline__ void pdl_wait() { asm volatile("griddepcontrol.wait;" ::: "memory"); }
__device__ __forceinline__ void pdl_launch() { asm volatile("griddepcontrol.launch_dependents;" ::: "memory"); }
__device__ __forceinline__ void named_bar(int id, int n) { asm volatile("bar.sync %0, %1;" ::"r"(id), "r"(n) : "memory"); }

__device__ __forceinline__ void wg_fence() { asm volatile("wgmma.fence.sync.aligned;" ::: "memory"); }
__device__ __forceinline__ void wg_commit() { asm volatile("wgmma.commit_group.sync.aligned;" ::: "memory"); }
template <int N> __device__ __forceinline__ void wg_wait() { asm volatile("wgmma.wait_group.sync.aligned %0;" ::"n"(N) : "memory"); }
template <int N> __device__ __forceinline__ void fence_regs(float (&d)[N]) {
#pragma unroll
    for (int i = 0; i < N; i++) asm volatile("" : "+f"(d[i])::"memory");
}
__device__ __forceinline__ uint64_t mkdesc(uint32_t addr, uint32_t lbo, uint32_t sbo, uint32_t swz) {
    uint64_t d = 0;
    d |= (uint64_t)((addr & 0x3FFFF) >> 4);
    d |= (uint64_t)((lbo & 0x3FFFF) >> 4) << 16;
    d |= (uint64_t)((sbo & 0x3FFFF) >> 4) << 32;
    d |= (uint64_t)swz << 62;
    return d;
}
__device__ __forceinline__ void ldsm_x4(uint32_t& r0, uint32_t& r1, uint32_t& r2, uint32_t& r3, uint32_t addr) {
    asm volatile("ldmatrix.sync.aligned.m8n8.x4.shared.b16 {%0,%1,%2,%3}, [%4];" : "=r"(r0), "=r"(r1), "=r"(r2), "=r"(r3) : "r"(addr) : "memory");
}
__device__ __forceinline__ void stsm_x4(uint32_t addr, uint32_t r0, uint32_t r1, uint32_t r2, uint32_t r3) {
    asm volatile("stmatrix.sync.aligned.m8n8.x4.shared.b16 [%0], {%1,%2,%3,%4};" ::"r"(addr), "r"(r0), "r"(r1), "r"(r2), "r"(r3) : "memory");
}
__device__ __forceinline__ uint32_t pack_bf16(float lo, float hi) {
    uint32_t r;
    asm("cvt.rn.bf16x2.f32 %0, %1, %2;" : "=r"(r) : "f"(hi), "f"(lo));
    return r;
}
__device__ __forceinline__ float bf_lo(uint32_t v) { return __uint_as_float(v << 16); }
__device__ __forceinline__ float bf_hi(uint32_t v) { return __uint_as_float(v & 0xFFFF0000u); }

#define WG_REGS_4(o) "+f"(d[o]), "+f"(d[o + 1]), "+f"(d[o + 2]), "+f"(d[o + 3])
#define WG_REGS_8(o) WG_REGS_4(o), WG_REGS_4(o + 4)
#define WG_REGS_16(o) WG_REGS_8(o), WG_REGS_8(o + 8)
#define WG_REGS_32(o) WG_REGS_16(o), WG_REGS_16(o + 16)

__device__ __forceinline__ void wgmma_ss_n32_tb(float (&d)[16], uint64_t dA, uint64_t dB, int sc) {
    asm volatile("{\n.reg .pred p;\nsetp.ne.b32 p, %18, 0;\n"
                 "wgmma.mma_async.sync.aligned.m64n32k16.f32.bf16.bf16 "
                 "{%0,%1,%2,%3,%4,%5,%6,%7,%8,%9,%10,%11,%12,%13,%14,%15}, %16, %17, p, 1, 1, 0, 1;\n}\n"
                 : WG_REGS_16(0) : "l"(dA), "l"(dB), "r"(sc));
}
__device__ __forceinline__ void wgmma_ss_n64_tb(float (&d)[32], uint64_t dA, uint64_t dB, int sc) {
    asm volatile("{\n.reg .pred p;\nsetp.ne.b32 p, %34, 0;\n"
                 "wgmma.mma_async.sync.aligned.m64n64k16.f32.bf16.bf16 "
                 "{%0,%1,%2,%3,%4,%5,%6,%7,%8,%9,%10,%11,%12,%13,%14,%15,%16,%17,%18,%19,%20,%21,%22,%23,%24,%25,%26,%27,%28,%29,%30,%31}, "
                 "%32, %33, p, 1, 1, 0, 1;\n}\n"
                 : WG_REGS_32(0) : "l"(dA), "l"(dB), "r"(sc));
}
__device__ __forceinline__ void wgmma_ss_n224_tb(float (&d)[112], uint64_t dA, uint64_t dB, int sc) {
    asm volatile("{\n.reg .pred p;\nsetp.ne.b32 p, %114, 0;\n"
                 "wgmma.mma_async.sync.aligned.m64n224k16.f32.bf16.bf16 "
                 "{%0,%1,%2,%3,%4,%5,%6,%7,%8,%9,%10,%11,%12,%13,%14,%15,%16,%17,%18,%19,%20,%21,%22,%23,%24,%25,%26,%27,%28,%29,%30,%31,"
                 "%32,%33,%34,%35,%36,%37,%38,%39,%40,%41,%42,%43,%44,%45,%46,%47,%48,%49,%50,%51,%52,%53,%54,%55,%56,%57,%58,%59,%60,%61,%62,%63,"
                 "%64,%65,%66,%67,%68,%69,%70,%71,%72,%73,%74,%75,%76,%77,%78,%79,%80,%81,%82,%83,%84,%85,%86,%87,%88,%89,%90,%91,%92,%93,%94,%95,"
                 "%96,%97,%98,%99,%100,%101,%102,%103,%104,%105,%106,%107,%108,%109,%110,%111}, "
                 "%112, %113, p, 1, 1, 0, 1;\n}\n"
                 : WG_REGS_32(0), WG_REGS_32(32), WG_REGS_32(64), WG_REGS_16(96) : "l"(dA), "l"(dB), "r"(sc));
}
template <int BN> __device__ __forceinline__ void wgmma_ss_tb(float (&d)[BN / 2], uint64_t dA, uint64_t dB, int sc) {
    if constexpr (BN == 32) wgmma_ss_n32_tb(d, dA, dB, sc);
    else if constexpr (BN == 64) wgmma_ss_n64_tb(d, dA, dB, sc);
    else wgmma_ss_n224_tb(d, dA, dB, sc);
}
__device__ __forceinline__ void wgmma_rs_n64_z(float (&d)[32], uint32_t a0, uint32_t a1, uint32_t a2, uint32_t a3, uint64_t dB) {
    asm volatile("{\n.reg .pred p;\nsetp.ne.b32 p, 0, 0;\n"
                 "wgmma.mma_async.sync.aligned.m64n64k16.f32.bf16.bf16 "
                 "{%0,%1,%2,%3,%4,%5,%6,%7,%8,%9,%10,%11,%12,%13,%14,%15,%16,%17,%18,%19,%20,%21,%22,%23,%24,%25,%26,%27,%28,%29,%30,%31}, "
                 "{%32,%33,%34,%35}, %36, p, 1, 1, 0;\n}\n"
                 : "=f"(d[0]), "=f"(d[1]), "=f"(d[2]), "=f"(d[3]), "=f"(d[4]), "=f"(d[5]), "=f"(d[6]), "=f"(d[7]),
                   "=f"(d[8]), "=f"(d[9]), "=f"(d[10]), "=f"(d[11]), "=f"(d[12]), "=f"(d[13]), "=f"(d[14]), "=f"(d[15]),
                   "=f"(d[16]), "=f"(d[17]), "=f"(d[18]), "=f"(d[19]), "=f"(d[20]), "=f"(d[21]), "=f"(d[22]), "=f"(d[23]),
                   "=f"(d[24]), "=f"(d[25]), "=f"(d[26]), "=f"(d[27]), "=f"(d[28]), "=f"(d[29]), "=f"(d[30]), "=f"(d[31])
                 : "r"(a0), "r"(a1), "r"(a2), "r"(a3), "l"(dB));
}
__device__ __forceinline__ void wgmma_rs_n24_tb(float (&d)[12], uint32_t a0, uint32_t a1, uint32_t a2, uint32_t a3, uint64_t dB) {
    asm volatile("{\n.reg .pred p;\nsetp.eq.b32 p, 0, 0;\n"
                 "wgmma.mma_async.sync.aligned.m64n24k16.f32.bf16.bf16 "
                 "{%0,%1,%2,%3,%4,%5,%6,%7,%8,%9,%10,%11}, {%12,%13,%14,%15}, %16, p, 1, 1, 1;\n}\n"
                 : WG_REGS_8(0), WG_REGS_4(8) : "r"(a0), "r"(a1), "r"(a2), "r"(a3), "l"(dB));
}

constexpr int PREP_STAT_CTAS = S_ / 8;
constexpr int PREP_CS_CTAS = 8 + 1 + F_ / 64;

__global__ void __launch_bounds__(256) prep_kernel(const __nv_bfloat16* __restrict__ x, const __nv_bfloat16* __restrict__ wq,
                                                   const __nv_bfloat16* __restrict__ wk, const __nv_bfloat16* __restrict__ wv,
                                                   const __nv_bfloat16* __restrict__ wo, const __nv_bfloat16* __restrict__ w1,
                                                   const __nv_bfloat16* __restrict__ w2) {
    pdl_launch();
    const int tid = threadIdx.x;
    if (tid == 0) { TL(0, 0); TL(0, 1); }
    if (blockIdx.x < PREP_CS_CTAS) {
        __shared__ float red[32][65];
        const int b = blockIdx.x;
        const int rg = tid >> 3, c8 = tid & 7;
        float acc[8];
#pragma unroll
        for (int i = 0; i < 8; i++) acc[i] = 0.f;
        const __nv_bfloat16* base;
        int ld;
        bool active = true;
        if (b < 8) { base = wq + b * 64 + c8 * 8; ld = D_; }
        else if (b == 8) { base = (c8 < 2 ? wk + c8 * 8 : wv + (c8 - 2) * 8); ld = 16; active = c8 < 4; }
        else { base = w1 + (b - 9) * 64 + c8 * 8; ld = F_; }
        if (active) {
            uint4 v[16];
#pragma unroll
            for (int i = 0; i < 16; i++) v[i] = __ldg((const uint4*)(base + (size_t)(rg + 32 * i) * ld));
#pragma unroll
            for (int i = 0; i < 16; i++) {
                acc[0] += bf_lo(v[i].x); acc[1] += bf_hi(v[i].x); acc[2] += bf_lo(v[i].y); acc[3] += bf_hi(v[i].y);
                acc[4] += bf_lo(v[i].z); acc[5] += bf_hi(v[i].z); acc[6] += bf_lo(v[i].w); acc[7] += bf_hi(v[i].w);
            }
        }
#pragma unroll
        for (int i = 0; i < 8; i++) red[rg][c8 * 8 + i] = acc[i];
        __syncthreads();
        if (tid < 64) {
            float s = 0.f;
#pragma unroll
            for (int i = 0; i < 32; i++) s += red[i][tid];
            if (b < 8) g_cs_q[b * 64 + tid] = s;
            else if (b == 8) { if (tid < 32) g_cs_kv[tid] = s; }
            else g_cs_1[(b - 9) * 64 + tid] = s;
        }
    } else {
        const int cb = blockIdx.x - PREP_CS_CTAS;
        if (tid < 72) {
            const int line = cb * 72 + tid;
            const char* p = line < 4096 ? (const char*)wo + (size_t)line * 128 : (const char*)w2 + (size_t)(line - 4096) * 128;
            asm volatile("prefetch.global.L2 [%0];" ::"l"(p));
        }
        const int warp = tid >> 5, lane = tid & 31;
        const int row = cb * 8 + warp;
        const uint4* p = (const uint4*)(x + (size_t)row * D_ + lane * 16);
        const uint4 a = __ldg(p), b = __ldg(p + 1);
        float v[16] = {bf_lo(a.x), bf_hi(a.x), bf_lo(a.y), bf_hi(a.y), bf_lo(a.z), bf_hi(a.z), bf_lo(a.w), bf_hi(a.w),
                       bf_lo(b.x), bf_hi(b.x), bf_lo(b.y), bf_hi(b.y), bf_lo(b.z), bf_hi(b.z), bf_lo(b.w), bf_hi(b.w)};
        float s = 0.f;
#pragma unroll
        for (int i = 0; i < 16; i++) s += v[i];
        s += __shfl_xor_sync(0xffffffffu, s, 1);
        s += __shfl_xor_sync(0xffffffffu, s, 2);
        const float mean = s * (1.f / 64.f);
        float m2 = 0.f;
#pragma unroll
        for (int i = 0; i < 16; i++) { const float d = v[i] - mean; m2 += d * d; }
        m2 += __shfl_xor_sync(0xffffffffu, m2, 1);
        m2 += __shfl_xor_sync(0xffffffffu, m2, 2);
        if ((lane & 3) == 0) g_stats[0][(lane >> 2) * S_ + row] = make_float2(mean, m2);
    }
    if (tid == 0) { TL(0, 2); TL(0, 3); }
}

enum { EPI_QKV = 0, EPI_RES = 1, EPI_FFN1 = 2 };

struct GemmParams {
    const float2* stats_in;
    float2* stats_out;
    int wait_in_epilogue;
    int tk;
};

template <int BN> struct Geo;
template <> struct Geo<64> {
    static constexpr int BK = 64, A_BYTES = 128 * 128, A_SWZ = 1, A_SBO = 1024;
    static constexpr int B_BYTES = 64 * 128, B_SWZ = 1, B_LBO = 8192, B_SBO = 1024, B_KSTEP = 2048;
};
template <> struct Geo<32> {
    static constexpr int BK = 64, A_BYTES = 128 * 128, A_SWZ = 1, A_SBO = 1024;
    static constexpr int B_BYTES = 2 * 64 * 32, B_SWZ = 3, B_LBO = 2048, B_SBO = 256, B_KSTEP = 512;
};
template <> struct Geo<224> {
    static constexpr int BK = 32, A_BYTES = 128 * 64, A_SWZ = 2, A_SBO = 512;
    static constexpr int B_BYTES = 7 * 32 * 64, B_SWZ = 2, B_LBO = 2048, B_SBO = 512, B_KSTEP = 1024;
};

template <int BN, int STAGES> struct GemmSmem {
    static constexpr int STAGE = Geo<BN>::A_BYTES + ((Geo<BN>::B_BYTES + 1023) / 1024) * 1024;
    static constexpr int AUX_OFF = STAGES * STAGE;
    static constexpr int TOTAL = AUX_OFF + 1024 + 1024;
};

__device__ __forceinline__ void load_row_stats(const float2* __restrict__ st, int row0, int c, float& mean0, float& rstd0, float& mean1, float& rstd1) {
    const float2 a0 = st[(2 * c) * S_ + row0], a1 = st[(2 * c + 1) * S_ + row0];
    const float2 b0 = st[(2 * c) * S_ + row0 + 8], b1 = st[(2 * c + 1) * S_ + row0 + 8];
    float sa = a0.x + a1.x, sb = b0.x + b1.x;
    sa += __shfl_xor_sync(0xffffffffu, sa, 1); sa += __shfl_xor_sync(0xffffffffu, sa, 2);
    sb += __shfl_xor_sync(0xffffffffu, sb, 1); sb += __shfl_xor_sync(0xffffffffu, sb, 2);
    mean0 = sa * 0.125f; mean1 = sb * 0.125f;
    float ma = a0.y + a1.y + 64.f * ((a0.x - mean0) * (a0.x - mean0) + (a1.x - mean0) * (a1.x - mean0));
    float mb = b0.y + b1.y + 64.f * ((b0.x - mean1) * (b0.x - mean1) + (b1.x - mean1) * (b1.x - mean1));
    ma += __shfl_xor_sync(0xffffffffu, ma, 1); ma += __shfl_xor_sync(0xffffffffu, ma, 2);
    mb += __shfl_xor_sync(0xffffffffu, mb, 1); mb += __shfl_xor_sync(0xffffffffu, mb, 2);
    rstd0 = 1.0f / sqrtf(ma * (1.f / 512.f) + 1e-5f);
    rstd1 = 1.0f / sqrtf(mb * (1.f / 512.f) + 1e-5f);
}

template <int BN, int KB, int STAGES, int EPI, int MC>
__device__ __forceinline__ void gemm_body(const CUtensorMap* mapA, const CUtensorMap* mapB, const CUtensorMap* mapB2, const CUtensorMap* mapR,
                                          const CUtensorMap* mapC, const GemmParams& prm, int tile_m, int tile_n, uint8_t* smem_raw) {
    using SM = GemmSmem<BN, STAGES>;
    using G = Geo<BN>;
    pdl_launch();
    const uint32_t sbase = (smem_u32(smem_raw) + 1023) & ~1023u;
    uint8_t* sgen = smem_raw + (sbase - smem_u32(smem_raw));
    const uint32_t bar_full = sbase + SM::AUX_OFF, bar_empty = bar_full + 8 * STAGES;
    float* s_cs = (float*)(sgen + SM::AUX_OFF + 128);
    float* s_red = (float*)(sgen + SM::AUX_OFF + 640);
    const int tid = threadIdx.x, warp = tid >> 5, lane = tid & 31;
    const uint32_t rank = MC ? cluster_rank() : 0;
    if (tid == 0) TL(prm.tk, 0);

    if (warp == 8 && lane == 0) {
        prefetch_tmap(mapB); prefetch_tmap(mapA); prefetch_tmap(mapC);
        for (int s = 0; s < STAGES; s++) { mbar_init(bar_full + 8 * s, 1); mbar_init(bar_empty + 8 * s, MC ? 4 : 2); }
        fence_mbar_init();
    }
    __syncthreads();
    if (MC) cluster_sync();

    const int m0 = tile_m * 128, n0 = tile_n * BN;
    if (warp == 8) {
        if (lane == 0) {
            constexpr uint32_t STAGE_TX = G::A_BYTES + G::B_BYTES;
            auto loadB = [&](int kb, int s) {
                const uint32_t dst = sbase + s * SM::STAGE + G::A_BYTES, bar = bar_full + 8 * s;
                if constexpr (BN == 64) {
                    tma2d(dst, mapB, n0, kb * 64, bar);
                } else if constexpr (BN == 224) {
                    if (rank == 0) tma3d_mc(dst, mapB, 0, kb * 32, tile_n * 7, bar, 3);
                    else tma3d_mc(dst + 4 * 2048, mapB2, 0, kb * 32, tile_n * 7 + 4, bar, 3);
                } else {
                    tma2d(dst, mapB, 0, kb * 64, bar);
                    tma2d(dst + 2048, mapB2, 0, kb * 64, bar);
                }
            };
            auto loadA = [&](int kb, int s) {
                const uint32_t dst = sbase + s * SM::STAGE, bar = bar_full + 8 * s;
                if constexpr (MC == 1) tma2d_mc(dst + rank * (G::A_BYTES / 2), mapA, kb * G::BK, m0 + rank * 64, bar, 3);
                else { tma2d(dst, mapA, kb * G::BK, m0, bar); tma2d(dst + G::A_BYTES / 2, mapA, kb * G::BK, m0 + 64, bar); }
            };
            constexpr int PRE = STAGES < KB ? STAGES : KB;
            for (int kb = 0; kb < PRE; kb++) { mbar_expect_tx(bar_full + 8 * kb, STAGE_TX); loadB(kb, kb); }
            if (!prm.wait_in_epilogue) pdl_wait();
            for (int kb = 0; kb < PRE; kb++) loadA(kb, kb);
            int s = PRE % STAGES, ph = (PRE / STAGES) & 1;
            for (int kb = PRE; kb < KB; kb++) {
                mbar_wait(bar_empty + 8 * s, ph ^ 1);
                mbar_expect_tx(bar_full + 8 * s, STAGE_TX);
                loadB(kb, s);
                loadA(kb, s);
                if (++s == STAGES) { s = 0; ph ^= 1; }
            }
            if constexpr (EPI == EPI_RES) {
                mbar_wait(bar_empty + 8 * s, ph ^ 1);
                mbar_expect_tx(bar_full + 8 * s, 16384);
                tma2d(sbase + s * SM::STAGE, mapR, n0, m0, bar_full + 8 * s);
                tma2d(sbase + s * SM::STAGE + 8192, mapR, n0, m0 + 64, bar_full + 8 * s);
            }
        }
    } else {
        const int wg = warp >> 2, g = lane >> 2, c = lane & 3;
        float acc[BN / 2];
        const uint64_t dA0 = mkdesc(sbase + wg * (G::A_BYTES / 2), 16, G::A_SBO, G::A_SWZ);
        const uint64_t dB0 = mkdesc(sbase + G::A_BYTES, G::B_LBO, G::B_SBO, G::B_SWZ);
        int s = 0, ph = 0;
#pragma unroll 1
        for (int kb = 0; kb < KB; kb++) {
            mbar_wait(bar_full + 8 * s, ph);
            const uint64_t dA = dA0 + (uint64_t)(s * (SM::STAGE >> 4)), dB = dB0 + (uint64_t)(s * (SM::STAGE >> 4));
            wg_fence();
#pragma unroll
            for (int k = 0; k < G::BK / 16; k++) wgmma_ss_tb<BN>(acc, dA + (uint64_t)(k * 2), dB + (uint64_t)(k * (G::B_KSTEP >> 4)), (kb | k) != 0);
            wg_commit();
            if (kb > 0) {
                wg_wait<1>();
                const int sp = s == 0 ? STAGES - 1 : s - 1;
                if ((tid & 127) == 0) {
                    if (MC) { mbar_arrive_remote(bar_empty + 8 * sp, 0); mbar_arrive_remote(bar_empty + 8 * sp, 1); }
                    else mbar_arrive(bar_empty + 8 * sp);
                }
            }
            if (++s == STAGES) { s = 0; ph ^= 1; }
        }
        pdl_wait();
        const int rloc = wg * 64 + (warp & 3) * 16 + g;
        const int row0 = m0 + rloc;
        float mean0 = 0.f, rstd0 = 1.f, mean1 = 0.f, rstd1 = 1.f;
        if constexpr (EPI != EPI_RES) {
            load_row_stats(prm.stats_in, row0, c, mean0, rstd0, mean1, rstd1);
            const float* cs = EPI == EPI_FFN1 ? g_cs_1 + n0 : (BN == 64 ? g_cs_q + n0 : g_cs_kv);
            if (tid < BN) s_cs[tid] = cs[tid];
        }
        wg_wait<0>();
        fence_regs(acc);
        if (tid == 0) TL(prm.tk, 2);
        if constexpr (EPI != EPI_RES) named_bar(1, 256);

        if constexpr (EPI == EPI_QKV && BN == 32) {
            const float rm0 = rstd0 * mean0, rm1 = rstd1 * mean1;
            float kn0 = 0.f, kn1 = 0.f, vmax = 0.f;
#pragma unroll
            for (int j = 0; j < 4; j++) {
                const float2 cs2 = *(const float2*)(s_cs + 8 * j + 2 * c);
                const uint32_t u0 = pack_bf16(acc[4 * j] * rstd0 - rm0 * cs2.x, acc[4 * j + 1] * rstd0 - rm0 * cs2.y);
                const uint32_t u1 = pack_bf16(acc[4 * j + 2] * rstd1 - rm1 * cs2.x, acc[4 * j + 3] * rstd1 - rm1 * cs2.y);
                if (j < 2) {
                    kn0 += bf_lo(u0) * bf_lo(u0) + bf_hi(u0) * bf_hi(u0);
                    kn1 += bf_lo(u1) * bf_lo(u1) + bf_hi(u1) * bf_hi(u1);
                    *(uint32_t*)(g_kimg + (row0 >> 3) * 256 + j * 128 + g * 16 + c * 4) = u0;
                    *(uint32_t*)(g_kimg + ((row0 + 8) >> 3) * 256 + j * 128 + g * 16 + c * 4) = u1;
                } else {
                    vmax = fmaxf(vmax, fmaxf(fmaxf(fabsf(bf_lo(u0)), fabsf(bf_hi(u0))), fmaxf(fabsf(bf_lo(u1)), fabsf(bf_hi(u1)))));
                    if (!(bf_lo(u0) + bf_hi(u0) + bf_lo(u1) + bf_hi(u1) < INFINITY)) vmax = INFINITY;
                    uint8_t* vb = g_vimg + (row0 >> 4) * 768 + (j - 2) * 256 + g * 16 + c * 4;
                    *(uint32_t*)(vb) = u0;
                    *(uint32_t*)(vb + 128) = u1;
                }
            }
            {
                uint8_t* vb = g_vimg + (row0 >> 4) * 768 + 512 + g * 16 + c * 4;
                const uint32_t one = c == 0 ? 0x00003F80u : 0u;
                *(uint32_t*)(vb) = one;
                *(uint32_t*)(vb + 128) = one;
            }
            kn0 += __shfl_xor_sync(0xffffffffu, kn0, 1); kn0 += __shfl_xor_sync(0xffffffffu, kn0, 2);
            kn1 += __shfl_xor_sync(0xffffffffu, kn1, 1); kn1 += __shfl_xor_sync(0xffffffffu, kn1, 2);
            float km = fmaxf(kn0, kn1);
            if (!(kn0 == kn0) || !(kn1 == kn1)) km = INFINITY;
#pragma unroll
            for (int o = 4; o < 32; o <<= 1) km = fmaxf(km, __shfl_xor_sync(0xffffffffu, km, o));
#pragma unroll
            for (int o = 1; o < 32; o <<= 1) vmax = fmaxf(vmax, __shfl_xor_sync(0xffffffffu, vmax, o));
            if (lane == 0) { s_red[warp * 2] = km; s_red[warp * 2 + 1] = vmax; }
            named_bar(1, 256);
            if (tid == 0) {
                float a = 0.f, b = 0.f;
                for (int i = 0; i < 8; i++) { a = fmaxf(a, s_red[2 * i]); b = fmaxf(b, s_red[2 * i + 1]); }
                g_kvmax[tile_m] = make_float2(a, b);
            }
        } else if constexpr (BN == 64) {
            const uint32_t stile = sbase + (EPI == EPI_RES ? s * SM::STAGE : 0);
            const int mrow = wg * 64 + (warp & 3) * 16 + (lane & 7) + ((lane >> 3) & 1) * 8;
            const uint32_t rbase = stile + mrow * 128;
            if constexpr (EPI == EPI_RES) {
                mbar_wait(bar_full + 8 * s, ph);
                float s0 = 0.f, s1 = 0.f;
#pragma unroll
                for (int jj = 0; jj < 4; jj++) {
                    uint32_t r0, r1, r2, r3;
                    const uint32_t addr = rbase + (((2 * jj + (lane >> 4)) ^ (mrow & 7)) << 4);
                    ldsm_x4(r0, r1, r2, r3, addr);
                    const uint32_t u0 = pack_bf16(acc[8 * jj] + bf_lo(r0), acc[8 * jj + 1] + bf_hi(r0));
                    const uint32_t u1 = pack_bf16(acc[8 * jj + 2] + bf_lo(r1), acc[8 * jj + 3] + bf_hi(r1));
                    const uint32_t u2 = pack_bf16(acc[8 * jj + 4] + bf_lo(r2), acc[8 * jj + 5] + bf_hi(r2));
                    const uint32_t u3 = pack_bf16(acc[8 * jj + 6] + bf_lo(r3), acc[8 * jj + 7] + bf_hi(r3));
                    stsm_x4(addr, u0, u1, u2, u3);
                    acc[8 * jj] = bf_lo(u0); acc[8 * jj + 1] = bf_hi(u0); acc[8 * jj + 4] = bf_lo(u2); acc[8 * jj + 5] = bf_hi(u2);
                    acc[8 * jj + 2] = bf_lo(u1); acc[8 * jj + 3] = bf_hi(u1); acc[8 * jj + 6] = bf_lo(u3); acc[8 * jj + 7] = bf_hi(u3);
                    s0 += (acc[8 * jj] + acc[8 * jj + 1]) + (acc[8 * jj + 4] + acc[8 * jj + 5]);
                    s1 += (acc[8 * jj + 2] + acc[8 * jj + 3]) + (acc[8 * jj + 6] + acc[8 * jj + 7]);
                }
                fence_async_smem();
                named_bar(2 + wg, 128);
                if ((tid & 127) == 0) { tma2d_store(mapC, stile + wg * 8192, n0, m0 + wg * 64); bulk_commit(); }
                if (prm.stats_out) {
                    s0 += __shfl_xor_sync(0xffffffffu, s0, 1); s0 += __shfl_xor_sync(0xffffffffu, s0, 2);
                    s1 += __shfl_xor_sync(0xffffffffu, s1, 1); s1 += __shfl_xor_sync(0xffffffffu, s1, 2);
                    const float mu0 = s0 * (1.f / 64.f), mu1 = s1 * (1.f / 64.f);
                    float q0 = 0.f, q1 = 0.f;
#pragma unroll
                    for (int j = 0; j < 8; j++) {
                        float d;
                        d = acc[4 * j] - mu0; q0 += d * d; d = acc[4 * j + 1] - mu0; q0 += d * d;
                        d = acc[4 * j + 2] - mu1; q1 += d * d; d = acc[4 * j + 3] - mu1; q1 += d * d;
                    }
                    q0 += __shfl_xor_sync(0xffffffffu, q0, 1); q0 += __shfl_xor_sync(0xffffffffu, q0, 2);
                    q1 += __shfl_xor_sync(0xffffffffu, q1, 1); q1 += __shfl_xor_sync(0xffffffffu, q1, 2);
                    if (c == 0) {
                        prm.stats_out[tile_n * S_ + row0] = make_float2(mu0, q0);
                        prm.stats_out[tile_n * S_ + row0 + 8] = make_float2(mu1, q1);
                    }
                }
            } else {
                const float sc = 0.25f * 1.4426950408889634f;
                const float a0 = rstd0 * sc, a1 = rstd1 * sc, rm0 = a0 * mean0, rm1 = a1 * mean1;
#pragma unroll
                for (int jj = 0; jj < 4; jj++) {
                    const float2 ca = *(const float2*)(s_cs + 16 * jj + 2 * c), cb = *(const float2*)(s_cs + 16 * jj + 8 + 2 * c);
                    const uint32_t u0 = pack_bf16(acc[8 * jj] * a0 - rm0 * ca.x, acc[8 * jj + 1] * a0 - rm0 * ca.y);
                    const uint32_t u1 = pack_bf16(acc[8 * jj + 2] * a1 - rm1 * ca.x, acc[8 * jj + 3] * a1 - rm1 * ca.y);
                    const uint32_t u2 = pack_bf16(acc[8 * jj + 4] * a0 - rm0 * cb.x, acc[8 * jj + 5] * a0 - rm0 * cb.y);
                    const uint32_t u3 = pack_bf16(acc[8 * jj + 6] * a1 - rm1 * cb.x, acc[8 * jj + 7] * a1 - rm1 * cb.y);
                    stsm_x4(rbase + (((2 * jj + (lane >> 4)) ^ (mrow & 7)) << 4), u0, u1, u2, u3);
                }
                fence_async_smem();
                named_bar(2 + wg, 128);
                if ((tid & 127) == 0) { tma2d_store(mapC, stile + wg * 8192, n0, m0 + wg * 64); bulk_commit(); }
            }
            if ((tid & 127) == 0) bulk_wait_read();
        } else {
            const uint32_t stile = sbase + wg * (7 * 4096);
            const int mrow = (warp & 3) * 16 + (lane & 7) + ((lane >> 3) & 1) * 8;
            const float a0 = 0.5f * rstd0, a1 = 0.5f * rstd1, rm0 = a0 * mean0, rm1 = a1 * mean1;
#pragma unroll
            for (int jj = 0; jj < 14; jj++) {
                const float2 ca = *(const float2*)(s_cs + 16 * jj + 2 * c), cb = *(const float2*)(s_cs + 16 * jj + 8 + 2 * c);
                float y[8] = {acc[8 * jj] * a0 - rm0 * ca.x,     acc[8 * jj + 1] * a0 - rm0 * ca.y,
                              acc[8 * jj + 2] * a1 - rm1 * ca.x, acc[8 * jj + 3] * a1 - rm1 * ca.y,
                              acc[8 * jj + 4] * a0 - rm0 * cb.x, acc[8 * jj + 5] * a0 - rm0 * cb.y,
                              acc[8 * jj + 6] * a1 - rm1 * cb.x, acc[8 * jj + 7] * a1 - rm1 * cb.y};
#pragma unroll
                for (int i = 0; i < 8; i++) {
                    float t;
                    asm("tanh.approx.f32 %0, %1;" : "=f"(t) : "f"(y[i]));
                    y[i] = fmaf(y[i], t, y[i]);
                }
                const int chunk = (2 * jj + (lane >> 4)) & 3, blk = jj >> 1;
                stsm_x4(stile + blk * 4096 + mrow * 64 + ((chunk ^ ((mrow >> 1) & 3)) << 4),
                        pack_bf16(y[0], y[1]), pack_bf16(y[2], y[3]), pack_bf16(y[4], y[5]), pack_bf16(y[6], y[7]));
                if (jj & 1) {
                    fence_async_smem();
                    __syncwarp();
                    if (lane == 0) {
                        tma2d_store(mapC, stile + blk * 4096 + (warp & 3) * 1024, n0 + blk * 32, m0 + wg * 64 + (warp & 3) * 16);
                        bulk_commit();
                    }
                }
            }
            if (lane == 0) bulk_wait_read();
        }
    }
    if (tid == 0) TL(prm.tk, 3);
    if (MC) cluster_sync();
}

constexpr int QKV_STAGES = 4, RES_STAGES = 4, FFN1_STAGES = 5;
__global__ void __launch_bounds__(288) qkv_kernel(const __grid_constant__ CUtensorMap mapA, const __grid_constant__ CUtensorMap mapWq,
                                                  const __grid_constant__ CUtensorMap mapWk, const __grid_constant__ CUtensorMap mapWv,
                                                  const __grid_constant__ CUtensorMap mapQ, const GemmParams prm) {
    extern __shared__ uint8_t smem_raw[];
    if (blockIdx.x < 128) gemm_body<64, 8, QKV_STAGES, EPI_QKV, 1>(&mapA, &mapWq, &mapWq, &mapA, &mapQ, prm, blockIdx.x >> 3, blockIdx.x & 7, smem_raw);
    else gemm_body<32, 8, QKV_STAGES, EPI_QKV, 0>(&mapA, &mapWk, &mapWv, &mapA, &mapQ, prm, blockIdx.x - 128, 0, smem_raw);
}
template <int KB>
__global__ void __launch_bounds__(288) res_gemm_kernel(const __grid_constant__ CUtensorMap mapA, const __grid_constant__ CUtensorMap mapW,
                                                       const __grid_constant__ CUtensorMap mapR, const __grid_constant__ CUtensorMap mapC, const GemmParams prm) {
    extern __shared__ uint8_t smem_raw[];
    gemm_body<64, KB, RES_STAGES, EPI_RES, 1>(&mapA, &mapW, &mapW, &mapR, &mapC, prm, blockIdx.x >> 3, blockIdx.x & 7, smem_raw);
}
__global__ void __launch_bounds__(288) ffn1_kernel(const __grid_constant__ CUtensorMap mapA, const __grid_constant__ CUtensorMap mapW4,
                                                   const __grid_constant__ CUtensorMap mapW3, const __grid_constant__ CUtensorMap mapH, const GemmParams prm) {
    extern __shared__ uint8_t smem_raw[];
    const int pair = blockIdx.x >> 1, tile_n = pair & 7, tile_m = (pair >> 3) * 2 + (blockIdx.x & 1);
    gemm_body<224, 16, FFN1_STAGES, EPI_FFN1, 2>(&mapA, &mapW4, &mapW3, &mapA, &mapH, prm, tile_m, tile_n, smem_raw);
}

constexpr int NPOLY = 10;
__host__ __device__ constexpr bool is_mufu(int i) { return ((i + 1) * (16 - NPOLY)) / 16 != (i * (16 - NPOLY)) / 16; }

__device__ __forceinline__ float ex2(float x) { float r; asm("ex2.approx.ftz.f32 %0, %1;" : "=f"(r) : "f"(x)); return r; }
__device__ __forceinline__ uint32_t exp_pair_mufu(float a, float b) { return pack_bf16(ex2(a), ex2(b)); }
__device__ __forceinline__ uint32_t exp_pair_fma(float a, float b, uint32_t c3f) {
    constexpr float MAGIC = 98430.4140625f;
    const float ta = a + MAGIC, tb = b + (MAGIC - 143.5f);
    uint32_t y, m, r;
    asm("mad.lo.u32 %0, %1, 65536, %2;" : "=r"(y) : "r"(__float_as_uint(tb)), "r"(__float_as_uint(ta)));
    asm("lop3.b32 %0, %1, 0x007F007F, %2, 0xEA;" : "=r"(m) : "r"(y), "r"(c3f));
    const uint32_t e = y & 0xFF80FF80u;
    asm("fma.rn.bf16x2 %0, %1, %2, %3;" : "=r"(r) : "r"(y), "r"(m), "r"(e));
    return r;
}

constexpr int KCH = 256, NCH = S_ / KCH;
constexpr int K_BYTES = S_ * 32, V_BYTES = (S_ / 16) * 768;
constexpr int ATT_SMEM = K_BYTES + V_BYTES;

__global__ void __launch_bounds__(512, 1) attn_kernel(int tk) {
    extern __shared__ __align__(1024) uint8_t smem[];
    __shared__ uint64_t bars[NCH];
    __shared__ int s_slow;
    const int tid = threadIdx.x, wg = tid >> 7, warp = (tid >> 5) & 3, lane = tid & 31;
    const uint32_t sK = smem_u32(smem), sV = sK + K_BYTES;
    if (tid == 0) TL(tk, 0);
    if (tid == 0) {
        for (int i = 0; i < NCH; i++) mbar_init(smem_u32(&bars[i]), 1);
        s_slow = 0;
        fence_mbar_init();
    }
    __syncthreads();
    pdl_launch();
    pdl_wait();
    if (tid == 0) TL(tk, 1);
    if (tid == 0) {
        for (int i = 0; i < NCH; i++) {
            mbar_expect_tx(smem_u32(&bars[i]), KCH * 32 + (KCH / 16) * 768);
            bulk_load(sK + i * KCH * 32, g_kimg + i * KCH * 32, KCH * 32, smem_u32(&bars[i]));
            bulk_load(sV + i * (KCH / 16) * 768, g_vimg + i * (KCH / 16) * 768, (KCH / 16) * 768, smem_u32(&bars[i]));
        }
    }
    const int tb = blockIdx.x >> 3, hg = blockIdx.x & 7;
    const int head = hg * 4 + wg;
    const int g = lane >> 2, c = lane & 3;
    uint32_t qa[2][4];
    float qn = 0.f;
#pragma unroll
    for (int m = 0; m < 2; m++) {
        const int row = tb * 128 + m * 64 + warp * 16 + g;
        const uint32_t* p0 = (const uint32_t*)(g_q + (size_t)row * D_ + head * 16);
        const uint32_t* p1 = (const uint32_t*)(g_q + (size_t)(row + 8) * D_ + head * 16);
        qa[m][0] = p0[c]; qa[m][1] = p1[c]; qa[m][2] = p0[c + 4]; qa[m][3] = p1[c + 4];
        float n0 = bf_lo(qa[m][0]) * bf_lo(qa[m][0]) + bf_hi(qa[m][0]) * bf_hi(qa[m][0]) + bf_lo(qa[m][2]) * bf_lo(qa[m][2]) + bf_hi(qa[m][2]) * bf_hi(qa[m][2]);
        float n1 = bf_lo(qa[m][1]) * bf_lo(qa[m][1]) + bf_hi(qa[m][1]) * bf_hi(qa[m][1]) + bf_lo(qa[m][3]) * bf_lo(qa[m][3]) + bf_hi(qa[m][3]) * bf_hi(qa[m][3]);
        n0 += __shfl_xor_sync(0xffffffffu, n0, 1); n0 += __shfl_xor_sync(0xffffffffu, n0, 2);
        n1 += __shfl_xor_sync(0xffffffffu, n1, 1); n1 += __shfl_xor_sync(0xffffffffu, n1, 2);
        if (!(n0 == n0) || !(n1 == n1)) n0 = __int_as_float(0x7f800000);
        qn = fmaxf(qn, fmaxf(n0, n1));
    }
    {
        float km = 0.f, vm = 0.f;
#pragma unroll
        for (int i = 0; i < 16; i++) { const float2 t = g_kvmax[i]; km = fmaxf(km, t.x); vm = fmaxf(vm, t.y); }
        const bool ok = (qn * km <= 10000.f) && (vm <= 16384.f);
        if (!ok) s_slow = 1;
    }
    float oacc[2][12];
#pragma unroll
    for (int m = 0; m < 2; m++)
#pragma unroll
        for (int i = 0; i < 12; i++) oacc[m][i] = 0.f;
    __syncthreads();
    const bool slow = s_slow != 0;

    const uint64_t dK0 = mkdesc(sK, 128, 256, 0);
    const uint64_t dV0 = mkdesc(sV, 128, 256, 0);
    uint32_t c3f;
    asm volatile("mov.b32 %0, 0x3F003F00;" : "=r"(c3f));
    if (!slow) {
#pragma unroll 1
        for (int t = 0; t < S_ / 64; t++) {
            if ((t & 3) == 0) mbar_wait(smem_u32(&bars[t >> 2]), 0);
            const uint64_t dK = dK0 + (uint64_t)(t * 64 * 32 / 16);
            const uint64_t dV = dV0 + (uint64_t)(t * 4 * 768 / 16);
#pragma unroll
            for (int m = 0; m < 2; m++) {
                float s[32];
                wg_fence();
                wgmma_rs_n64_z(s, qa[m][0], qa[m][1], qa[m][2], qa[m][3], dK);
                wg_commit();
                wg_wait<0>();
                fence_regs(s);
                uint32_t p[16];
#pragma unroll
                for (int i = 0; i < 16; i++) p[i] = is_mufu(i) ? exp_pair_mufu(s[2 * i], s[2 * i + 1]) : exp_pair_fma(s[2 * i], s[2 * i + 1], c3f);
                wg_fence();
#pragma unroll
                for (int kk = 0; kk < 4; kk++)
                    wgmma_rs_n24_tb(oacc[m], p[4 * kk], p[4 * kk + 1], p[4 * kk + 2], p[4 * kk + 3], dV + (uint64_t)(kk * 768 / 16));
                wg_commit();
            }
        }
        wg_wait<0>();
    } else {
        float mx[2][2] = {{-INFINITY, -INFINITY}, {-INFINITY, -INFINITY}};
#pragma unroll 1
        for (int t = 0; t < S_ / 64; t++) {
            if ((t & 3) == 0) mbar_wait(smem_u32(&bars[t >> 2]), 0);
            const uint64_t dK = dK0 + (uint64_t)(t * 64 * 32 / 16);
            const uint64_t dV = dV0 + (uint64_t)(t * 4 * 768 / 16);
#pragma unroll
            for (int m = 0; m < 2; m++) {
                float s[32];
                wg_fence();
                wgmma_rs_n64_z(s, qa[m][0], qa[m][1], qa[m][2], qa[m][3], dK);
                wg_commit();
                wg_wait<0>();
                fence_regs(s);
                fence_regs(oacc[m]);
                float r0 = mx[m][0], r1 = mx[m][1];
#pragma unroll
                for (int j = 0; j < 8; j++) {
                    r0 = fmaxf(r0, fmaxf(s[4 * j], s[4 * j + 1]));
                    r1 = fmaxf(r1, fmaxf(s[4 * j + 2], s[4 * j + 3]));
                }
                r0 = fmaxf(r0, __shfl_xor_sync(0xffffffffu, r0, 1)); r0 = fmaxf(r0, __shfl_xor_sync(0xffffffffu, r0, 2));
                r1 = fmaxf(r1, __shfl_xor_sync(0xffffffffu, r1, 1)); r1 = fmaxf(r1, __shfl_xor_sync(0xffffffffu, r1, 2));
                const float al0 = ex2(mx[m][0] - r0), al1 = ex2(mx[m][1] - r1);
                mx[m][0] = r0; mx[m][1] = r1;
#pragma unroll
                for (int j = 0; j < 3; j++) {
                    oacc[m][4 * j] *= al0; oacc[m][4 * j + 1] *= al0;
                    oacc[m][4 * j + 2] *= al1; oacc[m][4 * j + 3] *= al1;
                }
                uint32_t p[16];
#pragma unroll
                for (int j = 0; j < 8; j++) {
                    p[2 * j] = pack_bf16(ex2(s[4 * j] - r0), ex2(s[4 * j + 1] - r0));
                    p[2 * j + 1] = pack_bf16(ex2(s[4 * j + 2] - r1), ex2(s[4 * j + 3] - r1));
                }
                fence_regs(oacc[m]);
                wg_fence();
#pragma unroll
                for (int kk = 0; kk < 4; kk++)
                    wgmma_rs_n24_tb(oacc[m], p[4 * kk], p[4 * kk + 1], p[4 * kk + 2], p[4 * kk + 3], dV + (uint64_t)(kk * 768 / 16));
                wg_commit();
                wg_wait<0>();
            }
        }
    }
    fence_regs(oacc[0]); fence_regs(oacc[1]);
    if (tid == 0) TL(tk, 2);
#pragma unroll
    for (int m = 0; m < 2; m++) {
        const float l0 = __shfl_sync(0xffffffffu, oacc[m][8], lane & ~3);
        const float l1 = __shfl_sync(0xffffffffu, oacc[m][10], lane & ~3);
        const float r0 = 1.0f / l0, r1 = 1.0f / l1;
        const int row = tb * 128 + m * 64 + warp * 16 + g;
        uint32_t* p0 = (uint32_t*)(g_o + (size_t)row * D_ + head * 16);
        uint32_t* p1 = (uint32_t*)(g_o + (size_t)(row + 8) * D_ + head * 16);
        p0[c] = pack_bf16(oacc[m][0] * r0, oacc[m][1] * r0);
        p1[c] = pack_bf16(oacc[m][2] * r1, oacc[m][3] * r1);
        p0[c + 4] = pack_bf16(oacc[m][4] * r0, oacc[m][5] * r0);
        p1[c + 4] = pack_bf16(oacc[m][6] * r1, oacc[m][7] * r1);
    }
    if (tid == 0) TL(tk, 3);
}

typedef CUresult (*EncodeFn)(CUtensorMap*, CUtensorMapDataType, cuuint32_t, void*, const cuuint64_t*, const cuuint64_t*, const cuuint32_t*,
                             const cuuint32_t*, CUtensorMapInterleave, CUtensorMapSwizzle, CUtensorMapL2promotion, CUtensorMapFloatOOBfill);

EncodeFn get_encode() {
    static EncodeFn fn = nullptr;
    if (!fn) {
        void* p = nullptr;
        cudaDriverEntryPointQueryResult qr;
        cudaGetDriverEntryPoint("cuTensorMapEncodeTiled", &p, cudaEnableDefault, &qr);
        fn = (EncodeFn)p;
    }
    return fn;
}
CUtensorMap map2d(const void* ptr, uint64_t cols, uint64_t rows, uint32_t bc, uint32_t br, CUtensorMapSwizzle sw) {
    CUtensorMap m;
    cuuint64_t gd[2] = {cols, rows}, gs[1] = {cols * 2};
    cuuint32_t bx[2] = {bc, br}, es[2] = {1, 1};
    get_encode()(&m, CU_TENSOR_MAP_DATA_TYPE_BFLOAT16, 2, (void*)ptr, gd, gs, bx, es, CU_TENSOR_MAP_INTERLEAVE_NONE, sw,
                 CU_TENSOR_MAP_L2_PROMOTION_L2_128B, CU_TENSOR_MAP_FLOAT_OOB_FILL_NONE);
    return m;
}
CUtensorMap map3d32(const void* ptr, uint64_t cols, uint64_t rows, uint32_t br, uint32_t nb) {
    CUtensorMap m;
    cuuint64_t gd[3] = {32, rows, cols / 32}, gs[2] = {cols * 2, 64};
    cuuint32_t bx[3] = {32, br, nb}, es[3] = {1, 1, 1};
    get_encode()(&m, CU_TENSOR_MAP_DATA_TYPE_BFLOAT16, 3, (void*)ptr, gd, gs, bx, es, CU_TENSOR_MAP_INTERLEAVE_NONE, CU_TENSOR_MAP_SWIZZLE_64B,
                 CU_TENSOR_MAP_L2_PROMOTION_L2_128B, CU_TENSOR_MAP_FLOAT_OOB_FILL_NONE);
    return m;
}

template <typename... KArgs, typename... Args>
void launch(void (*kern)(KArgs...), int grid, int block, int smem, int cluster, bool pdl, Args... args) {
    cudaLaunchConfig_t cfg = {};
    cfg.gridDim = dim3(grid);
    cfg.blockDim = dim3(block);
    cfg.dynamicSmemBytes = smem;
    cfg.stream = cudaStreamPerThread;
    cudaLaunchAttribute at[2];
    int n = 0;
    if (cluster > 1) { at[n].id = cudaLaunchAttributeClusterDimension; at[n].val.clusterDim.x = cluster; at[n].val.clusterDim.y = 1; at[n].val.clusterDim.z = 1; n++; }
    if (pdl) { at[n].id = cudaLaunchAttributeProgrammaticStreamSerialization; at[n].val.programmaticStreamSerializationAllowed = 1; n++; }
    cfg.attrs = at;
    cfg.numAttrs = n;
    cudaLaunchKernelEx(&cfg, kern, KArgs(args)...);
}

template <typename T> void* sym(const T& s) { void* p = nullptr; cudaGetSymbolAddress(&p, s); return p; }

}

extern "C" void kernel_launch(void* const* d_in, const int* in_sizes, int n_in, void* d_out, int out_size) {
    const __nv_bfloat16* x = (const __nv_bfloat16*)d_in[0];
    const __nv_bfloat16* wq = (const __nv_bfloat16*)d_in[1];
    const __nv_bfloat16* wk = (const __nv_bfloat16*)d_in[2];
    const __nv_bfloat16* wv = (const __nv_bfloat16*)d_in[3];
    const __nv_bfloat16* wo = (const __nv_bfloat16*)d_in[4];
    const __nv_bfloat16* w1 = (const __nv_bfloat16*)d_in[6];
    const __nv_bfloat16* w2 = (const __nv_bfloat16*)d_in[7];

    constexpr int SM_QKV = GemmSmem<64, QKV_STAGES>::TOTAL;
    constexpr int SM_RES = GemmSmem<64, RES_STAGES>::TOTAL;
    constexpr int SM_FFN1 = GemmSmem<224, FFN1_STAGES>::TOTAL;
    cudaFuncSetAttribute(qkv_kernel, cudaFuncAttributeMaxDynamicSharedMemorySize, SM_QKV);
    cudaFuncSetAttribute(res_gemm_kernel<8>, cudaFuncAttributeMaxDynamicSharedMemorySize, SM_RES);
    cudaFuncSetAttribute(ffn1_kernel, cudaFuncAttributeMaxDynamicSharedMemorySize, SM_FFN1);
    cudaFuncSetAttribute(res_gemm_kernel<28>, cudaFuncAttributeMaxDynamicSharedMemorySize, SM_RES);
    cudaFuncSetAttribute(attn_kernel, cudaFuncAttributeMaxDynamicSharedMemorySize, ATT_SMEM);

    void *q = sym(g_q), *o = sym(g_o), *x1 = sym(g_x1), *x2 = sym(g_x2), *x3 = sym(g_x3), *h = sym(g_h);
    float2* stats = (float2*)sym(g_stats);
    const void* xs[5] = {x, x1, x2, x3, d_out};

    const CUtensorMapSwizzle SW128 = CU_TENSOR_MAP_SWIZZLE_128B, SW64 = CU_TENSOR_MAP_SWIZZLE_64B;
    const CUtensorMap mWq = map2d(wq, D_, D_, 64, 64, SW128);
    const CUtensorMap mWk = map2d(wk, 16, D_, 16, 64, CU_TENSOR_MAP_SWIZZLE_32B);
    const CUtensorMap mWv = map2d(wv, 16, D_, 16, 64, CU_TENSOR_MAP_SWIZZLE_32B);
    const CUtensorMap mWo = map2d(wo, D_, D_, 64, 64, SW128);
    const CUtensorMap mW1a = map3d32(w1, F_, D_, 32, 4), mW1b = map3d32(w1, F_, D_, 32, 3);
    const CUtensorMap mW2 = map2d(w2, D_, F_, 64, 64, SW128);
    const CUtensorMap mQ = map2d(q, D_, S_, 64, 64, SW128);
    const CUtensorMap mO = map2d(o, D_, S_, 64, 64, SW128);
    const CUtensorMap mHst = map2d(h, F_, S_, 32, 16, SW64);
    const CUtensorMap mHld = map2d(h, F_, S_, 64, 64, SW128);
    CUtensorMap mX[5], mX32[2];
    for (int i = 0; i < 5; i++) mX[i] = map2d(xs[i], D_, S_, 64, 64, SW128);
    mX32[0] = map2d(x1, D_, S_, 32, 64, SW64);
    mX32[1] = map2d(x3, D_, S_, 32, 64, SW64);

    launch(prep_kernel, PREP_CS_CTAS + PREP_STAT_CTAS, 256, 0, 1, false, x, wq, wk, wv, wo, w1, w2);
    for (int layer = 0; layer < 2; layer++) {
        const int xi = layer * 2;
        GemmParams p;
        p.stats_in = stats + (size_t)xi * 8 * S_; p.stats_out = nullptr; p.wait_in_epilogue = layer == 0; p.tk = 1 + 5 * layer;
        launch(qkv_kernel, 144, 288, SM_QKV, 2, true, mX[xi], mWq, mWk, mWv, mQ, p);
        launch(attn_kernel, 128, 512, ATT_SMEM, 1, true, 2 + 5 * layer);
        p.stats_in = nullptr; p.stats_out = stats + (size_t)(xi + 1) * 8 * S_; p.wait_in_epilogue = 0; p.tk = 3 + 5 * layer;
        launch(res_gemm_kernel<8>, 128, 288, SM_RES, 2, true, mO, mWo, mX[xi], mX[xi + 1], p);
        p.stats_in = stats + (size_t)(xi + 1) * 8 * S_; p.stats_out = nullptr; p.tk = 4 + 5 * layer;
        launch(ffn1_kernel, 128, 288, SM_FFN1, 2, true, mX32[layer], mW1a, mW1b, mHst, p);
        p.stats_in = nullptr; p.stats_out = layer == 0 ? stats + (size_t)2 * 8 * S_ : nullptr; p.tk = 5 + 5 * layer;
        launch(res_gemm_kernel<28>, 128, 288, SM_RES, 2, true, mHld, mW2, mX[xi + 1], mX[xi + 2], p);
    }
}
```

```cpp
#include <cuda_runtime.h>
#include <cuda_bf16.h>
#include <cuda.h>
#include <stdint.h>

namespace {

constexpr int S_ = 2048, D_ = 512, H_ = 32, F_ = 1792;

__device__ __align__(1024) __nv_bfloat16 g_q[S_ * D_];
__device__ __align__(1024) __nv_bfloat16 g_o[S_ * D_];
__device__ __align__(1024) __nv_bfloat16 g_x1[S_ * D_];
__device__ __align__(1024) __nv_bfloat16 g_x2[S_ * D_];
__device__ __align__(1024) __nv_bfloat16 g_x3[S_ * D_];
__device__ __align__(1024) __nv_bfloat16 g_h[S_ * F_];
__device__ __align__(1024) uint8_t g_kimg[S_ * 32];
__device__ __align__(1024) uint8_t g_vimg[(S_ / 16) * 768];
__device__ __align__(1024) float2 g_stats[4][8 * S_];
__device__ __align__(16) float g_cs_q[D_];
__device__ __align__(16) float g_cs_kv[32];
__device__ __align__(16) float g_cs_1[F_];
__device__ __align__(16) float g_kvmax[32];

#define TL(k, slot)

__device__ __forceinline__ uint32_t smem_u32(const void* p) { return (uint32_t)__cvta_generic_to_shared(p); }
__device__ __forceinline__ void mbar_init(uint32_t bar, uint32_t cnt) {
    asm volatile("mbarrier.init.shared::cta.b64 [%0], %1;" ::"r"(bar), "r"(cnt));
}
__device__ __forceinline__ void mbar_expect_tx(uint32_t bar, uint32_t bytes) {
    asm volatile("mbarrier.arrive.expect_tx.shared::cta.b64 _, [%0], %1;" ::"r"(bar), "r"(bytes) : "memory");
}
__device__ __forceinline__ void mbar_arrive(uint32_t bar) {
    asm volatile("mbarrier.arrive.shared::cta.b64 _, [%0];" ::"r"(bar) : "memory");
}
__device__ __forceinline__ void mbar_arrive_remote(uint32_t bar, uint32_t cta) {
    asm volatile("{\n.reg .b32 ra;\nmapa.shared::cluster.u32 ra, %0, %1;\nmbarrier.arrive.shared::cluster.b64 _, [ra];\n}" ::"r"(bar), "r"(cta) : "memory");
}
__device__ __forceinline__ void mbar_wait(uint32_t bar, uint32_t parity) {
    asm volatile("{\n.reg .pred p;\nWAIT_%=:\nmbarrier.try_wait.parity.shared::cta.b64 p, [%0], %1;\n@p bra DONE_%=;\nbra WAIT_%=;\nDONE_%=:\n}" ::"r"(bar), "r"(parity) : "memory");
}
__device__ __forceinline__ void bulk_load(uint32_t dst, const void* src, uint32_t bytes, uint32_t bar) {
    asm volatile("cp.async.bulk.shared::cluster.global.mbarrier::complete_tx::bytes [%0], [%1], %2, [%3];" ::"r"(dst), "l"(src), "r"(bytes), "r"(bar) : "memory");
}
__device__ __forceinline__ void tma2d(uint32_t dst, const CUtensorMap* m, int c0, int c1, uint32_t bar) {
    asm volatile("cp.async.bulk.tensor.2d.shared::cluster.global.mbarrier::complete_tx::bytes [%0], [%1, {%3, %4}], [%2];" ::"r"(dst), "l"(m), "r"(bar), "r"(c0), "r"(c1) : "memory");
}
__device__ __forceinline__ void tma2d_mc(uint32_t dst, const CUtensorMap* m, int c0, int c1, uint32_t bar, uint16_t mask) {
    asm volatile("cp.async.bulk.tensor.2d.shared::cluster.global.mbarrier::complete_tx::bytes.multicast::cluster [%0], [%1, {%3, %4}], [%2], %5;" ::"r"(dst), "l"(m), "r"(bar), "r"(c0), "r"(c1), "h"(mask) : "memory");
}
__device__ __forceinline__ void tma3d(uint32_t dst, const CUtensorMap* m, int c0, int c1, int c2, uint32_t bar) {
    asm volatile("cp.async.bulk.tensor.3d.shared::cluster.global.mbarrier::complete_tx::bytes [%0], [%1, {%3, %4, %5}], [%2];" ::"r"(dst), "l"(m), "r"(bar), "r"(c0), "r"(c1), "r"(c2) : "memory");
}
__device__ __forceinline__ void tma3d_mc(uint32_t dst, const CUtensorMap* m, int c0, int c1, int c2, uint32_t bar, uint16_t mask) {
    asm volatile("cp.async.bulk.tensor.3d.shared::cluster.global.mbarrier::complete_tx::bytes.multicast::cluster [%0], [%1, {%3, %4, %5}], [%2], %6;" ::"r"(dst), "l"(m), "r"(bar), "r"(c0), "r"(c1), "r"(c2), "h"(mask) : "memory");
}
__device__ __forceinline__ void tma2d_store(const CUtensorMap* m, uint32_t src, int c0, int c1) {
    asm volatile("cp.async.bulk.tensor.2d.global.shared::cta.bulk_group [%0, {%2, %3}], [%1];" ::"l"(m), "r"(src), "r"(c0), "r"(c1) : "memory");
}
__device__ __forceinline__ void tma3d_store(const CUtensorMap* m, uint32_t src, int c0, int c1, int c2) {
    asm volatile("cp.async.bulk.tensor.3d.global.shared::cta.bulk_group [%0, {%2, %3, %4}], [%1];" ::"l"(m), "r"(src), "r"(c0), "r"(c1), "r"(c2) : "memory");
}
__device__ __forceinline__ void bulk_commit() { asm volatile("cp.async.bulk.commit_group;" ::: "memory"); }
__device__ __forceinline__ void bulk_wait_read() { asm volatile("cp.async.bulk.wait_group.read 0;" ::: "memory"); }
__device__ __forceinline__ void prefetch_tmap(const CUtensorMap* m) { asm volatile("prefetch.tensormap [%0];" ::"l"(m) : "memory"); }
__device__ __forceinline__ void fence_async_smem() { asm volatile("fence.proxy.async.shared::cta;" ::: "memory"); }
__device__ __forceinline__ void fence_mbar_init() { asm volatile("fence.mbarrier_init.release.cluster;" ::: "memory"); }
__device__ __forceinline__ void cluster_sync() { asm volatile("barrier.cluster.arrive.release.aligned;\nbarrier.cluster.wait.acquire.aligned;" ::: "memory"); }
__device__ __forceinline__ uint32_t cluster_rank() { uint32_t r; asm volatile("mov.u32 %0, %%cluster_ctarank;" : "=r"(r)); return r; }
__device__ __forceinline__ void pdl_wait() { asm volatile("griddepcontrol.wait;" ::: "memory"); }
__device__ __forceinline__ void pdl_launch() { asm volatile("griddepcontrol.launch_dependents;" ::: "memory"); }
__device__ __forceinline__ void named_bar(int id, int n) { asm volatile("bar.sync %0, %1;" ::"r"(id), "r"(n) : "memory"); }

__device__ __forceinline__ void wg_fence() { asm volatile("wgmma.fence.sync.aligned;" ::: "memory"); }
__device__ __forceinline__ void wg_commit() { asm volatile("wgmma.commit_group.sync.aligned;" ::: "memory"); }
template <int N> __device__ __forceinline__ void wg_wait() { asm volatile("wgmma.wait_group.sync.aligned %0;" ::"n"(N) : "memory"); }
template <int N> __device__ __forceinline__ void fence_regs(float (&d)[N]) {
#pragma unroll
    for (int i = 0; i < N; i++) asm volatile("" : "+f"(d[i])::"memory");
}
__device__ __forceinline__ uint64_t mkdesc(uint32_t addr, uint32_t lbo, uint32_t sbo, uint32_t swz) {
    uint64_t d = 0;
    d |= (uint64_t)((addr & 0x3FFFF) >> 4);
    d |= (uint64_t)((lbo & 0x3FFFF) >> 4) << 16;
    d |= (uint64_t)((sbo & 0x3FFFF) >> 4) << 32;
    d |= (uint64_t)swz << 62;
    return d;
}
__device__ __forceinline__ void ldsm_x4(uint32_t& r0, uint32_t& r1, uint32_t& r2, uint32_t& r3, uint32_t addr) {
    asm volatile("ldmatrix.sync.aligned.m8n8.x4.shared.b16 {%0,%1,%2,%3}, [%4];" : "=r"(r0), "=r"(r1), "=r"(r2), "=r"(r3) : "r"(addr) : "memory");
}
__device__ __forceinline__ void stsm_x4(uint32_t addr, uint32_t r0, uint32_t r1, uint32_t r2, uint32_t r3) {
    asm volatile("stmatrix.sync.aligned.m8n8.x4.shared.b16 [%0], {%1,%2,%3,%4};" ::"r"(addr), "r"(r0), "r"(r1), "r"(r2), "r"(r3) : "memory");
}
__device__ __forceinline__ uint32_t pack_bf16(float lo, float hi) {
    uint32_t r;
    asm("cvt.rn.bf16x2.f32 %0, %1, %2;" : "=r"(r) : "f"(hi), "f"(lo));
    return r;
}
__device__ __forceinline__ float bf_lo(uint32_t v) { return __uint_as_float(v << 16); }
__device__ __forceinline__ float bf_hi(uint32_t v) { return __uint_as_float(v & 0xFFFF0000u); }

#define WG_REGS_4(o) "+f"(d[o]), "+f"(d[o + 1]), "+f"(d[o + 2]), "+f"(d[o + 3])
#define WG_REGS_8(o) WG_REGS_4(o), WG_REGS_4(o + 4)
#define WG_REGS_16(o) WG_REGS_8(o), WG_REGS_8(o + 8)
#define WG_REGS_32(o) WG_REGS_16(o), WG_REGS_16(o + 16)

__device__ __forceinline__ void wgmma_ss_n16_tb(float (&d)[8], uint64_t dA, uint64_t dB, int sc) {
    asm volatile("{\n.reg .pred p;\nsetp.ne.b32 p, %10, 0;\n"
                 "wgmma.mma_async.sync.aligned.m64n16k16.f32.bf16.bf16 "
                 "{%0,%1,%2,%3,%4,%5,%6,%7}, %8, %9, p, 1, 1, 0, 1;\n}\n"
                 : WG_REGS_8(0) : "l"(dA), "l"(dB), "r"(sc));
}
__device__ __forceinline__ void wgmma_ss_n32_tb(float (&d)[16], uint64_t dA, uint64_t dB, int sc) {
    asm volatile("{\n.reg .pred p;\nsetp.ne.b32 p, %18, 0;\n"
                 "wgmma.mma_async.sync.aligned.m64n32k16.f32.bf16.bf16 "
                 "{%0,%1,%2,%3,%4,%5,%6,%7,%8,%9,%10,%11,%12,%13,%14,%15}, %16, %17, p, 1, 1, 0, 1;\n}\n"
                 : WG_REGS_16(0) : "l"(dA), "l"(dB), "r"(sc));
}
__device__ __forceinline__ void wgmma_ss_n64_tb(float (&d)[32], uint64_t dA, uint64_t dB, int sc) {
    asm volatile("{\n.reg .pred p;\nsetp.ne.b32 p, %34, 0;\n"
                 "wgmma.mma_async.sync.aligned.m64n64k16.f32.bf16.bf16 "
                 "{%0,%1,%2,%3,%4,%5,%6,%7,%8,%9,%10,%11,%12,%13,%14,%15,%16,%17,%18,%19,%20,%21,%22,%23,%24,%25,%26,%27,%28,%29,%30,%31}, "
                 "%32, %33, p, 1, 1, 0, 1;\n}\n"
                 : WG_REGS_32(0) : "l"(dA), "l"(dB), "r"(sc));
}
__device__ __forceinline__ void wgmma_ss_n224_tb(float (&d)[112], uint64_t dA, uint64_t dB, int sc) {
    asm volatile("{\n.reg .pred p;\nsetp.ne.b32 p, %114, 0;\n"
                 "wgmma.mma_async.sync.aligned.m64n224k16.f32.bf16.bf16 "
                 "{%0,%1,%2,%3,%4,%5,%6,%7,%8,%9,%10,%11,%12,%13,%14,%15,%16,%17,%18,%19,%20,%21,%22,%23,%24,%25,%26,%27,%28,%29,%30,%31,"
                 "%32,%33,%34,%35,%36,%37,%38,%39,%40,%41,%42,%43,%44,%45,%46,%47,%48,%49,%50,%51,%52,%53,%54,%55,%56,%57,%58,%59,%60,%61,%62,%63,"
                 "%64,%65,%66,%67,%68,%69,%70,%71,%72,%73,%74,%75,%76,%77,%78,%79,%80,%81,%82,%83,%84,%85,%86,%87,%88,%89,%90,%91,%92,%93,%94,%95,"
                 "%96,%97,%98,%99,%100,%101,%102,%103,%104,%105,%106,%107,%108,%109,%110,%111}, "
                 "%112, %113, p, 1, 1, 0, 1;\n}\n"
                 : WG_REGS_32(0), WG_REGS_32(32), WG_REGS_32(64), WG_REGS_16(96) : "l"(dA), "l"(dB), "r"(sc));
}
template <int BN> __device__ __forceinline__ void wgmma_ss_tb(float (&d)[BN / 2], uint64_t dA, uint64_t dB, int sc) {
    if constexpr (BN == 32) wgmma_ss_n32_tb(d, dA, dB, sc);
    else if constexpr (BN == 64) wgmma_ss_n64_tb(d, dA, dB, sc);
    else wgmma_ss_n224_tb(d, dA, dB, sc);
}
__device__ __forceinline__ void wgmma_rs_n64_z(float (&d)[32], uint32_t a0, uint32_t a1, uint32_t a2, uint32_t a3, uint64_t dB) {
    asm volatile("{\n.reg .pred p;\nsetp.ne.b32 p, 0, 0;\n"
                 "wgmma.mma_async.sync.aligned.m64n64k16.f32.bf16.bf16 "
                 "{%0,%1,%2,%3,%4,%5,%6,%7,%8,%9,%10,%11,%12,%13,%14,%15,%16,%17,%18,%19,%20,%21,%22,%23,%24,%25,%26,%27,%28,%29,%30,%31}, "
                 "{%32,%33,%34,%35}, %36, p, 1, 1, 0;\n}\n"
                 : "=f"(d[0]), "=f"(d[1]), "=f"(d[2]), "=f"(d[3]), "=f"(d[4]), "=f"(d[5]), "=f"(d[6]), "=f"(d[7]),
                   "=f"(d[8]), "=f"(d[9]), "=f"(d[10]), "=f"(d[11]), "=f"(d[12]), "=f"(d[13]), "=f"(d[14]), "=f"(d[15]),
                   "=f"(d[16]), "=f"(d[17]), "=f"(d[18]), "=f"(d[19]), "=f"(d[20]), "=f"(d[21]), "=f"(d[22]), "=f"(d[23]),
                   "=f"(d[24]), "=f"(d[25]), "=f"(d[26]), "=f"(d[27]), "=f"(d[28]), "=f"(d[29]), "=f"(d[30]), "=f"(d[31])
                 : "r"(a0), "r"(a1), "r"(a2), "r"(a3), "l"(dB));
}
__device__ __forceinline__ void wgmma_rs_n24_tb(float (&d)[12], uint32_t a0, uint32_t a1, uint32_t a2, uint32_t a3, uint64_t dB) {
    asm volatile("{\n.reg .pred p;\nsetp.eq.b32 p, 0, 0;\n"
                 "wgmma.mma_async.sync.aligned.m64n24k16.f32.bf16.bf16 "
                 "{%0,%1,%2,%3,%4,%5,%6,%7,%8,%9,%10,%11}, {%12,%13,%14,%15}, %16, p, 1, 1, 1;\n}\n"
                 : WG_REGS_8(0), WG_REGS_4(8) : "r"(a0), "r"(a1), "r"(a2), "r"(a3), "l"(dB));
}

constexpr int PREP_STAT_CTAS = S_ / 8;
constexpr int PREP_CS_CTAS = 8 + 1 + F_ / 64;

__global__ void __launch_bounds__(256) prep_kernel(const __nv_bfloat16* __restrict__ x, const __nv_bfloat16* __restrict__ wq,
                                                   const __nv_bfloat16* __restrict__ wk, const __nv_bfloat16* __restrict__ wv,
                                                   const __nv_bfloat16* __restrict__ wo, const __nv_bfloat16* __restrict__ w1,
                                                   const __nv_bfloat16* __restrict__ w2) {
    pdl_launch();
    const int tid = threadIdx.x;
    if (tid == 0) { TL(0, 0); TL(0, 1); }
    if (blockIdx.x < PREP_CS_CTAS) {
        __shared__ float red[32][65];
        const int b = blockIdx.x;
        const int rg = tid >> 3, c8 = tid & 7;
        float acc[8];
#pragma unroll
        for (int i = 0; i < 8; i++) acc[i] = 0.f;
        const __nv_bfloat16* base;
        int ld;
        bool active = true;
        if (b < 8) { base = wq + b * 64 + c8 * 8; ld = D_; }
        else if (b == 8) { base = (c8 < 2 ? wk + c8 * 8 : wv + (c8 - 2) * 8); ld = 16; active = c8 < 4; }
        else { base = w1 + (b - 9) * 64 + c8 * 8; ld = F_; }
        if (active) {
            uint4 v[16];
#pragma unroll
            for (int i = 0; i < 16; i++) v[i] = __ldg((const uint4*)(base + (size_t)(rg + 32 * i) * ld));
#pragma unroll
            for (int i = 0; i < 16; i++) {
                acc[0] += bf_lo(v[i].x); acc[1] += bf_hi(v[i].x); acc[2] += bf_lo(v[i].y); acc[3] += bf_hi(v[i].y);
                acc[4] += bf_lo(v[i].z); acc[5] += bf_hi(v[i].z); acc[6] += bf_lo(v[i].w); acc[7] += bf_hi(v[i].w);
            }
        }
#pragma unroll
        for (int i = 0; i < 8; i++) red[rg][c8 * 8 + i] = acc[i];
        __syncthreads();
        if (tid < 64) {
            float s = 0.f;
#pragma unroll
            for (int i = 0; i < 32; i++) s += red[i][tid];
            if (b < 8) g_cs_q[b * 64 + tid] = s;
            else if (b == 8) { if (tid < 32) g_cs_kv[tid] = s; }
            else g_cs_1[(b - 9) * 64 + tid] = s;
        }
    } else {
        const int cb = blockIdx.x - PREP_CS_CTAS;
        if (tid < 72) {
            const int line = cb * 72 + tid;
            const char* p = line < 4096 ? (const char*)wo + (size_t)line * 128 : (const char*)w2 + (size_t)(line - 4096) * 128;
            asm volatile("prefetch.global.L2 [%0];" ::"l"(p));
        }
        const int warp = tid >> 5, lane = tid & 31;
        const int row = cb * 8 + warp;
        const uint4* p = (const uint4*)(x + (size_t)row * D_ + lane * 16);
        const uint4 a = __ldg(p), b = __ldg(p + 1);
        float v[16] = {bf_lo(a.x), bf_hi(a.x), bf_lo(a.y), bf_hi(a.y), bf_lo(a.z), bf_hi(a.z), bf_lo(a.w), bf_hi(a.w),
                       bf_lo(b.x), bf_hi(b.x), bf_lo(b.y), bf_hi(b.y), bf_lo(b.z), bf_hi(b.z), bf_lo(b.w), bf_hi(b.w)};
        float s = 0.f;
#pragma unroll
        for (int i = 0; i < 16; i++) s += v[i];
        s += __shfl_xor_sync(0xffffffffu, s, 1);
        s += __shfl_xor_sync(0xffffffffu, s, 2);
        const float mean = s * (1.f / 64.f);
        float m2 = 0.f;
#pragma unroll
        for (int i = 0; i < 16; i++) { const float d = v[i] - mean; m2 += d * d; }
        m2 += __shfl_xor_sync(0xffffffffu, m2, 1);
        m2 += __shfl_xor_sync(0xffffffffu, m2, 2);
        if ((lane & 3) == 0) g_stats[0][(lane >> 2) * S_ + row] = make_float2(mean, m2);
    }
    if (tid == 0) { TL(0, 2); TL(0, 3); }
}

enum { EPI_QKV = 0, EPI_RES = 1, EPI_FFN1 = 2 };

struct GemmParams {
    const float2* stats_in;
    float2* stats_out;
    int wait_in_epilogue;
    int tk;
};

template <int BN> struct Geo;
template <> struct Geo<64> {
    static constexpr int BK = 64, A_BYTES = 128 * 128, A_SWZ = 1, A_SBO = 1024;
    static constexpr int B_BYTES = 64 * 128, B_SWZ = 1, B_LBO = 8192, B_SBO = 1024, B_KSTEP = 2048;
};
template <> struct Geo<224> {
    static constexpr int BK = 32, A_BYTES = 128 * 64, A_SWZ = 2, A_SBO = 512;
    static constexpr int B_BYTES = 7 * 32 * 64, B_SWZ = 2, B_LBO = 2048, B_SBO = 512, B_KSTEP = 1024;
};

template <int BN, int STAGES, int EPI> struct GemmSmem {
    static constexpr int XB_OFF = Geo<BN>::A_BYTES + Geo<BN>::B_BYTES;
    static constexpr int STAGE = XB_OFF + (EPI == EPI_QKV ? 2048 : 0);
    static constexpr int AUX_OFF = STAGES * STAGE;
    static constexpr int TOTAL = AUX_OFF + 1024;
};

__device__ __forceinline__ void load_row_stats(const float2* __restrict__ st, int row0, int c, float& mean0, float& rstd0, float& mean1, float& rstd1) {
    const float2 a0 = st[(2 * c) * S_ + row0], a1 = st[(2 * c + 1) * S_ + row0];
    const float2 b0 = st[(2 * c) * S_ + row0 + 8], b1 = st[(2 * c + 1) * S_ + row0 + 8];
    float sa = a0.x + a1.x, sb = b0.x + b1.x;
    sa += __shfl_xor_sync(0xffffffffu, sa, 1); sa += __shfl_xor_sync(0xffffffffu, sa, 2);
    sb += __shfl_xor_sync(0xffffffffu, sb, 1); sb += __shfl_xor_sync(0xffffffffu, sb, 2);
    mean0 = sa * 0.125f; mean1 = sb * 0.125f;
    float ma = a0.y + a1.y + 64.f * ((a0.x - mean0) * (a0.x - mean0) + (a1.x - mean0) * (a1.x - mean0));
    float mb = b0.y + b1.y + 64.f * ((b0.x - mean1) * (b0.x - mean1) + (b1.x - mean1) * (b1.x - mean1));
    ma += __shfl_xor_sync(0xffffffffu, ma, 1); ma += __shfl_xor_sync(0xffffffffu, ma, 2);
    mb += __shfl_xor_sync(0xffffffffu, mb, 1); mb += __shfl_xor_sync(0xffffffffu, mb, 2);
    rstd0 = 1.0f / sqrtf(ma * (1.f / 512.f) + 1e-5f);
    rstd1 = 1.0f / sqrtf(mb * (1.f / 512.f) + 1e-5f);
}

template <int BN, int KB, int STAGES, int EPI, int MC>
__device__ __forceinline__ void gemm_body(const CUtensorMap* mapA, const CUtensorMap* mapB, const CUtensorMap* mapB2, const CUtensorMap* mapR,
                                          const CUtensorMap* mapC, const GemmParams& prm, int tile_m, int tile_n, uint8_t* smem_raw) {
    using SM = GemmSmem<BN, STAGES, EPI>;
    using G = Geo<BN>;
    pdl_launch();
    const uint32_t sbase = smem_u32(smem_raw);
    if (sbase & 1023) __trap();
    uint8_t* sgen = smem_raw;
    const uint32_t bar_full = sbase + SM::AUX_OFF, bar_empty = bar_full + 8 * STAGES;
    float* s_cs = (float*)(sgen + SM::AUX_OFF + 128);
    float* s_red = (float*)(sgen + SM::AUX_OFF + 640);
    const bool xkv = EPI == EPI_QKV && tile_n < 2;
    const int tid = threadIdx.x, warp = tid >> 5, lane = tid & 31;
    const uint32_t rank = MC ? cluster_rank() : 0;
    if (tid == 0) TL(prm.tk, 0);

    if (warp == 8 && lane == 0) {
        prefetch_tmap(mapB); prefetch_tmap(mapA); prefetch_tmap(mapC);
        for (int s = 0; s < STAGES; s++) { mbar_init(bar_full + 8 * s, 1); mbar_init(bar_empty + 8 * s, MC ? 4 : 2); }
        fence_mbar_init();
    }
    __syncthreads();
    if (MC) cluster_sync();

    const int m0 = tile_m * 128, n0 = tile_n * BN;
    if (warp == 8) {
        if (lane == 0) {
            const uint32_t STAGE_TX = G::A_BYTES + G::B_BYTES + (xkv ? 2048 : 0);
            auto loadB = [&](int kb, int s) {
                const uint32_t dst = sbase + s * SM::STAGE + G::A_BYTES, bar = bar_full + 8 * s;
                if constexpr (BN == 64) {
                    tma2d(dst, mapB, n0, kb * 64, bar);
                    if (xkv) tma2d(dst + G::B_BYTES, mapB2, 0, kb * 64, bar);
                } else {
                    if (rank == 0) tma3d_mc(dst, mapB, 0, kb * 32, tile_n * 7, bar, 3);
                    else tma3d_mc(dst + 4 * 2048, mapB2, 0, kb * 32, tile_n * 7 + 4, bar, 3);
                }
            };
            auto loadA = [&](int kb, int s) {
                const uint32_t dst = sbase + s * SM::STAGE, bar = bar_full + 8 * s;
                if constexpr (MC == 1) tma2d_mc(dst + rank * (G::A_BYTES / 2), mapA, kb * G::BK, m0 + rank * 64, bar, 3);
                else { tma2d(dst, mapA, kb * G::BK, m0, bar); tma2d(dst + G::A_BYTES / 2, mapA, kb * G::BK, m0 + 64, bar); }
            };
            constexpr int PRE = STAGES < KB ? STAGES : KB;
            for (int kb = 0; kb < PRE; kb++) { mbar_expect_tx(bar_full + 8 * kb, STAGE_TX); loadB(kb, kb); }
            if (!prm.wait_in_epilogue) pdl_wait();
            for (int kb = 0; kb < PRE; kb++) loadA(kb, kb);
            int s = PRE % STAGES, ph = (PRE / STAGES) & 1;
            for (int kb = PRE; kb < KB; kb++) {
                mbar_wait(bar_empty + 8 * s, ph ^ 1);
                mbar_expect_tx(bar_full + 8 * s, STAGE_TX);
                loadB(kb, s);
                loadA(kb, s);
                if (++s == STAGES) { s = 0; ph ^= 1; }
            }
            if constexpr (EPI == EPI_RES) {
                mbar_wait(bar_empty + 8 * s, ph ^ 1);
                mbar_expect_tx(bar_full + 8 * s, 16384);
                tma2d(sbase + s * SM::STAGE, mapR, n0, m0, bar_full + 8 * s);
                tma2d(sbase + s * SM::STAGE + 8192, mapR, n0, m0 + 64, bar_full + 8 * s);
            }
        }
    } else {
        const int wg = warp >> 2, g = lane >> 2, c = lane & 3;
        float acc[BN / 2];
        float acx[8];
        const uint64_t dX0 = mkdesc(sbase + SM::XB_OFF, 16, 256, 3);
        const uint64_t dA0 = mkdesc(sbase + wg * (G::A_BYTES / 2), 16, G::A_SBO, G::A_SWZ);
        const uint64_t dB0 = mkdesc(sbase + G::A_BYTES, G::B_LBO, G::B_SBO, G::B_SWZ);
        int s = 0, ph = 0;
#pragma unroll 1
        for (int kb = 0; kb < KB; kb++) {
            mbar_wait(bar_full + 8 * s, ph);
            const uint64_t dA = dA0 + (uint64_t)(s * (SM::STAGE >> 4)), dB = dB0 + (uint64_t)(s * (SM::STAGE >> 4));
            wg_fence();
#pragma unroll
            for (int k = 0; k < G::BK / 16; k++) wgmma_ss_tb<BN>(acc, dA + (uint64_t)(k * 2), dB + (uint64_t)(k * (G::B_KSTEP >> 4)), (kb | k) != 0);
            if constexpr (EPI == EPI_QKV) {
                if (xkv) {
                    const uint64_t dX = dX0 + (uint64_t)(s * (SM::STAGE >> 4));
#pragma unroll
                    for (int k = 0; k < 4; k++) wgmma_ss_n16_tb(acx, dA + (uint64_t)(k * 2), dX + (uint64_t)(k * 32), (kb | k) != 0);
                }
            }
            wg_commit();
            if constexpr (BN <= 64) {
                wg_wait<0>();
                if ((tid & 127) == 0) {
                    if (MC) { mbar_arrive_remote(bar_empty + 8 * s, 0); mbar_arrive_remote(bar_empty + 8 * s, 1); }
                    else mbar_arrive(bar_empty + 8 * s);
                }
            } else if (kb > 0) {
                wg_wait<1>();
                const int sp = s == 0 ? STAGES - 1 : s - 1;
                if ((tid & 127) == 0) {
                    if (MC) { mbar_arrive_remote(bar_empty + 8 * sp, 0); mbar_arrive_remote(bar_empty + 8 * sp, 1); }
                    else mbar_arrive(bar_empty + 8 * sp);
                }
            }
            if (++s == STAGES) { s = 0; ph ^= 1; }
        }
        pdl_wait();
        const int rloc = wg * 64 + (warp & 3) * 16 + g;
        const int row0 = m0 + rloc;
        float mean0 = 0.f, rstd0 = 1.f, mean1 = 0.f, rstd1 = 1.f;
        if constexpr (EPI != EPI_RES) {
            load_row_stats(prm.stats_in, row0, c, mean0, rstd0, mean1, rstd1);
            const float* cs = EPI == EPI_FFN1 ? g_cs_1 + n0 : g_cs_q + n0;
            if (tid < BN) s_cs[tid] = cs[tid];
        }
        wg_wait<0>();
        fence_regs(acc);
        if (tid == 0) TL(prm.tk, 2);
        if constexpr (EPI != EPI_RES) named_bar(1, 256);

        if constexpr (EPI == EPI_QKV) {
            if (xkv) {
                fence_regs(acx);
                const float rm0 = rstd0 * mean0, rm1 = rstd1 * mean1;
                float n0s = 0.f, n1s = 0.f, vmax = 0.f;
#pragma unroll
                for (int j = 0; j < 2; j++) {
                    const float2 cs2 = *(const float2*)(g_cs_kv + tile_n * 16 + 8 * j + 2 * c);
                    const uint32_t u0 = pack_bf16(acx[4 * j] * rstd0 - rm0 * cs2.x, acx[4 * j + 1] * rstd0 - rm0 * cs2.y);
                    const uint32_t u1 = pack_bf16(acx[4 * j + 2] * rstd1 - rm1 * cs2.x, acx[4 * j + 3] * rstd1 - rm1 * cs2.y);
                    n0s += bf_lo(u0) * bf_lo(u0) + bf_hi(u0) * bf_hi(u0);
                    n1s += bf_lo(u1) * bf_lo(u1) + bf_hi(u1) * bf_hi(u1);
                    vmax = fmaxf(vmax, fmaxf(fmaxf(fabsf(bf_lo(u0)), fabsf(bf_hi(u0))), fmaxf(fabsf(bf_lo(u1)), fabsf(bf_hi(u1)))));
                    if (tile_n == 0) {
                        *(uint32_t*)(g_kimg + (row0 >> 3) * 256 + j * 128 + g * 16 + c * 4) = u0;
                        *(uint32_t*)(g_kimg + ((row0 + 8) >> 3) * 256 + j * 128 + g * 16 + c * 4) = u1;
                    } else {
                        uint8_t* vb = g_vimg + (row0 >> 4) * 768 + j * 256 + g * 16 + c * 4;
                        *(uint32_t*)(vb) = u0;
                        *(uint32_t*)(vb + 128) = u1;
                    }
                }
                if (tile_n == 1) {
                    uint8_t* vb = g_vimg + (row0 >> 4) * 768 + 512 + g * 16 + c * 4;
                    const uint32_t one = c == 0 ? 0x00003F80u : 0u;
                    *(uint32_t*)(vb) = one;
                    *(uint32_t*)(vb + 128) = one;
                }
                n0s += __shfl_xor_sync(0xffffffffu, n0s, 1); n0s += __shfl_xor_sync(0xffffffffu, n0s, 2);
                n1s += __shfl_xor_sync(0xffffffffu, n1s, 1); n1s += __shfl_xor_sync(0xffffffffu, n1s, 2);
                float km = tile_n == 0 ? fmaxf(n0s, n1s) : vmax;
                if (!(n0s + n1s < INFINITY)) km = INFINITY;
#pragma unroll
                for (int o = 1; o < 32; o <<= 1) km = fmaxf(km, __shfl_xor_sync(0xffffffffu, km, o));
                if (lane == 0) s_red[warp] = km;
                named_bar(1, 256);
                if (tid == 0) {
                    float a = 0.f;
                    for (int i = 0; i < 8; i++) a = fmaxf(a, s_red[i]);
                    g_kvmax[tile_n * 16 + tile_m] = a;
                }
            }
        }
        if constexpr (BN == 64) {
            const uint32_t stile = sbase + (EPI == EPI_RES ? s * SM::STAGE : 0);
            const int mrow = wg * 64 + (warp & 3) * 16 + (lane & 7) + ((lane >> 3) & 1) * 8;
            const uint32_t rbase = stile + mrow * 128;
            if constexpr (EPI == EPI_RES) {
                mbar_wait(bar_full + 8 * s, ph);
                float s0 = 0.f, s1 = 0.f;
#pragma unroll
                for (int jj = 0; jj < 4; jj++) {
                    uint32_t r0, r1, r2, r3;
                    const uint32_t addr = rbase + (((2 * jj + (lane >> 4)) ^ (mrow & 7)) << 4);
                    ldsm_x4(r0, r1, r2, r3, addr);
                    const uint32_t u0 = pack_bf16(acc[8 * jj] + bf_lo(r0), acc[8 * jj + 1] + bf_hi(r0));
                    const uint32_t u1 = pack_bf16(acc[8 * jj + 2] + bf_lo(r1), acc[8 * jj + 3] + bf_hi(r1));
                    const uint32_t u2 = pack_bf16(acc[8 * jj + 4] + bf_lo(r2), acc[8 * jj + 5] + bf_hi(r2));
                    const uint32_t u3 = pack_bf16(acc[8 * jj + 6] + bf_lo(r3), acc[8 * jj + 7] + bf_hi(r3));
                    stsm_x4(addr, u0, u1, u2, u3);
                    acc[8 * jj] = bf_lo(u0); acc[8 * jj + 1] = bf_hi(u0); acc[8 * jj + 4] = bf_lo(u2); acc[8 * jj + 5] = bf_hi(u2);
                    acc[8 * jj + 2] = bf_lo(u1); acc[8 * jj + 3] = bf_hi(u1); acc[8 * jj + 6] = bf_lo(u3); acc[8 * jj + 7] = bf_hi(u3);
                    s0 += (acc[8 * jj] + acc[8 * jj + 1]) + (acc[8 * jj + 4] + acc[8 * jj + 5]);
                    s1 += (acc[8 * jj + 2] + acc[8 * jj + 3]) + (acc[8 * jj + 6] + acc[8 * jj + 7]);
                }
                fence_async_smem();
                named_bar(2 + wg, 128);
                if ((tid & 127) == 0) { tma2d_store(mapC, stile + wg * 8192, n0, m0 + wg * 64); bulk_commit(); }
                if (prm.stats_out) {
                    s0 += __shfl_xor_sync(0xffffffffu, s0, 1); s0 += __shfl_xor_sync(0xffffffffu, s0, 2);
                    s1 += __shfl_xor_sync(0xffffffffu, s1, 1); s1 += __shfl_xor_sync(0xffffffffu, s1, 2);
                    const float mu0 = s0 * (1.f / 64.f), mu1 = s1 * (1.f / 64.f);
                    float q0 = 0.f, q1 = 0.f;
#pragma unroll
                    for (int j = 0; j < 8; j++) {
                        float d;
                        d = acc[4 * j] - mu0; q0 += d * d; d = acc[4 * j + 1] - mu0; q0 += d * d;
                        d = acc[4 * j + 2] - mu1; q1 += d * d; d = acc[4 * j + 3] - mu1; q1 += d * d;
                    }
                    q0 += __shfl_xor_sync(0xffffffffu, q0, 1); q0 += __shfl_xor_sync(0xffffffffu, q0, 2);
                    q1 += __shfl_xor_sync(0xffffffffu, q1, 1); q1 += __shfl_xor_sync(0xffffffffu, q1, 2);
                    if (c == 0) {
                        prm.stats_out[tile_n * S_ + row0] = make_float2(mu0, q0);
                        prm.stats_out[tile_n * S_ + row0 + 8] = make_float2(mu1, q1);
                    }
                }
            } else {
                const float sc = 0.25f * 1.4426950408889634f;
                const float a0 = rstd0 * sc, a1 = rstd1 * sc, rm0 = a0 * mean0, rm1 = a1 * mean1;
#pragma unroll
                for (int jj = 0; jj < 4; jj++) {
                    const float2 ca = *(const float2*)(s_cs + 16 * jj + 2 * c), cb = *(const float2*)(s_cs + 16 * jj + 8 + 2 * c);
                    const uint32_t u0 = pack_bf16(acc[8 * jj] * a0 - rm0 * ca.x, acc[8 * jj + 1] * a0 - rm0 * ca.y);
                    const uint32_t u1 = pack_bf16(acc[8 * jj + 2] * a1 - rm1 * ca.x, acc[8 * jj + 3] * a1 - rm1 * ca.y);
                    const uint32_t u2 = pack_bf16(acc[8 * jj + 4] * a0 - rm0 * cb.x, acc[8 * jj + 5] * a0 - rm0 * cb.y);
                    const uint32_t u3 = pack_bf16(acc[8 * jj + 6] * a1 - rm1 * cb.x, acc[8 * jj + 7] * a1 - rm1 * cb.y);
                    stsm_x4(rbase + (((2 * jj + (lane >> 4)) ^ (mrow & 7)) << 4), u0, u1, u2, u3);
                }
                fence_async_smem();
                named_bar(2 + wg, 128);
                if ((tid & 127) == 0) { tma2d_store(mapC, stile + wg * 8192, n0, m0 + wg * 64); bulk_commit(); }
            }
            if ((tid & 127) == 0) bulk_wait_read();
        } else {
            const uint32_t stile = sbase + wg * (7 * 4096);
            const int mrow = (warp & 3) * 16 + (lane & 7) + ((lane >> 3) & 1) * 8;
            const float a0 = 0.5f * rstd0, a1 = 0.5f * rstd1, rm0 = a0 * mean0, rm1 = a1 * mean1;
#pragma unroll
            for (int jj = 0; jj < 14; jj++) {
                const float2 ca = *(const float2*)(s_cs + 16 * jj + 2 * c), cb = *(const float2*)(s_cs + 16 * jj + 8 + 2 * c);
                float y[8] = {acc[8 * jj] * a0 - rm0 * ca.x,     acc[8 * jj + 1] * a0 - rm0 * ca.y,
                              acc[8 * jj + 2] * a1 - rm1 * ca.x, acc[8 * jj + 3] * a1 - rm1 * ca.y,
                              acc[8 * jj + 4] * a0 - rm0 * cb.x, acc[8 * jj + 5] * a0 - rm0 * cb.y,
                              acc[8 * jj + 6] * a1 - rm1 * cb.x, acc[8 * jj + 7] * a1 - rm1 * cb.y};
#pragma unroll
                for (int i = 0; i < 8; i++) {
                    float t;
                    asm("tanh.approx.f32 %0, %1;" : "=f"(t) : "f"(y[i]));
                    y[i] = fmaf(y[i], t, y[i]);
                }
                const int chunk = (2 * jj + (lane >> 4)) & 3, blk = jj >> 1;
                stsm_x4(stile + blk * 4096 + mrow * 64 + ((chunk ^ ((mrow >> 1) & 3)) << 4),
                        pack_bf16(y[0], y[1]), pack_bf16(y[2], y[3]), pack_bf16(y[4], y[5]), pack_bf16(y[6], y[7]));
                if (jj & 1) {
                    fence_async_smem();
                    __syncwarp();
                    if (lane == 0) {
                        tma2d_store(mapC, stile + blk * 4096 + (warp & 3) * 1024, n0 + blk * 32, m0 + wg * 64 + (warp & 3) * 16);
                        bulk_commit();
                    }
                }
            }
            if (lane == 0) bulk_wait_read();
        }
    }
    if (tid == 0) TL(prm.tk, 3);
    if (MC) cluster_sync();
}

#define WO_ST 5
#define F2_ST 5
#define F1_ST 4
constexpr int QKV_STAGES = 4, WO_STAGES = WO_ST, FFN2_STAGES = F2_ST, FFN1_STAGES = F1_ST;
__global__ void __launch_bounds__(288) qkv_kernel(const __grid_constant__ CUtensorMap mapA, const __grid_constant__ CUtensorMap mapWq,
                                                  const __grid_constant__ CUtensorMap mapWk, const __grid_constant__ CUtensorMap mapWv,
                                                  const __grid_constant__ CUtensorMap mapQ, const GemmParams prm) {
    extern __shared__ __align__(1024) uint8_t smem_raw[];
    uint32_t pad[64];
#pragma unroll
    for (int i = 0; i < 64; i++) asm volatile("mov.u32 %0, %%clock;" : "=r"(pad[i]));
    const int tn = blockIdx.x & 7;
    gemm_body<64, 8, QKV_STAGES, EPI_QKV, 1>(&mapA, &mapWq, tn == 0 ? &mapWk : &mapWv, &mapA, &mapQ, prm, blockIdx.x >> 3, tn, smem_raw);
    if (prm.stats_in == nullptr) {
#pragma unroll
        for (int i = 0; i < 64; i++) asm volatile("st.volatile.global.u32 [%0], %1;" ::"l"(g_kimg + 4 * i), "r"(pad[i]) : "memory");
    }
}
template <int KB, int STAGES>
__global__ void __launch_bounds__(288) res_gemm_kernel(const __grid_constant__ CUtensorMap mapA, const __grid_constant__ CUtensorMap mapW,
                                                       const __grid_constant__ CUtensorMap mapR, const __grid_constant__ CUtensorMap mapC, const GemmParams prm) {
    extern __shared__ __align__(1024) uint8_t smem_raw[];
    gemm_body<64, KB, STAGES, EPI_RES, 1>(&mapA, &mapW, &mapW, &mapR, &mapC, prm, blockIdx.x >> 3, blockIdx.x & 7, smem_raw);
}
__global__ void __launch_bounds__(288) ffn1_kernel(const __grid_constant__ CUtensorMap mapA, const __grid_constant__ CUtensorMap mapW4,
                                                   const __grid_constant__ CUtensorMap mapW3, const __grid_constant__ CUtensorMap mapH, const GemmParams prm) {
    extern __shared__ __align__(1024) uint8_t smem_raw[];
    const int pair = blockIdx.x >> 1, tile_n = pair & 7, tile_m = (pair >> 3) * 2 + (blockIdx.x & 1);
    gemm_body<224, 16, FFN1_STAGES, EPI_FFN1, 2>(&mapA, &mapW4, &mapW3, &mapA, &mapH, prm, tile_m, tile_n, smem_raw);
}

constexpr int NPOLY = 10;
__host__ __device__ constexpr bool is_mufu(int i) { return ((i + 1) * (16 - NPOLY)) / 16 != (i * (16 - NPOLY)) / 16; }

__device__ __forceinline__ float ex2(float x) { float r; asm("ex2.approx.ftz.f32 %0, %1;" : "=f"(r) : "f"(x)); return r; }
__device__ __forceinline__ uint32_t exp_pair_mufu(float a, float b) { return pack_bf16(ex2(a), ex2(b)); }
__device__ __forceinline__ uint32_t exp_pair_fma(float a, float b, uint32_t c3f) {
    constexpr float MAGIC = 98430.4140625f;
    const float ta = a + MAGIC, tb = b + (MAGIC - 143.5f);
    uint32_t y, m, r;
    asm("mad.lo.u32 %0, %1, 65536, %2;" : "=r"(y) : "r"(__float_as_uint(tb)), "r"(__float_as_uint(ta)));
    asm("lop3.b32 %0, %1, 0x007F007F, %2, 0xEA;" : "=r"(m) : "r"(y), "r"(c3f));
    const uint32_t e = y & 0xFF80FF80u;
    asm("fma.rn.bf16x2 %0, %1, %2, %3;" : "=r"(r) : "r"(y), "r"(m), "r"(e));
    return r;
}

constexpr int KCH = 256, NCH = S_ / KCH;
constexpr int K_BYTES = S_ * 32, V_BYTES = (S_ / 16) * 768;
constexpr int ATT_SMEM = K_BYTES + V_BYTES;

__global__ void __launch_bounds__(512, 1) attn_kernel(int tk) {
    extern __shared__ __align__(1024) uint8_t smem[];
    __shared__ uint64_t bars[NCH];
    __shared__ int s_slow;
    const int tid = threadIdx.x, wg = tid >> 7, warp = (tid >> 5) & 3, lane = tid & 31;
    const uint32_t sK = smem_u32(smem), sV = sK + K_BYTES;
    if (tid == 0) TL(tk, 0);
    if (tid == 0) {
        for (int i = 0; i < NCH; i++) mbar_init(smem_u32(&bars[i]), 1);
        s_slow = 0;
        fence_mbar_init();
    }
    __syncthreads();
    pdl_launch();
    pdl_wait();
    if (tid == 0) TL(tk, 1);
    if (tid == 0) {
        for (int i = 0; i < NCH; i++) {
            mbar_expect_tx(smem_u32(&bars[i]), KCH * 32 + (KCH / 16) * 768);
            bulk_load(sK + i * KCH * 32, g_kimg + i * KCH * 32, KCH * 32, smem_u32(&bars[i]));
            bulk_load(sV + i * (KCH / 16) * 768, g_vimg + i * (KCH / 16) * 768, (KCH / 16) * 768, smem_u32(&bars[i]));
        }
    }
    const int tb = blockIdx.x >> 3, hg = blockIdx.x & 7;
    const int head = hg * 4 + wg;
    const int g = lane >> 2, c = lane & 3;
    uint32_t qa[2][4];
    float qn = 0.f;
#pragma unroll
    for (int m = 0; m < 2; m++) {
        const int row = tb * 128 + m * 64 + warp * 16 + g;
        const uint32_t* p0 = (const uint32_t*)(g_q + (size_t)row * D_ + head * 16);
        const uint32_t* p1 = (const uint32_t*)(g_q + (size_t)(row + 8) * D_ + head * 16);
        qa[m][0] = p0[c]; qa[m][1] = p1[c]; qa[m][2] = p0[c + 4]; qa[m][3] = p1[c + 4];
        float n0 = bf_lo(qa[m][0]) * bf_lo(qa[m][0]) + bf_hi(qa[m][0]) * bf_hi(qa[m][0]) + bf_lo(qa[m][2]) * bf_lo(qa[m][2]) + bf_hi(qa[m][2]) * bf_hi(qa[m][2]);
        float n1 = bf_lo(qa[m][1]) * bf_lo(qa[m][1]) + bf_hi(qa[m][1]) * bf_hi(qa[m][1]) + bf_lo(qa[m][3]) * bf_lo(qa[m][3]) + bf_hi(qa[m][3]) * bf_hi(qa[m][3]);
        n0 += __shfl_xor_sync(0xffffffffu, n0, 1); n0 += __shfl_xor_sync(0xffffffffu, n0, 2);
        n1 += __shfl_xor_sync(0xffffffffu, n1, 1); n1 += __shfl_xor_sync(0xffffffffu, n1, 2);
        if (!(n0 == n0) || !(n1 == n1)) n0 = __int_as_float(0x7f800000);
        qn = fmaxf(qn, fmaxf(n0, n1));
    }
    {
        float km = 0.f, vm = 0.f;
#pragma unroll
        for (int i = 0; i < 16; i++) { km = fmaxf(km, g_kvmax[i]); vm = fmaxf(vm, g_kvmax[16 + i]); }
        const bool ok = (qn * km <= 10000.f) && (vm <= 16384.f);
        if (!ok) s_slow = 1;
    }
    float oacc[2][12];
#pragma unroll
    for (int m = 0; m < 2; m++)
#pragma unroll
        for (int i = 0; i < 12; i++) oacc[m][i] = 0.f;
    __syncthreads();
    const bool slow = s_slow != 0;

    const uint64_t dK0 = mkdesc(sK, 128, 256, 0);
    const uint64_t dV0 = mkdesc(sV, 128, 256, 0);
    uint32_t c3f;
    asm volatile("mov.b32 %0, 0x3F003F00;" : "=r"(c3f));
    if (!slow) {
#pragma unroll 1
        for (int t = 0; t < S_ / 64; t++) {
            if ((t & 3) == 0) mbar_wait(smem_u32(&bars[t >> 2]), 0);
            const uint64_t dK = dK0 + (uint64_t)(t * 64 * 32 / 16);
            const uint64_t dV = dV0 + (uint64_t)(t * 4 * 768 / 16);
#pragma unroll
            for (int m = 0; m < 2; m++) {
                float s[32];
                wg_fence();
                wgmma_rs_n64_z(s, qa[m][0], qa[m][1], qa[m][2], qa[m][3], dK);
                wg_commit();
                wg_wait<0>();
                fence_regs(s);
                uint32_t p[16];
#pragma unroll
                for (int i = 0; i < 16; i++) p[i] = is_mufu(i) ? exp_pair_mufu(s[2 * i], s[2 * i + 1]) : exp_pair_fma(s[2 * i], s[2 * i + 1], c3f);
                wg_fence();
#pragma unroll
                for (int kk = 0; kk < 4; kk++)
                    wgmma_rs_n24_tb(oacc[m], p[4 * kk], p[4 * kk + 1], p[4 * kk + 2], p[4 * kk + 3], dV + (uint64_t)(kk * 768 / 16));
                wg_commit();
            }
        }
        wg_wait<0>();
    } else {
        float mx[2][2] = {{-INFINITY, -INFINITY}, {-INFINITY, -INFINITY}};
#pragma unroll 1
        for (int t = 0; t < S_ / 64; t++) {
            if ((t & 3) == 0) mbar_wait(smem_u32(&bars[t >> 2]), 0);
            const uint64_t dK = dK0 + (uint64_t)(t * 64 * 32 / 16);
            const uint64_t dV = dV0 + (uint64_t)(t * 4 * 768 / 16);
#pragma unroll
            for (int m = 0; m < 2; m++) {
                float s[32];
                wg_fence();
                wgmma_rs_n64_z(s, qa[m][0], qa[m][1], qa[m][2], qa[m][3], dK);
                wg_commit();
                wg_wait<0>();
                fence_regs(s);
                fence_regs(oacc[m]);
                float r0 = mx[m][0], r1 = mx[m][1];
#pragma unroll
                for (int j = 0; j < 8; j++) {
                    r0 = fmaxf(r0, fmaxf(s[4 * j], s[4 * j + 1]));
                    r1 = fmaxf(r1, fmaxf(s[4 * j + 2], s[4 * j + 3]));
                }
                r0 = fmaxf(r0, __shfl_xor_sync(0xffffffffu, r0, 1)); r0 = fmaxf(r0, __shfl_xor_sync(0xffffffffu, r0, 2));
                r1 = fmaxf(r1, __shfl_xor_sync(0xffffffffu, r1, 1)); r1 = fmaxf(r1, __shfl_xor_sync(0xffffffffu, r1, 2));
                const float al0 = ex2(mx[m][0] - r0), al1 = ex2(mx[m][1] - r1);
                mx[m][0] = r0; mx[m][1] = r1;
#pragma unroll
                for (int j = 0; j < 3; j++) {
                    oacc[m][4 * j] *= al0; oacc[m][4 * j + 1] *= al0;
                    oacc[m][4 * j + 2] *= al1; oacc[m][4 * j + 3] *= al1;
                }
                uint32_t p[16];
#pragma unroll
                for (int j = 0; j < 8; j++) {
                    p[2 * j] = pack_bf16(ex2(s[4 * j] - r0), ex2(s[4 * j + 1] - r0));
                    p[2 * j + 1] = pack_bf16(ex2(s[4 * j + 2] - r1), ex2(s[4 * j + 3] - r1));
                }
                fence_regs(oacc[m]);
                wg_fence();
#pragma unroll
                for (int kk = 0; kk < 4; kk++)
                    wgmma_rs_n24_tb(oacc[m], p[4 * kk], p[4 * kk + 1], p[4 * kk + 2], p[4 * kk + 3], dV + (uint64_t)(kk * 768 / 16));
                wg_commit();
                wg_wait<0>();
            }
        }
    }
    fence_regs(oacc[0]); fence_regs(oacc[1]);
    if (tid == 0) TL(tk, 2);
#pragma unroll
    for (int m = 0; m < 2; m++) {
        const float l0 = __shfl_sync(0xffffffffu, oacc[m][8], lane & ~3);
        const float l1 = __shfl_sync(0xffffffffu, oacc[m][10], lane & ~3);
        const float r0 = 1.0f / l0, r1 = 1.0f / l1;
        const int row = tb * 128 + m * 64 + warp * 16 + g;
        uint32_t* p0 = (uint32_t*)(g_o + (size_t)row * D_ + head * 16);
        uint32_t* p1 = (uint32_t*)(g_o + (size_t)(row + 8) * D_ + head * 16);
        p0[c] = pack_bf16(oacc[m][0] * r0, oacc[m][1] * r0);
        p1[c] = pack_bf16(oacc[m][2] * r1, oacc[m][3] * r1);
        p0[c + 4] = pack_bf16(oacc[m][4] * r0, oacc[m][5] * r0);
        p1[c + 4] = pack_bf16(oacc[m][6] * r1, oacc[m][7] * r1);
    }
    if (tid == 0) TL(tk, 3);
}

typedef CUresult (*EncodeFn)(CUtensorMap*, CUtensorMapDataType, cuuint32_t, void*, const cuuint64_t*, const cuuint64_t*, const cuuint32_t*,
                             const cuuint32_t*, CUtensorMapInterleave, CUtensorMapSwizzle, CUtensorMapL2promotion, CUtensorMapFloatOOBfill);

EncodeFn get_encode() {
    static EncodeFn fn = nullptr;
    if (!fn) {
        void* p = nullptr;
        cudaDriverEntryPointQueryResult qr;
        cudaGetDriverEntryPoint("cuTensorMapEncodeTiled", &p, cudaEnableDefault, &qr);
        fn = (EncodeFn)p;
    }
    return fn;
}
CUtensorMap map2d(const void* ptr, uint64_t cols, uint64_t rows, uint32_t bc, uint32_t br, CUtensorMapSwizzle sw) {
    CUtensorMap m;
    cuuint64_t gd[2] = {cols, rows}, gs[1] = {cols * 2};
    cuuint32_t bx[2] = {bc, br}, es[2] = {1, 1};
    get_encode()(&m, CU_TENSOR_MAP_DATA_TYPE_BFLOAT16, 2, (void*)ptr, gd, gs, bx, es, CU_TENSOR_MAP_INTERLEAVE_NONE, sw,
                 CU_TENSOR_MAP_L2_PROMOTION_L2_128B, CU_TENSOR_MAP_FLOAT_OOB_FILL_NONE);
    return m;
}
CUtensorMap map3d32(const void* ptr, uint64_t cols, uint64_t rows, uint32_t br, uint32_t nb) {
    CUtensorMap m;
    cuuint64_t gd[3] = {32, rows, cols / 32}, gs[2] = {cols * 2, 64};
    cuuint32_t bx[3] = {32, br, nb}, es[3] = {1, 1, 1};
    get_encode()(&m, CU_TENSOR_MAP_DATA_TYPE_BFLOAT16, 3, (void*)ptr, gd, gs, bx, es, CU_TENSOR_MAP_INTERLEAVE_NONE, CU_TENSOR_MAP_SWIZZLE_64B,
                 CU_TENSOR_MAP_L2_PROMOTION_L2_128B, CU_TENSOR_MAP_FLOAT_OOB_FILL_NONE);
    return m;
}

template <typename... KArgs, typename... Args>
void launch(void (*kern)(KArgs...), int grid, int block, int smem, int cluster, bool pdl, Args... args) {
    cudaLaunchConfig_t cfg = {};
    cfg.gridDim = dim3(grid);
    cfg.blockDim = dim3(block);
    cfg.dynamicSmemBytes = smem;
    cfg.stream = cudaStreamPerThread;
    cudaLaunchAttribute at[2];
    int n = 0;
    if (cluster > 1) { at[n].id = cudaLaunchAttributeClusterDimension; at[n].val.clusterDim.x = cluster; at[n].val.clusterDim.y = 1; at[n].val.clusterDim.z = 1; n++; }
    if (pdl) { at[n].id = cudaLaunchAttributeProgrammaticStreamSerialization; at[n].val.programmaticStreamSerializationAllowed = 1; n++; }
    cfg.attrs = at;
    cfg.numAttrs = n;
    cudaLaunchKernelEx(&cfg, kern, KArgs(args)...);
}

template <typename T> void* sym(const T& s) { void* p = nullptr; cudaGetSymbolAddress(&p, s); return p; }

}

extern "C" void kernel_launch(void* const* d_in, const int* in_sizes, int n_in, void* d_out, int out_size) {
    const __nv_bfloat16* x = (const __nv_bfloat16*)d_in[0];
    const __nv_bfloat16* wq = (const __nv_bfloat16*)d_in[1];
    const __nv_bfloat16* wk = (const __nv_bfloat16*)d_in[2];
    const __nv_bfloat16* wv = (const __nv_bfloat16*)d_in[3];
    const __nv_bfloat16* wo = (const __nv_bfloat16*)d_in[4];
    const __nv_bfloat16* w1 = (const __nv_bfloat16*)d_in[6];
    const __nv_bfloat16* w2 = (const __nv_bfloat16*)d_in[7];

    constexpr int SM_QKV = GemmSmem<64, QKV_STAGES, EPI_QKV>::TOTAL;
    constexpr int SM_WO = GemmSmem<64, WO_STAGES, EPI_RES>::TOTAL, SM_FFN2 = GemmSmem<64, FFN2_STAGES, EPI_RES>::TOTAL;
    constexpr int SM_FFN1 = GemmSmem<224, FFN1_STAGES, EPI_FFN1>::TOTAL;
    cudaFuncSetAttribute(qkv_kernel, cudaFuncAttributeMaxDynamicSharedMemorySize, SM_QKV);
    cudaFuncSetAttribute(res_gemm_kernel<8, WO_STAGES>, cudaFuncAttributeMaxDynamicSharedMemorySize, SM_WO);
    cudaFuncSetAttribute(ffn1_kernel, cudaFuncAttributeMaxDynamicSharedMemorySize, SM_FFN1);
    cudaFuncSetAttribute(res_gemm_kernel<28, FFN2_STAGES>, cudaFuncAttributeMaxDynamicSharedMemorySize, SM_FFN2);
    cudaFuncSetAttribute(attn_kernel, cudaFuncAttributeMaxDynamicSharedMemorySize, ATT_SMEM);
    cudaFuncSetAttribute(prep_kernel, cudaFuncAttributePreferredSharedMemoryCarveout, 100);
    cudaFuncSetAttribute(qkv_kernel, cudaFuncAttributePreferredSharedMemoryCarveout, 100);
    cudaFuncSetAttribute(res_gemm_kernel<8, WO_STAGES>, cudaFuncAttributePreferredSharedMemoryCarveout, 100);
    cudaFuncSetAttribute(ffn1_kernel, cudaFuncAttributePreferredSharedMemoryCarveout, 100);
    cudaFuncSetAttribute(res_gemm_kernel<28, FFN2_STAGES>, cudaFuncAttributePreferredSharedMemoryCarveout, 100);
    cudaFuncSetAttribute(attn_kernel, cudaFuncAttributePreferredSharedMemoryCarveout, 100);

    void *q = sym(g_q), *o = sym(g_o), *x1 = sym(g_x1), *x2 = sym(g_x2), *x3 = sym(g_x3), *h = sym(g_h);
    float2* stats = (float2*)sym(g_stats);
    const void* xs[5] = {x, x1, x2, x3, d_out};

    const CUtensorMapSwizzle SW128 = CU_TENSOR_MAP_SWIZZLE_128B, SW64 = CU_TENSOR_MAP_SWIZZLE_64B;
    const CUtensorMap mWq = map2d(wq, D_, D_, 64, 64, SW128);
    const CUtensorMap mWk = map2d(wk, 16, D_, 16, 64, CU_TENSOR_MAP_SWIZZLE_32B);
    const CUtensorMap mWv = map2d(wv, 16, D_, 16, 64, CU_TENSOR_MAP_SWIZZLE_32B);
    const CUtensorMap mWo = map2d(wo, D_, D_, 64, 64, SW128);
    const CUtensorMap mW1a = map3d32(w1, F_, D_, 32, 4), mW1b = map3d32(w1, F_, D_, 32, 3);
    const CUtensorMap mW2 = map2d(w2, D_, F_, 64, 64, SW128);
    const CUtensorMap mQ = map2d(q, D_, S_, 64, 64, SW128);
    const CUtensorMap mO = map2d(o, D_, S_, 64, 64, SW128);
    const CUtensorMap mHst = map2d(h, F_, S_, 32, 16, SW64);
    const CUtensorMap mHld = map2d(h, F_, S_, 64, 64, SW128);
    CUtensorMap mX[5], mX32[2];
    for (int i = 0; i < 5; i++) mX[i] = map2d(xs[i], D_, S_, 64, 64, SW128);
    mX32[0] = map2d(x1, D_, S_, 32, 64, SW64);
    mX32[1] = map2d(x3, D_, S_, 32, 64, SW64);

    launch(prep_kernel, PREP_CS_CTAS + PREP_STAT_CTAS, 256, 0, 1, false, x, wq, wk, wv, wo, w1, w2);
    for (int layer = 0; layer < 2; layer++) {
        const int xi = layer * 2;
        GemmParams p;
        p.stats_in = stats + (size_t)xi * 8 * S_; p.stats_out = nullptr; p.wait_in_epilogue = layer == 0; p.tk = 1 + 5 * layer;
        launch(qkv_kernel, 128, 288, SM_QKV, 2, true, mX[xi], mWq, mWk, mWv, mQ, p);
        launch(attn_kernel, 128, 512, ATT_SMEM, 1, true, 2 + 5 * layer);
        p.stats_in = nullptr; p.stats_out = stats + (size_t)(xi + 1) * 8 * S_; p.wait_in_epilogue = 0; p.tk = 3 + 5 * layer;
        launch(res_gemm_kernel<8, WO_STAGES>, 128, 288, SM_WO, 2, true, mO, mWo, mX[xi], mX[xi + 1], p);
        p.stats_in = stats + (size_t)(xi + 1) * 8 * S_; p.stats_out = nullptr; p.tk = 4 + 5 * layer;
        launch(ffn1_kernel, 128, 288, SM_FFN1, 2, true, mX32[layer], mW1a, mW1b, mHst, p);
        p.stats_in = nullptr; p.stats_out = layer == 0 ? stats + (size_t)2 * 8 * S_ : nullptr; p.tk = 5 + 5 * layer;
        launch(res_gemm_kernel<28, FFN2_STAGES>, 128, 288, SM_FFN2, 2, true, mHld, mW2, mX[xi + 1], mX[xi + 2], p);
    }
}
```

```cpp
#include <cuda_runtime.h>
#include <cuda_bf16.h>
#include <cuda.h>
#include <stdint.h>

namespace {

constexpr int S_ = 2048, D_ = 512, H_ = 32, F_ = 1792;

__device__ __align__(1024) __nv_bfloat16 g_q[S_ * D_];
__device__ __align__(1024) __nv_bfloat16 g_o[S_ * D_];
__device__ __align__(1024) __nv_bfloat16 g_x1[S_ * D_];
__device__ __align__(1024) __nv_bfloat16 g_x2[S_ * D_];
__device__ __align__(1024) __nv_bfloat16 g_x3[S_ * D_];
__device__ __align__(1024) __nv_bfloat16 g_h[S_ * F_];
__device__ __align__(1024) uint8_t g_kimg[S_ * 32];
__device__ __align__(1024) uint8_t g_vimg[(S_ / 16) * 768];
__device__ __align__(1024) float2 g_stats[4][8 * S_];
__device__ __align__(16) float g_cs_q[D_];
__device__ __align__(16) float g_cs_kv[32];
__device__ __align__(16) float g_cs_1[F_];
__device__ __align__(16) float g_kvmax[32];

#define TL(k, slot)

__device__ __forceinline__ uint32_t smem_u32(const void* p) { return (uint32_t)__cvta_generic_to_shared(p); }
__device__ __forceinline__ void mbar_init(uint32_t bar, uint32_t cnt) {
    asm volatile("mbarrier.init.shared::cta.b64 [%0], %1;" ::"r"(bar), "r"(cnt));
}
__device__ __forceinline__ void mbar_expect_tx(uint32_t bar, uint32_t bytes) {
    asm volatile("mbarrier.arrive.expect_tx.shared::cta.b64 _, [%0], %1;" ::"r"(bar), "r"(bytes) : "memory");
}
__device__ __forceinline__ void mbar_arrive(uint32_t bar) {
    asm volatile("mbarrier.arrive.shared::cta.b64 _, [%0];" ::"r"(bar) : "memory");
}
__device__ __forceinline__ void mbar_arrive_remote(uint32_t bar, uint32_t cta) {
    asm volatile("{\n.reg .b32 ra;\nmapa.shared::cluster.u32 ra, %0, %1;\nmbarrier.arrive.shared::cluster.b64 _, [ra];\n}" ::"r"(bar), "r"(cta) : "memory");
}
__device__ __forceinline__ void mbar_wait(uint32_t bar, uint32_t parity) {
    asm volatile("{\n.reg .pred p;\nWAIT_%=:\nmbarrier.try_wait.parity.shared::cta.b64 p, [%0], %1;\n@p bra DONE_%=;\nbra WAIT_%=;\nDONE_%=:\n}" ::"r"(bar), "r"(parity) : "memory");
}
__device__ __forceinline__ void bulk_load(uint32_t dst, const void* src, uint32_t bytes, uint32_t bar) {
    asm volatile("cp.async.bulk.shared::cluster.global.mbarrier::complete_tx::bytes [%0], [%1], %2, [%3];" ::"r"(dst), "l"(src), "r"(bytes), "r"(bar) : "memory");
}
__device__ __forceinline__ void tma2d(uint32_t dst, const CUtensorMap* m, int c0, int c1, uint32_t bar) {
    asm volatile("cp.async.bulk.tensor.2d.shared::cluster.global.mbarrier::complete_tx::bytes [%0], [%1, {%3, %4}], [%2];" ::"r"(dst), "l"(m), "r"(bar), "r"(c0), "r"(c1) : "memory");
}
__device__ __forceinline__ void tma2d_mc(uint32_t dst, const CUtensorMap* m, int c0, int c1, uint32_t bar, uint16_t mask) {
    asm volatile("cp.async.bulk.tensor.2d.shared::cluster.global.mbarrier::complete_tx::bytes.multicast::cluster [%0], [%1, {%3, %4}], [%2], %5;" ::"r"(dst), "l"(m), "r"(bar), "r"(c0), "r"(c1), "h"(mask) : "memory");
}
__device__ __forceinline__ void tma3d(uint32_t dst, const CUtensorMap* m, int c0, int c1, int c2, uint32_t bar) {
    asm volatile("cp.async.bulk.tensor.3d.shared::cluster.global.mbarrier::complete_tx::bytes [%0], [%1, {%3, %4, %5}], [%2];" ::"r"(dst), "l"(m), "r"(bar), "r"(c0), "r"(c1), "r"(c2) : "memory");
}
__device__ __forceinline__ void tma3d_mc(uint32_t dst, const CUtensorMap* m, int c0, int c1, int c2, uint32_t bar, uint16_t mask) {
    asm volatile("cp.async.bulk.tensor.3d.shared::cluster.global.mbarrier::complete_tx::bytes.multicast::cluster [%0], [%1, {%3, %4, %5}], [%2], %6;" ::"r"(dst), "l"(m), "r"(bar), "r"(c0), "r"(c1), "r"(c2), "h"(mask) : "memory");
}
__device__ __forceinline__ void tma2d_store(const CUtensorMap* m, uint32_t src, int c0, int c1) {
    asm volatile("cp.async.bulk.tensor.2d.global.shared::cta.bulk_group [%0, {%2, %3}], [%1];" ::"l"(m), "r"(src), "r"(c0), "r"(c1) : "memory");
}
__device__ __forceinline__ void tma3d_store(const CUtensorMap* m, uint32_t src, int c0, int c1, int c2) {
    asm volatile("cp.async.bulk.tensor.3d.global.shared::cta.bulk_group [%0, {%2, %3, %4}], [%1];" ::"l"(m), "r"(src), "r"(c0), "r"(c1), "r"(c2) : "memory");
}
__device__ __forceinline__ void bulk_commit() { asm volatile("cp.async.bulk.commit_group;" ::: "memory"); }
__device__ __forceinline__ void bulk_wait_read() { asm volatile("cp.async.bulk.wait_group.read 0;" ::: "memory"); }
__device__ __forceinline__ void prefetch_tmap(const CUtensorMap* m) { asm volatile("prefetch.tensormap [%0];" ::"l"(m) : "memory"); }
__device__ __forceinline__ void fence_async_smem() { asm volatile("fence.proxy.async.shared::cta;" ::: "memory"); }
__device__ __forceinline__ void fence_mbar_init() { asm volatile("fence.mbarrier_init.release.cluster;" ::: "memory"); }
__device__ __forceinline__ void cluster_sync() { asm volatile("barrier.cluster.arrive.release.aligned;\nbarrier.cluster.wait.acquire.aligned;" ::: "memory"); }
__device__ __forceinline__ uint32_t cluster_rank() { uint32_t r; asm volatile("mov.u32 %0, %%cluster_ctarank;" : "=r"(r)); return r; }
__device__ __forceinline__ void pdl_wait() { asm volatile("griddepcontrol.wait;" ::: "memory"); }
__device__ __forceinline__ void pdl_launch() { asm volatile("griddepcontrol.launch_dependents;" ::: "memory"); }
__device__ __forceinline__ void named_bar(int id, int n) { asm volatile("bar.sync %0, %1;" ::"r"(id), "r"(n) : "memory"); }

__device__ __forceinline__ void wg_fence() { asm volatile("wgmma.fence.sync.aligned;" ::: "memory"); }
__device__ __forceinline__ void wg_commit() { asm volatile("wgmma.commit_group.sync.aligned;" ::: "memory"); }
template <int N> __device__ __forceinline__ void wg_wait() { asm volatile("wgmma.wait_group.sync.aligned %0;" ::"n"(N) : "memory"); }
template <int N> __device__ __forceinline__ void fence_regs(float (&d)[N]) {
#pragma unroll
    for (int i = 0; i < N; i++) asm volatile("" : "+f"(d[i])::"memory");
}
__device__ __forceinline__ uint64_t mkdesc(uint32_t addr, uint32_t lbo, uint32_t sbo, uint32_t swz) {
    uint64_t d = 0;
    d |= (uint64_t)((addr & 0x3FFFF) >> 4);
    d |= (uint64_t)((lbo & 0x3FFFF) >> 4) << 16;
    d |= (uint64_t)((sbo & 0x3FFFF) >> 4) << 32;
    d |= (uint64_t)swz << 62;
    return d;
}
__device__ __forceinline__ void ldsm_x4(uint32_t& r0, uint32_t& r1, uint32_t& r2, uint32_t& r3, uint32_t addr) {
    asm volatile("ldmatrix.sync.aligned.m8n8.x4.shared.b16 {%0,%1,%2,%3}, [%4];" : "=r"(r0), "=r"(r1), "=r"(r2), "=r"(r3) : "r"(addr) : "memory");
}
__device__ __forceinline__ void stsm_x4(uint32_t addr, uint32_t r0, uint32_t r1, uint32_t r2, uint32_t r3) {
    asm volatile("stmatrix.sync.aligned.m8n8.x4.shared.b16 [%0], {%1,%2,%3,%4};" ::"r"(addr), "r"(r0), "r"(r1), "r"(r2), "r"(r3) : "memory");
}
__device__ __forceinline__ uint32_t pack_bf16(float lo, float hi) {
    uint32_t r;
    asm("cvt.rn.bf16x2.f32 %0, %1, %2;" : "=r"(r) : "f"(hi), "f"(lo));
    return r;
}
__device__ __forceinline__ float bf_lo(uint32_t v) { return __uint_as_float(v << 16); }
__device__ __forceinline__ float bf_hi(uint32_t v) { return __uint_as_float(v & 0xFFFF0000u); }

#define WG_REGS_4(o) "+f"(d[o]), "+f"(d[o + 1]), "+f"(d[o + 2]), "+f"(d[o + 3])
#define WG_REGS_8(o) WG_REGS_4(o), WG_REGS_4(o + 4)
#define WG_REGS_16(o) WG_REGS_8(o), WG_REGS_8(o + 8)
#define WG_REGS_32(o) WG_REGS_16(o), WG_REGS_16(o + 16)

__device__ __forceinline__ void wgmma_ss_n16_tb(float (&d)[8], uint64_t dA, uint64_t dB, int sc) {
    asm volatile("{\n.reg .pred p;\nsetp.ne.b32 p, %10, 0;\n"
                 "wgmma.mma_async.sync.aligned.m64n16k16.f32.bf16.bf16 "
                 "{%0,%1,%2,%3,%4,%5,%6,%7}, %8, %9, p, 1, 1, 0, 1;\n}\n"
                 : WG_REGS_8(0) : "l"(dA), "l"(dB), "r"(sc));
}
__device__ __forceinline__ void wgmma_ss_n32_tb(float (&d)[16], uint64_t dA, uint64_t dB, int sc) {
    asm volatile("{\n.reg .pred p;\nsetp.ne.b32 p, %18, 0;\n"
                 "wgmma.mma_async.sync.aligned.m64n32k16.f32.bf16.bf16 "
                 "{%0,%1,%2,%3,%4,%5,%6,%7,%8,%9,%10,%11,%12,%13,%14,%15}, %16, %17, p, 1, 1, 0, 1;\n}\n"
                 : WG_REGS_16(0) : "l"(dA), "l"(dB), "r"(sc));
}
__device__ __forceinline__ void wgmma_ss_n64_tb(float (&d)[32], uint64_t dA, uint64_t dB, int sc) {
    asm volatile("{\n.reg .pred p;\nsetp.ne.b32 p, %34, 0;\n"
                 "wgmma.mma_async.sync.aligned.m64n64k16.f32.bf16.bf16 "
                 "{%0,%1,%2,%3,%4,%5,%6,%7,%8,%9,%10,%11,%12,%13,%14,%15,%16,%17,%18,%19,%20,%21,%22,%23,%24,%25,%26,%27,%28,%29,%30,%31}, "
                 "%32, %33, p, 1, 1, 0, 1;\n}\n"
                 : WG_REGS_32(0) : "l"(dA), "l"(dB), "r"(sc));
}
__device__ __forceinline__ void wgmma_ss_n224_tb(float (&d)[112], uint64_t dA, uint64_t dB, int sc) {
    asm volatile("{\n.reg .pred p;\nsetp.ne.b32 p, %114, 0;\n"
                 "wgmma.mma_async.sync.aligned.m64n224k16.f32.bf16.bf16 "
                 "{%0,%1,%2,%3,%4,%5,%6,%7,%8,%9,%10,%11,%12,%13,%14,%15,%16,%17,%18,%19,%20,%21,%22,%23,%24,%25,%26,%27,%28,%29,%30,%31,"
                 "%32,%33,%34,%35,%36,%37,%38,%39,%40,%41,%42,%43,%44,%45,%46,%47,%48,%49,%50,%51,%52,%53,%54,%55,%56,%57,%58,%59,%60,%61,%62,%63,"
                 "%64,%65,%66,%67,%68,%69,%70,%71,%72,%73,%74,%75,%76,%77,%78,%79,%80,%81,%82,%83,%84,%85,%86,%87,%88,%89,%90,%91,%92,%93,%94,%95,"
                 "%96,%97,%98,%99,%100,%101,%102,%103,%104,%105,%106,%107,%108,%109,%110,%111}, "
                 "%112, %113, p, 1, 1, 0, 1;\n}\n"
                 : WG_REGS_32(0), WG_REGS_32(32), WG_REGS_32(64), WG_REGS_16(96) : "l"(dA), "l"(dB), "r"(sc));
}
template <int BN> __device__ __forceinline__ void wgmma_ss_tb(float (&d)[BN / 2], uint64_t dA, uint64_t dB, int sc) {
    if constexpr (BN == 32) wgmma_ss_n32_tb(d, dA, dB, sc);
    else if constexpr (BN == 64) wgmma_ss_n64_tb(d, dA, dB, sc);
    else wgmma_ss_n224_tb(d, dA, dB, sc);
}
__device__ __forceinline__ void wgmma_rs_n64_z(float (&d)[32], uint32_t a0, uint32_t a1, uint32_t a2, uint32_t a3, uint64_t dB) {
    asm volatile("{\n.reg .pred p;\nsetp.ne.b32 p, 0, 0;\n"
                 "wgmma.mma_async.sync.aligned.m64n64k16.f32.bf16.bf16 "
                 "{%0,%1,%2,%3,%4,%5,%6,%7,%8,%9,%10,%11,%12,%13,%14,%15,%16,%17,%18,%19,%20,%21,%22,%23,%24,%25,%26,%27,%28,%29,%30,%31}, "
                 "{%32,%33,%34,%35}, %36, p, 1, 1, 0;\n}\n"
                 : "=f"(d[0]), "=f"(d[1]), "=f"(d[2]), "=f"(d[3]), "=f"(d[4]), "=f"(d[5]), "=f"(d[6]), "=f"(d[7]),
                   "=f"(d[8]), "=f"(d[9]), "=f"(d[10]), "=f"(d[11]), "=f"(d[12]), "=f"(d[13]), "=f"(d[14]), "=f"(d[15]),
                   "=f"(d[16]), "=f"(d[17]), "=f"(d[18]), "=f"(d[19]), "=f"(d[20]), "=f"(d[21]), "=f"(d[22]), "=f"(d[23]),
                   "=f"(d[24]), "=f"(d[25]), "=f"(d[26]), "=f"(d[27]), "=f"(d[28]), "=f"(d[29]), "=f"(d[30]), "=f"(d[31])
                 : "r"(a0), "r"(a1), "r"(a2), "r"(a3), "l"(dB));
}
__device__ __forceinline__ void wgmma_rs_n24_tb(float (&d)[12], uint32_t a0, uint32_t a1, uint32_t a2, uint32_t a3, uint64_t dB) {
    asm volatile("{\n.reg .pred p;\nsetp.eq.b32 p, 0, 0;\n"
                 "wgmma.mma_async.sync.aligned.m64n24k16.f32.bf16.bf16 "
                 "{%0,%1,%2,%3,%4,%5,%6,%7,%8,%9,%10,%11}, {%12,%13,%14,%15}, %16, p, 1, 1, 1;\n}\n"
                 : WG_REGS_8(0), WG_REGS_4(8) : "r"(a0), "r"(a1), "r"(a2), "r"(a3), "l"(dB));
}

constexpr int PREP_STAT_CTAS = S_ / 8;
constexpr int PREP_CS_CTAS = 8 + 1 + F_ / 64;

__global__ void __launch_bounds__(256) prep_kernel(const __nv_bfloat16* __restrict__ x, const __nv_bfloat16* __restrict__ wq,
                                                   const __nv_bfloat16* __restrict__ wk, const __nv_bfloat16* __restrict__ wv,
                                                   const __nv_bfloat16* __restrict__ wo, const __nv_bfloat16* __restrict__ w1,
                                                   const __nv_bfloat16* __restrict__ w2) {
    pdl_launch();
    const int tid = threadIdx.x;
    if (tid == 0) { TL(0, 0); TL(0, 1); }
    if (blockIdx.x < PREP_CS_CTAS) {
        __shared__ float red[32][65];
        const int b = blockIdx.x;
        const int rg = tid >> 3, c8 = tid & 7;
        float acc[8];
#pragma unroll
        for (int i = 0; i < 8; i++) acc[i] = 0.f;
        const __nv_bfloat16* base;
        int ld;
        bool active = true;
        if (b < 8) { base = wq + b * 64 + c8 * 8; ld = D_; }
        else if (b == 8) { base = (c8 < 2 ? wk + c8 * 8 : wv + (c8 - 2) * 8); ld = 16; active = c8 < 4; }
        else { base = w1 + (b - 9) * 64 + c8 * 8; ld = F_; }
        if (active) {
            uint4 v[16];
#pragma unroll
            for (int i = 0; i < 16; i++) v[i] = __ldg((const uint4*)(base + (size_t)(rg + 32 * i) * ld));
#pragma unroll
            for (int i = 0; i < 16; i++) {
                acc[0] += bf_lo(v[i].x); acc[1] += bf_hi(v[i].x); acc[2] += bf_lo(v[i].y); acc[3] += bf_hi(v[i].y);
                acc[4] += bf_lo(v[i].z); acc[5] += bf_hi(v[i].z); acc[6] += bf_lo(v[i].w); acc[7] += bf_hi(v[i].w);
            }
        }
#pragma unroll
        for (int i = 0; i < 8; i++) red[rg][c8 * 8 + i] = acc[i];
        __syncthreads();
        if (tid < 64) {
            float s = 0.f;
#pragma unroll
            for (int i = 0; i < 32; i++) s += red[i][tid];
            if (b < 8) g_cs_q[b * 64 + tid] = s;
            else if (b == 8) { if (tid < 32) g_cs_kv[tid] = s; }
            else g_cs_1[(b - 9) * 64 + tid] = s;
        }
    } else {
        const int cb = blockIdx.x - PREP_CS_CTAS;
        if (tid < 72) {
            const int line = cb * 72 + tid;
            const char* p = line < 4096 ? (const char*)wo + (size_t)line * 128 : (const char*)w2 + (size_t)(line - 4096) * 128;
            asm volatile("prefetch.global.L2 [%0];" ::"l"(p));
        }
        const int warp = tid >> 5, lane = tid & 31;
        const int row = cb * 8 + warp;
        const uint4* p = (const uint4*)(x + (size_t)row * D_ + lane * 16);
        const uint4 a = __ldg(p), b = __ldg(p + 1);
        float v[16] = {bf_lo(a.x), bf_hi(a.x), bf_lo(a.y), bf_hi(a.y), bf_lo(a.z), bf_hi(a.z), bf_lo(a.w), bf_hi(a.w),
                       bf_lo(b.x), bf_hi(b.x), bf_lo(b.y), bf_hi(b.y), bf_lo(b.z), bf_hi(b.z), bf_lo(b.w), bf_hi(b.w)};
        float s = 0.f;
#pragma unroll
        for (int i = 0; i < 16; i++) s += v[i];
        s += __shfl_xor_sync(0xffffffffu, s, 1);
        s += __shfl_xor_sync(0xffffffffu, s, 2);
        const float mean = s * (1.f / 64.f);
        float m2 = 0.f;
#pragma unroll
        for (int i = 0; i < 16; i++) { const float d = v[i] - mean; m2 += d * d; }
        m2 += __shfl_xor_sync(0xffffffffu, m2, 1);
        m2 += __shfl_xor_sync(0xffffffffu, m2, 2);
        if ((lane & 3) == 0) g_stats[0][(lane >> 2) * S_ + row] = make_float2(mean, m2);
    }
    if (tid == 0) { TL(0, 2); TL(0, 3); }
}

enum { EPI_QKV = 0, EPI_RES = 1, EPI_FFN1 = 2 };

struct GemmParams {
    const float2* stats_in;
    float2* stats_out;
    int wait_in_epilogue;
    int tk;
};

template <int BN> struct Geo;
template <> struct Geo<64> {
    static constexpr int BK = 64, A_BYTES = 128 * 128, A_SWZ = 1, A_SBO = 1024;
    static constexpr int B_BYTES = 64 * 128, B_SWZ = 1, B_LBO = 8192, B_SBO = 1024, B_KSTEP = 2048;
};
template <> struct Geo<224> {
    static constexpr int BK = 32, A_BYTES = 128 * 64, A_SWZ = 2, A_SBO = 512;
    static constexpr int B_BYTES = 7 * 32 * 64, B_SWZ = 2, B_LBO = 2048, B_SBO = 512, B_KSTEP = 1024;
};

template <int BN, int STAGES, int EPI> struct GemmSmem {
    static constexpr int XB_OFF = Geo<BN>::A_BYTES + Geo<BN>::B_BYTES;
    static constexpr int STAGE = XB_OFF + (EPI == EPI_QKV ? 2048 : 0);
    static constexpr int AUX_OFF = STAGES * STAGE;
    static constexpr int TOTAL = AUX_OFF + 1024;
};

__device__ __forceinline__ void load_row_stats(const float2* __restrict__ st, int row0, int c, float& mean0, float& rstd0, float& mean1, float& rstd1) {
    const float2 a0 = st[(2 * c) * S_ + row0], a1 = st[(2 * c + 1) * S_ + row0];
    const float2 b0 = st[(2 * c) * S_ + row0 + 8], b1 = st[(2 * c + 1) * S_ + row0 + 8];
    float sa = a0.x + a1.x, sb = b0.x + b1.x;
    sa += __shfl_xor_sync(0xffffffffu, sa, 1); sa += __shfl_xor_sync(0xffffffffu, sa, 2);
    sb += __shfl_xor_sync(0xffffffffu, sb, 1); sb += __shfl_xor_sync(0xffffffffu, sb, 2);
    mean0 = sa * 0.125f; mean1 = sb * 0.125f;
    float ma = a0.y + a1.y + 64.f * ((a0.x - mean0) * (a0.x - mean0) + (a1.x - mean0) * (a1.x - mean0));
    float mb = b0.y + b1.y + 64.f * ((b0.x - mean1) * (b0.x - mean1) + (b1.x - mean1) * (b1.x - mean1));
    ma += __shfl_xor_sync(0xffffffffu, ma, 1); ma += __shfl_xor_sync(0xffffffffu, ma, 2);
    mb += __shfl_xor_sync(0xffffffffu, mb, 1); mb += __shfl_xor_sync(0xffffffffu, mb, 2);
    rstd0 = 1.0f / sqrtf(ma * (1.f / 512.f) + 1e-5f);
    rstd1 = 1.0f / sqrtf(mb * (1.f / 512.f) + 1e-5f);
}

template <int BN, int KB, int STAGES, int EPI, int MC>
__device__ __forceinline__ void gemm_body(const CUtensorMap* mapA, const CUtensorMap* mapB, const CUtensorMap* mapB2, const CUtensorMap* mapR,
                                          const CUtensorMap* mapC, const GemmParams& prm, int tile_m, int tile_n, uint8_t* smem_raw) {
    using SM = GemmSmem<BN, STAGES, EPI>;
    using G = Geo<BN>;
    pdl_launch();
    const uint32_t sbase = smem_u32(smem_raw);
    if (sbase & 1023) __trap();
    uint8_t* sgen = smem_raw;
    const uint32_t bar_full = sbase + SM::AUX_OFF, bar_empty = bar_full + 8 * STAGES;
    float* s_cs = (float*)(sgen + SM::AUX_OFF + 128);
    float* s_red = (float*)(sgen + SM::AUX_OFF + 640);
    const bool xkv = EPI == EPI_QKV && tile_n < 2;
    const int tid = threadIdx.x, warp = tid >> 5, lane = tid & 31;
    const uint32_t rank = MC ? cluster_rank() : 0;
    if (tid == 0) TL(prm.tk, 0);

    constexpr bool INLINE_PROD = BN == 224;
    if (tid == (INLINE_PROD ? 0 : 256)) {
        prefetch_tmap(mapB); prefetch_tmap(mapA); prefetch_tmap(mapC);
        for (int s = 0; s < STAGES; s++) { mbar_init(bar_full + 8 * s, 1); mbar_init(bar_empty + 8 * s, MC ? 4 : 2); }
        fence_mbar_init();
    }
    __syncthreads();
    if (MC) cluster_sync();

    const int m0 = tile_m * 128, n0 = tile_n * BN;
    const uint32_t STAGE_TX = G::A_BYTES + G::B_BYTES + (xkv ? 2048 : 0);
    auto loadB = [&](int kb, int s) {
        const uint32_t dst = sbase + s * SM::STAGE + G::A_BYTES, bar = bar_full + 8 * s;
        if constexpr (BN == 64) {
            tma2d(dst, mapB, n0, kb * 64, bar);
            if (xkv) tma2d(dst + G::B_BYTES, mapB2, 0, kb * 64, bar);
        } else {
            if (rank == 0) tma3d_mc(dst, mapB, 0, kb * 32, tile_n * 7, bar, 3);
            else tma3d_mc(dst + 4 * 2048, mapB2, 0, kb * 32, tile_n * 7 + 4, bar, 3);
        }
    };
    auto loadA = [&](int kb, int s) {
        const uint32_t dst = sbase + s * SM::STAGE, bar = bar_full + 8 * s;
        if constexpr (MC == 1) tma2d_mc(dst + rank * (G::A_BYTES / 2), mapA, kb * G::BK, m0 + rank * 64, bar, 3);
        else { tma2d(dst, mapA, kb * G::BK, m0, bar); tma2d(dst + G::A_BYTES / 2, mapA, kb * G::BK, m0 + 64, bar); }
    };
    constexpr int PRE = STAGES < KB ? STAGES : KB;
    auto prologue_loads = [&]() {
        for (int kb = 0; kb < PRE; kb++) { mbar_expect_tx(bar_full + 8 * kb, STAGE_TX); loadB(kb, kb); }
        if (!prm.wait_in_epilogue) pdl_wait();
        for (int kb = 0; kb < PRE; kb++) loadA(kb, kb);
    };
    if (!INLINE_PROD && warp == 8) {
        if (lane == 0) {
            prologue_loads();
            int s = PRE % STAGES, ph = (PRE / STAGES) & 1;
            for (int kb = PRE; kb < KB; kb++) {
                mbar_wait(bar_empty + 8 * s, ph ^ 1);
                mbar_expect_tx(bar_full + 8 * s, STAGE_TX);
                loadB(kb, s);
                loadA(kb, s);
                if (++s == STAGES) { s = 0; ph ^= 1; }
            }
            if constexpr (EPI == EPI_RES) {
                mbar_wait(bar_empty + 8 * s, ph ^ 1);
                mbar_expect_tx(bar_full + 8 * s, 16384);
                tma2d(sbase + s * SM::STAGE, mapR, n0, m0, bar_full + 8 * s);
                tma2d(sbase + s * SM::STAGE + 8192, mapR, n0, m0 + 64, bar_full + 8 * s);
            }
        }
    } else {
        if (INLINE_PROD && tid == 0) prologue_loads();
        const int wg = warp >> 2, g = lane >> 2, c = lane & 3;
        float acc[BN / 2];
        float acx[8];
        const uint64_t dX0 = mkdesc(sbase + SM::XB_OFF, 16, 256, 3);
        const uint64_t dA0 = mkdesc(sbase + wg * (G::A_BYTES / 2), 16, G::A_SBO, G::A_SWZ);
        const uint64_t dB0 = mkdesc(sbase + G::A_BYTES, G::B_LBO, G::B_SBO, G::B_SWZ);
        int s = 0, ph = 0;
#pragma unroll 1
        for (int kb = 0; kb < KB; kb++) {
            mbar_wait(bar_full + 8 * s, ph);
            const uint64_t dA = dA0 + (uint64_t)(s * (SM::STAGE >> 4)), dB = dB0 + (uint64_t)(s * (SM::STAGE >> 4));
            wg_fence();
#pragma unroll
            for (int k = 0; k < G::BK / 16; k++) wgmma_ss_tb<BN>(acc, dA + (uint64_t)(k * 2), dB + (uint64_t)(k * (G::B_KSTEP >> 4)), (kb | k) != 0);
            if constexpr (EPI == EPI_QKV) {
                if (xkv) {
                    const uint64_t dX = dX0 + (uint64_t)(s * (SM::STAGE >> 4));
#pragma unroll
                    for (int k = 0; k < 4; k++) wgmma_ss_n16_tb(acx, dA + (uint64_t)(k * 2), dX + (uint64_t)(k * 32), (kb | k) != 0);
                }
            }
            wg_commit();
            if constexpr (BN <= 64) {
                wg_wait<0>();
                if ((tid & 127) == 0) {
                    if (MC) { mbar_arrive_remote(bar_empty + 8 * s, 0); mbar_arrive_remote(bar_empty + 8 * s, 1); }
                    else mbar_arrive(bar_empty + 8 * s);
                }
            } else if (kb > 0) {
                wg_wait<1>();
                const int sp = s == 0 ? STAGES - 1 : s - 1;
                if ((tid & 127) == 0) {
                    if (MC) { mbar_arrive_remote(bar_empty + 8 * sp, 0); mbar_arrive_remote(bar_empty + 8 * sp, 1); }
                    else mbar_arrive(bar_empty + 8 * sp);
                }
                if (INLINE_PROD && tid == 0 && kb - 1 + STAGES < KB) {
                    mbar_wait(bar_empty + 8 * sp, ((kb - 1) / STAGES) & 1);
                    mbar_expect_tx(bar_full + 8 * sp, STAGE_TX);
                    loadB(kb - 1 + STAGES, sp);
                    loadA(kb - 1 + STAGES, sp);
                }
                if (INLINE_PROD) __syncwarp();
            }
            if (++s == STAGES) { s = 0; ph ^= 1; }
        }
        pdl_wait();
        const int rloc = wg * 64 + (warp & 3) * 16 + g;
        const int row0 = m0 + rloc;
        float mean0 = 0.f, rstd0 = 1.f, mean1 = 0.f, rstd1 = 1.f;
        if constexpr (EPI != EPI_RES) {
            load_row_stats(prm.stats_in, row0, c, mean0, rstd0, mean1, rstd1);
            const float* cs = EPI == EPI_FFN1 ? g_cs_1 + n0 : g_cs_q + n0;
            if (tid < BN) s_cs[tid] = cs[tid];
        }
        wg_wait<0>();
        fence_regs(acc);
        if (tid == 0) TL(prm.tk, 2);
        if constexpr (EPI != EPI_RES) named_bar(1, 256);

        if constexpr (EPI == EPI_QKV) {
            if (xkv) {
                fence_regs(acx);
                const float rm0 = rstd0 * mean0, rm1 = rstd1 * mean1;
                float n0s = 0.f, n1s = 0.f, vmax = 0.f;
#pragma unroll
                for (int j = 0; j < 2; j++) {
                    const float2 cs2 = *(const float2*)(g_cs_kv + tile_n * 16 + 8 * j + 2 * c);
                    const uint32_t u0 = pack_bf16(acx[4 * j] * rstd0 - rm0 * cs2.x, acx[4 * j + 1] * rstd0 - rm0 * cs2.y);
                    const uint32_t u1 = pack_bf16(acx[4 * j + 2] * rstd1 - rm1 * cs2.x, acx[4 * j + 3] * rstd1 - rm1 * cs2.y);
                    n0s += bf_lo(u0) * bf_lo(u0) + bf_hi(u0) * bf_hi(u0);
                    n1s += bf_lo(u1) * bf_lo(u1) + bf_hi(u1) * bf_hi(u1);
                    vmax = fmaxf(vmax, fmaxf(fmaxf(fabsf(bf_lo(u0)), fabsf(bf_hi(u0))), fmaxf(fabsf(bf_lo(u1)), fabsf(bf_hi(u1)))));
                    if (tile_n == 0) {
                        *(uint32_t*)(g_kimg + (row0 >> 3) * 256 + j * 128 + g * 16 + c * 4) = u0;
                        *(uint32_t*)(g_kimg + ((row0 + 8) >> 3) * 256 + j * 128 + g * 16 + c * 4) = u1;
                    } else {
                        uint8_t* vb = g_vimg + (row0 >> 4) * 768 + j * 256 + g * 16 + c * 4;
                        *(uint32_t*)(vb) = u0;
                        *(uint32_t*)(vb + 128) = u1;
                    }
                }
                if (tile_n == 1) {
                    uint8_t* vb = g_vimg + (row0 >> 4) * 768 + 512 + g * 16 + c * 4;
                    const uint32_t one = c == 0 ? 0x00003F80u : 0u;
                    *(uint32_t*)(vb) = one;
                    *(uint32_t*)(vb + 128) = one;
                }
                n0s += __shfl_xor_sync(0xffffffffu, n0s, 1); n0s += __shfl_xor_sync(0xffffffffu, n0s, 2);
                n1s += __shfl_xor_sync(0xffffffffu, n1s, 1); n1s += __shfl_xor_sync(0xffffffffu, n1s, 2);
                float km = tile_n == 0 ? fmaxf(n0s, n1s) : vmax;
                if (!(n0s + n1s < INFINITY)) km = INFINITY;
#pragma unroll
                for (int o = 1; o < 32; o <<= 1) km = fmaxf(km, __shfl_xor_sync(0xffffffffu, km, o));
                if (lane == 0) s_red[warp] = km;
                named_bar(1, 256);
                if (tid == 0) {
                    float a = 0.f;
                    for (int i = 0; i < 8; i++) a = fmaxf(a, s_red[i]);
                    g_kvmax[tile_n * 16 + tile_m] = a;
                }
            }
        }
        if constexpr (BN == 64) {
            const uint32_t stile = sbase + (EPI == EPI_RES ? s * SM::STAGE : 0);
            const int mrow = wg * 64 + (warp & 3) * 16 + (lane & 7) + ((lane >> 3) & 1) * 8;
            const uint32_t rbase = stile + mrow * 128;
            if constexpr (EPI == EPI_RES) {
                mbar_wait(bar_full + 8 * s, ph);
                float s0 = 0.f, s1 = 0.f;
#pragma unroll
                for (int jj = 0; jj < 4; jj++) {
                    uint32_t r0, r1, r2, r3;
                    const uint32_t addr = rbase + (((2 * jj + (lane >> 4)) ^ (mrow & 7)) << 4);
                    ldsm_x4(r0, r1, r2, r3, addr);
                    const uint32_t u0 = pack_bf16(acc[8 * jj] + bf_lo(r0), acc[8 * jj + 1] + bf_hi(r0));
                    const uint32_t u1 = pack_bf16(acc[8 * jj + 2] + bf_lo(r1), acc[8 * jj + 3] + bf_hi(r1));
                    const uint32_t u2 = pack_bf16(acc[8 * jj + 4] + bf_lo(r2), acc[8 * jj + 5] + bf_hi(r2));
                    const uint32_t u3 = pack_bf16(acc[8 * jj + 6] + bf_lo(r3), acc[8 * jj + 7] + bf_hi(r3));
                    stsm_x4(addr, u0, u1, u2, u3);
                    acc[8 * jj] = bf_lo(u0); acc[8 * jj + 1] = bf_hi(u0); acc[8 * jj + 4] = bf_lo(u2); acc[8 * jj + 5] = bf_hi(u2);
                    acc[8 * jj + 2] = bf_lo(u1); acc[8 * jj + 3] = bf_hi(u1); acc[8 * jj + 6] = bf_lo(u3); acc[8 * jj + 7] = bf_hi(u3);
                    s0 += (acc[8 * jj] + acc[8 * jj + 1]) + (acc[8 * jj + 4] + acc[8 * jj + 5]);
                    s1 += (acc[8 * jj + 2] + acc[8 * jj + 3]) + (acc[8 * jj + 6] + acc[8 * jj + 7]);
                }
                fence_async_smem();
                named_bar(2 + wg, 128);
                if ((tid & 127) == 0) { tma2d_store(mapC, stile + wg * 8192, n0, m0 + wg * 64); bulk_commit(); }
                if (prm.stats_out) {
                    s0 += __shfl_xor_sync(0xffffffffu, s0, 1); s0 += __shfl_xor_sync(0xffffffffu, s0, 2);
                    s1 += __shfl_xor_sync(0xffffffffu, s1, 1); s1 += __shfl_xor_sync(0xffffffffu, s1, 2);
                    const float mu0 = s0 * (1.f / 64.f), mu1 = s1 * (1.f / 64.f);
                    float q0 = 0.f, q1 = 0.f;
#pragma unroll
                    for (int j = 0; j < 8; j++) {
                        float d;
                        d = acc[4 * j] - mu0; q0 += d * d; d = acc[4 * j + 1] - mu0; q0 += d * d;
                        d = acc[4 * j + 2] - mu1; q1 += d * d; d = acc[4 * j + 3] - mu1; q1 += d * d;
                    }
                    q0 += __shfl_xor_sync(0xffffffffu, q0, 1); q0 += __shfl_xor_sync(0xffffffffu, q0, 2);
                    q1 += __shfl_xor_sync(0xffffffffu, q1, 1); q1 += __shfl_xor_sync(0xffffffffu, q1, 2);
                    if (c == 0) {
                        prm.stats_out[tile_n * S_ + row0] = make_float2(mu0, q0);
                        prm.stats_out[tile_n * S_ + row0 + 8] = make_float2(mu1, q1);
                    }
                }
            } else {
                const float sc = 0.25f * 1.4426950408889634f;
                const float a0 = rstd0 * sc, a1 = rstd1 * sc, rm0 = a0 * mean0, rm1 = a1 * mean1;
#pragma unroll
                for (int jj = 0; jj < 4; jj++) {
                    const float2 ca = *(const float2*)(s_cs + 16 * jj + 2 * c), cb = *(const float2*)(s_cs + 16 * jj + 8 + 2 * c);
                    const uint32_t u0 = pack_bf16(acc[8 * jj] * a0 - rm0 * ca.x, acc[8 * jj + 1] * a0 - rm0 * ca.y);
                    const uint32_t u1 = pack_bf16(acc[8 * jj + 2] * a1 - rm1 * ca.x, acc[8 * jj + 3] * a1 - rm1 * ca.y);
                    const uint32_t u2 = pack_bf16(acc[8 * jj + 4] * a0 - rm0 * cb.x, acc[8 * jj + 5] * a0 - rm0 * cb.y);
                    const uint32_t u3 = pack_bf16(acc[8 * jj + 6] * a1 - rm1 * cb.x, acc[8 * jj + 7] * a1 - rm1 * cb.y);
                    stsm_x4(rbase + (((2 * jj + (lane >> 4)) ^ (mrow & 7)) << 4), u0, u1, u2, u3);
                }
                fence_async_smem();
                named_bar(2 + wg, 128);
                if ((tid & 127) == 0) { tma2d_store(mapC, stile + wg * 8192, n0, m0 + wg * 64); bulk_commit(); }
            }
            if ((tid & 127) == 0) bulk_wait_read();
        } else {
            const uint32_t stile = sbase + wg * (7 * 4096);
            const int mrow = (warp & 3) * 16 + (lane & 7) + ((lane >> 3) & 1) * 8;
            const float a0 = 0.5f * rstd0, a1 = 0.5f * rstd1, rm0 = a0 * mean0, rm1 = a1 * mean1;
#pragma unroll
            for (int jj = 0; jj < 14; jj++) {
                const float2 ca = *(const float2*)(s_cs + 16 * jj + 2 * c), cb = *(const float2*)(s_cs + 16 * jj + 8 + 2 * c);
                float y[8] = {acc[8 * jj] * a0 - rm0 * ca.x,     acc[8 * jj + 1] * a0 - rm0 * ca.y,
                              acc[8 * jj + 2] * a1 - rm1 * ca.x, acc[8 * jj + 3] * a1 - rm1 * ca.y,
                              acc[8 * jj + 4] * a0 - rm0 * cb.x, acc[8 * jj + 5] * a0 - rm0 * cb.y,
                              acc[8 * jj + 6] * a1 - rm1 * cb.x, acc[8 * jj + 7] * a1 - rm1 * cb.y};
#pragma unroll
                for (int i = 0; i < 8; i++) {
                    float t;
                    asm("tanh.approx.f32 %0, %1;" : "=f"(t) : "f"(y[i]));
                    y[i] = fmaf(y[i], t, y[i]);
                }
                const int chunk = (2 * jj + (lane >> 4)) & 3, blk = jj >> 1;
                stsm_x4(stile + blk * 4096 + mrow * 64 + ((chunk ^ ((mrow >> 1) & 3)) << 4),
                        pack_bf16(y[0], y[1]), pack_bf16(y[2], y[3]), pack_bf16(y[4], y[5]), pack_bf16(y[6], y[7]));
                if (jj & 1) {
                    fence_async_smem();
                    __syncwarp();
                    if (lane == 0) {
                        tma2d_store(mapC, stile + blk * 4096 + (warp & 3) * 1024, n0 + blk * 32, m0 + wg * 64 + (warp & 3) * 16);
                        bulk_commit();
                    }
                }
            }
            if (lane == 0) bulk_wait_read();
        }
    }
    if (tid == 0) TL(prm.tk, 3);
    if (MC) cluster_sync();
}

#define WO_ST 5
#define F2_ST 5
#define F1_ST 4
constexpr int QKV_STAGES = 4, WO_STAGES = WO_ST, FFN2_STAGES = F2_ST, FFN1_STAGES = F1_ST;
__global__ void __launch_bounds__(288) qkv_kernel(const __grid_constant__ CUtensorMap mapA, const __grid_constant__ CUtensorMap mapWq,
                                                  const __grid_constant__ CUtensorMap mapWk, const __grid_constant__ CUtensorMap mapWv,
                                                  const __grid_constant__ CUtensorMap mapQ, const GemmParams prm) {
    extern __shared__ __align__(1024) uint8_t smem_raw[];
    uint32_t pad[64];
#pragma unroll
    for (int i = 0; i < 64; i++) asm volatile("mov.u32 %0, %%clock;" : "=r"(pad[i]));
    const int tn = blockIdx.x & 7;
    gemm_body<64, 8, QKV_STAGES, EPI_QKV, 1>(&mapA, &mapWq, tn == 0 ? &mapWk : &mapWv, &mapA, &mapQ, prm, blockIdx.x >> 3, tn, smem_raw);
    if (prm.stats_in == nullptr) {
#pragma unroll
        for (int i = 0; i < 64; i++) asm volatile("st.volatile.global.u32 [%0], %1;" ::"l"(g_kimg + 4 * i), "r"(pad[i]) : "memory");
    }
}
template <int KB, int STAGES>
__global__ void __launch_bounds__(288) res_gemm_kernel(const __grid_constant__ CUtensorMap mapA, const __grid_constant__ CUtensorMap mapW,
                                                       const __grid_constant__ CUtensorMap mapR, const __grid_constant__ CUtensorMap mapC, const GemmParams prm) {
    extern __shared__ __align__(1024) uint8_t smem_raw[];
    gemm_body<64, KB, STAGES, EPI_RES, 1>(&mapA, &mapW, &mapW, &mapR, &mapC, prm, blockIdx.x >> 3, blockIdx.x & 7, smem_raw);
}
__global__ void __launch_bounds__(256) ffn1_kernel(const __grid_constant__ CUtensorMap mapA, const __grid_constant__ CUtensorMap mapW4,
                                                   const __grid_constant__ CUtensorMap mapW3, const __grid_constant__ CUtensorMap mapH, const GemmParams prm) {
    extern __shared__ __align__(1024) uint8_t smem_raw[];
    const int pair = blockIdx.x >> 1, tile_n = pair & 7, tile_m = (pair >> 3) * 2 + (blockIdx.x & 1);
    gemm_body<224, 16, FFN1_STAGES, EPI_FFN1, 2>(&mapA, &mapW4, &mapW3, &mapA, &mapH, prm, tile_m, tile_n, smem_raw);
}

constexpr int NPOLY = 10;
__host__ __device__ constexpr bool is_mufu(int i) { return ((i + 1) * (16 - NPOLY)) / 16 != (i * (16 - NPOLY)) / 16; }

__device__ __forceinline__ float ex2(float x) { float r; asm("ex2.approx.ftz.f32 %0, %1;" : "=f"(r) : "f"(x)); return r; }
__device__ __forceinline__ uint32_t exp_pair_mufu(float a, float b) { return pack_bf16(ex2(a), ex2(b)); }
__device__ __forceinline__ uint32_t exp_pair_fma(float a, float b, uint32_t c3f) {
    constexpr float MAGIC = 98430.4140625f;
    const float ta = a + MAGIC, tb = b + (MAGIC - 143.5f);
    uint32_t y, m, r;
    asm("mad.lo.u32 %0, %1, 65536, %2;" : "=r"(y) : "r"(__float_as_uint(tb)), "r"(__float_as_uint(ta)));
    asm("lop3.b32 %0, %1, 0x007F007F, %2, 0xEA;" : "=r"(m) : "r"(y), "r"(c3f));
    const uint32_t e = y & 0xFF80FF80u;
    asm("fma.rn.bf16x2 %0, %1, %2, %3;" : "=r"(r) : "r"(y), "r"(m), "r"(e));
    return r;
}

constexpr int KCH = 256, NCH = S_ / KCH;
constexpr int K_BYTES = S_ * 32, V_BYTES = (S_ / 16) * 768;
constexpr int ATT_SMEM = K_BYTES + V_BYTES;

__global__ void __launch_bounds__(512, 1) attn_kernel(int tk) {
    extern __shared__ __align__(1024) uint8_t smem[];
    __shared__ uint64_t bars[NCH];
    __shared__ int s_slow;
    const int tid = threadIdx.x, wg = tid >> 7, warp = (tid >> 5) & 3, lane = tid & 31;
    const uint32_t sK = smem_u32(smem), sV = sK + K_BYTES;
    if (tid == 0) TL(tk, 0);
    if (tid == 0) {
        for (int i = 0; i < NCH; i++) mbar_init(smem_u32(&bars[i]), 1);
        s_slow = 0;
        fence_mbar_init();
    }
    __syncthreads();
    pdl_launch();
    pdl_wait();
    if (tid == 0) TL(tk, 1);
    if (tid == 0) {
        for (int i = 0; i < NCH; i++) {
            mbar_expect_tx(smem_u32(&bars[i]), KCH * 32 + (KCH / 16) * 768);
            bulk_load(sK + i * KCH * 32, g_kimg + i * KCH * 32, KCH * 32, smem_u32(&bars[i]));
            bulk_load(sV + i * (KCH / 16) * 768, g_vimg + i * (KCH / 16) * 768, (KCH / 16) * 768, smem_u32(&bars[i]));
        }
    }
    const int tb = blockIdx.x >> 3, hg = blockIdx.x & 7;
    const int head = hg * 4 + wg;
    const int g = lane >> 2, c = lane & 3;
    uint32_t qa[2][4];
    float qn = 0.f;
#pragma unroll
    for (int m = 0; m < 2; m++) {
        const int row = tb * 128 + m * 64 + warp * 16 + g;
        const uint32_t* p0 = (const uint32_t*)(g_q + (size_t)row * D_ + head * 16);
        const uint32_t* p1 = (const uint32_t*)(g_q + (size_t)(row + 8) * D_ + head * 16);
        qa[m][0] = p0[c]; qa[m][1] = p1[c]; qa[m][2] = p0[c + 4]; qa[m][3] = p1[c + 4];
        float n0 = bf_lo(qa[m][0]) * bf_lo(qa[m][0]) + bf_hi(qa[m][0]) * bf_hi(qa[m][0]) + bf_lo(qa[m][2]) * bf_lo(qa[m][2]) + bf_hi(qa[m][2]) * bf_hi(qa[m][2]);
        float n1 = bf_lo(qa[m][1]) * bf_lo(qa[m][1]) + bf_hi(qa[m][1]) * bf_hi(qa[m][1]) + bf_lo(qa[m][3]) * bf_lo(qa[m][3]) + bf_hi(qa[m][3]) * bf_hi(qa[m][3]);
        n0 += __shfl_xor_sync(0xffffffffu, n0, 1); n0 += __shfl_xor_sync(0xffffffffu, n0, 2);
        n1 += __shfl_xor_sync(0xffffffffu, n1, 1); n1 += __shfl_xor_sync(0xffffffffu, n1, 2);
        if (!(n0 == n0) || !(n1 == n1)) n0 = __int_as_float(0x7f800000);
        qn = fmaxf(qn, fmaxf(n0, n1));
    }
    {
        float km = 0.f, vm = 0.f;
#pragma unroll
        for (int i = 0; i < 16; i++) { km = fmaxf(km, g_kvmax[i]); vm = fmaxf(vm, g_kvmax[16 + i]); }
        const bool ok = (qn * km <= 10000.f) && (vm <= 16384.f);
        if (!ok) s_slow = 1;
    }
    float oacc[2][12];
#pragma unroll
    for (int m = 0; m < 2; m++)
#pragma unroll
        for (int i = 0; i < 12; i++) oacc[m][i] = 0.f;
    __syncthreads();
    const bool slow = s_slow != 0;

    const uint64_t dK0 = mkdesc(sK, 128, 256, 0);
    const uint64_t dV0 = mkdesc(sV, 128, 256, 0);
    uint32_t c3f;
    asm volatile("mov.b32 %0, 0x3F003F00;" : "=r"(c3f));
    if (!slow) {
#pragma unroll 1
        for (int t = 0; t < S_ / 64; t++) {
            if ((t & 3) == 0) mbar_wait(smem_u32(&bars[t >> 2]), 0);
            const uint64_t dK = dK0 + (uint64_t)(t * 64 * 32 / 16);
            const uint64_t dV = dV0 + (uint64_t)(t * 4 * 768 / 16);
#pragma unroll
            for (int m = 0; m < 2; m++) {
                float s[32];
                wg_fence();
                wgmma_rs_n64_z(s, qa[m][0], qa[m][1], qa[m][2], qa[m][3], dK);
                wg_commit();
                wg_wait<0>();
                fence_regs(s);
                uint32_t p[16];
#pragma unroll
                for (int i = 0; i < 16; i++) p[i] = is_mufu(i) ? exp_pair_mufu(s[2 * i], s[2 * i + 1]) : exp_pair_fma(s[2 * i], s[2 * i + 1], c3f);
                wg_fence();
#pragma unroll
                for (int kk = 0; kk < 4; kk++)
                    wgmma_rs_n24_tb(oacc[m], p[4 * kk], p[4 * kk + 1], p[4 * kk + 2], p[4 * kk + 3], dV + (uint64_t)(kk * 768 / 16));
                wg_commit();
            }
        }
        wg_wait<0>();
    } else {
        float mx[2][2] = {{-INFINITY, -INFINITY}, {-INFINITY, -INFINITY}};
#pragma unroll 1
        for (int t = 0; t < S_ / 64; t++) {
            if ((t & 3) == 0) mbar_wait(smem_u32(&bars[t >> 2]), 0);
            const uint64_t dK = dK0 + (uint64_t)(t * 64 * 32 / 16);
            const uint64_t dV = dV0 + (uint64_t)(t * 4 * 768 / 16);
#pragma unroll
            for (int m = 0; m < 2; m++) {
                float s[32];
                wg_fence();
                wgmma_rs_n64_z(s, qa[m][0], qa[m][1], qa[m][2], qa[m][3], dK);
                wg_commit();
                wg_wait<0>();
                fence_regs(s);
                fence_regs(oacc[m]);
                float r0 = mx[m][0], r1 = mx[m][1];
#pragma unroll
                for (int j = 0; j < 8; j++) {
                    r0 = fmaxf(r0, fmaxf(s[4 * j], s[4 * j + 1]));
                    r1 = fmaxf(r1, fmaxf(s[4 * j + 2], s[4 * j + 3]));
                }
                r0 = fmaxf(r0, __shfl_xor_sync(0xffffffffu, r0, 1)); r0 = fmaxf(r0, __shfl_xor_sync(0xffffffffu, r0, 2));
                r1 = fmaxf(r1, __shfl_xor_sync(0xffffffffu, r1, 1)); r1 = fmaxf(r1, __shfl_xor_sync(0xffffffffu, r1, 2));
                const float al0 = ex2(mx[m][0] - r0), al1 = ex2(mx[m][1] - r1);
                mx[m][0] = r0; mx[m][1] = r1;
#pragma unroll
                for (int j = 0; j < 3; j++) {
                    oacc[m][4 * j] *= al0; oacc[m][4 * j + 1] *= al0;
                    oacc[m][4 * j + 2] *= al1; oacc[m][4 * j + 3] *= al1;
                }
                uint32_t p[16];
#pragma unroll
                for (int j = 0; j < 8; j++) {
                    p[2 * j] = pack_bf16(ex2(s[4 * j] - r0), ex2(s[4 * j + 1] - r0));
                    p[2 * j + 1] = pack_bf16(ex2(s[4 * j + 2] - r1), ex2(s[4 * j + 3] - r1));
                }
                fence_regs(oacc[m]);
                wg_fence();
#pragma unroll
                for (int kk = 0; kk < 4; kk++)
                    wgmma_rs_n24_tb(oacc[m], p[4 * kk], p[4 * kk + 1], p[4 * kk + 2], p[4 * kk + 3], dV + (uint64_t)(kk * 768 / 16));
                wg_commit();
                wg_wait<0>();
            }
        }
    }
    fence_regs(oacc[0]); fence_regs(oacc[1]);
    if (tid == 0) TL(tk, 2);
#pragma unroll
    for (int m = 0; m < 2; m++) {
        const float l0 = __shfl_sync(0xffffffffu, oacc[m][8], lane & ~3);
        const float l1 = __shfl_sync(0xffffffffu, oacc[m][10], lane & ~3);
        const float r0 = 1.0f / l0, r1 = 1.0f / l1;
        const int row = tb * 128 + m * 64 + warp * 16 + g;
        uint32_t* p0 = (uint32_t*)(g_o + (size_t)row * D_ + head * 16);
        uint32_t* p1 = (uint32_t*)(g_o + (size_t)(row + 8) * D_ + head * 16);
        p0[c] = pack_bf16(oacc[m][0] * r0, oacc[m][1] * r0);
        p1[c] = pack_bf16(oacc[m][2] * r1, oacc[m][3] * r1);
        p0[c + 4] = pack_bf16(oacc[m][4] * r0, oacc[m][5] * r0);
        p1[c + 4] = pack_bf16(oacc[m][6] * r1, oacc[m][7] * r1);
    }
    if (tid == 0) TL(tk, 3);
}

typedef CUresult (*EncodeFn)(CUtensorMap*, CUtensorMapDataType, cuuint32_t, void*, const cuuint64_t*, const cuuint64_t*, const cuuint32_t*,
                             const cuuint32_t*, CUtensorMapInterleave, CUtensorMapSwizzle, CUtensorMapL2promotion, CUtensorMapFloatOOBfill);

EncodeFn get_encode() {
    static EncodeFn fn = nullptr;
    if (!fn) {
        void* p = nullptr;
        cudaDriverEntryPointQueryResult qr;
        cudaGetDriverEntryPoint("cuTensorMapEncodeTiled", &p, cudaEnableDefault, &qr);
        fn = (EncodeFn)p;
    }
    return fn;
}
CUtensorMap map2d(const void* ptr, uint64_t cols, uint64_t rows, uint32_t bc, uint32_t br, CUtensorMapSwizzle sw) {
    CUtensorMap m;
    cuuint64_t gd[2] = {cols, rows}, gs[1] = {cols * 2};
    cuuint32_t bx[2] = {bc, br}, es[2] = {1, 1};
    get_encode()(&m, CU_TENSOR_MAP_DATA_TYPE_BFLOAT16, 2, (void*)ptr, gd, gs, bx, es, CU_TENSOR_MAP_INTERLEAVE_NONE, sw,
                 CU_TENSOR_MAP_L2_PROMOTION_L2_128B, CU_TENSOR_MAP_FLOAT_OOB_FILL_NONE);
    return m;
}
CUtensorMap map3d32(const void* ptr, uint64_t cols, uint64_t rows, uint32_t br, uint32_t nb) {
    CUtensorMap m;
    cuuint64_t gd[3] = {32, rows, cols / 32}, gs[2] = {cols * 2, 64};
    cuuint32_t bx[3] = {32, br, nb}, es[3] = {1, 1, 1};
    get_encode()(&m, CU_TENSOR_MAP_DATA_TYPE_BFLOAT16, 3, (void*)ptr, gd, gs, bx, es, CU_TENSOR_MAP_INTERLEAVE_NONE, CU_TENSOR_MAP_SWIZZLE_64B,
                 CU_TENSOR_MAP_L2_PROMOTION_L2_128B, CU_TENSOR_MAP_FLOAT_OOB_FILL_NONE);
    return m;
}

template <typename... KArgs, typename... Args>
void launch(void (*kern)(KArgs...), int grid, int block, int smem, int cluster, bool pdl, Args... args) {
    cudaLaunchConfig_t cfg = {};
    cfg.gridDim = dim3(grid);
    cfg.blockDim = dim3(block);
    cfg.dynamicSmemBytes = smem;
    cfg.stream = cudaStreamPerThread;
    cudaLaunchAttribute at[2];
    int n = 0;
    if (cluster > 1) { at[n].id = cudaLaunchAttributeClusterDimension; at[n].val.clusterDim.x = cluster; at[n].val.clusterDim.y = 1; at[n].val.clusterDim.z = 1; n++; }
    if (pdl) { at[n].id = cudaLaunchAttributeProgrammaticStreamSerialization; at[n].val.programmaticStreamSerializationAllowed = 1; n++; }
    cfg.attrs = at;
    cfg.numAttrs = n;
    cudaLaunchKernelEx(&cfg, kern, KArgs(args)...);
}

template <typename T> void* sym(const T& s) { void* p = nullptr; cudaGetSymbolAddress(&p, s); return p; }

}

extern "C" void kernel_launch(void* const* d_in, const int* in_sizes, int n_in, void* d_out, int out_size) {
    const __nv_bfloat16* x = (const __nv_bfloat16*)d_in[0];
    const __nv_bfloat16* wq = (const __nv_bfloat16*)d_in[1];
    const __nv_bfloat16* wk = (const __nv_bfloat16*)d_in[2];
    const __nv_bfloat16* wv = (const __nv_bfloat16*)d_in[3];
    const __nv_bfloat16* wo = (const __nv_bfloat16*)d_in[4];
    const __nv_bfloat16* w1 = (const __nv_bfloat16*)d_in[6];
    const __nv_bfloat16* w2 = (const __nv_bfloat16*)d_in[7];

    constexpr int SM_QKV = GemmSmem<64, QKV_STAGES, EPI_QKV>::TOTAL;
    constexpr int SM_WO = GemmSmem<64, WO_STAGES, EPI_RES>::TOTAL, SM_FFN2 = GemmSmem<64, FFN2_STAGES, EPI_RES>::TOTAL;
    constexpr int SM_FFN1 = GemmSmem<224, FFN1_STAGES, EPI_FFN1>::TOTAL;
    cudaFuncSetAttribute(qkv_kernel, cudaFuncAttributeMaxDynamicSharedMemorySize, SM_QKV);
    cudaFuncSetAttribute(res_gemm_kernel<8, WO_STAGES>, cudaFuncAttributeMaxDynamicSharedMemorySize, SM_WO);
    cudaFuncSetAttribute(ffn1_kernel, cudaFuncAttributeMaxDynamicSharedMemorySize, SM_FFN1);
    cudaFuncSetAttribute(res_gemm_kernel<28, FFN2_STAGES>, cudaFuncAttributeMaxDynamicSharedMemorySize, SM_FFN2);
    cudaFuncSetAttribute(attn_kernel, cudaFuncAttributeMaxDynamicSharedMemorySize, ATT_SMEM);
    cudaFuncSetAttribute(prep_kernel, cudaFuncAttributePreferredSharedMemoryCarveout, 100);
    cudaFuncSetAttribute(qkv_kernel, cudaFuncAttributePreferredSharedMemoryCarveout, 100);
    cudaFuncSetAttribute(res_gemm_kernel<8, WO_STAGES>, cudaFuncAttributePreferredSharedMemoryCarveout, 100);
    cudaFuncSetAttribute(ffn1_kernel, cudaFuncAttributePreferredSharedMemoryCarveout, 100);
    cudaFuncSetAttribute(res_gemm_kernel<28, FFN2_STAGES>, cudaFuncAttributePreferredSharedMemoryCarveout, 100);
    cudaFuncSetAttribute(attn_kernel, cudaFuncAttributePreferredSharedMemoryCarveout, 100);

    void *q = sym(g_q), *o = sym(g_o), *x1 = sym(g_x1), *x2 = sym(g_x2), *x3 = sym(g_x3), *h = sym(g_h);
    float2* stats = (float2*)sym(g_stats);
    const void* xs[5] = {x, x1, x2, x3, d_out};

    const CUtensorMapSwizzle SW128 = CU_TENSOR_MAP_SWIZZLE_128B, SW64 = CU_TENSOR_MAP_SWIZZLE_64B;
    const CUtensorMap mWq = map2d(wq, D_, D_, 64, 64, SW128);
    const CUtensorMap mWk = map2d(wk, 16, D_, 16, 64, CU_TENSOR_MAP_SWIZZLE_32B);
    const CUtensorMap mWv = map2d(wv, 16, D_, 16, 64, CU_TENSOR_MAP_SWIZZLE_32B);
    const CUtensorMap mWo = map2d(wo, D_, D_, 64, 64, SW128);
    const CUtensorMap mW1a = map3d32(w1, F_, D_, 32, 4), mW1b = map3d32(w1, F_, D_, 32, 3);
    const CUtensorMap mW2 = map2d(w2, D_, F_, 64, 64, SW128);
    const CUtensorMap mQ = map2d(q, D_, S_, 64, 64, SW128);
    const CUtensorMap mO = map2d(o, D_, S_, 64, 64, SW128);
    const CUtensorMap mHst = map2d(h, F_, S_, 32, 16, SW64);
    const CUtensorMap mHld = map2d(h, F_, S_, 64, 64, SW128);
    CUtensorMap mX[5], mX32[2];
    for (int i = 0; i < 5; i++) mX[i] = map2d(xs[i], D_, S_, 64, 64, SW128);
    mX32[0] = map2d(x1, D_, S_, 32, 64, SW64);
    mX32[1] = map2d(x3, D_, S_, 32, 64, SW64);

    launch(prep_kernel, PREP_CS_CTAS + PREP_STAT_CTAS, 256, 0, 1, false, x, wq, wk, wv, wo, w1, w2);
    for (int layer = 0; layer < 2; layer++) {
        const int xi = layer * 2;
        GemmParams p;
        p.stats_in = stats + (size_t)xi * 8 * S_; p.stats_out = nullptr; p.wait_in_epilogue = layer == 0; p.tk = 1 + 5 * layer;
        launch(qkv_kernel, 128, 288, SM_QKV, 2, true, mX[xi], mWq, mWk, mWv, mQ, p);
        launch(attn_kernel, 128, 512, ATT_SMEM, 1, true, 2 + 5 * layer);
        p.stats_in = nullptr; p.stats_out = stats + (size_t)(xi + 1) * 8 * S_; p.wait_in_epilogue = 0; p.tk = 3 + 5 * layer;
        launch(res_gemm_kernel<8, WO_STAGES>, 128, 288, SM_WO, 2, true, mO, mWo, mX[xi], mX[xi + 1], p);
        p.stats_in = stats + (size_t)(xi + 1) * 8 * S_; p.stats_out = nullptr; p.tk = 4 + 5 * layer;
        launch(ffn1_kernel, 128, 256, SM_FFN1, 2, true, mX32[layer], mW1a, mW1b, mHst, p);
        p.stats_in = nullptr; p.stats_out = layer == 0 ? stats + (size_t)2 * 8 * S_ : nullptr; p.tk = 5 + 5 * layer;
        launch(res_gemm_kernel<28, FFN2_STAGES>, 128, 288, SM_FFN2, 2, true, mHld, mW2, mX[xi + 1], mX[xi + 2], p);
    }
}
```

```cpp
#include <cuda_runtime.h>
#include <cuda_bf16.h>
#include <cuda.h>
#include <stdint.h>

namespace {

constexpr int S_ = 2048, D_ = 512, H_ = 32, F_ = 1792;

__device__ __align__(1024) __nv_bfloat16 g_q[S_ * D_];
__device__ __align__(1024) __nv_bfloat16 g_o[S_ * D_];
__device__ __align__(1024) __nv_bfloat16 g_x1[S_ * D_];
__device__ __align__(1024) __nv_bfloat16 g_x2[S_ * D_];
__device__ __align__(1024) __nv_bfloat16 g_x3[S_ * D_];
__device__ __align__(1024) __nv_bfloat16 g_h[S_ * F_];
__device__ __align__(1024) uint8_t g_kimg[S_ * 32];
__device__ __align__(1024) uint8_t g_vimg[(S_ / 16) * 768];
__device__ __align__(1024) float2 g_stats[4][8 * S_];
__device__ __align__(16) float g_cs_q[D_];
__device__ __align__(16) float g_cs_kv[32];
__device__ __align__(16) float g_cs_1[F_];
__device__ __align__(16) float g_kvmax[32];

#define TL(k, slot)

__device__ __forceinline__ uint32_t smem_u32(const void* p) { return (uint32_t)__cvta_generic_to_shared(p); }
__device__ __forceinline__ void mbar_init(uint32_t bar, uint32_t cnt) {
    asm volatile("mbarrier.init.shared::cta.b64 [%0], %1;" ::"r"(bar), "r"(cnt));
}
__device__ __forceinline__ void mbar_expect_tx(uint32_t bar, uint32_t bytes) {
    asm volatile("mbarrier.arrive.expect_tx.shared::cta.b64 _, [%0], %1;" ::"r"(bar), "r"(bytes) : "memory");
}
__device__ __forceinline__ void mbar_arrive(uint32_t bar) {
    asm volatile("mbarrier.arrive.shared::cta.b64 _, [%0];" ::"r"(bar) : "memory");
}
__device__ __forceinline__ void mbar_arrive_remote(uint32_t bar, uint32_t cta) {
    asm volatile("{\n.reg .b32 ra;\nmapa.shared::cluster.u32 ra, %0, %1;\nmbarrier.arrive.shared::cluster.b64 _, [ra];\n}" ::"r"(bar), "r"(cta) : "memory");
}
__device__ __forceinline__ void mbar_wait(uint32_t bar, uint32_t parity) {
    asm volatile("{\n.reg .pred p;\nWAIT_%=:\nmbarrier.try_wait.parity.shared::cta.b64 p, [%0], %1;\n@p bra DONE_%=;\nbra WAIT_%=;\nDONE_%=:\n}" ::"r"(bar), "r"(parity) : "memory");
}
__device__ __forceinline__ void bulk_load(uint32_t dst, const void* src, uint32_t bytes, uint32_t bar) {
    asm volatile("cp.async.bulk.shared::cluster.global.mbarrier::complete_tx::bytes [%0], [%1], %2, [%3];" ::"r"(dst), "l"(src), "r"(bytes), "r"(bar) : "memory");
}
__device__ __forceinline__ void tma2d(uint32_t dst, const CUtensorMap* m, int c0, int c1, uint32_t bar) {
    asm volatile("cp.async.bulk.tensor.2d.shared::cluster.global.mbarrier::complete_tx::bytes [%0], [%1, {%3, %4}], [%2];" ::"r"(dst), "l"(m), "r"(bar), "r"(c0), "r"(c1) : "memory");
}
__device__ __forceinline__ void tma2d_mc(uint32_t dst, const CUtensorMap* m, int c0, int c1, uint32_t bar, uint16_t mask) {
    asm volatile("cp.async.bulk.tensor.2d.shared::cluster.global.mbarrier::complete_tx::bytes.multicast::cluster [%0], [%1, {%3, %4}], [%2], %5;" ::"r"(dst), "l"(m), "r"(bar), "r"(c0), "r"(c1), "h"(mask) : "memory");
}
__device__ __forceinline__ void tma3d(uint32_t dst, const CUtensorMap* m, int c0, int c1, int c2, uint32_t bar) {
    asm volatile("cp.async.bulk.tensor.3d.shared::cluster.global.mbarrier::complete_tx::bytes [%0], [%1, {%3, %4, %5}], [%2];" ::"r"(dst), "l"(m), "r"(bar), "r"(c0), "r"(c1), "r"(c2) : "memory");
}
__device__ __forceinline__ void tma3d_mc(uint32_t dst, const CUtensorMap* m, int c0, int c1, int c2, uint32_t bar, uint16_t mask) {
    asm volatile("cp.async.bulk.tensor.3d.shared::cluster.global.mbarrier::complete_tx::bytes.multicast::cluster [%0], [%1, {%3, %4, %5}], [%2], %6;" ::"r"(dst), "l"(m), "r"(bar), "r"(c0), "r"(c1), "r"(c2), "h"(mask) : "memory");
}
__device__ __forceinline__ void tma2d_store(const CUtensorMap* m, uint32_t src, int c0, int c1) {
    asm volatile("cp.async.bulk.tensor.2d.global.shared::cta.bulk_group [%0, {%2, %3}], [%1];" ::"l"(m), "r"(src), "r"(c0), "r"(c1) : "memory");
}
__device__ __forceinline__ void tma3d_store(const CUtensorMap* m, uint32_t src, int c0, int c1, int c2) {
    asm volatile("cp.async.bulk.tensor.3d.global.shared::cta.bulk_group [%0, {%2, %3, %4}], [%1];" ::"l"(m), "r"(src), "r"(c0), "r"(c1), "r"(c2) : "memory");
}
__device__ __forceinline__ void bulk_commit() { asm volatile("cp.async.bulk.commit_group;" ::: "memory"); }
__device__ __forceinline__ void bulk_wait_read() { asm volatile("cp.async.bulk.wait_group.read 0;" ::: "memory"); }
__device__ __forceinline__ void prefetch_tmap(const CUtensorMap* m) { asm volatile("prefetch.tensormap [%0];" ::"l"(m) : "memory"); }
__device__ __forceinline__ void fence_async_smem() { asm volatile("fence.proxy.async.shared::cta;" ::: "memory"); }
__device__ __forceinline__ void fence_mbar_init() { asm volatile("fence.mbarrier_init.release.cluster;" ::: "memory"); }
__device__ __forceinline__ void cluster_sync() { asm volatile("barrier.cluster.arrive.release.aligned;\nbarrier.cluster.wait.acquire.aligned;" ::: "memory"); }
__device__ __forceinline__ uint32_t cluster_rank() { uint32_t r; asm volatile("mov.u32 %0, %%cluster_ctarank;" : "=r"(r)); return r; }
__device__ __forceinline__ void pdl_wait() { asm volatile("griddepcontrol.wait;" ::: "memory"); }
__device__ __forceinline__ void pdl_launch() { asm volatile("griddepcontrol.launch_dependents;" ::: "memory"); }
__device__ __forceinline__ void named_bar(int id, int n) { asm volatile("bar.sync %0, %1;" ::"r"(id), "r"(n) : "memory"); }

__device__ __forceinline__ void wg_fence() { asm volatile("wgmma.fence.sync.aligned;" ::: "memory"); }
__device__ __forceinline__ void wg_commit() { asm volatile("wgmma.commit_group.sync.aligned;" ::: "memory"); }
template <int N> __device__ __forceinline__ void wg_wait() { asm volatile("wgmma.wait_group.sync.aligned %0;" ::"n"(N) : "memory"); }
template <int N> __device__ __forceinline__ void fence_regs(float (&d)[N]) {
#pragma unroll
    for (int i = 0; i < N; i++) asm volatile("" : "+f"(d[i])::"memory");
}
__device__ __forceinline__ uint64_t mkdesc(uint32_t addr, uint32_t lbo, uint32_t sbo, uint32_t swz) {
    uint64_t d = 0;
    d |= (uint64_t)((addr & 0x3FFFF) >> 4);
    d |= (uint64_t)((lbo & 0x3FFFF) >> 4) << 16;
    d |= (uint64_t)((sbo & 0x3FFFF) >> 4) << 32;
    d |= (uint64_t)swz << 62;
    return d;
}
__device__ __forceinline__ void ldsm_x4(uint32_t& r0, uint32_t& r1, uint32_t& r2, uint32_t& r3, uint32_t addr) {
    asm volatile("ldmatrix.sync.aligned.m8n8.x4.shared.b16 {%0,%1,%2,%3}, [%4];" : "=r"(r0), "=r"(r1), "=r"(r2), "=r"(r3) : "r"(addr) : "memory");
}
__device__ __forceinline__ void stsm_x4(uint32_t addr, uint32_t r0, uint32_t r1, uint32_t r2, uint32_t r3) {
    asm volatile("stmatrix.sync.aligned.m8n8.x4.shared.b16 [%0], {%1,%2,%3,%4};" ::"r"(addr), "r"(r0), "r"(r1), "r"(r2), "r"(r3) : "memory");
}
__device__ __forceinline__ uint32_t pack_bf16(float lo, float hi) {
    uint32_t r;
    asm("cvt.rn.bf16x2.f32 %0, %1, %2;" : "=r"(r) : "f"(hi), "f"(lo));
    return r;
}
__device__ __forceinline__ float bf_lo(uint32_t v) { return __uint_as_float(v << 16); }
__device__ __forceinline__ float bf_hi(uint32_t v) { return __uint_as_float(v & 0xFFFF0000u); }

#define WG_REGS_4(o) "+f"(d[o]), "+f"(d[o + 1]), "+f"(d[o + 2]), "+f"(d[o + 3])
#define WG_REGS_8(o) WG_REGS_4(o), WG_REGS_4(o + 4)
#define WG_REGS_16(o) WG_REGS_8(o), WG_REGS_8(o + 8)
#define WG_REGS_32(o) WG_REGS_16(o), WG_REGS_16(o + 16)

__device__ __forceinline__ void wgmma_ss_n16_tb(float (&d)[8], uint64_t dA, uint64_t dB, int sc) {
    asm volatile("{\n.reg .pred p;\nsetp.ne.b32 p, %10, 0;\n"
                 "wgmma.mma_async.sync.aligned.m64n16k16.f32.bf16.bf16 "
                 "{%0,%1,%2,%3,%4,%5,%6,%7}, %8, %9, p, 1, 1, 0, 1;\n}\n"
                 : WG_REGS_8(0) : "l"(dA), "l"(dB), "r"(sc));
}
__device__ __forceinline__ void wgmma_ss_n32_tb(float (&d)[16], uint64_t dA, uint64_t dB, int sc) {
    asm volatile("{\n.reg .pred p;\nsetp.ne.b32 p, %18, 0;\n"
                 "wgmma.mma_async.sync.aligned.m64n32k16.f32.bf16.bf16 "
                 "{%0,%1,%2,%3,%4,%5,%6,%7,%8,%9,%10,%11,%12,%13,%14,%15}, %16, %17, p, 1, 1, 0, 1;\n}\n"
                 : WG_REGS_16(0) : "l"(dA), "l"(dB), "r"(sc));
}
__device__ __forceinline__ void wgmma_ss_n64_tb(float (&d)[32], uint64_t dA, uint64_t dB, int sc) {
    asm volatile("{\n.reg .pred p;\nsetp.ne.b32 p, %34, 0;\n"
                 "wgmma.mma_async.sync.aligned.m64n64k16.f32.bf16.bf16 "
                 "{%0,%1,%2,%3,%4,%5,%6,%7,%8,%9,%10,%11,%12,%13,%14,%15,%16,%17,%18,%19,%20,%21,%22,%23,%24,%25,%26,%27,%28,%29,%30,%31}, "
                 "%32, %33, p, 1, 1, 0, 1;\n}\n"
                 : WG_REGS_32(0) : "l"(dA), "l"(dB), "r"(sc));
}
__device__ __forceinline__ void wgmma_ss_n224_tb(float (&d)[112], uint64_t dA, uint64_t dB, int sc) {
    asm volatile("{\n.reg .pred p;\nsetp.ne.b32 p, %114, 0;\n"
                 "wgmma.mma_async.sync.aligned.m64n224k16.f32.bf16.bf16 "
                 "{%0,%1,%2,%3,%4,%5,%6,%7,%8,%9,%10,%11,%12,%13,%14,%15,%16,%17,%18,%19,%20,%21,%22,%23,%24,%25,%26,%27,%28,%29,%30,%31,"
                 "%32,%33,%34,%35,%36,%37,%38,%39,%40,%41,%42,%43,%44,%45,%46,%47,%48,%49,%50,%51,%52,%53,%54,%55,%56,%57,%58,%59,%60,%61,%62,%63,"
                 "%64,%65,%66,%67,%68,%69,%70,%71,%72,%73,%74,%75,%76,%77,%78,%79,%80,%81,%82,%83,%84,%85,%86,%87,%88,%89,%90,%91,%92,%93,%94,%95,"
                 "%96,%97,%98,%99,%100,%101,%102,%103,%104,%105,%106,%107,%108,%109,%110,%111}, "
                 "%112, %113, p, 1, 1, 0, 1;\n}\n"
                 : WG_REGS_32(0), WG_REGS_32(32), WG_REGS_32(64), WG_REGS_16(96) : "l"(dA), "l"(dB), "r"(sc));
}
template <int BN> __device__ __forceinline__ void wgmma_ss_tb(float (&d)[BN / 2], uint64_t dA, uint64_t dB, int sc) {
    if constexpr (BN == 32) wgmma_ss_n32_tb(d, dA, dB, sc);
    else if constexpr (BN == 64) wgmma_ss_n64_tb(d, dA, dB, sc);
    else wgmma_ss_n224_tb(d, dA, dB, sc);
}
__device__ __forceinline__ void wgmma_rs_n64_z(float (&d)[32], uint32_t a0, uint32_t a1, uint32_t a2, uint32_t a3, uint64_t dB) {
    asm volatile("{\n.reg .pred p;\nsetp.ne.b32 p, 0, 0;\n"
                 "wgmma.mma_async.sync.aligned.m64n64k16.f32.bf16.bf16 "
                 "{%0,%1,%2,%3,%4,%5,%6,%7,%8,%9,%10,%11,%12,%13,%14,%15,%16,%17,%18,%19,%20,%21,%22,%23,%24,%25,%26,%27,%28,%29,%30,%31}, "
                 "{%32,%33,%34,%35}, %36, p, 1, 1, 0;\n}\n"
                 : "=f"(d[0]), "=f"(d[1]), "=f"(d[2]), "=f"(d[3]), "=f"(d[4]), "=f"(d[5]), "=f"(d[6]), "=f"(d[7]),
                   "=f"(d[8]), "=f"(d[9]), "=f"(d[10]), "=f"(d[11]), "=f"(d[12]), "=f"(d[13]), "=f"(d[14]), "=f"(d[15]),
                   "=f"(d[16]), "=f"(d[17]), "=f"(d[18]), "=f"(d[19]), "=f"(d[20]), "=f"(d[21]), "=f"(d[22]), "=f"(d[23]),
                   "=f"(d[24]), "=f"(d[25]), "=f"(d[26]), "=f"(d[27]), "=f"(d[28]), "=f"(d[29]), "=f"(d[30]), "=f"(d[31])
                 : "r"(a0), "r"(a1), "r"(a2), "r"(a3), "l"(dB));
}
__device__ __forceinline__ void wgmma_rs_n24_tb(float (&d)[12], uint32_t a0, uint32_t a1, uint32_t a2, uint32_t a3, uint64_t dB) {
    asm volatile("{\n.reg .pred p;\nsetp.eq.b32 p, 0, 0;\n"
                 "wgmma.mma_async.sync.aligned.m64n24k16.f32.bf16.bf16 "
                 "{%0,%1,%2,%3,%4,%5,%6,%7,%8,%9,%10,%11}, {%12,%13,%14,%15}, %16, p, 1, 1, 1;\n}\n"
                 : WG_REGS_8(0), WG_REGS_4(8) : "r"(a0), "r"(a1), "r"(a2), "r"(a3), "l"(dB));
}

constexpr int PREP_STAT_CTAS = S_ / 8;
constexpr int PREP_CS_CTAS = 8 + 1 + F_ / 64;

__global__ void __launch_bounds__(256) prep_kernel(const __nv_bfloat16* __restrict__ x, const __nv_bfloat16* __restrict__ wq,
                                                   const __nv_bfloat16* __restrict__ wk, const __nv_bfloat16* __restrict__ wv,
                                                   const __nv_bfloat16* __restrict__ wo, const __nv_bfloat16* __restrict__ w1,
                                                   const __nv_bfloat16* __restrict__ w2) {
    pdl_launch();
    const int tid = threadIdx.x;
    if (tid == 0) { TL(0, 0); TL(0, 1); }
    if (blockIdx.x < PREP_CS_CTAS) {
        __shared__ float red[32][65];
        const int b = blockIdx.x;
        const int rg = tid >> 3, c8 = tid & 7;
        float acc[8];
#pragma unroll
        for (int i = 0; i < 8; i++) acc[i] = 0.f;
        const __nv_bfloat16* base;
        int ld;
        bool active = true;
        if (b < 8) { base = wq + b * 64 + c8 * 8; ld = D_; }
        else if (b == 8) { base = (c8 < 2 ? wk + c8 * 8 : wv + (c8 - 2) * 8); ld = 16; active = c8 < 4; }
        else { base = w1 + (b - 9) * 64 + c8 * 8; ld = F_; }
        if (active) {
            uint4 v[16];
#pragma unroll
            for (int i = 0; i < 16; i++) v[i] = __ldg((const uint4*)(base + (size_t)(rg + 32 * i) * ld));
#pragma unroll
            for (int i = 0; i < 16; i++) {
                acc[0] += bf_lo(v[i].x); acc[1] += bf_hi(v[i].x); acc[2] += bf_lo(v[i].y); acc[3] += bf_hi(v[i].y);
                acc[4] += bf_lo(v[i].z); acc[5] += bf_hi(v[i].z); acc[6] += bf_lo(v[i].w); acc[7] += bf_hi(v[i].w);
            }
        }
#pragma unroll
        for (int i = 0; i < 8; i++) red[rg][c8 * 8 + i] = acc[i];
        __syncthreads();
        if (tid < 64) {
            float s = 0.f;
#pragma unroll
            for (int i = 0; i < 32; i++) s += red[i][tid];
            if (b < 8) g_cs_q[b * 64 + tid] = s;
            else if (b == 8) { if (tid < 32) g_cs_kv[tid] = s; }
            else g_cs_1[(b - 9) * 64 + tid] = s;
        }
    } else {
        const int cb = blockIdx.x - PREP_CS_CTAS;
        if (tid < 72) {
            const int line = cb * 72 + tid;
            const char* p = line < 4096 ? (const char*)wo + (size_t)line * 128 : (const char*)w2 + (size_t)(line - 4096) * 128;
            asm volatile("prefetch.global.L2 [%0];" ::"l"(p));
        }
        const int warp = tid >> 5, lane = tid & 31;
        const int row = cb * 8 + warp;
        const uint4* p = (const uint4*)(x + (size_t)row * D_ + lane * 16);
        const uint4 a = __ldg(p), b = __ldg(p + 1);
        float v[16] = {bf_lo(a.x), bf_hi(a.x), bf_lo(a.y), bf_hi(a.y), bf_lo(a.z), bf_hi(a.z), bf_lo(a.w), bf_hi(a.w),
                       bf_lo(b.x), bf_hi(b.x), bf_lo(b.y), bf_hi(b.y), bf_lo(b.z), bf_hi(b.z), bf_lo(b.w), bf_hi(b.w)};
        float s = 0.f;
#pragma unroll
        for (int i = 0; i < 16; i++) s += v[i];
        s += __shfl_xor_sync(0xffffffffu, s, 1);
        s += __shfl_xor_sync(0xffffffffu, s, 2);
        const float mean = s * (1.f / 64.f);
        float m2 = 0.f;
#pragma unroll
        for (int i = 0; i < 16; i++) { const float d = v[i] - mean; m2 += d * d; }
        m2 += __shfl_xor_sync(0xffffffffu, m2, 1);
        m2 += __shfl_xor_sync(0xffffffffu, m2, 2);
        if ((lane & 3) == 0) g_stats[0][(lane >> 2) * S_ + row] = make_float2(mean, m2);
    }
    if (tid == 0) { TL(0, 2); TL(0, 3); }
}

enum { EPI_QKV = 0, EPI_RES = 1, EPI_FFN1 = 2 };

struct GemmParams {
    const float2* stats_in;
    float2* stats_out;
    int wait_in_epilogue;
    int tk;
};

template <int BN> struct Geo;
template <> struct Geo<64> {
    static constexpr int BK = 64, A_BYTES = 128 * 128, A_SWZ = 1, A_SBO = 1024;
    static constexpr int B_BYTES = 64 * 128, B_SWZ = 1, B_LBO = 8192, B_SBO = 1024, B_KSTEP = 2048;
};
template <> struct Geo<224> {
    static constexpr int BK = 32, A_BYTES = 128 * 64, A_SWZ = 2, A_SBO = 512;
    static constexpr int B_BYTES = 7 * 32 * 64, B_SWZ = 2, B_LBO = 2048, B_SBO = 512, B_KSTEP = 1024;
};

template <int BN, int STAGES, int EPI> struct GemmSmem {
    static constexpr int XB_OFF = Geo<BN>::A_BYTES + Geo<BN>::B_BYTES;
    static constexpr int STAGE = XB_OFF + (EPI == EPI_QKV ? 2048 : 0);
    static constexpr int AUX_OFF = STAGES * STAGE;
    static constexpr int TOTAL = AUX_OFF + 1024;
};

__device__ __forceinline__ void load_row_stats(const float2* __restrict__ st, int row0, int c, float& mean0, float& rstd0, float& mean1, float& rstd1) {
    const float2 a0 = st[(2 * c) * S_ + row0], a1 = st[(2 * c + 1) * S_ + row0];
    const float2 b0 = st[(2 * c) * S_ + row0 + 8], b1 = st[(2 * c + 1) * S_ + row0 + 8];
    float sa = a0.x + a1.x, sb = b0.x + b1.x;
    sa += __shfl_xor_sync(0xffffffffu, sa, 1); sa += __shfl_xor_sync(0xffffffffu, sa, 2);
    sb += __shfl_xor_sync(0xffffffffu, sb, 1); sb += __shfl_xor_sync(0xffffffffu, sb, 2);
    mean0 = sa * 0.125f; mean1 = sb * 0.125f;
    float ma = a0.y + a1.y + 64.f * ((a0.x - mean0) * (a0.x - mean0) + (a1.x - mean0) * (a1.x - mean0));
    float mb = b0.y + b1.y + 64.f * ((b0.x - mean1) * (b0.x - mean1) + (b1.x - mean1) * (b1.x - mean1));
    ma += __shfl_xor_sync(0xffffffffu, ma, 1); ma += __shfl_xor_sync(0xffffffffu, ma, 2);
    mb += __shfl_xor_sync(0xffffffffu, mb, 1); mb += __shfl_xor_sync(0xffffffffu, mb, 2);
    rstd0 = 1.0f / sqrtf(ma * (1.f / 512.f) + 1e-5f);
    rstd1 = 1.0f / sqrtf(mb * (1.f / 512.f) + 1e-5f);
}

template <int BN, int KB, int STAGES, int EPI, int MC>
__device__ __forceinline__ void gemm_body(const CUtensorMap* mapA, const CUtensorMap* mapB, const CUtensorMap* mapB2, const CUtensorMap* mapR,
                                          const CUtensorMap* mapC, const GemmParams& prm, int tile_m, int tile_n, uint8_t* smem_raw) {
    using SM = GemmSmem<BN, STAGES, EPI>;
    using G = Geo<BN>;
    pdl_launch();
    const uint32_t sbase = smem_u32(smem_raw);
    if (sbase & 1023) __trap();
    uint8_t* sgen = smem_raw;
    const uint32_t bar_full = sbase + SM::AUX_OFF, bar_empty = bar_full + 8 * STAGES;
    float* s_cs = (float*)(sgen + SM::AUX_OFF + 128);
    float* s_red = (float*)(sgen + SM::AUX_OFF + 640);
    const bool xkv = EPI == EPI_QKV && tile_n < 2;
    const int tid = threadIdx.x, warp = tid >> 5, lane = tid & 31;
    const uint32_t rank = MC ? cluster_rank() : 0;
    if (tid == 0) TL(prm.tk, 0);

    constexpr bool INLINE_PROD = BN == 224;
    if (tid == (INLINE_PROD ? 0 : 256)) {
        prefetch_tmap(mapB); prefetch_tmap(mapA); prefetch_tmap(mapC);
        for (int s = 0; s < STAGES; s++) { mbar_init(bar_full + 8 * s, 1); mbar_init(bar_empty + 8 * s, MC ? 4 : 2); }
        fence_mbar_init();
    }
    __syncthreads();
    if (MC) cluster_sync();

    const int m0 = tile_m * 128, n0 = tile_n * BN;
    const uint32_t STAGE_TX = G::A_BYTES + G::B_BYTES + (xkv ? 2048 : 0);
    auto loadB = [&](int kb, int s) {
        const uint32_t dst = sbase + s * SM::STAGE + G::A_BYTES, bar = bar_full + 8 * s;
        if constexpr (BN == 64) {
            tma2d(dst, mapB, n0, kb * 64, bar);
            if (xkv) tma2d(dst + G::B_BYTES, mapB2, 0, kb * 64, bar);
        } else {
            if (rank == 0) tma3d_mc(dst, mapB, 0, kb * 32, tile_n * 7, bar, 3);
            else tma3d_mc(dst + 4 * 2048, mapB2, 0, kb * 32, tile_n * 7 + 4, bar, 3);
        }
    };
    auto loadA = [&](int kb, int s) {
        const uint32_t dst = sbase + s * SM::STAGE, bar = bar_full + 8 * s;
        if constexpr (MC == 1) tma2d_mc(dst + rank * (G::A_BYTES / 2), mapA, kb * G::BK, m0 + rank * 64, bar, 3);
        else { tma2d(dst, mapA, kb * G::BK, m0, bar); tma2d(dst + G::A_BYTES / 2, mapA, kb * G::BK, m0 + 64, bar); }
    };
    constexpr int PRE = STAGES < KB ? STAGES : KB;
    auto prologue_loads = [&]() {
        for (int kb = 0; kb < PRE; kb++) { mbar_expect_tx(bar_full + 8 * kb, STAGE_TX); loadB(kb, kb); }
        if (!prm.wait_in_epilogue) pdl_wait();
        for (int kb = 0; kb < PRE; kb++) loadA(kb, kb);
    };
    if (!INLINE_PROD && warp == 8) {
        if (lane == 0) {
            prologue_loads();
            int s = PRE % STAGES, ph = (PRE / STAGES) & 1;
            for (int kb = PRE; kb < KB; kb++) {
                mbar_wait(bar_empty + 8 * s, ph ^ 1);
                mbar_expect_tx(bar_full + 8 * s, STAGE_TX);
                loadB(kb, s);
                loadA(kb, s);
                if (++s == STAGES) { s = 0; ph ^= 1; }
            }
            if constexpr (EPI == EPI_RES) {
                mbar_wait(bar_empty + 8 * s, ph ^ 1);
                mbar_expect_tx(bar_full + 8 * s, 16384);
                tma2d(sbase + s * SM::STAGE, mapR, n0, m0, bar_full + 8 * s);
                tma2d(sbase + s * SM::STAGE + 8192, mapR, n0, m0 + 64, bar_full + 8 * s);
            }
        }
    } else {
        if (INLINE_PROD && tid == 0) prologue_loads();
        const int wg = warp >> 2, g = lane >> 2, c = lane & 3;
        const int rloc = wg * 64 + (warp & 3) * 16 + g;
        const int row0 = m0 + rloc;
        float mean0 = 0.f, rstd0 = 1.f, mean1 = 0.f, rstd1 = 1.f;
        auto ln_inputs = [&]() {
            pdl_wait();
            if constexpr (EPI != EPI_RES) {
                load_row_stats(prm.stats_in, row0, c, mean0, rstd0, mean1, rstd1);
                const float* cs = EPI == EPI_FFN1 ? g_cs_1 + n0 : g_cs_q + n0;
                if (tid < BN) s_cs[tid] = cs[tid];
            }
        };
        if (!prm.wait_in_epilogue) ln_inputs();
        float acc[BN / 2];
        float acx[8];
        const uint64_t dX0 = mkdesc(sbase + SM::XB_OFF, 16, 256, 3);
        const uint64_t dA0 = mkdesc(sbase + wg * (G::A_BYTES / 2), 16, G::A_SBO, G::A_SWZ);
        const uint64_t dB0 = mkdesc(sbase + G::A_BYTES, G::B_LBO, G::B_SBO, G::B_SWZ);
        int s = 0, ph = 0;
#pragma unroll 1
        for (int kb = 0; kb < KB; kb++) {
            mbar_wait(bar_full + 8 * s, ph);
            const uint64_t dA = dA0 + (uint64_t)(s * (SM::STAGE >> 4)), dB = dB0 + (uint64_t)(s * (SM::STAGE >> 4));
            wg_fence();
#pragma unroll
            for (int k = 0; k < G::BK / 16; k++) wgmma_ss_tb<BN>(acc, dA + (uint64_t)(k * 2), dB + (uint64_t)(k * (G::B_KSTEP >> 4)), (kb | k) != 0);
            if constexpr (EPI == EPI_QKV) {
                if (xkv) {
                    const uint64_t dX = dX0 + (uint64_t)(s * (SM::STAGE >> 4));
#pragma unroll
                    for (int k = 0; k < 4; k++) wgmma_ss_n16_tb(acx, dA + (uint64_t)(k * 2), dX + (uint64_t)(k * 32), (kb | k) != 0);
                }
            }
            wg_commit();
            if constexpr (BN <= 64) {
                wg_wait<0>();
                if ((tid & 127) == 0) {
                    if (MC) { mbar_arrive_remote(bar_empty + 8 * s, 0); mbar_arrive_remote(bar_empty + 8 * s, 1); }
                    else mbar_arrive(bar_empty + 8 * s);
                }
            } else if (kb > 0) {
                wg_wait<1>();
                const int sp = s == 0 ? STAGES - 1 : s - 1;
                if ((tid & 127) == 0) {
                    if (MC) { mbar_arrive_remote(bar_empty + 8 * sp, 0); mbar_arrive_remote(bar_empty + 8 * sp, 1); }
                    else mbar_arrive(bar_empty + 8 * sp);
                }
                if (INLINE_PROD && tid == 0 && kb >= 2 && kb - 2 + STAGES < KB) {
                    const int sq = sp == 0 ? STAGES - 1 : sp - 1;
                    mbar_wait(bar_empty + 8 * sq, ((kb - 2) / STAGES) & 1);
                    mbar_expect_tx(bar_full + 8 * sq, STAGE_TX);
                    loadB(kb - 2 + STAGES, sq);
                    loadA(kb - 2 + STAGES, sq);
                }
                if (INLINE_PROD) __syncwarp();
            }
            if (++s == STAGES) { s = 0; ph ^= 1; }
        }
        if (prm.wait_in_epilogue) ln_inputs();
        wg_wait<0>();
        fence_regs(acc);
        if (tid == 0) TL(prm.tk, 2);
        if constexpr (EPI != EPI_RES) named_bar(1, 256);

        if constexpr (EPI == EPI_QKV) {
            if (xkv) {
                fence_regs(acx);
                const float rm0 = rstd0 * mean0, rm1 = rstd1 * mean1;
                float n0s = 0.f, n1s = 0.f, vmax = 0.f;
#pragma unroll
                for (int j = 0; j < 2; j++) {
                    const float2 cs2 = *(const float2*)(g_cs_kv + tile_n * 16 + 8 * j + 2 * c);
                    const uint32_t u0 = pack_bf16(acx[4 * j] * rstd0 - rm0 * cs2.x, acx[4 * j + 1] * rstd0 - rm0 * cs2.y);
                    const uint32_t u1 = pack_bf16(acx[4 * j + 2] * rstd1 - rm1 * cs2.x, acx[4 * j + 3] * rstd1 - rm1 * cs2.y);
                    n0s += bf_lo(u0) * bf_lo(u0) + bf_hi(u0) * bf_hi(u0);
                    n1s += bf_lo(u1) * bf_lo(u1) + bf_hi(u1) * bf_hi(u1);
                    vmax = fmaxf(vmax, fmaxf(fmaxf(fabsf(bf_lo(u0)), fabsf(bf_hi(u0))), fmaxf(fabsf(bf_lo(u1)), fabsf(bf_hi(u1)))));
                    if (tile_n == 0) {
                        *(uint32_t*)(g_kimg + (row0 >> 3) * 256 + j * 128 + g * 16 + c * 4) = u0;
                        *(uint32_t*)(g_kimg + ((row0 + 8) >> 3) * 256 + j * 128 + g * 16 + c * 4) = u1;
                    } else {
                        uint8_t* vb = g_vimg + (row0 >> 4) * 768 + j * 256 + g * 16 + c * 4;
                        *(uint32_t*)(vb) = u0;
                        *(uint32_t*)(vb + 128) = u1;
                    }
                }
                if (tile_n == 1) {
                    uint8_t* vb = g_vimg + (row0 >> 4) * 768 + 512 + g * 16 + c * 4;
                    const uint32_t one = c == 0 ? 0x00003F80u : 0u;
                    *(uint32_t*)(vb) = one;
                    *(uint32_t*)(vb + 128) = one;
                }
                n0s += __shfl_xor_sync(0xffffffffu, n0s, 1); n0s += __shfl_xor_sync(0xffffffffu, n0s, 2);
                n1s += __shfl_xor_sync(0xffffffffu, n1s, 1); n1s += __shfl_xor_sync(0xffffffffu, n1s, 2);
                float km = tile_n == 0 ? fmaxf(n0s, n1s) : vmax;
                if (!(n0s + n1s < INFINITY)) km = INFINITY;
#pragma unroll
                for (int o = 1; o < 32; o <<= 1) km = fmaxf(km, __shfl_xor_sync(0xffffffffu, km, o));
                if (lane == 0) s_red[warp] = km;
                named_bar(1, 256);
                if (tid == 0) {
                    float a = 0.f;
                    for (int i = 0; i < 8; i++) a = fmaxf(a, s_red[i]);
                    g_kvmax[tile_n * 16 + tile_m] = a;
                }
            }
        }
        if constexpr (BN == 64) {
            const uint32_t stile = sbase + (EPI == EPI_RES ? s * SM::STAGE : 0);
            const int mrow = wg * 64 + (warp & 3) * 16 + (lane & 7) + ((lane >> 3) & 1) * 8;
            const uint32_t rbase = stile + mrow * 128;
            if constexpr (EPI == EPI_RES) {
                mbar_wait(bar_full + 8 * s, ph);
                float s0 = 0.f, s1 = 0.f;
#pragma unroll
                for (int jj = 0; jj < 4; jj++) {
                    uint32_t r0, r1, r2, r3;
                    const uint32_t addr = rbase + (((2 * jj + (lane >> 4)) ^ (mrow & 7)) << 4);
                    ldsm_x4(r0, r1, r2, r3, addr);
                    const uint32_t u0 = pack_bf16(acc[8 * jj] + bf_lo(r0), acc[8 * jj + 1] + bf_hi(r0));
                    const uint32_t u1 = pack_bf16(acc[8 * jj + 2] + bf_lo(r1), acc[8 * jj + 3] + bf_hi(r1));
                    const uint32_t u2 = pack_bf16(acc[8 * jj + 4] + bf_lo(r2), acc[8 * jj + 5] + bf_hi(r2));
                    const uint32_t u3 = pack_bf16(acc[8 * jj + 6] + bf_lo(r3), acc[8 * jj + 7] + bf_hi(r3));
                    stsm_x4(addr, u0, u1, u2, u3);
                    acc[8 * jj] = bf_lo(u0); acc[8 * jj + 1] = bf_hi(u0); acc[8 * jj + 4] = bf_lo(u2); acc[8 * jj + 5] = bf_hi(u2);
                    acc[8 * jj + 2] = bf_lo(u1); acc[8 * jj + 3] = bf_hi(u1); acc[8 * jj + 6] = bf_lo(u3); acc[8 * jj + 7] = bf_hi(u3);
                    s0 += (acc[8 * jj] + acc[8 * jj + 1]) + (acc[8 * jj + 4] + acc[8 * jj + 5]);
                    s1 += (acc[8 * jj + 2] + acc[8 * jj + 3]) + (acc[8 * jj + 6] + acc[8 * jj + 7]);
                }
                fence_async_smem();
                named_bar(2 + wg, 128);
                if ((tid & 127) == 0) { tma2d_store(mapC, stile + wg * 8192, n0, m0 + wg * 64); bulk_commit(); }
                if (prm.stats_out) {
                    s0 += __shfl_xor_sync(0xffffffffu, s0, 1); s0 += __shfl_xor_sync(0xffffffffu, s0, 2);
                    s1 += __shfl_xor_sync(0xffffffffu, s1, 1); s1 += __shfl_xor_sync(0xffffffffu, s1, 2);
                    const float mu0 = s0 * (1.f / 64.f), mu1 = s1 * (1.f / 64.f);
                    float q0 = 0.f, q1 = 0.f;
#pragma unroll
                    for (int j = 0; j < 8; j++) {
                        float d;
                        d = acc[4 * j] - mu0; q0 += d * d; d = acc[4 * j + 1] - mu0; q0 += d * d;
                        d = acc[4 * j + 2] - mu1; q1 += d * d; d = acc[4 * j + 3] - mu1; q1 += d * d;
                    }
                    q0 += __shfl_xor_sync(0xffffffffu, q0, 1); q0 += __shfl_xor_sync(0xffffffffu, q0, 2);
                    q1 += __shfl_xor_sync(0xffffffffu, q1, 1); q1 += __shfl_xor_sync(0xffffffffu, q1, 2);
                    if (c == 0) {
                        prm.stats_out[tile_n * S_ + row0] = make_float2(mu0, q0);
                        prm.stats_out[tile_n * S_ + row0 + 8] = make_float2(mu1, q1);
                    }
                }
            } else {
                const float sc = 0.25f * 1.4426950408889634f;
                const float a0 = rstd0 * sc, a1 = rstd1 * sc, rm0 = a0 * mean0, rm1 = a1 * mean1;
#pragma unroll
                for (int jj = 0; jj < 4; jj++) {
                    const float2 ca = *(const float2*)(s_cs + 16 * jj + 2 * c), cb = *(const float2*)(s_cs + 16 * jj + 8 + 2 * c);
                    const uint32_t u0 = pack_bf16(acc[8 * jj] * a0 - rm0 * ca.x, acc[8 * jj + 1] * a0 - rm0 * ca.y);
                    const uint32_t u1 = pack_bf16(acc[8 * jj + 2] * a1 - rm1 * ca.x, acc[8 * jj + 3] * a1 - rm1 * ca.y);
                    const uint32_t u2 = pack_bf16(acc[8 * jj + 4] * a0 - rm0 * cb.x, acc[8 * jj + 5] * a0 - rm0 * cb.y);
                    const uint32_t u3 = pack_bf16(acc[8 * jj + 6] * a1 - rm1 * cb.x, acc[8 * jj + 7] * a1 - rm1 * cb.y);
                    stsm_x4(rbase + (((2 * jj + (lane >> 4)) ^ (mrow & 7)) << 4), u0, u1, u2, u3);
                }
                fence_async_smem();
                named_bar(2 + wg, 128);
                if ((tid & 127) == 0) { tma2d_store(mapC, stile + wg * 8192, n0, m0 + wg * 64); bulk_commit(); }
            }
            if ((tid & 127) == 0) bulk_wait_read();
        } else {
            const uint32_t stile = sbase + wg * (7 * 4096);
            const int mrow = (warp & 3) * 16 + (lane & 7) + ((lane >> 3) & 1) * 8;
            const float a0 = 0.5f * rstd0, a1 = 0.5f * rstd1, rm0 = a0 * mean0, rm1 = a1 * mean1;
#pragma unroll
            for (int jj = 0; jj < 14; jj++) {
                const float2 ca = *(const float2*)(s_cs + 16 * jj + 2 * c), cb = *(const float2*)(s_cs + 16 * jj + 8 + 2 * c);
                float y[8] = {acc[8 * jj] * a0 - rm0 * ca.x,     acc[8 * jj + 1] * a0 - rm0 * ca.y,
                              acc[8 * jj + 2] * a1 - rm1 * ca.x, acc[8 * jj + 3] * a1 - rm1 * ca.y,
                              acc[8 * jj + 4] * a0 - rm0 * cb.x, acc[8 * jj + 5] * a0 - rm0 * cb.y,
                              acc[8 * jj + 6] * a1 - rm1 * cb.x, acc[8 * jj + 7] * a1 - rm1 * cb.y};
#pragma unroll
                for (int i = 0; i < 8; i++) {
                    float t;
                    asm("tanh.approx.f32 %0, %1;" : "=f"(t) : "f"(y[i]));
                    y[i] = fmaf(y[i], t, y[i]);
                }
                const int chunk = (2 * jj + (lane >> 4)) & 3, blk = jj >> 1;
                stsm_x4(stile + blk * 4096 + mrow * 64 + ((chunk ^ ((mrow >> 1) & 3)) << 4),
                        pack_bf16(y[0], y[1]), pack_bf16(y[2], y[3]), pack_bf16(y[4], y[5]), pack_bf16(y[6], y[7]));
                if (jj & 1) {
                    fence_async_smem();
                    __syncwarp();
                    if (lane == 0) {
                        tma2d_store(mapC, stile + blk * 4096 + (warp & 3) * 1024, n0 + blk * 32, m0 + wg * 64 + (warp & 3) * 16);
                        bulk_commit();
                    }
                }
            }
            if (lane == 0) bulk_wait_read();
        }
    }
    if (tid == 0) TL(prm.tk, 3);
    if (MC) cluster_sync();
}

#define WO_ST 4
#define F2_ST 4
#define F1_ST 5
constexpr int QKV_STAGES = 4, WO_STAGES = WO_ST, FFN2_STAGES = F2_ST, FFN1_STAGES = F1_ST;
__global__ void __launch_bounds__(288) qkv_kernel(const __grid_constant__ CUtensorMap mapA, const __grid_constant__ CUtensorMap mapWq,
                                                  const __grid_constant__ CUtensorMap mapWk, const __grid_constant__ CUtensorMap mapWv,
                                                  const __grid_constant__ CUtensorMap mapQ, const GemmParams prm) {
    extern __shared__ __align__(1024) uint8_t smem_raw[];
    uint32_t pad[64];
#pragma unroll
    for (int i = 0; i < 64; i++) asm volatile("mov.u32 %0, %%clock;" : "=r"(pad[i]));
    const int tn = blockIdx.x & 7;
    gemm_body<64, 8, QKV_STAGES, EPI_QKV, 1>(&mapA, &mapWq, tn == 0 ? &mapWk : &mapWv, &mapA, &mapQ, prm, blockIdx.x >> 3, tn, smem_raw);
    if (prm.stats_in == nullptr) {
#pragma unroll
        for (int i = 0; i < 64; i++) asm volatile("st.volatile.global.u32 [%0], %1;" ::"l"(g_kimg + 4 * i), "r"(pad[i]) : "memory");
    }
}
template <int KB, int STAGES>
__global__ void __launch_bounds__(288) res_gemm_kernel(const __grid_constant__ CUtensorMap mapA, const __grid_constant__ CUtensorMap mapW,
                                                       const __grid_constant__ CUtensorMap mapR, const __grid_constant__ CUtensorMap mapC, const GemmParams prm) {
    extern __shared__ __align__(1024) uint8_t smem_raw[];
    gemm_body<64, KB, STAGES, EPI_RES, 1>(&mapA, &mapW, &mapW, &mapR, &mapC, prm, blockIdx.x >> 3, blockIdx.x & 7, smem_raw);
}
__global__ void __launch_bounds__(256) ffn1_kernel(const __grid_constant__ CUtensorMap mapA, const __grid_constant__ CUtensorMap mapW4,
                                                   const __grid_constant__ CUtensorMap mapW3, const __grid_constant__ CUtensorMap mapH, const GemmParams prm) {
    extern __shared__ __align__(1024) uint8_t smem_raw[];
    const int pair = blockIdx.x >> 1, tile_n = pair & 7, tile_m = (pair >> 3) * 2 + (blockIdx.x & 1);
    gemm_body<224, 16, FFN1_STAGES, EPI_FFN1, 2>(&mapA, &mapW4, &mapW3, &mapA, &mapH, prm, tile_m, tile_n, smem_raw);
}

constexpr int NPOLY = 10;
__host__ __device__ constexpr bool is_mufu(int i) { return ((i + 1) * (16 - NPOLY)) / 16 != (i * (16 - NPOLY)) / 16; }

__device__ __forceinline__ float ex2(float x) { float r; asm("ex2.approx.ftz.f32 %0, %1;" : "=f"(r) : "f"(x)); return r; }
__device__ __forceinline__ uint32_t exp_pair_mufu(float a, float b) { return pack_bf16(ex2(a), ex2(b)); }
__device__ __forceinline__ uint32_t exp_pair_fma(float a, float b, uint32_t c3f) {
    constexpr float MAGIC = 98430.4140625f;
    const float ta = a + MAGIC, tb = b + (MAGIC - 143.5f);
    uint32_t y, m, r;
    asm("mad.lo.u32 %0, %1, 65536, %2;" : "=r"(y) : "r"(__float_as_uint(tb)), "r"(__float_as_uint(ta)));
    asm("lop3.b32 %0, %1, 0x007F007F, %2, 0xEA;" : "=r"(m) : "r"(y), "r"(c3f));
    const uint32_t e = y & 0xFF80FF80u;
    asm("fma.rn.bf16x2 %0, %1, %2, %3;" : "=r"(r) : "r"(y), "r"(m), "r"(e));
    return r;
}

constexpr int KCH = 256, NCH = S_ / KCH;
constexpr int K_BYTES = S_ * 32, V_BYTES = (S_ / 16) * 768;
constexpr int ATT_SMEM = K_BYTES + V_BYTES;

__global__ void __launch_bounds__(512, 1) attn_kernel(int tk) {
    extern __shared__ __align__(1024) uint8_t smem[];
    __shared__ uint64_t bars[NCH];
    __shared__ int s_slow;
    const int tid = threadIdx.x, wg = tid >> 7, warp = (tid >> 5) & 3, lane = tid & 31;
    const uint32_t sK = smem_u32(smem), sV = sK + K_BYTES;
    if (tid == 0) TL(tk, 0);
    if (tid == 0) {
        for (int i = 0; i < NCH; i++) mbar_init(smem_u32(&bars[i]), 1);
        s_slow = 0;
        fence_mbar_init();
    }
    __syncthreads();
    pdl_launch();
    pdl_wait();
    if (tid == 0) TL(tk, 1);
    if (tid == 0) {
        for (int i = 0; i < NCH; i++) {
            mbar_expect_tx(smem_u32(&bars[i]), KCH * 32 + (KCH / 16) * 768);
            bulk_load(sK + i * KCH * 32, g_kimg + i * KCH * 32, KCH * 32, smem_u32(&bars[i]));
            bulk_load(sV + i * (KCH / 16) * 768, g_vimg + i * (KCH / 16) * 768, (KCH / 16) * 768, smem_u32(&bars[i]));
        }
    }
    const int tb = blockIdx.x >> 3, hg = blockIdx.x & 7;
    const int head = hg * 4 + wg;
    const int g = lane >> 2, c = lane & 3;
    uint32_t qa[2][4];
    float qn = 0.f;
#pragma unroll
    for (int m = 0; m < 2; m++) {
        const int row = tb * 128 + m * 64 + warp * 16 + g;
        const uint32_t* p0 = (const uint32_t*)(g_q + (size_t)row * D_ + head * 16);
        const uint32_t* p1 = (const uint32_t*)(g_q + (size_t)(row + 8) * D_ + head * 16);
        qa[m][0] = p0[c]; qa[m][1] = p1[c]; qa[m][2] = p0[c + 4]; qa[m][3] = p1[c + 4];
        float n0 = bf_lo(qa[m][0]) * bf_lo(qa[m][0]) + bf_hi(qa[m][0]) * bf_hi(qa[m][0]) + bf_lo(qa[m][2]) * bf_lo(qa[m][2]) + bf_hi(qa[m][2]) * bf_hi(qa[m][2]);
        float n1 = bf_lo(qa[m][1]) * bf_lo(qa[m][1]) + bf_hi(qa[m][1]) * bf_hi(qa[m][1]) + bf_lo(qa[m][3]) * bf_lo(qa[m][3]) + bf_hi(qa[m][3]) * bf_hi(qa[m][3]);
        n0 += __shfl_xor_sync(0xffffffffu, n0, 1); n0 += __shfl_xor_sync(0xffffffffu, n0, 2);
        n1 += __shfl_xor_sync(0xffffffffu, n1, 1); n1 += __shfl_xor_sync(0xffffffffu, n1, 2);
        if (!(n0 == n0) || !(n1 == n1)) n0 = __int_as_float(0x7f800000);
        qn = fmaxf(qn, fmaxf(n0, n1));
    }
    {
        float km = 0.f, vm = 0.f;
#pragma unroll
        for (int i = 0; i < 16; i++) { km = fmaxf(km, g_kvmax[i]); vm = fmaxf(vm, g_kvmax[16 + i]); }
        const bool ok = (qn * km <= 10000.f) && (vm <= 16384.f);
        if (!ok) s_slow = 1;
    }
    float oacc[2][12];
#pragma unroll
    for (int m = 0; m < 2; m++)
#pragma unroll
        for (int i = 0; i < 12; i++) oacc[m][i] = 0.f;
    __syncthreads();
    const bool slow = s_slow != 0;

    const uint64_t dK0 = mkdesc(sK, 128, 256, 0);
    const uint64_t dV0 = mkdesc(sV, 128, 256, 0);
    uint32_t c3f;
    asm volatile("mov.b32 %0, 0x3F003F00;" : "=r"(c3f));
    if (!slow) {
#pragma unroll 1
        for (int t = 0; t < S_ / 64; t++) {
            if ((t & 3) == 0) mbar_wait(smem_u32(&bars[t >> 2]), 0);
            const uint64_t dK = dK0 + (uint64_t)(t * 64 * 32 / 16);
            const uint64_t dV = dV0 + (uint64_t)(t * 4 * 768 / 16);
#pragma unroll
            for (int m = 0; m < 2; m++) {
                float s[32];
                wg_fence();
                wgmma_rs_n64_z(s, qa[m][0], qa[m][1], qa[m][2], qa[m][3], dK);
                wg_commit();
                wg_wait<0>();
                fence_regs(s);
                uint32_t p[16];
#pragma unroll
                for (int i = 0; i < 16; i++) p[i] = is_mufu(i) ? exp_pair_mufu(s[2 * i], s[2 * i + 1]) : exp_pair_fma(s[2 * i], s[2 * i + 1], c3f);
                wg_fence();
#pragma unroll
                for (int kk = 0; kk < 4; kk++)
                    wgmma_rs_n24_tb(oacc[m], p[4 * kk], p[4 * kk + 1], p[4 * kk + 2], p[4 * kk + 3], dV + (uint64_t)(kk * 768 / 16));
                wg_commit();
            }
        }
        wg_wait<0>();
    } else {
        float mx[2][2] = {{-INFINITY, -INFINITY}, {-INFINITY, -INFINITY}};
#pragma unroll 1
        for (int t = 0; t < S_ / 64; t++) {
            if ((t & 3) == 0) mbar_wait(smem_u32(&bars[t >> 2]), 0);
            const uint64_t dK = dK0 + (uint64_t)(t * 64 * 32 / 16);
            const uint64_t dV = dV0 + (uint64_t)(t * 4 * 768 / 16);
#pragma unroll
            for (int m = 0; m < 2; m++) {
                float s[32];
                wg_fence();
                wgmma_rs_n64_z(s, qa[m][0], qa[m][1], qa[m][2], qa[m][3], dK);
                wg_commit();
                wg_wait<0>();
                fence_regs(s);
                fence_regs(oacc[m]);
                float r0 = mx[m][0], r1 = mx[m][1];
#pragma unroll
                for (int j = 0; j < 8; j++) {
                    r0 = fmaxf(r0, fmaxf(s[4 * j], s[4 * j + 1]));
                    r1 = fmaxf(r1, fmaxf(s[4 * j + 2], s[4 * j + 3]));
                }
                r0 = fmaxf(r0, __shfl_xor_sync(0xffffffffu, r0, 1)); r0 = fmaxf(r0, __shfl_xor_sync(0xffffffffu, r0, 2));
                r1 = fmaxf(r1, __shfl_xor_sync(0xffffffffu, r1, 1)); r1 = fmaxf(r1, __shfl_xor_sync(0xffffffffu, r1, 2));
                const float al0 = ex2(mx[m][0] - r0), al1 = ex2(mx[m][1] - r1);
                mx[m][0] = r0; mx[m][1] = r1;
#pragma unroll
                for (int j = 0; j < 3; j++) {
                    oacc[m][4 * j] *= al0; oacc[m][4 * j + 1] *= al0;
                    oacc[m][4 * j + 2] *= al1; oacc[m][4 * j + 3] *= al1;
                }
                uint32_t p[16];
#pragma unroll
                for (int j = 0; j < 8; j++) {
                    p[2 * j] = pack_bf16(ex2(s[4 * j] - r0), ex2(s[4 * j + 1] - r0));
                    p[2 * j + 1] = pack_bf16(ex2(s[4 * j + 2] - r1), ex2(s[4 * j + 3] - r1));
                }
                fence_regs(oacc[m]);
                wg_fence();
#pragma unroll
                for (int kk = 0; kk < 4; kk++)
                    wgmma_rs_n24_tb(oacc[m], p[4 * kk], p[4 * kk + 1], p[4 * kk + 2], p[4 * kk + 3], dV + (uint64_t)(kk * 768 / 16));
                wg_commit();
                wg_wait<0>();
            }
        }
    }
    fence_regs(oacc[0]); fence_regs(oacc[1]);
    if (tid == 0) TL(tk, 2);
#pragma unroll
    for (int m = 0; m < 2; m++) {
        const float l0 = __shfl_sync(0xffffffffu, oacc[m][8], lane & ~3);
        const float l1 = __shfl_sync(0xffffffffu, oacc[m][10], lane & ~3);
        const float r0 = 1.0f / l0, r1 = 1.0f / l1;
        const int row = tb * 128 + m * 64 + warp * 16 + g;
        uint32_t* p0 = (uint32_t*)(g_o + (size_t)row * D_ + head * 16);
        uint32_t* p1 = (uint32_t*)(g_o + (size_t)(row + 8) * D_ + head * 16);
        p0[c] = pack_bf16(oacc[m][0] * r0, oacc[m][1] * r0);
        p1[c] = pack_bf16(oacc[m][2] * r1, oacc[m][3] * r1);
        p0[c + 4] = pack_bf16(oacc[m][4] * r0, oacc[m][5] * r0);
        p1[c + 4] = pack_bf16(oacc[m][6] * r1, oacc[m][7] * r1);
    }
    if (tid == 0) TL(tk, 3);
}

typedef CUresult (*EncodeFn)(CUtensorMap*, CUtensorMapDataType, cuuint32_t, void*, const cuuint64_t*, const cuuint64_t*, const cuuint32_t*,
                             const cuuint32_t*, CUtensorMapInterleave, CUtensorMapSwizzle, CUtensorMapL2promotion, CUtensorMapFloatOOBfill);

EncodeFn get_encode() {
    static EncodeFn fn = nullptr;
    if (!fn) {
        void* p = nullptr;
        cudaDriverEntryPointQueryResult qr;
        cudaGetDriverEntryPoint("cuTensorMapEncodeTiled", &p, cudaEnableDefault, &qr);
        fn = (EncodeFn)p;
    }
    return fn;
}
CUtensorMap map2d(const void* ptr, uint64_t cols, uint64_t rows, uint32_t bc, uint32_t br, CUtensorMapSwizzle sw) {
    CUtensorMap m;
    cuuint64_t gd[2] = {cols, rows}, gs[1] = {cols * 2};
    cuuint32_t bx[2] = {bc, br}, es[2] = {1, 1};
    get_encode()(&m, CU_TENSOR_MAP_DATA_TYPE_BFLOAT16, 2, (void*)ptr, gd, gs, bx, es, CU_TENSOR_MAP_INTERLEAVE_NONE, sw,
                 CU_TENSOR_MAP_L2_PROMOTION_L2_128B, CU_TENSOR_MAP_FLOAT_OOB_FILL_NONE);
    return m;
}
CUtensorMap map3d32(const void* ptr, uint64_t cols, uint64_t rows, uint32_t br, uint32_t nb) {
    CUtensorMap m;
    cuuint64_t gd[3] = {32, rows, cols / 32}, gs[2] = {cols * 2, 64};
    cuuint32_t bx[3] = {32, br, nb}, es[3] = {1, 1, 1};
    get_encode()(&m, CU_TENSOR_MAP_DATA_TYPE_BFLOAT16, 3, (void*)ptr, gd, gs, bx, es, CU_TENSOR_MAP_INTERLEAVE_NONE, CU_TENSOR_MAP_SWIZZLE_64B,
                 CU_TENSOR_MAP_L2_PROMOTION_L2_128B, CU_TENSOR_MAP_FLOAT_OOB_FILL_NONE);
    return m;
}

template <typename... KArgs, typename... Args>
void launch(void (*kern)(KArgs...), int grid, int block, int smem, int cluster, bool pdl, Args... args) {
    cudaLaunchConfig_t cfg = {};
    cfg.gridDim = dim3(grid);
    cfg.blockDim = dim3(block);
    cfg.dynamicSmemBytes = smem;
    cfg.stream = cudaStreamPerThread;
    cudaLaunchAttribute at[2];
    int n = 0;
    if (cluster > 1) { at[n].id = cudaLaunchAttributeClusterDimension; at[n].val.clusterDim.x = cluster; at[n].val.clusterDim.y = 1; at[n].val.clusterDim.z = 1; n++; }
    if (pdl) { at[n].id = cudaLaunchAttributeProgrammaticStreamSerialization; at[n].val.programmaticStreamSerializationAllowed = 1; n++; }
    cfg.attrs = at;
    cfg.numAttrs = n;
    cudaLaunchKernelEx(&cfg, kern, KArgs(args)...);
}

template <typename T> void* sym(const T& s) { void* p = nullptr; cudaGetSymbolAddress(&p, s); return p; }

}

extern "C" void kernel_launch(void* const* d_in, const int* in_sizes, int n_in, void* d_out, int out_size) {
    const __nv_bfloat16* x = (const __nv_bfloat16*)d_in[0];
    const __nv_bfloat16* wq = (const __nv_bfloat16*)d_in[1];
    const __nv_bfloat16* wk = (const __nv_bfloat16*)d_in[2];
    const __nv_bfloat16* wv = (const __nv_bfloat16*)d_in[3];
    const __nv_bfloat16* wo = (const __nv_bfloat16*)d_in[4];
    const __nv_bfloat16* w1 = (const __nv_bfloat16*)d_in[6];
    const __nv_bfloat16* w2 = (const __nv_bfloat16*)d_in[7];

    constexpr int SM_QKV = GemmSmem<64, QKV_STAGES, EPI_QKV>::TOTAL;
    constexpr int HALF_PLUS = 116736;
    constexpr int SM_WO = GemmSmem<64, WO_STAGES, EPI_RES>::TOTAL > HALF_PLUS ? GemmSmem<64, WO_STAGES, EPI_RES>::TOTAL : HALF_PLUS;
    constexpr int SM_FFN2 = GemmSmem<64, FFN2_STAGES, EPI_RES>::TOTAL > HALF_PLUS ? GemmSmem<64, FFN2_STAGES, EPI_RES>::TOTAL : HALF_PLUS;
    constexpr int SM_FFN1 = GemmSmem<224, FFN1_STAGES, EPI_FFN1>::TOTAL;
    cudaFuncSetAttribute(qkv_kernel, cudaFuncAttributeMaxDynamicSharedMemorySize, SM_QKV);
    cudaFuncSetAttribute(res_gemm_kernel<8, WO_STAGES>, cudaFuncAttributeMaxDynamicSharedMemorySize, SM_WO);
    cudaFuncSetAttribute(ffn1_kernel, cudaFuncAttributeMaxDynamicSharedMemorySize, SM_FFN1);
    cudaFuncSetAttribute(res_gemm_kernel<28, FFN2_STAGES>, cudaFuncAttributeMaxDynamicSharedMemorySize, SM_FFN2);
    cudaFuncSetAttribute(attn_kernel, cudaFuncAttributeMaxDynamicSharedMemorySize, ATT_SMEM);
    cudaFuncSetAttribute(prep_kernel, cudaFuncAttributePreferredSharedMemoryCarveout, 100);
    cudaFuncSetAttribute(qkv_kernel, cudaFuncAttributePreferredSharedMemoryCarveout, 100);
    cudaFuncSetAttribute(res_gemm_kernel<8, WO_STAGES>, cudaFuncAttributePreferredSharedMemoryCarveout, 100);
    cudaFuncSetAttribute(ffn1_kernel, cudaFuncAttributePreferredSharedMemoryCarveout, 100);
    cudaFuncSetAttribute(res_gemm_kernel<28, FFN2_STAGES>, cudaFuncAttributePreferredSharedMemoryCarveout, 100);
    cudaFuncSetAttribute(attn_kernel, cudaFuncAttributePreferredSharedMemoryCarveout, 100);

    void *q = sym(g_q), *o = sym(g_o), *x1 = sym(g_x1), *x2 = sym(g_x2), *x3 = sym(g_x3), *h = sym(g_h);
    float2* stats = (float2*)sym(g_stats);
    const void* xs[5] = {x, x1, x2, x3, d_out};

    const CUtensorMapSwizzle SW128 = CU_TENSOR_MAP_SWIZZLE_128B, SW64 = CU_TENSOR_MAP_SWIZZLE_64B;
    const CUtensorMap mWq = map2d(wq, D_, D_, 64, 64, SW128);
    const CUtensorMap mWk = map2d(wk, 16, D_, 16, 64, CU_TENSOR_MAP_SWIZZLE_32B);
    const CUtensorMap mWv = map2d(wv, 16, D_, 16, 64, CU_TENSOR_MAP_SWIZZLE_32B);
    const CUtensorMap mWo = map2d(wo, D_, D_, 64, 64, SW128);
    const CUtensorMap mW1a = map3d32(w1, F_, D_, 32, 4), mW1b = map3d32(w1, F_, D_, 32, 3);
    const CUtensorMap mW2 = map2d(w2, D_, F_, 64, 64, SW128);
    const CUtensorMap mQ = map2d(q, D_, S_, 64, 64, SW128);
    const CUtensorMap mO = map2d(o, D_, S_, 64, 64, SW128);
    const CUtensorMap mHst = map2d(h, F_, S_, 32, 16, SW64);
    const CUtensorMap mHld = map2d(h, F_, S_, 64, 64, SW128);
    CUtensorMap mX[5], mX32[2];
    for (int i = 0; i < 5; i++) mX[i] = map2d(xs[i], D_, S_, 64, 64, SW128);
    mX32[0] = map2d(x1, D_, S_, 32, 64, SW64);
    mX32[1] = map2d(x3, D_, S_, 32, 64, SW64);

    launch(prep_kernel, PREP_CS_CTAS + PREP_STAT_CTAS, 256, 0, 1, false, x, wq, wk, wv, wo, w1, w2);
    for (int layer = 0; layer < 2; layer++) {
        const int xi = layer * 2;
        GemmParams p;
        p.stats_in = stats + (size_t)xi * 8 * S_; p.stats_out = nullptr; p.wait_in_epilogue = layer == 0; p.tk = 1 + 5 * layer;
        launch(qkv_kernel, 128, 288, SM_QKV, 2, true, mX[xi], mWq, mWk, mWv, mQ, p);
        launch(attn_kernel, 128, 512, ATT_SMEM, 1, true, 2 + 5 * layer);
        p.stats_in = nullptr; p.stats_out = stats + (size_t)(xi + 1) * 8 * S_; p.wait_in_epilogue = 0; p.tk = 3 + 5 * layer;
        launch(res_gemm_kernel<8, WO_STAGES>, 128, 288, SM_WO, 2, true, mO, mWo, mX[xi], mX[xi + 1], p);
        p.stats_in = stats + (size_t)(xi + 1) * 8 * S_; p.stats_out = nullptr; p.tk = 4 + 5 * layer;
        launch(ffn1_kernel, 128, 256, SM_FFN1, 2, true, mX32[layer], mW1a, mW1b, mHst, p);
        p.stats_in = nullptr; p.stats_out = layer == 0 ? stats + (size_t)2 * 8 * S_ : nullptr; p.tk = 5 + 5 * layer;
        launch(res_gemm_kernel<28, FFN2_STAGES>, 128, 288, SM_FFN2, 2, true, mHld, mW2, mX[xi + 1], mX[xi + 2], p);
    }
}
```

```cpp
#include <cuda_runtime.h>
#include <cuda_bf16.h>
#include <cuda.h>
#include <stdint.h>

namespace {

constexpr int S_ = 2048, D_ = 512, H_ = 32, F_ = 1792;

__device__ __align__(1024) __nv_bfloat16 g_q[S_ * D_];
__device__ __align__(1024) __nv_bfloat16 g_o[S_ * D_];
__device__ __align__(1024) __nv_bfloat16 g_x1[S_ * D_];
__device__ __align__(1024) __nv_bfloat16 g_x2[S_ * D_];
__device__ __align__(1024) __nv_bfloat16 g_x3[S_ * D_];
__device__ __align__(1024) __nv_bfloat16 g_h[S_ * F_];
__device__ __align__(1024) uint8_t g_kimg[S_ * 32];
__device__ __align__(1024) uint8_t g_vimg[(S_ / 16) * 768];
__device__ __align__(1024) float2 g_stats[4][8 * S_];
__device__ __align__(16) float g_cs_q[D_];
__device__ __align__(16) float g_cs_kv[32];
__device__ __align__(16) float g_cs_1[F_];
__device__ __align__(16) float g_kvmax[32];

#define TL(k, slot)

__device__ __forceinline__ uint32_t smem_u32(const void* p) { return (uint32_t)__cvta_generic_to_shared(p); }
__device__ __forceinline__ void mbar_init(uint32_t bar, uint32_t cnt) {
    asm volatile("mbarrier.init.shared::cta.b64 [%0], %1;" ::"r"(bar), "r"(cnt));
}
__device__ __forceinline__ void mbar_expect_tx(uint32_t bar, uint32_t bytes) {
    asm volatile("mbarrier.arrive.expect_tx.shared::cta.b64 _, [%0], %1;" ::"r"(bar), "r"(bytes) : "memory");
}
__device__ __forceinline__ void mbar_arrive(uint32_t bar) {
    asm volatile("mbarrier.arrive.shared::cta.b64 _, [%0];" ::"r"(bar) : "memory");
}
__device__ __forceinline__ void mbar_arrive_remote(uint32_t bar, uint32_t cta) {
    asm volatile("{\n.reg .b32 ra;\nmapa.shared::cluster.u32 ra, %0, %1;\nmbarrier.arrive.shared::cluster.b64 _, [ra];\n}" ::"r"(bar), "r"(cta) : "memory");
}
__device__ __forceinline__ void mbar_wait(uint32_t bar, uint32_t parity) {
    asm volatile("{\n.reg .pred p;\nWAIT_%=:\nmbarrier.try_wait.parity.shared::cta.b64 p, [%0], %1;\n@p bra DONE_%=;\nbra WAIT_%=;\nDONE_%=:\n}" ::"r"(bar), "r"(parity) : "memory");
}
__device__ __forceinline__ void bulk_load(uint32_t dst, const void* src, uint32_t bytes, uint32_t bar) {
    asm volatile("cp.async.bulk.shared::cluster.global.mbarrier::complete_tx::bytes [%0], [%1], %2, [%3];" ::"r"(dst), "l"(src), "r"(bytes), "r"(bar) : "memory");
}
__device__ __forceinline__ void tma2d(uint32_t dst, const CUtensorMap* m, int c0, int c1, uint32_t bar) {
    asm volatile("cp.async.bulk.tensor.2d.shared::cluster.global.mbarrier::complete_tx::bytes [%0], [%1, {%3, %4}], [%2];" ::"r"(dst), "l"(m), "r"(bar), "r"(c0), "r"(c1) : "memory");
}
__device__ __forceinline__ void tma2d_mc(uint32_t dst, const CUtensorMap* m, int c0, int c1, uint32_t bar, uint16_t mask) {
    asm volatile("cp.async.bulk.tensor.2d.shared::cluster.global.mbarrier::complete_tx::bytes.multicast::cluster [%0], [%1, {%3, %4}], [%2], %5;" ::"r"(dst), "l"(m), "r"(bar), "r"(c0), "r"(c1), "h"(mask) : "memory");
}
__device__ __forceinline__ void tma3d(uint32_t dst, const CUtensorMap* m, int c0, int c1, int c2, uint32_t bar) {
    asm volatile("cp.async.bulk.tensor.3d.shared::cluster.global.mbarrier::complete_tx::bytes [%0], [%1, {%3, %4, %5}], [%2];" ::"r"(dst), "l"(m), "r"(bar), "r"(c0), "r"(c1), "r"(c2) : "memory");
}
__device__ __forceinline__ void tma3d_mc(uint32_t dst, const CUtensorMap* m, int c0, int c1, int c2, uint32_t bar, uint16_t mask) {
    asm volatile("cp.async.bulk.tensor.3d.shared::cluster.global.mbarrier::complete_tx::bytes.multicast::cluster [%0], [%1, {%3, %4, %5}], [%2], %6;" ::"r"(dst), "l"(m), "r"(bar), "r"(c0), "r"(c1), "r"(c2), "h"(mask) : "memory");
}
__device__ __forceinline__ void tma2d_store(const CUtensorMap* m, uint32_t src, int c0, int c1) {
    asm volatile("cp.async.bulk.tensor.2d.global.shared::cta.bulk_group [%0, {%2, %3}], [%1];" ::"l"(m), "r"(src), "r"(c0), "r"(c1) : "memory");
}
__device__ __forceinline__ void tma3d_store(const CUtensorMap* m, uint32_t src, int c0, int c1, int c2) {
    asm volatile("cp.async.bulk.tensor.3d.global.shared::cta.bulk_group [%0, {%2, %3, %4}], [%1];" ::"l"(m), "r"(src), "r"(c0), "r"(c1), "r"(c2) : "memory");
}
__device__ __forceinline__ void bulk_commit() { asm volatile("cp.async.bulk.commit_group;" ::: "memory"); }
__device__ __forceinline__ void bulk_wait_read() { asm volatile("cp.async.bulk.wait_group.read 0;" ::: "memory"); }
__device__ __forceinline__ void prefetch_tmap(const CUtensorMap* m) { asm volatile("prefetch.tensormap [%0];" ::"l"(m) : "memory"); }
__device__ __forceinline__ void fence_async_smem() { asm volatile("fence.proxy.async.shared::cta;" ::: "memory"); }
__device__ __forceinline__ void fence_mbar_init() { asm volatile("fence.mbarrier_init.release.cluster;" ::: "memory"); }
__device__ __forceinline__ void cluster_sync() { asm volatile("barrier.cluster.arrive.release.aligned;\nbarrier.cluster.wait.acquire.aligned;" ::: "memory"); }
__device__ __forceinline__ uint32_t cluster_rank() { uint32_t r; asm volatile("mov.u32 %0, %%cluster_ctarank;" : "=r"(r)); return r; }
__device__ __forceinline__ void pdl_wait() { asm volatile("griddepcontrol.wait;" ::: "memory"); }
__device__ __forceinline__ void pdl_launch() { asm volatile("griddepcontrol.launch_dependents;" ::: "memory"); }
__device__ __forceinline__ void named_bar(int id, int n) { asm volatile("bar.sync %0, %1;" ::"r"(id), "r"(n) : "memory"); }

__device__ __forceinline__ void wg_fence() { asm volatile("wgmma.fence.sync.aligned;" ::: "memory"); }
__device__ __forceinline__ void wg_commit() { asm volatile("wgmma.commit_group.sync.aligned;" ::: "memory"); }
template <int N> __device__ __forceinline__ void wg_wait() { asm volatile("wgmma.wait_group.sync.aligned %0;" ::"n"(N) : "memory"); }
template <int N> __device__ __forceinline__ void fence_regs(float (&d)[N]) {
#pragma unroll
    for (int i = 0; i < N; i++) asm volatile("" : "+f"(d[i])::"memory");
}
__device__ __forceinline__ uint64_t mkdesc(uint32_t addr, uint32_t lbo, uint32_t sbo, uint32_t swz) {
    uint64_t d = 0;
    d |= (uint64_t)((addr & 0x3FFFF) >> 4);
    d |= (uint64_t)((lbo & 0x3FFFF) >> 4) << 16;
    d |= (uint64_t)((sbo & 0x3FFFF) >> 4) << 32;
    d |= (uint64_t)swz << 62;
    return d;
}
__device__ __forceinline__ void ldsm_x4(uint32_t& r0, uint32_t& r1, uint32_t& r2, uint32_t& r3, uint32_t addr) {
    asm volatile("ldmatrix.sync.aligned.m8n8.x4.shared.b16 {%0,%1,%2,%3}, [%4];" : "=r"(r0), "=r"(r1), "=r"(r2), "=r"(r3) : "r"(addr) : "memory");
}
__device__ __forceinline__ void stsm_x4(uint32_t addr, uint32_t r0, uint32_t r1, uint32_t r2, uint32_t r3) {
    asm volatile("stmatrix.sync.aligned.m8n8.x4.shared.b16 [%0], {%1,%2,%3,%4};" ::"r"(addr), "r"(r0), "r"(r1), "r"(r2), "r"(r3) : "memory");
}
__device__ __forceinline__ uint32_t pack_bf16(float lo, float hi) {
    uint32_t r;
    asm("cvt.rn.bf16x2.f32 %0, %1, %2;" : "=r"(r) : "f"(hi), "f"(lo));
    return r;
}
__device__ __forceinline__ float bf_lo(uint32_t v) { return __uint_as_float(v << 16); }
__device__ __forceinline__ float bf_hi(uint32_t v) { return __uint_as_float(v & 0xFFFF0000u); }

#define WG_REGS_4(o) "+f"(d[o]), "+f"(d[o + 1]), "+f"(d[o + 2]), "+f"(d[o + 3])
#define WG_REGS_8(o) WG_REGS_4(o), WG_REGS_4(o + 4)
#define WG_REGS_16(o) WG_REGS_8(o), WG_REGS_8(o + 8)
#define WG_REGS_32(o) WG_REGS_16(o), WG_REGS_16(o + 16)

__device__ __forceinline__ void wgmma_ss_n80_tb(float (&d)[40], uint64_t dA, uint64_t dB, int sc) {
    asm volatile("{\n.reg .pred p;\nsetp.ne.b32 p, %42, 0;\n"
                 "wgmma.mma_async.sync.aligned.m64n80k16.f32.bf16.bf16 "
                 "{%0,%1,%2,%3,%4,%5,%6,%7,%8,%9,%10,%11,%12,%13,%14,%15,%16,%17,%18,%19,%20,%21,%22,%23,%24,%25,%26,%27,%28,%29,%30,%31,"
                 "%32,%33,%34,%35,%36,%37,%38,%39}, %40, %41, p, 1, 1, 0, 1;\n}\n"
                 : WG_REGS_32(0), WG_REGS_8(32) : "l"(dA), "l"(dB), "r"(sc));
}
__device__ __forceinline__ void wgmma_ss_n64_tb(float (&d)[32], uint64_t dA, uint64_t dB, int sc) {
    asm volatile("{\n.reg .pred p;\nsetp.ne.b32 p, %34, 0;\n"
                 "wgmma.mma_async.sync.aligned.m64n64k16.f32.bf16.bf16 "
                 "{%0,%1,%2,%3,%4,%5,%6,%7,%8,%9,%10,%11,%12,%13,%14,%15,%16,%17,%18,%19,%20,%21,%22,%23,%24,%25,%26,%27,%28,%29,%30,%31}, "
                 "%32, %33, p, 1, 1, 0, 1;\n}\n"
                 : WG_REGS_32(0) : "l"(dA), "l"(dB), "r"(sc));
}
__device__ __forceinline__ void wgmma_ss_n224_tb(float (&d)[112], uint64_t dA, uint64_t dB, int sc) {
    asm volatile("{\n.reg .pred p;\nsetp.ne.b32 p, %114, 0;\n"
                 "wgmma.mma_async.sync.aligned.m64n224k16.f32.bf16.bf16 "
                 "{%0,%1,%2,%3,%4,%5,%6,%7,%8,%9,%10,%11,%12,%13,%14,%15,%16,%17,%18,%19,%20,%21,%22,%23,%24,%25,%26,%27,%28,%29,%30,%31,"
                 "%32,%33,%34,%35,%36,%37,%38,%39,%40,%41,%42,%43,%44,%45,%46,%47,%48,%49,%50,%51,%52,%53,%54,%55,%56,%57,%58,%59,%60,%61,%62,%63,"
                 "%64,%65,%66,%67,%68,%69,%70,%71,%72,%73,%74,%75,%76,%77,%78,%79,%80,%81,%82,%83,%84,%85,%86,%87,%88,%89,%90,%91,%92,%93,%94,%95,"
                 "%96,%97,%98,%99,%100,%101,%102,%103,%104,%105,%106,%107,%108,%109,%110,%111}, "
                 "%112, %113, p, 1, 1, 0, 1;\n}\n"
                 : WG_REGS_32(0), WG_REGS_32(32), WG_REGS_32(64), WG_REGS_16(96) : "l"(dA), "l"(dB), "r"(sc));
}
template <int BN> __device__ __forceinline__ void wgmma_ss_tb(float (&d)[BN / 2], uint64_t dA, uint64_t dB, int sc) {
    if constexpr (BN == 64) wgmma_ss_n64_tb(d, dA, dB, sc);
    else if constexpr (BN == 80) wgmma_ss_n80_tb(d, dA, dB, sc);
    else wgmma_ss_n224_tb(d, dA, dB, sc);
}
__device__ __forceinline__ void wgmma_rs_n64_z(float (&d)[32], uint32_t a0, uint32_t a1, uint32_t a2, uint32_t a3, uint64_t dB) {
    asm volatile("{\n.reg .pred p;\nsetp.ne.b32 p, 0, 0;\n"
                 "wgmma.mma_async.sync.aligned.m64n64k16.f32.bf16.bf16 "
                 "{%0,%1,%2,%3,%4,%5,%6,%7,%8,%9,%10,%11,%12,%13,%14,%15,%16,%17,%18,%19,%20,%21,%22,%23,%24,%25,%26,%27,%28,%29,%30,%31}, "
                 "{%32,%33,%34,%35}, %36, p, 1, 1, 0;\n}\n"
                 : "=f"(d[0]), "=f"(d[1]), "=f"(d[2]), "=f"(d[3]), "=f"(d[4]), "=f"(d[5]), "=f"(d[6]), "=f"(d[7]),
                   "=f"(d[8]), "=f"(d[9]), "=f"(d[10]), "=f"(d[11]), "=f"(d[12]), "=f"(d[13]), "=f"(d[14]), "=f"(d[15]),
                   "=f"(d[16]), "=f"(d[17]), "=f"(d[18]), "=f"(d[19]), "=f"(d[20]), "=f"(d[21]), "=f"(d[22]), "=f"(d[23]),
                   "=f"(d[24]), "=f"(d[25]), "=f"(d[26]), "=f"(d[27]), "=f"(d[28]), "=f"(d[29]), "=f"(d[30]), "=f"(d[31])
                 : "r"(a0), "r"(a1), "r"(a2), "r"(a3), "l"(dB));
}
__device__ __forceinline__ void wgmma_rs_n24_tb(float (&d)[12], uint32_t a0, uint32_t a1, uint32_t a2, uint32_t a3, uint64_t dB) {
    asm volatile("{\n.reg .pred p;\nsetp.eq.b32 p, 0, 0;\n"
                 "wgmma.mma_async.sync.aligned.m64n24k16.f32.bf16.bf16 "
                 "{%0,%1,%2,%3,%4,%5,%6,%7,%8,%9,%10,%11}, {%12,%13,%14,%15}, %16, p, 1, 1, 1;\n}\n"
                 : WG_REGS_8(0), WG_REGS_4(8) : "r"(a0), "r"(a1), "r"(a2), "r"(a3), "l"(dB));
}

constexpr int PREP_STAT_CTAS = S_ / 8;
constexpr int PREP_CS_CTAS = 8 + 1 + F_ / 64;

__global__ void __launch_bounds__(256) prep_kernel(const __nv_bfloat16* __restrict__ x, const __nv_bfloat16* __restrict__ wq,
                                                   const __nv_bfloat16* __restrict__ wk, const __nv_bfloat16* __restrict__ wv,
                                                   const __nv_bfloat16* __restrict__ wo, const __nv_bfloat16* __restrict__ w1,
                                                   const __nv_bfloat16* __restrict__ w2) {
    pdl_launch();
    const int tid = threadIdx.x;
    if (tid == 0) { TL(0, 0); TL(0, 1); }
    if (blockIdx.x < PREP_CS_CTAS) {
        __shared__ float red[32][65];
        const int b = blockIdx.x;
        const int rg = tid >> 3, c8 = tid & 7;
        float acc[8];
#pragma unroll
        for (int i = 0; i < 8; i++) acc[i] = 0.f;
        const __nv_bfloat16* base;
        int ld;
        bool active = true;
        if (b < 8) { base = wq + b * 64 + c8 * 8; ld = D_; }
        else if (b == 8) { base = (c8 < 2 ? wk + c8 * 8 : wv + (c8 - 2) * 8); ld = 16; active = c8 < 4; }
        else { base = w1 + (b - 9) * 64 + c8 * 8; ld = F_; }
        if (active) {
            uint4 v[16];
#pragma unroll
            for (int i = 0; i < 16; i++) v[i] = __ldg((const uint4*)(base + (size_t)(rg + 32 * i) * ld));
#pragma unroll
            for (int i = 0; i < 16; i++) {
                acc[0] += bf_lo(v[i].x); acc[1] += bf_hi(v[i].x); acc[2] += bf_lo(v[i].y); acc[3] += bf_hi(v[i].y);
                acc[4] += bf_lo(v[i].z); acc[5] += bf_hi(v[i].z); acc[6] += bf_lo(v[i].w); acc[7] += bf_hi(v[i].w);
            }
        }
#pragma unroll
        for (int i = 0; i < 8; i++) red[rg][c8 * 8 + i] = acc[i];
        __syncthreads();
        if (tid < 64) {
            float s = 0.f;
#pragma unroll
            for (int i = 0; i < 32; i++) s += red[i][tid];
            if (b < 8) g_cs_q[b * 64 + tid] = s;
            else if (b == 8) { if (tid < 32) g_cs_kv[tid] = s; }
            else g_cs_1[(b - 9) * 64 + tid] = s;
        }
    } else {
        const int cb = blockIdx.x - PREP_CS_CTAS;
        if (tid < 72) {
            const int line = cb * 72 + tid;
            const char* p = line < 4096 ? (const char*)wo + (size_t)line * 128 : (const char*)w2 + (size_t)(line - 4096) * 128;
            asm volatile("prefetch.global.L2 [%0];" ::"l"(p));
        }
        const int warp = tid >> 5, lane = tid & 31;
        const int row = cb * 8 + warp;
        const uint4* p = (const uint4*)(x + (size_t)row * D_ + lane * 16);
        const uint4 a = __ldg(p), b = __ldg(p + 1);
        float v[16] = {bf_lo(a.x), bf_hi(a.x), bf_lo(a.y), bf_hi(a.y), bf_lo(a.z), bf_hi(a.z), bf_lo(a.w), bf_hi(a.w),
                       bf_lo(b.x), bf_hi(b.x), bf_lo(b.y), bf_hi(b.y), bf_lo(b.z), bf_hi(b.z), bf_lo(b.w), bf_hi(b.w)};
        float s = 0.f;
#pragma unroll
        for (int i = 0; i < 16; i++) s += v[i];
        s += __shfl_xor_sync(0xffffffffu, s, 1);
        s += __shfl_xor_sync(0xffffffffu, s, 2);
        const float mean = s * (1.f / 64.f);
        float m2 = 0.f;
#pragma unroll
        for (int i = 0; i < 16; i++) { const float d = v[i] - mean; m2 += d * d; }
        m2 += __shfl_xor_sync(0xffffffffu, m2, 1);
        m2 += __shfl_xor_sync(0xffffffffu, m2, 2);
        if ((lane & 3) == 0) g_stats[0][(lane >> 2) * S_ + row] = make_float2(mean, m2);
    }
    if (tid == 0) { TL(0, 2); TL(0, 3); }
}

enum { EPI_QKV = 0, EPI_RES = 1, EPI_FFN1 = 2 };

struct GemmParams {
    const float2* stats_in;
    float2* stats_out;
    int wait_in_epilogue;
    int tk;
};

template <int BK_, int NBLK> struct Geo;
template <> struct Geo<64, 1> {
    static constexpr int BK = 64, A_BYTES = 128 * 128, A_SWZ = 1, A_SBO = 1024;
    static constexpr int B_BYTES = 64 * 128, B_SWZ = 1, B_LBO = 8192, B_SBO = 1024, B_KSTEP = 2048;
};
template <int NBLK> struct Geo<32, NBLK> {
    static constexpr int BK = 32, A_BYTES = 128 * 64, A_SWZ = 2, A_SBO = 512;
    static constexpr int B_BYTES = NBLK * 32 * 64, B_SWZ = 2, B_LBO = 2048, B_SBO = 512, B_KSTEP = 1024;
};
template <int EPI> struct EpiGeo;
template <> struct EpiGeo<EPI_QKV> { using G = Geo<32, 3>; };
template <> struct EpiGeo<EPI_RES> { using G = Geo<64, 1>; };
template <> struct EpiGeo<EPI_FFN1> { using G = Geo<32, 7>; };

template <int STAGES, int EPI> struct GemmSmem {
    using G = typename EpiGeo<EPI>::G;
    static constexpr int STAGE = G::A_BYTES + G::B_BYTES;
    static constexpr int AUX_OFF = STAGES * STAGE;
    static constexpr int TOTAL = AUX_OFF + 1024;
};

struct RowStatRaw { float2 a0, a1, b0, b1; };
__device__ __forceinline__ RowStatRaw load_row_stats(const float2* __restrict__ st, int row0, int c) {
    RowStatRaw r;
    r.a0 = st[(2 * c) * S_ + row0]; r.a1 = st[(2 * c + 1) * S_ + row0];
    r.b0 = st[(2 * c) * S_ + row0 + 8]; r.b1 = st[(2 * c + 1) * S_ + row0 + 8];
    return r;
}
__device__ __forceinline__ void finish_row_stats(const RowStatRaw& r, float& mean0, float& rstd0, float& mean1, float& rstd1) {
    float sa = r.a0.x + r.a1.x, sb = r.b0.x + r.b1.x;
    sa += __shfl_xor_sync(0xffffffffu, sa, 1); sa += __shfl_xor_sync(0xffffffffu, sa, 2);
    sb += __shfl_xor_sync(0xffffffffu, sb, 1); sb += __shfl_xor_sync(0xffffffffu, sb, 2);
    mean0 = sa * 0.125f; mean1 = sb * 0.125f;
    float ma = r.a0.y + r.a1.y + 64.f * ((r.a0.x - mean0) * (r.a0.x - mean0) + (r.a1.x - mean0) * (r.a1.x - mean0));
    float mb = r.b0.y + r.b1.y + 64.f * ((r.b0.x - mean1) * (r.b0.x - mean1) + (r.b1.x - mean1) * (r.b1.x - mean1));
    ma += __shfl_xor_sync(0xffffffffu, ma, 1); ma += __shfl_xor_sync(0xffffffffu, ma, 2);
    mb += __shfl_xor_sync(0xffffffffu, mb, 1); mb += __shfl_xor_sync(0xffffffffu, mb, 2);
    rstd0 = 1.0f / sqrtf(ma * (1.f / 512.f) + 1e-5f);
    rstd1 = 1.0f / sqrtf(mb * (1.f / 512.f) + 1e-5f);
}

template <int BN, int KB, int STAGES, int EPI, int MC>
__device__ __forceinline__ void gemm_body(const CUtensorMap* mapA, const CUtensorMap* mapB, const CUtensorMap* mapB2, const CUtensorMap* mapR,
                                          const CUtensorMap* mapC, const GemmParams& prm, int tile_m, int tile_n, uint8_t* smem_raw) {
    using SM = GemmSmem<STAGES, EPI>;
    using G = typename SM::G;
    constexpr bool XKV = BN == 80;
    constexpr int TN = EPI == EPI_QKV ? 64 : BN;
    pdl_launch();
    const uint32_t sbase = smem_u32(smem_raw);
    if (sbase & 1023) __trap();
    uint8_t* sgen = smem_raw;
    const uint32_t bar_full = sbase + SM::AUX_OFF, bar_empty = bar_full + 8 * STAGES;
    float* s_cs = (float*)(sgen + SM::AUX_OFF + 128);
    float* s_red = (float*)(sgen + SM::AUX_OFF + 640);
    const int tid = threadIdx.x, warp = tid >> 5, lane = tid & 31;
    const uint32_t rank = MC ? cluster_rank() : 0;
    if (tid == 0) TL(prm.tk, 0);

    constexpr bool INLINE_PROD = EPI == EPI_FFN1;
    if (tid == (INLINE_PROD ? 0 : 256)) {
        prefetch_tmap(mapB); prefetch_tmap(mapA); prefetch_tmap(mapC);
        for (int s = 0; s < STAGES; s++) { mbar_init(bar_full + 8 * s, 1); mbar_init(bar_empty + 8 * s, MC ? 4 : 2); }
        fence_mbar_init();
    }
    __syncthreads();
    if (MC) cluster_sync();

    const int m0 = tile_m * 128, n0 = tile_n * TN;
    constexpr uint32_t STAGE_TX = G::A_BYTES + (EPI == EPI_QKV ? (XKV ? 3 : 2) * 2048 : G::B_BYTES);
    auto loadB = [&](int kb, int s) {
        const uint32_t dst = sbase + s * SM::STAGE + G::A_BYTES, bar = bar_full + 8 * s;
        if constexpr (EPI == EPI_RES) {
            tma2d(dst, mapB, n0, kb * 64, bar);
        } else if constexpr (EPI == EPI_QKV) {
            tma3d(dst, mapB, 0, kb * 32, tile_n * 2, bar);
            if constexpr (XKV) tma2d(dst + 2 * 2048, mapB2, 0, kb * 32, bar);
        } else {
            if (rank == 0) tma3d_mc(dst, mapB, 0, kb * 32, tile_n * 7, bar, 3);
            else tma3d_mc(dst + 4 * 2048, mapB2, 0, kb * 32, tile_n * 7 + 4, bar, 3);
        }
    };
    auto loadA = [&](int kb, int s) {
        const uint32_t dst = sbase + s * SM::STAGE, bar = bar_full + 8 * s;
        if constexpr (MC == 1) tma2d_mc(dst + rank * (G::A_BYTES / 2), mapA, kb * G::BK, m0 + rank * 64, bar, 3);
        else { tma2d(dst, mapA, kb * G::BK, m0, bar); tma2d(dst + G::A_BYTES / 2, mapA, kb * G::BK, m0 + 64, bar); }
    };
    constexpr int PRE = STAGES < KB ? STAGES : KB;
    auto prologue_loads = [&]() {
        for (int kb = 0; kb < PRE; kb++) { mbar_expect_tx(bar_full + 8 * kb, STAGE_TX); loadB(kb, kb); }
        if (!prm.wait_in_epilogue) pdl_wait();
        for (int kb = 0; kb < PRE; kb++) loadA(kb, kb);
    };
    if (!INLINE_PROD && warp == 8) {
        if (lane == 0) {
            prologue_loads();
            int s = PRE % STAGES, ph = (PRE / STAGES) & 1;
            for (int kb = PRE; kb < KB; kb++) {
                mbar_wait(bar_empty + 8 * s, ph ^ 1);
                mbar_expect_tx(bar_full + 8 * s, STAGE_TX);
                loadB(kb, s);
                loadA(kb, s);
                if (++s == STAGES) { s = 0; ph ^= 1; }
            }
            if constexpr (EPI == EPI_RES) {
                mbar_wait(bar_empty + 8 * s, ph ^ 1);
                mbar_expect_tx(bar_full + 8 * s, 16384);
                tma2d(sbase + s * SM::STAGE, mapR, n0, m0, bar_full + 8 * s);
                tma2d(sbase + s * SM::STAGE + 8192, mapR, n0, m0 + 64, bar_full + 8 * s);
            }
        }
    } else {
        if (INLINE_PROD && tid == 0) prologue_loads();
        const int wg = warp >> 2, g = lane >> 2, c = lane & 3;
        const int rloc = wg * 64 + (warp & 3) * 16 + g;
        const int row0 = m0 + rloc;
        float mean0 = 0.f, rstd0 = 1.f, mean1 = 0.f, rstd1 = 1.f;
        RowStatRaw raw;
        float csv = 0.f;
        auto ln_inputs = [&]() {
            pdl_wait();
            if constexpr (EPI != EPI_RES) {
                raw = load_row_stats(prm.stats_in, row0, c);
                const float* cs = EPI == EPI_FFN1 ? g_cs_1 + n0 : g_cs_q + n0;
                if (tid < TN) csv = cs[tid];
            }
        };
        if (!prm.wait_in_epilogue) ln_inputs();
        float acc[BN / 2];
        const uint64_t dA0 = mkdesc(sbase + wg * (G::A_BYTES / 2), 16, G::A_SBO, G::A_SWZ);
        const uint64_t dB0 = mkdesc(sbase + G::A_BYTES, G::B_LBO, G::B_SBO, G::B_SWZ);
        int s = 0, ph = 0;
#pragma unroll 1
        for (int kb = 0; kb < KB; kb++) {
            mbar_wait(bar_full + 8 * s, ph);
            const uint64_t dA = dA0 + (uint64_t)(s * (SM::STAGE >> 4)), dB = dB0 + (uint64_t)(s * (SM::STAGE >> 4));
            wg_fence();
#pragma unroll
            for (int k = 0; k < G::BK / 16; k++) wgmma_ss_tb<BN>(acc, dA + (uint64_t)(k * 2), dB + (uint64_t)(k * (G::B_KSTEP >> 4)), (kb | k) != 0);
            wg_commit();
            if constexpr (EPI == EPI_RES) {
                wg_wait<0>();
                if ((tid & 127) == 0) {
                    if (MC) { mbar_arrive_remote(bar_empty + 8 * s, 0); mbar_arrive_remote(bar_empty + 8 * s, 1); }
                    else mbar_arrive(bar_empty + 8 * s);
                }
            } else if (kb > 0) {
                wg_wait<1>();
                const int sp = s == 0 ? STAGES - 1 : s - 1;
                if ((tid & 127) == 0) {
                    if (MC) { mbar_arrive_remote(bar_empty + 8 * sp, 0); mbar_arrive_remote(bar_empty + 8 * sp, 1); }
                    else mbar_arrive(bar_empty + 8 * sp);
                }
                if (INLINE_PROD && tid == 0 && kb >= 2 && kb - 2 + STAGES < KB) {
                    const int sq = sp == 0 ? STAGES - 1 : sp - 1;
                    mbar_wait(bar_empty + 8 * sq, ((kb - 2) / STAGES) & 1);
                    mbar_expect_tx(bar_full + 8 * sq, STAGE_TX);
                    loadB(kb - 2 + STAGES, sq);
                    loadA(kb - 2 + STAGES, sq);
                }
                if (INLINE_PROD) __syncwarp();
            }
            if (++s == STAGES) { s = 0; ph ^= 1; }
        }
        if (prm.wait_in_epilogue) ln_inputs();
        if constexpr (EPI != EPI_RES) {
            finish_row_stats(raw, mean0, rstd0, mean1, rstd1);
            if (tid < TN) s_cs[tid] = csv;
        }
        wg_wait<0>();
        fence_regs(acc);
        if (tid == 0) TL(prm.tk, 2);
        if constexpr (EPI != EPI_RES) named_bar(1, 256);

        if constexpr (XKV) {
            {
                const float* acx = &acc[32];
                const float rm0 = rstd0 * mean0, rm1 = rstd1 * mean1;
                float n0s = 0.f, n1s = 0.f, vmax = 0.f;
#pragma unroll
                for (int j = 0; j < 2; j++) {
                    const float2 cs2 = *(const float2*)(g_cs_kv + tile_n * 16 + 8 * j + 2 * c);
                    const uint32_t u0 = pack_bf16(acx[4 * j] * rstd0 - rm0 * cs2.x, acx[4 * j + 1] * rstd0 - rm0 * cs2.y);
                    const uint32_t u1 = pack_bf16(acx[4 * j + 2] * rstd1 - rm1 * cs2.x, acx[4 * j + 3] * rstd1 - rm1 * cs2.y);
                    n0s += bf_lo(u0) * bf_lo(u0) + bf_hi(u0) * bf_hi(u0);
                    n1s += bf_lo(u1) * bf_lo(u1) + bf_hi(u1) * bf_hi(u1);
                    vmax = fmaxf(vmax, fmaxf(fmaxf(fabsf(bf_lo(u0)), fabsf(bf_hi(u0))), fmaxf(fabsf(bf_lo(u1)), fabsf(bf_hi(u1)))));
                    if (tile_n == 0) {
                        *(uint32_t*)(g_kimg + (row0 >> 3) * 256 + j * 128 + g * 16 + c * 4) = u0;
                        *(uint32_t*)(g_kimg + ((row0 + 8) >> 3) * 256 + j * 128 + g * 16 + c * 4) = u1;
                    } else {
                        uint8_t* vb = g_vimg + (row0 >> 4) * 768 + j * 256 + g * 16 + c * 4;
                        *(uint32_t*)(vb) = u0;
                        *(uint32_t*)(vb + 128) = u1;
                    }
                }
                if (tile_n == 1) {
                    uint8_t* vb = g_vimg + (row0 >> 4) * 768 + 512 + g * 16 + c * 4;
                    const uint32_t one = c == 0 ? 0x00003F80u : 0u;
                    *(uint32_t*)(vb) = one;
                    *(uint32_t*)(vb + 128) = one;
                }
                n0s += __shfl_xor_sync(0xffffffffu, n0s, 1); n0s += __shfl_xor_sync(0xffffffffu, n0s, 2);
                n1s += __shfl_xor_sync(0xffffffffu, n1s, 1); n1s += __shfl_xor_sync(0xffffffffu, n1s, 2);
                float km = tile_n == 0 ? fmaxf(n0s, n1s) : vmax;
                if (!(n0s + n1s < INFINITY)) km = INFINITY;
#pragma unroll
                for (int o = 1; o < 32; o <<= 1) km = fmaxf(km, __shfl_xor_sync(0xffffffffu, km, o));
                if (lane == 0) s_red[warp] = km;
                named_bar(1, 256);
                if (tid == 0) {
                    float a = 0.f;
                    for (int i = 0; i < 8; i++) a = fmaxf(a, s_red[i]);
                    g_kvmax[tile_n * 16 + tile_m] = a;
                }
            }
        }
        if constexpr (EPI != EPI_FFN1) {
            const uint32_t stile = sbase + (EPI == EPI_RES ? s * SM::STAGE : 0);
            const int mrow = wg * 64 + (warp & 3) * 16 + (lane & 7) + ((lane >> 3) & 1) * 8;
            const uint32_t rbase = stile + mrow * 128;
            if constexpr (EPI == EPI_RES) {
                mbar_wait(bar_full + 8 * s, ph);
                float s0 = 0.f, s1 = 0.f;
#pragma unroll
                for (int jj = 0; jj < 4; jj++) {
                    uint32_t r0, r1, r2, r3;
                    const uint32_t addr = rbase + (((2 * jj + (lane >> 4)) ^ (mrow & 7)) << 4);
                    ldsm_x4(r0, r1, r2, r3, addr);
                    const uint32_t u0 = pack_bf16(acc[8 * jj] + bf_lo(r0), acc[8 * jj + 1] + bf_hi(r0));
                    const uint32_t u1 = pack_bf16(acc[8 * jj + 2] + bf_lo(r1), acc[8 * jj + 3] + bf_hi(r1));
                    const uint32_t u2 = pack_bf16(acc[8 * jj + 4] + bf_lo(r2), acc[8 * jj + 5] + bf_hi(r2));
                    const uint32_t u3 = pack_bf16(acc[8 * jj + 6] + bf_lo(r3), acc[8 * jj + 7] + bf_hi(r3));
                    stsm_x4(addr, u0, u1, u2, u3);
                    acc[8 * jj] = bf_lo(u0); acc[8 * jj + 1] = bf_hi(u0); acc[8 * jj + 4] = bf_lo(u2); acc[8 * jj + 5] = bf_hi(u2);
                    acc[8 * jj + 2] = bf_lo(u1); acc[8 * jj + 3] = bf_hi(u1); acc[8 * jj + 6] = bf_lo(u3); acc[8 * jj + 7] = bf_hi(u3);
                    s0 += (acc[8 * jj] + acc[8 * jj + 1]) + (acc[8 * jj + 4] + acc[8 * jj + 5]);
                    s1 += (acc[8 * jj + 2] + acc[8 * jj + 3]) + (acc[8 * jj + 6] + acc[8 * jj + 7]);
                }
                fence_async_smem();
                named_bar(2 + wg, 128);
                if ((tid & 127) == 0) { tma2d_store(mapC, stile + wg * 8192, n0, m0 + wg * 64); bulk_commit(); }
                if (prm.stats_out) {
                    s0 += __shfl_xor_sync(0xffffffffu, s0, 1); s0 += __shfl_xor_sync(0xffffffffu, s0, 2);
                    s1 += __shfl_xor_sync(0xffffffffu, s1, 1); s1 += __shfl_xor_sync(0xffffffffu, s1, 2);
                    const float mu0 = s0 * (1.f / 64.f), mu1 = s1 * (1.f / 64.f);
                    float q0 = 0.f, q1 = 0.f;
#pragma unroll
                    for (int j = 0; j < 8; j++) {
                        float d;
                        d = acc[4 * j] - mu0; q0 += d * d; d = acc[4 * j + 1] - mu0; q0 += d * d;
                        d = acc[4 * j + 2] - mu1; q1 += d * d; d = acc[4 * j + 3] - mu1; q1 += d * d;
                    }
                    q0 += __shfl_xor_sync(0xffffffffu, q0, 1); q0 += __shfl_xor_sync(0xffffffffu, q0, 2);
                    q1 += __shfl_xor_sync(0xffffffffu, q1, 1); q1 += __shfl_xor_sync(0xffffffffu, q1, 2);
                    if (c == 0) {
                        prm.stats_out[tile_n * S_ + row0] = make_float2(mu0, q0);
                        prm.stats_out[tile_n * S_ + row0 + 8] = make_float2(mu1, q1);
                    }
                }
            } else {
                const float sc = 0.25f * 1.4426950408889634f;
                const float a0 = rstd0 * sc, a1 = rstd1 * sc, rm0 = a0 * mean0, rm1 = a1 * mean1;
#pragma unroll
                for (int jj = 0; jj < 4; jj++) {
                    const float2 ca = *(const float2*)(s_cs + 16 * jj + 2 * c), cb = *(const float2*)(s_cs + 16 * jj + 8 + 2 * c);
                    const uint32_t u0 = pack_bf16(acc[8 * jj] * a0 - rm0 * ca.x, acc[8 * jj + 1] * a0 - rm0 * ca.y);
                    const uint32_t u1 = pack_bf16(acc[8 * jj + 2] * a1 - rm1 * ca.x, acc[8 * jj + 3] * a1 - rm1 * ca.y);
                    const uint32_t u2 = pack_bf16(acc[8 * jj + 4] * a0 - rm0 * cb.x, acc[8 * jj + 5] * a0 - rm0 * cb.y);
                    const uint32_t u3 = pack_bf16(acc[8 * jj + 6] * a1 - rm1 * cb.x, acc[8 * jj + 7] * a1 - rm1 * cb.y);
                    stsm_x4(rbase + (((2 * jj + (lane >> 4)) ^ (mrow & 7)) << 4), u0, u1, u2, u3);
                }
                fence_async_smem();
                named_bar(2 + wg, 128);
                if ((tid & 127) == 0) { tma2d_store(mapC, stile + wg * 8192, n0, m0 + wg * 64); bulk_commit(); }
            }
            if ((tid & 127) == 0) bulk_wait_read();
        } else {
            const uint32_t stile = sbase + wg * (7 * 4096);
            const int mrow = (warp & 3) * 16 + (lane & 7) + ((lane >> 3) & 1) * 8;
            const float a0 = 0.5f * rstd0, a1 = 0.5f * rstd1, rm0 = a0 * mean0, rm1 = a1 * mean1;
#pragma unroll
            for (int jj = 0; jj < 14; jj++) {
                const float2 ca = *(const float2*)(s_cs + 16 * jj + 2 * c), cb = *(const float2*)(s_cs + 16 * jj + 8 + 2 * c);
                float y[8] = {acc[8 * jj] * a0 - rm0 * ca.x,     acc[8 * jj + 1] * a0 - rm0 * ca.y,
                              acc[8 * jj + 2] * a1 - rm1 * ca.x, acc[8 * jj + 3] * a1 - rm1 * ca.y,
                              acc[8 * jj + 4] * a0 - rm0 * cb.x, acc[8 * jj + 5] * a0 - rm0 * cb.y,
                              acc[8 * jj + 6] * a1 - rm1 * cb.x, acc[8 * jj + 7] * a1 - rm1 * cb.y};
#pragma unroll
                for (int i = 0; i < 8; i++) {
                    float t;
                    asm("tanh.approx.f32 %0, %1;" : "=f"(t) : "f"(y[i]));
                    y[i] = fmaf(y[i], t, y[i]);
                }
                const int chunk = (2 * jj + (lane >> 4)) & 3, blk = jj >> 1;
                stsm_x4(stile + blk * 4096 + mrow * 64 + ((chunk ^ ((mrow >> 1) & 3)) << 4),
                        pack_bf16(y[0], y[1]), pack_bf16(y[2], y[3]), pack_bf16(y[4], y[5]), pack_bf16(y[6], y[7]));
                if (jj & 1) {
                    fence_async_smem();
                    __syncwarp();
                    if (lane == 0) {
                        tma2d_store(mapC, stile + blk * 4096 + (warp & 3) * 1024, n0 + blk * 32, m0 + wg * 64 + (warp & 3) * 16);
                        bulk_commit();
                    }
                }
            }
            if (lane == 0) bulk_wait_read();
        }
    }
    if (tid == 0) TL(prm.tk, 3);
    if (MC) cluster_sync();
}

#define WO_ST 5
#define F2_ST 5
#define F1_ST 4
constexpr int QKV_STAGES = 7, WO_STAGES = WO_ST, FFN2_STAGES = F2_ST, FFN1_STAGES = F1_ST;
__global__ void __launch_bounds__(288) qkv_kernel(const __grid_constant__ CUtensorMap mapA, const __grid_constant__ CUtensorMap mapWq,
                                                  const __grid_constant__ CUtensorMap mapWk, const __grid_constant__ CUtensorMap mapWv,
                                                  const __grid_constant__ CUtensorMap mapQ, const GemmParams prm) {
    extern __shared__ __align__(1024) uint8_t smem_raw[];
    uint32_t pad[40];
#pragma unroll
    for (int i = 0; i < 40; i++) asm volatile("mov.u32 %0, %%clock;" : "=r"(pad[i]));
    const int tn = blockIdx.x & 7;
    if (tn < 2) gemm_body<80, 16, QKV_STAGES, EPI_QKV, 1>(&mapA, &mapWq, tn == 0 ? &mapWk : &mapWv, &mapA, &mapQ, prm, blockIdx.x >> 3, tn, smem_raw);
    else gemm_body<64, 16, QKV_STAGES, EPI_QKV, 1>(&mapA, &mapWq, &mapWq, &mapA, &mapQ, prm, blockIdx.x >> 3, tn, smem_raw);
    if (prm.stats_in == nullptr) {
#pragma unroll
        for (int i = 0; i < 40; i++) asm volatile("st.volatile.global.u32 [%0], %1;" ::"l"(g_kimg + 4 * i), "r"(pad[i]) : "memory");
    }
}
template <int KB, int STAGES>
__global__ void __launch_bounds__(288) res_gemm_kernel(const __grid_constant__ CUtensorMap mapA, const __grid_constant__ CUtensorMap mapW,
                                                       const __grid_constant__ CUtensorMap mapR, const __grid_constant__ CUtensorMap mapC, const GemmParams prm) {
    extern __shared__ __align__(1024) uint8_t smem_raw[];
    gemm_body<64, KB, STAGES, EPI_RES, 1>(&mapA, &mapW, &mapW, &mapR, &mapC, prm, blockIdx.x >> 3, blockIdx.x & 7, smem_raw);
}
__global__ void __launch_bounds__(256) ffn1_kernel(const __grid_constant__ CUtensorMap mapA, const __grid_constant__ CUtensorMap mapW4,
                                                   const __grid_constant__ CUtensorMap mapW3, const __grid_constant__ CUtensorMap mapH, const GemmParams prm) {
    extern __shared__ __align__(1024) uint8_t smem_raw[];
    const int pair = blockIdx.x >> 1, tile_n = pair & 7, tile_m = (pair >> 3) * 2 + (blockIdx.x & 1);
    gemm_body<224, 16, FFN1_STAGES, EPI_FFN1, 2>(&mapA, &mapW4, &mapW3, &mapA, &mapH, prm, tile_m, tile_n, smem_raw);
}

constexpr int NPOLY = 10;
__host__ __device__ constexpr bool is_mufu(int i) { return ((i + 1) * (16 - NPOLY)) / 16 != (i * (16 - NPOLY)) / 16; }

__device__ __forceinline__ float ex2(float x) { float r; asm("ex2.approx.ftz.f32 %0, %1;" : "=f"(r) : "f"(x)); return r; }
__device__ __forceinline__ uint32_t exp_pair_mufu(float a, float b) { return pack_bf16(ex2(a), ex2(b)); }
__device__ __forceinline__ uint32_t exp_pair_fma(float a, float b, uint32_t c3f) {
    constexpr float MAGIC = 98430.4140625f;
    const float ta = a + MAGIC, tb = b + (MAGIC - 143.5f);
    uint32_t y, m, r;
    asm("mad.lo.u32 %0, %1, 65536, %2;" : "=r"(y) : "r"(__float_as_uint(tb)), "r"(__float_as_uint(ta)));
    asm("lop3.b32 %0, %1, 0x007F007F, %2, 0xEA;" : "=r"(m) : "r"(y), "r"(c3f));
    const uint32_t e = y & 0xFF80FF80u;
    asm("fma.rn.bf16x2 %0, %1, %2, %3;" : "=r"(r) : "r"(y), "r"(m), "r"(e));
    return r;
}

constexpr int KCH = 256, NCH = S_ / KCH;
constexpr int K_BYTES = S_ * 32, V_BYTES = (S_ / 16) * 768;
constexpr int ATT_SMEM = K_BYTES + V_BYTES;

__global__ void __launch_bounds__(512, 1) attn_kernel(int tk) {
    extern __shared__ __align__(1024) uint8_t smem[];
    __shared__ uint64_t bars[NCH];
    __shared__ int s_slow;
    const int tid = threadIdx.x, wg = tid >> 7, warp = (tid >> 5) & 3, lane = tid & 31;
    const uint32_t sK = smem_u32(smem), sV = sK + K_BYTES;
    if (tid == 0) TL(tk, 0);
    if (tid == 0) {
        for (int i = 0; i < NCH; i++) mbar_init(smem_u32(&bars[i]), 1);
        s_slow = 0;
        fence_mbar_init();
    }
    __syncthreads();
    pdl_launch();
    pdl_wait();
    if (tid == 0) TL(tk, 1);
    if (tid == 0) {
        for (int i = 0; i < NCH; i++) {
            mbar_expect_tx(smem_u32(&bars[i]), KCH * 32 + (KCH / 16) * 768);
            bulk_load(sK + i * KCH * 32, g_kimg + i * KCH * 32, KCH * 32, smem_u32(&bars[i]));
            bulk_load(sV + i * (KCH / 16) * 768, g_vimg + i * (KCH / 16) * 768, (KCH / 16) * 768, smem_u32(&bars[i]));
        }
    }
    const int tb = blockIdx.x >> 3, hg = blockIdx.x & 7;
    const int head = hg * 4 + wg;
    const int g = lane >> 2, c = lane & 3;
    uint32_t qa[2][4];
    float qn = 0.f;
#pragma unroll
    for (int m = 0; m < 2; m++) {
        const int row = tb * 128 + m * 64 + warp * 16 + g;
        const uint32_t* p0 = (const uint32_t*)(g_q + (size_t)row * D_ + head * 16);
        const uint32_t* p1 = (const uint32_t*)(g_q + (size_t)(row + 8) * D_ + head * 16);
        qa[m][0] = p0[c]; qa[m][1] = p1[c]; qa[m][2] = p0[c + 4]; qa[m][3] = p1[c + 4];
        float n0 = bf_lo(qa[m][0]) * bf_lo(qa[m][0]) + bf_hi(qa[m][0]) * bf_hi(qa[m][0]) + bf_lo(qa[m][2]) * bf_lo(qa[m][2]) + bf_hi(qa[m][2]) * bf_hi(qa[m][2]);
        float n1 = bf_lo(qa[m][1]) * bf_lo(qa[m][1]) + bf_hi(qa[m][1]) * bf_hi(qa[m][1]) + bf_lo(qa[m][3]) * bf_lo(qa[m][3]) + bf_hi(qa[m][3]) * bf_hi(qa[m][3]);
        n0 += __shfl_xor_sync(0xffffffffu, n0, 1); n0 += __shfl_xor_sync(0xffffffffu, n0, 2);
        n1 += __shfl_xor_sync(0xffffffffu, n1, 1); n1 += __shfl_xor_sync(0xffffffffu, n1, 2);
        if (!(n0 == n0) || !(n1 == n1)) n0 = __int_as_float(0x7f800000);
        qn = fmaxf(qn, fmaxf(n0, n1));
    }
    {
        float km = 0.f, vm = 0.f;
#pragma unroll
        for (int i = 0; i < 16; i++) { km = fmaxf(km, g_kvmax[i]); vm = fmaxf(vm, g_kvmax[16 + i]); }
        const bool ok = (qn * km <= 10000.f) && (vm <= 16384.f);
        if (!ok) s_slow = 1;
    }
    float oacc[2][12];
#pragma unroll
    for (int m = 0; m < 2; m++)
#pragma unroll
        for (int i = 0; i < 12; i++) oacc[m][i] = 0.f;
    __syncthreads();
    const bool slow = s_slow != 0;

    const uint64_t dK0 = mkdesc(sK, 128, 256, 0);
    const uint64_t dV0 = mkdesc(sV, 128, 256, 0);
    uint32_t c3f;
    asm volatile("mov.b32 %0, 0x3F003F00;" : "=r"(c3f));
    if (!slow) {
#pragma unroll 1
        for (int t = 0; t < S_ / 64; t++) {
            if ((t & 3) == 0) mbar_wait(smem_u32(&bars[t >> 2]), 0);
            const uint64_t dK = dK0 + (uint64_t)(t * 64 * 32 / 16);
            const uint64_t dV = dV0 + (uint64_t)(t * 4 * 768 / 16);
#pragma unroll
            for (int m = 0; m < 2; m++) {
                float s[32];
                wg_fence();
                wgmma_rs_n64_z(s, qa[m][0], qa[m][1], qa[m][2], qa[m][3], dK);
                wg_commit();
                wg_wait<0>();
                fence_regs(s);
                uint32_t p[16];
#pragma unroll
                for (int i = 0; i < 16; i++) p[i] = is_mufu(i) ? exp_pair_mufu(s[2 * i], s[2 * i + 1]) : exp_pair_fma(s[2 * i], s[2 * i + 1], c3f);
                wg_fence();
#pragma unroll
                for (int kk = 0; kk < 4; kk++)
                    wgmma_rs_n24_tb(oacc[m], p[4 * kk], p[4 * kk + 1], p[4 * kk + 2], p[4 * kk + 3], dV + (uint64_t)(kk * 768 / 16));
                wg_commit();
            }
        }
        wg_wait<0>();
    } else {
        float mx[2][2] = {{-INFINITY, -INFINITY}, {-INFINITY, -INFINITY}};
#pragma unroll 1
        for (int t = 0; t < S_ / 64; t++) {
            if ((t & 3) == 0) mbar_wait(smem_u32(&bars[t >> 2]), 0);
            const uint64_t dK = dK0 + (uint64_t)(t * 64 * 32 / 16);
            const uint64_t dV = dV0 + (uint64_t)(t * 4 * 768 / 16);
#pragma unroll
            for (int m = 0; m < 2; m++) {
                float s[32];
                wg_fence();
                wgmma_rs_n64_z(s, qa[m][0], qa[m][1], qa[m][2], qa[m][3], dK);
                wg_commit();
                wg_wait<0>();
                fence_regs(s);
                fence_regs(oacc[m]);
                float r0 = mx[m][0], r1 = mx[m][1];
#pragma unroll
                for (int j = 0; j < 8; j++) {
                    r0 = fmaxf(r0, fmaxf(s[4 * j], s[4 * j + 1]));
                    r1 = fmaxf(r1, fmaxf(s[4 * j + 2], s[4 * j + 3]));
                }
                r0 = fmaxf(r0, __shfl_xor_sync(0xffffffffu, r0, 1)); r0 = fmaxf(r0, __shfl_xor_sync(0xffffffffu, r0, 2));
                r1 = fmaxf(r1, __shfl_xor_sync(0xffffffffu, r1, 1)); r1 = fmaxf(r1, __shfl_xor_sync(0xffffffffu, r1, 2));
                const float al0 = ex2(mx[m][0] - r0), al1 = ex2(mx[m][1] - r1);
                mx[m][0] = r0; mx[m][1] = r1;
#pragma unroll
                for (int j = 0; j < 3; j++) {
                    oacc[m][4 * j] *= al0; oacc[m][4 * j + 1] *= al0;
                    oacc[m][4 * j + 2] *= al1; oacc[m][4 * j + 3] *= al1;
                }
                uint32_t p[16];
#pragma unroll
                for (int j = 0; j < 8; j++) {
                    p[2 * j] = pack_bf16(ex2(s[4 * j] - r0), ex2(s[4 * j + 1] - r0));
                    p[2 * j + 1] = pack_bf16(ex2(s[4 * j + 2] - r1), ex2(s[4 * j + 3] - r1));
                }
                fence_regs(oacc[m]);
                wg_fence();
#pragma unroll
                for (int kk = 0; kk < 4; kk++)
                    wgmma_rs_n24_tb(oacc[m], p[4 * kk], p[4 * kk + 1], p[4 * kk + 2], p[4 * kk + 3], dV + (uint64_t)(kk * 768 / 16));
                wg_commit();
                wg_wait<0>();
            }
        }
    }
    fence_regs(oacc[0]); fence_regs(oacc[1]);
    if (tid == 0) TL(tk, 2);
#pragma unroll
    for (int m = 0; m < 2; m++) {
        const float l0 = __shfl_sync(0xffffffffu, oacc[m][8], lane & ~3);
        const float l1 = __shfl_sync(0xffffffffu, oacc[m][10], lane & ~3);
        const float r0 = 1.0f / l0, r1 = 1.0f / l1;
        const int row = tb * 128 + m * 64 + warp * 16 + g;
        uint32_t* p0 = (uint32_t*)(g_o + (size_t)row * D_ + head * 16);
        uint32_t* p1 = (uint32_t*)(g_o + (size_t)(row + 8) * D_ + head * 16);
        p0[c] = pack_bf16(oacc[m][0] * r0, oacc[m][1] * r0);
        p1[c] = pack_bf16(oacc[m][2] * r1, oacc[m][3] * r1);
        p0[c + 4] = pack_bf16(oacc[m][4] * r0, oacc[m][5] * r0);
        p1[c + 4] = pack_bf16(oacc[m][6] * r1, oacc[m][7] * r1);
    }
    if (tid == 0) TL(tk, 3);
}

typedef CUresult (*EncodeFn)(CUtensorMap*, CUtensorMapDataType, cuuint32_t, void*, const cuuint64_t*, const cuuint64_t*, const cuuint32_t*,
                             const cuuint32_t*, CUtensorMapInterleave, CUtensorMapSwizzle, CUtensorMapL2promotion, CUtensorMapFloatOOBfill);

EncodeFn get_encode() {
    static EncodeFn fn = nullptr;
    if (!fn) {
        void* p = nullptr;
        cudaDriverEntryPointQueryResult qr;
        cudaGetDriverEntryPoint("cuTensorMapEncodeTiled", &p, cudaEnableDefault, &qr);
        fn = (EncodeFn)p;
    }
    return fn;
}
CUtensorMap map2d(const void* ptr, uint64_t cols, uint64_t rows, uint32_t bc, uint32_t br, CUtensorMapSwizzle sw) {
    CUtensorMap m;
    cuuint64_t gd[2] = {cols, rows}, gs[1] = {cols * 2};
    cuuint32_t bx[2] = {bc, br}, es[2] = {1, 1};
    get_encode()(&m, CU_TENSOR_MAP_DATA_TYPE_BFLOAT16, 2, (void*)ptr, gd, gs, bx, es, CU_TENSOR_MAP_INTERLEAVE_NONE, sw,
                 CU_TENSOR_MAP_L2_PROMOTION_L2_128B, CU_TENSOR_MAP_FLOAT_OOB_FILL_NONE);
    return m;
}
CUtensorMap map3d32(const void* ptr, uint64_t cols, uint64_t rows, uint32_t br, uint32_t nb) {
    CUtensorMap m;
    cuuint64_t gd[3] = {32, rows, cols / 32}, gs[2] = {cols * 2, 64};
    cuuint32_t bx[3] = {32, br, nb}, es[3] = {1, 1, 1};
    get_encode()(&m, CU_TENSOR_MAP_DATA_TYPE_BFLOAT16, 3, (void*)ptr, gd, gs, bx, es, CU_TENSOR_MAP_INTERLEAVE_NONE, CU_TENSOR_MAP_SWIZZLE_64B,
                 CU_TENSOR_MAP_L2_PROMOTION_L2_128B, CU_TENSOR_MAP_FLOAT_OOB_FILL_NONE);
    return m;
}

template <typename... KArgs, typename... Args>
void launch(void (*kern)(KArgs...), int grid, int block, int smem, int cluster, bool pdl, Args... args) {
    cudaLaunchConfig_t cfg = {};
    cfg.gridDim = dim3(grid);
    cfg.blockDim = dim3(block);
    cfg.dynamicSmemBytes = smem;
    cfg.stream = cudaStreamPerThread;
    cudaLaunchAttribute at[2];
    int n = 0;
    if (cluster > 1) { at[n].id = cudaLaunchAttributeClusterDimension; at[n].val.clusterDim.x = cluster; at[n].val.clusterDim.y = 1; at[n].val.clusterDim.z = 1; n++; }
    if (pdl) { at[n].id = cudaLaunchAttributeProgrammaticStreamSerialization; at[n].val.programmaticStreamSerializationAllowed = 1; n++; }
    cfg.attrs = at;
    cfg.numAttrs = n;
    cudaLaunchKernelEx(&cfg, kern, KArgs(args)...);
}

template <typename T> void* sym(const T& s) { void* p = nullptr; cudaGetSymbolAddress(&p, s); return p; }

}

extern "C" void kernel_launch(void* const* d_in, const int* in_sizes, int n_in, void* d_out, int out_size) {
    const __nv_bfloat16* x = (const __nv_bfloat16*)d_in[0];
    const __nv_bfloat16* wq = (const __nv_bfloat16*)d_in[1];
    const __nv_bfloat16* wk = (const __nv_bfloat16*)d_in[2];
    const __nv_bfloat16* wv = (const __nv_bfloat16*)d_in[3];
    const __nv_bfloat16* wo = (const __nv_bfloat16*)d_in[4];
    const __nv_bfloat16* w1 = (const __nv_bfloat16*)d_in[6];
    const __nv_bfloat16* w2 = (const __nv_bfloat16*)d_in[7];

    constexpr int SM_QKV = GemmSmem<QKV_STAGES, EPI_QKV>::TOTAL;
    constexpr int HALF_PLUS = 116736;
    constexpr int SM_WO = GemmSmem<WO_STAGES, EPI_RES>::TOTAL > HALF_PLUS ? GemmSmem<WO_STAGES, EPI_RES>::TOTAL : HALF_PLUS;
    constexpr int SM_FFN2 = GemmSmem<FFN2_STAGES, EPI_RES>::TOTAL > HALF_PLUS ? GemmSmem<FFN2_STAGES, EPI_RES>::TOTAL : HALF_PLUS;
    constexpr int SM_FFN1 = GemmSmem<FFN1_STAGES, EPI_FFN1>::TOTAL;
    cudaFuncSetAttribute(qkv_kernel, cudaFuncAttributeMaxDynamicSharedMemorySize, SM_QKV);
    cudaFuncSetAttribute(res_gemm_kernel<8, WO_STAGES>, cudaFuncAttributeMaxDynamicSharedMemorySize, SM_WO);
    cudaFuncSetAttribute(ffn1_kernel, cudaFuncAttributeMaxDynamicSharedMemorySize, SM_FFN1);
    cudaFuncSetAttribute(res_gemm_kernel<28, FFN2_STAGES>, cudaFuncAttributeMaxDynamicSharedMemorySize, SM_FFN2);
    cudaFuncSetAttribute(attn_kernel, cudaFuncAttributeMaxDynamicSharedMemorySize, ATT_SMEM);
    cudaFuncSetAttribute(prep_kernel, cudaFuncAttributePreferredSharedMemoryCarveout, 100);
    cudaFuncSetAttribute(qkv_kernel, cudaFuncAttributePreferredSharedMemoryCarveout, 100);
    cudaFuncSetAttribute(res_gemm_kernel<8, WO_STAGES>, cudaFuncAttributePreferredSharedMemoryCarveout, 100);
    cudaFuncSetAttribute(ffn1_kernel, cudaFuncAttributePreferredSharedMemoryCarveout, 100);
    cudaFuncSetAttribute(res_gemm_kernel<28, FFN2_STAGES>, cudaFuncAttributePreferredSharedMemoryCarveout, 100);
    cudaFuncSetAttribute(attn_kernel, cudaFuncAttributePreferredSharedMemoryCarveout, 100);

    void *q = sym(g_q), *o = sym(g_o), *x1 = sym(g_x1), *x2 = sym(g_x2), *x3 = sym(g_x3), *h = sym(g_h);
    float2* stats = (float2*)sym(g_stats);
    const void* xs[5] = {x, x1, x2, x3, d_out};

    const CUtensorMapSwizzle SW128 = CU_TENSOR_MAP_SWIZZLE_128B, SW64 = CU_TENSOR_MAP_SWIZZLE_64B;
    const CUtensorMap mWq = map3d32(wq, D_, D_, 32, 2);
    const CUtensorMap mWk = map2d(wk, 16, D_, 32, 32, SW64);
    const CUtensorMap mWv = map2d(wv, 16, D_, 32, 32, SW64);
    const CUtensorMap mWo = map2d(wo, D_, D_, 64, 64, SW128);
    const CUtensorMap mW1a = map3d32(w1, F_, D_, 32, 4), mW1b = map3d32(w1, F_, D_, 32, 3);
    const CUtensorMap mW2 = map2d(w2, D_, F_, 64, 64, SW128);
    const CUtensorMap mQ = map2d(q, D_, S_, 64, 64, SW128);
    const CUtensorMap mO = map2d(o, D_, S_, 64, 64, SW128);
    const CUtensorMap mHst = map2d(h, F_, S_, 32, 16, SW64);
    const CUtensorMap mHld = map2d(h, F_, S_, 64, 64, SW128);
    CUtensorMap mX[5], mX32[4];
    for (int i = 0; i < 5; i++) mX[i] = map2d(xs[i], D_, S_, 64, 64, SW128);
    for (int i = 0; i < 4; i++) mX32[i] = map2d(xs[i], D_, S_, 32, 64, SW64);

    launch(prep_kernel, PREP_CS_CTAS + PREP_STAT_CTAS, 256, 0, 1, false, x, wq, wk, wv, wo, w1, w2);
    for (int layer = 0; layer < 2; layer++) {
        const int xi = layer * 2;
        GemmParams p;
        p.stats_in = stats + (size_t)xi * 8 * S_; p.stats_out = nullptr; p.wait_in_epilogue = layer == 0; p.tk = 1 + 5 * layer;
        launch(qkv_kernel, 128, 288, SM_QKV, 2, true, mX32[xi], mWq, mWk, mWv, mQ, p);
        launch(attn_kernel, 128, 512, ATT_SMEM, 1, true, 2 + 5 * layer);
        p.stats_in = nullptr; p.stats_out = stats + (size_t)(xi + 1) * 8 * S_; p.wait_in_epilogue = 0; p.tk = 3 + 5 * layer;
        launch(res_gemm_kernel<8, WO_STAGES>, 128, 288, SM_WO, 2, true, mO, mWo, mX[xi], mX[xi + 1], p);
        p.stats_in = stats + (size_t)(xi + 1) * 8 * S_; p.stats_out = nullptr; p.tk = 4 + 5 * layer;
        launch(ffn1_kernel, 128, 256, SM_FFN1, 2, true, mX32[xi + 1], mW1a, mW1b, mHst, p);
        p.stats_in = nullptr; p.stats_out = layer == 0 ? stats + (size_t)2 * 8 * S_ : nullptr; p.tk = 5 + 5 * layer;
        launch(res_gemm_kernel<28, FFN2_STAGES>, 128, 288, SM_FFN2, 2, true, mHld, mW2, mX[xi + 1], mX[xi + 2], p);
    }
}
```

```cpp
#include <cuda_runtime.h>
#include <cuda_bf16.h>
#include <cuda.h>
#include <stdint.h>

namespace {

constexpr int S_ = 2048, D_ = 512, H_ = 32, F_ = 1792;

__device__ __align__(1024) __nv_bfloat16 g_q[S_ * D_];
__device__ __align__(1024) __nv_bfloat16 g_o[S_ * D_];
__device__ __align__(1024) __nv_bfloat16 g_x1[S_ * D_];
__device__ __align__(1024) __nv_bfloat16 g_x2[S_ * D_];
__device__ __align__(1024) __nv_bfloat16 g_x3[S_ * D_];
__device__ __align__(1024) __nv_bfloat16 g_h[S_ * F_];
__device__ __align__(1024) uint8_t g_kimg[S_ * 32];
__device__ __align__(1024) uint8_t g_vimg[(S_ / 16) * 768];
__device__ __align__(1024) float2 g_stats[4][8 * S_];
__device__ __align__(16) float g_cs_q[D_];
__device__ __align__(16) float g_cs_kv[32];
__device__ __align__(16) float g_cs_1[F_];
__device__ __align__(16) float g_kvmax[32];

#define TL(k, slot)

__device__ __forceinline__ uint32_t smem_u32(const void* p) { return (uint32_t)__cvta_generic_to_shared(p); }
__device__ __forceinline__ void mbar_init(uint32_t bar, uint32_t cnt) {
    asm volatile("mbarrier.init.shared::cta.b64 [%0], %1;" ::"r"(bar), "r"(cnt));
}
__device__ __forceinline__ void mbar_expect_tx(uint32_t bar, uint32_t bytes) {
    asm volatile("mbarrier.arrive.expect_tx.shared::cta.b64 _, [%0], %1;" ::"r"(bar), "r"(bytes) : "memory");
}
__device__ __forceinline__ void mbar_arrive(uint32_t bar) {
    asm volatile("mbarrier.arrive.shared::cta.b64 _, [%0];" ::"r"(bar) : "memory");
}
__device__ __forceinline__ void mbar_arrive_remote(uint32_t bar, uint32_t cta) {
    asm volatile("{\n.reg .b32 ra;\nmapa.shared::cluster.u32 ra, %0, %1;\nmbarrier.arrive.shared::cluster.b64 _, [ra];\n}" ::"r"(bar), "r"(cta) : "memory");
}
__device__ __forceinline__ void mbar_wait(uint32_t bar, uint32_t parity) {
    asm volatile("{\n.reg .pred p;\nWAIT_%=:\nmbarrier.try_wait.parity.shared::cta.b64 p, [%0], %1;\n@p bra DONE_%=;\nbra WAIT_%=;\nDONE_%=:\n}" ::"r"(bar), "r"(parity) : "memory");
}
__device__ __forceinline__ void bulk_load(uint32_t dst, const void* src, uint32_t bytes, uint32_t bar) {
    asm volatile("cp.async.bulk.shared::cluster.global.mbarrier::complete_tx::bytes [%0], [%1], %2, [%3];" ::"r"(dst), "l"(src), "r"(bytes), "r"(bar) : "memory");
}
__device__ __forceinline__ void tma2d(uint32_t dst, const CUtensorMap* m, int c0, int c1, uint32_t bar) {
    asm volatile("cp.async.bulk.tensor.2d.shared::cluster.global.mbarrier::complete_tx::bytes [%0], [%1, {%3, %4}], [%2];" ::"r"(dst), "l"(m), "r"(bar), "r"(c0), "r"(c1) : "memory");
}
__device__ __forceinline__ void tma2d_mc(uint32_t dst, const CUtensorMap* m, int c0, int c1, uint32_t bar, uint16_t mask) {
    asm volatile("cp.async.bulk.tensor.2d.shared::cluster.global.mbarrier::complete_tx::bytes.multicast::cluster [%0], [%1, {%3, %4}], [%2], %5;" ::"r"(dst), "l"(m), "r"(bar), "r"(c0), "r"(c1), "h"(mask) : "memory");
}
__device__ __forceinline__ void tma3d(uint32_t dst, const CUtensorMap* m, int c0, int c1, int c2, uint32_t bar) {
    asm volatile("cp.async.bulk.tensor.3d.shared::cluster.global.mbarrier::complete_tx::bytes [%0], [%1, {%3, %4, %5}], [%2];" ::"r"(dst), "l"(m), "r"(bar), "r"(c0), "r"(c1), "r"(c2) : "memory");
}
__device__ __forceinline__ void tma3d_mc(uint32_t dst, const CUtensorMap* m, int c0, int c1, int c2, uint32_t bar, uint16_t mask) {
    asm volatile("cp.async.bulk.tensor.3d.shared::cluster.global.mbarrier::complete_tx::bytes.multicast::cluster [%0], [%1, {%3, %4, %5}], [%2], %6;" ::"r"(dst), "l"(m), "r"(bar), "r"(c0), "r"(c1), "r"(c2), "h"(mask) : "memory");
}
__device__ __forceinline__ void tma2d_store(const CUtensorMap* m, uint32_t src, int c0, int c1) {
    asm volatile("cp.async.bulk.tensor.2d.global.shared::cta.bulk_group [%0, {%2, %3}], [%1];" ::"l"(m), "r"(src), "r"(c0), "r"(c1) : "memory");
}
__device__ __forceinline__ void tma3d_store(const CUtensorMap* m, uint32_t src, int c0, int c1, int c2) {
    asm volatile("cp.async.bulk.tensor.3d.global.shared::cta.bulk_group [%0, {%2, %3, %4}], [%1];" ::"l"(m), "r"(src), "r"(c0), "r"(c1), "r"(c2) : "memory");
}
__device__ __forceinline__ void bulk_commit() { asm volatile("cp.async.bulk.commit_group;" ::: "memory"); }
__device__ __forceinline__ void bulk_wait_read() { asm volatile("cp.async.bulk.wait_group.read 0;" ::: "memory"); }
__device__ __forceinline__ void prefetch_tmap(const CUtensorMap* m) { asm volatile("prefetch.tensormap [%0];" ::"l"(m) : "memory"); }
__device__ __forceinline__ void fence_async_smem() { asm volatile("fence.proxy.async.shared::cta;" ::: "memory"); }
__device__ __forceinline__ void fence_mbar_init() { asm volatile("fence.mbarrier_init.release.cluster;" ::: "memory"); }
__device__ __forceinline__ void cluster_sync() { asm volatile("barrier.cluster.arrive.release.aligned;\nbarrier.cluster.wait.acquire.aligned;" ::: "memory"); }
__device__ __forceinline__ uint32_t cluster_rank() { uint32_t r; asm volatile("mov.u32 %0, %%cluster_ctarank;" : "=r"(r)); return r; }
__device__ __forceinline__ void pdl_wait() { asm volatile("griddepcontrol.wait;" ::: "memory"); }
__device__ __forceinline__ void pdl_launch() { asm volatile("griddepcontrol.launch_dependents;" ::: "memory"); }
__device__ __forceinline__ bool elect_one() {
    uint32_t p;
    asm volatile("{\n.reg .pred p;\nelect.sync _|p, 0xffffffff;\nselp.b32 %0, 1, 0, p;\n}" : "=r"(p));
    return p != 0;
}
__device__ __forceinline__ void named_bar(int id, int n) { asm volatile("bar.sync %0, %1;" ::"r"(id), "r"(n) : "memory"); }

__device__ __forceinline__ void wg_fence() { asm volatile("wgmma.fence.sync.aligned;" ::: "memory"); }
__device__ __forceinline__ void wg_commit() { asm volatile("wgmma.commit_group.sync.aligned;" ::: "memory"); }
template <int N> __device__ __forceinline__ void wg_wait() { asm volatile("wgmma.wait_group.sync.aligned %0;" ::"n"(N) : "memory"); }
template <int N> __device__ __forceinline__ void fence_regs(float (&d)[N]) {
#pragma unroll
    for (int i = 0; i < N; i++) asm volatile("" : "+f"(d[i])::"memory");
}
__device__ __forceinline__ uint64_t mkdesc(uint32_t addr, uint32_t lbo, uint32_t sbo, uint32_t swz) {
    uint64_t d = 0;
    d |= (uint64_t)((addr & 0x3FFFF) >> 4);
    d |= (uint64_t)((lbo & 0x3FFFF) >> 4) << 16;
    d |= (uint64_t)((sbo & 0x3FFFF) >> 4) << 32;
    d |= (uint64_t)swz << 62;
    return d;
}
__device__ __forceinline__ void ldsm_x4(uint32_t& r0, uint32_t& r1, uint32_t& r2, uint32_t& r3, uint32_t addr) {
    asm volatile("ldmatrix.sync.aligned.m8n8.x4.shared.b16 {%0,%1,%2,%3}, [%4];" : "=r"(r0), "=r"(r1), "=r"(r2), "=r"(r3) : "r"(addr) : "memory");
}
__device__ __forceinline__ void stsm_x4(uint32_t addr, uint32_t r0, uint32_t r1, uint32_t r2, uint32_t r3) {
    asm volatile("stmatrix.sync.aligned.m8n8.x4.shared.b16 [%0], {%1,%2,%3,%4};" ::"r"(addr), "r"(r0), "r"(r1), "r"(r2), "r"(r3) : "memory");
}
__device__ __forceinline__ uint32_t pack_bf16(float lo, float hi) {
    uint32_t r;
    asm("cvt.rn.bf16x2.f32 %0, %1, %2;" : "=r"(r) : "f"(hi), "f"(lo));
    return r;
}
__device__ __forceinline__ float bf_lo(uint32_t v) { return __uint_as_float(v << 16); }
__device__ __forceinline__ float bf_hi(uint32_t v) { return __uint_as_float(v & 0xFFFF0000u); }

#define WG_REGS_4(o) "+f"(d[o]), "+f"(d[o + 1]), "+f"(d[o + 2]), "+f"(d[o + 3])
#define WG_REGS_8(o) WG_REGS_4(o), WG_REGS_4(o + 4)
#define WG_REGS_16(o) WG_REGS_8(o), WG_REGS_8(o + 8)
#define WG_REGS_32(o) WG_REGS_16(o), WG_REGS_16(o + 16)

__device__ __forceinline__ void wgmma_ss_n80_tb(float (&d)[40], uint64_t dA, uint64_t dB, int sc) {
    asm volatile("{\n.reg .pred p;\nsetp.ne.b32 p, %42, 0;\n"
                 "wgmma.mma_async.sync.aligned.m64n80k16.f32.bf16.bf16 "
                 "{%0,%1,%2,%3,%4,%5,%6,%7,%8,%9,%10,%11,%12,%13,%14,%15,%16,%17,%18,%19,%20,%21,%22,%23,%24,%25,%26,%27,%28,%29,%30,%31,"
                 "%32,%33,%34,%35,%36,%37,%38,%39}, %40, %41, p, 1, 1, 0, 1;\n}\n"
                 : WG_REGS_32(0), WG_REGS_8(32) : "l"(dA), "l"(dB), "r"(sc));
}
__device__ __forceinline__ void wgmma_ss_n64_tb(float (&d)[32], uint64_t dA, uint64_t dB, int sc) {
    asm volatile("{\n.reg .pred p;\nsetp.ne.b32 p, %34, 0;\n"
                 "wgmma.mma_async.sync.aligned.m64n64k16.f32.bf16.bf16 "
                 "{%0,%1,%2,%3,%4,%5,%6,%7,%8,%9,%10,%11,%12,%13,%14,%15,%16,%17,%18,%19,%20,%21,%22,%23,%24,%25,%26,%27,%28,%29,%30,%31}, "
                 "%32, %33, p, 1, 1, 0, 1;\n}\n"
                 : WG_REGS_32(0) : "l"(dA), "l"(dB), "r"(sc));
}
__device__ __forceinline__ void wgmma_ss_n224_tb(float (&d)[112], uint64_t dA, uint64_t dB, int sc) {
    asm volatile("{\n.reg .pred p;\nsetp.ne.b32 p, %114, 0;\n"
                 "wgmma.mma_async.sync.aligned.m64n224k16.f32.bf16.bf16 "
                 "{%0,%1,%2,%3,%4,%5,%6,%7,%8,%9,%10,%11,%12,%13,%14,%15,%16,%17,%18,%19,%20,%21,%22,%23,%24,%25,%26,%27,%28,%29,%30,%31,"
                 "%32,%33,%34,%35,%36,%37,%38,%39,%40,%41,%42,%43,%44,%45,%46,%47,%48,%49,%50,%51,%52,%53,%54,%55,%56,%57,%58,%59,%60,%61,%62,%63,"
                 "%64,%65,%66,%67,%68,%69,%70,%71,%72,%73,%74,%75,%76,%77,%78,%79,%80,%81,%82,%83,%84,%85,%86,%87,%88,%89,%90,%91,%92,%93,%94,%95,"
                 "%96,%97,%98,%99,%100,%101,%102,%103,%104,%105,%106,%107,%108,%109,%110,%111}, "
                 "%112, %113, p, 1, 1, 0, 1;\n}\n"
                 : WG_REGS_32(0), WG_REGS_32(32), WG_REGS_32(64), WG_REGS_16(96) : "l"(dA), "l"(dB), "r"(sc));
}
template <int BN> __device__ __forceinline__ void wgmma_ss_tb(float (&d)[BN / 2], uint64_t dA, uint64_t dB, int sc) {
    if constexpr (BN == 64) wgmma_ss_n64_tb(d, dA, dB, sc);
    else if constexpr (BN == 80) wgmma_ss_n80_tb(d, dA, dB, sc);
    else wgmma_ss_n224_tb(d, dA, dB, sc);
}
__device__ __forceinline__ void wgmma_rs_n64_z(float (&d)[32], uint32_t a0, uint32_t a1, uint32_t a2, uint32_t a3, uint64_t dB) {
    asm volatile("{\n.reg .pred p;\nsetp.ne.b32 p, 0, 0;\n"
                 "wgmma.mma_async.sync.aligned.m64n64k16.f32.bf16.bf16 "
                 "{%0,%1,%2,%3,%4,%5,%6,%7,%8,%9,%10,%11,%12,%13,%14,%15,%16,%17,%18,%19,%20,%21,%22,%23,%24,%25,%26,%27,%28,%29,%30,%31}, "
                 "{%32,%33,%34,%35}, %36, p, 1, 1, 0;\n}\n"
                 : "=f"(d[0]), "=f"(d[1]), "=f"(d[2]), "=f"(d[3]), "=f"(d[4]), "=f"(d[5]), "=f"(d[6]), "=f"(d[7]),
                   "=f"(d[8]), "=f"(d[9]), "=f"(d[10]), "=f"(d[11]), "=f"(d[12]), "=f"(d[13]), "=f"(d[14]), "=f"(d[15]),
                   "=f"(d[16]), "=f"(d[17]), "=f"(d[18]), "=f"(d[19]), "=f"(d[20]), "=f"(d[21]), "=f"(d[22]), "=f"(d[23]),
                   "=f"(d[24]), "=f"(d[25]), "=f"(d[26]), "=f"(d[27]), "=f"(d[28]), "=f"(d[29]), "=f"(d[30]), "=f"(d[31])
                 : "r"(a0), "r"(a1), "r"(a2), "r"(a3), "l"(dB));
}
__device__ __forceinline__ void wgmma_rs_n24_tb(float (&d)[12], uint32_t a0, uint32_t a1, uint32_t a2, uint32_t a3, uint64_t dB) {
    asm volatile("{\n.reg .pred p;\nsetp.eq.b32 p, 0, 0;\n"
                 "wgmma.mma_async.sync.aligned.m64n24k16.f32.bf16.bf16 "
                 "{%0,%1,%2,%3,%4,%5,%6,%7,%8,%9,%10,%11}, {%12,%13,%14,%15}, %16, p, 1, 1, 1;\n}\n"
                 : WG_REGS_8(0), WG_REGS_4(8) : "r"(a0), "r"(a1), "r"(a2), "r"(a3), "l"(dB));
}

constexpr int PREP_STAT_CTAS = S_ / 8;
constexpr int PREP_CS_CTAS = 8 + 1 + F_ / 64;

__global__ void __launch_bounds__(256) prep_kernel(const __nv_bfloat16* __restrict__ x, const __nv_bfloat16* __restrict__ wq,
                                                   const __nv_bfloat16* __restrict__ wk, const __nv_bfloat16* __restrict__ wv,
                                                   const __nv_bfloat16* __restrict__ wo, const __nv_bfloat16* __restrict__ w1,
                                                   const __nv_bfloat16* __restrict__ w2) {
    pdl_launch();
    const int tid = threadIdx.x;
    if (tid == 0) { TL(0, 0); TL(0, 1); }
    if (blockIdx.x < PREP_CS_CTAS) {
        __shared__ float red[32][65];
        const int b = blockIdx.x;
        const int rg = tid >> 3, c8 = tid & 7;
        float acc[8];
#pragma unroll
        for (int i = 0; i < 8; i++) acc[i] = 0.f;
        const __nv_bfloat16* base;
        int ld;
        bool active = true;
        if (b < 8) { base = wq + b * 64 + c8 * 8; ld = D_; }
        else if (b == 8) { base = (c8 < 2 ? wk + c8 * 8 : wv + (c8 - 2) * 8); ld = 16; active = c8 < 4; }
        else { base = w1 + (b - 9) * 64 + c8 * 8; ld = F_; }
        if (active) {
            uint4 v[16];
#pragma unroll
            for (int i = 0; i < 16; i++) v[i] = __ldg((const uint4*)(base + (size_t)(rg + 32 * i) * ld));
#pragma unroll
            for (int i = 0; i < 16; i++) {
                acc[0] += bf_lo(v[i].x); acc[1] += bf_hi(v[i].x); acc[2] += bf_lo(v[i].y); acc[3] += bf_hi(v[i].y);
                acc[4] += bf_lo(v[i].z); acc[5] += bf_hi(v[i].z); acc[6] += bf_lo(v[i].w); acc[7] += bf_hi(v[i].w);
            }
        }
#pragma unroll
        for (int i = 0; i < 8; i++) red[rg][c8 * 8 + i] = acc[i];
        __syncthreads();
        if (tid < 64) {
            float s = 0.f;
#pragma unroll
            for (int i = 0; i < 32; i++) s += red[i][tid];
            if (b < 8) g_cs_q[b * 64 + tid] = s;
            else if (b == 8) { if (tid < 32) g_cs_kv[tid] = s; }
            else g_cs_1[(b - 9) * 64 + tid] = s;
        }
    } else {
        const int cb = blockIdx.x - PREP_CS_CTAS;
        if (tid < 72) {
            const int line = cb * 72 + tid;
            const char* p = line < 4096 ? (const char*)wo + (size_t)line * 128 : (const char*)w2 + (size_t)(line - 4096) * 128;
            asm volatile("prefetch.global.L2 [%0];" ::"l"(p));
        }
        const int warp = tid >> 5, lane = tid & 31;
        const int row = cb * 8 + warp;
        const uint4* p = (const uint4*)(x + (size_t)row * D_ + lane * 16);
        const uint4 a = __ldg(p), b = __ldg(p + 1);
        float v[16] = {bf_lo(a.x), bf_hi(a.x), bf_lo(a.y), bf_hi(a.y), bf_lo(a.z), bf_hi(a.z), bf_lo(a.w), bf_hi(a.w),
                       bf_lo(b.x), bf_hi(b.x), bf_lo(b.y), bf_hi(b.y), bf_lo(b.z), bf_hi(b.z), bf_lo(b.w), bf_hi(b.w)};
        float s = 0.f;
#pragma unroll
        for (int i = 0; i < 16; i++) s += v[i];
        s += __shfl_xor_sync(0xffffffffu, s, 1);
        s += __shfl_xor_sync(0xffffffffu, s, 2);
        const float mean = s * (1.f / 64.f);
        float m2 = 0.f;
#pragma unroll
        for (int i = 0; i < 16; i++) { const float d = v[i] - mean; m2 += d * d; }
        m2 += __shfl_xor_sync(0xffffffffu, m2, 1);
        m2 += __shfl_xor_sync(0xffffffffu, m2, 2);
        if ((lane & 3) == 0) g_stats[0][(lane >> 2) * S_ + row] = make_float2(mean, m2);
    }
    if (tid == 0) { TL(0, 2); TL(0, 3); }
}

enum { EPI_QKV = 0, EPI_RES = 1, EPI_FFN1 = 2 };

struct GemmParams {
    const float2* stats_in;
    float2* stats_out;
    int wait_in_epilogue;
    int tk;
};

template <int BK_, int NBLK> struct Geo;
template <> struct Geo<64, 1> {
    static constexpr int BK = 64, A_BYTES = 128 * 128, A_SWZ = 1, A_SBO = 1024;
    static constexpr int B_BYTES = 64 * 128, B_SWZ = 1, B_LBO = 8192, B_SBO = 1024, B_KSTEP = 2048;
};
template <int NBLK> struct Geo<32, NBLK> {
    static constexpr int BK = 32, A_BYTES = 128 * 64, A_SWZ = 2, A_SBO = 512;
    static constexpr int B_BYTES = NBLK * 32 * 64, B_SWZ = 2, B_LBO = 2048, B_SBO = 512, B_KSTEP = 1024;
};
template <int EPI> struct EpiGeo;
template <> struct EpiGeo<EPI_QKV> { using G = Geo<32, 3>; };
template <> struct EpiGeo<EPI_RES> { using G = Geo<64, 1>; };
template <> struct EpiGeo<EPI_FFN1> { using G = Geo<32, 7>; };

template <int STAGES, int EPI> struct GemmSmem {
    using G = typename EpiGeo<EPI>::G;
    static constexpr int STAGE = G::A_BYTES + G::B_BYTES;
    static constexpr int AUX_OFF = STAGES * STAGE;
    static constexpr int TOTAL = AUX_OFF + 1024;
};

struct RowStatRaw { float2 a0, a1, b0, b1; };
__device__ __forceinline__ RowStatRaw load_row_stats(const float2* __restrict__ st, int row0, int c) {
    RowStatRaw r;
    r.a0 = st[(2 * c) * S_ + row0]; r.a1 = st[(2 * c + 1) * S_ + row0];
    r.b0 = st[(2 * c) * S_ + row0 + 8]; r.b1 = st[(2 * c + 1) * S_ + row0 + 8];
    return r;
}
__device__ __forceinline__ void finish_row_stats(const RowStatRaw& r, float& mean0, float& rstd0, float& mean1, float& rstd1) {
    float sa = r.a0.x + r.a1.x, sb = r.b0.x + r.b1.x;
    sa += __shfl_xor_sync(0xffffffffu, sa, 1); sa += __shfl_xor_sync(0xffffffffu, sa, 2);
    sb += __shfl_xor_sync(0xffffffffu, sb, 1); sb += __shfl_xor_sync(0xffffffffu, sb, 2);
    mean0 = sa * 0.125f; mean1 = sb * 0.125f;
    float ma = r.a0.y + r.a1.y + 64.f * ((r.a0.x - mean0) * (r.a0.x - mean0) + (r.a1.x - mean0) * (r.a1.x - mean0));
    float mb = r.b0.y + r.b1.y + 64.f * ((r.b0.x - mean1) * (r.b0.x - mean1) + (r.b1.x - mean1) * (r.b1.x - mean1));
    ma += __shfl_xor_sync(0xffffffffu, ma, 1); ma += __shfl_xor_sync(0xffffffffu, ma, 2);
    mb += __shfl_xor_sync(0xffffffffu, mb, 1); mb += __shfl_xor_sync(0xffffffffu, mb, 2);
    rstd0 = 1.0f / sqrtf(ma * (1.f / 512.f) + 1e-5f);
    rstd1 = 1.0f / sqrtf(mb * (1.f / 512.f) + 1e-5f);
}

template <int BN, int KB, int STAGES, int EPI, int MC>
__device__ __forceinline__ void gemm_body(const CUtensorMap* mapA, const CUtensorMap* mapB, const CUtensorMap* mapB2, const CUtensorMap* mapR,
                                          const CUtensorMap* mapC, const GemmParams& prm, int tile_m, int tile_n, uint8_t* smem_raw) {
    using SM = GemmSmem<STAGES, EPI>;
    using G = typename SM::G;
    constexpr bool XKV = BN == 80;
    constexpr int TN = EPI == EPI_QKV ? 64 : BN;
    pdl_launch();
    const uint32_t sbase = smem_u32(smem_raw);
    if (sbase & 1023) __trap();
    uint8_t* sgen = smem_raw;
    const uint32_t bar_full = sbase + SM::AUX_OFF, bar_empty = bar_full + 8 * STAGES;
    float* s_cs = (float*)(sgen + SM::AUX_OFF + 128);
    float* s_red = (float*)(sgen + SM::AUX_OFF + 640);
    const int tid = threadIdx.x, lane = tid & 31;
    const int warp = __shfl_sync(0xffffffffu, tid >> 5, 0);
    const uint32_t rank = MC ? cluster_rank() : 0;
    if (tid == 0) TL(prm.tk, 0);

    constexpr bool INLINE_PROD = EPI == EPI_FFN1;
    constexpr int PWARP = INLINE_PROD ? 0 : 8;
    if (warp == PWARP && elect_one()) {
        prefetch_tmap(mapB); prefetch_tmap(mapA); prefetch_tmap(mapC);
        for (int s = 0; s < STAGES; s++) { mbar_init(bar_full + 8 * s, 1); mbar_init(bar_empty + 8 * s, MC ? 4 : 2); }
        fence_mbar_init();
    }
    __syncthreads();
    if (MC) cluster_sync();

    const int m0 = tile_m * 128, n0 = tile_n * TN;
    constexpr uint32_t STAGE_TX = G::A_BYTES + (EPI == EPI_QKV ? (XKV ? 3 : 2) * 2048 : G::B_BYTES);
    auto loadB = [&](int kb, int s) {
        const uint32_t dst = sbase + s * SM::STAGE + G::A_BYTES, bar = bar_full + 8 * s;
        if constexpr (EPI == EPI_RES) {
            tma2d(dst, mapB, n0, kb * 64, bar);
        } else if constexpr (EPI == EPI_QKV) {
            tma3d(dst, mapB, 0, kb * 32, tile_n * 2, bar);
            if constexpr (XKV) tma2d(dst + 2 * 2048, mapB2, 0, kb * 32, bar);
        } else {
            if (rank == 0) tma3d_mc(dst, mapB, 0, kb * 32, tile_n * 7, bar, 3);
            else tma3d_mc(dst + 4 * 2048, mapB2, 0, kb * 32, tile_n * 7 + 4, bar, 3);
        }
    };
    auto loadA = [&](int kb, int s) {
        const uint32_t dst = sbase + s * SM::STAGE, bar = bar_full + 8 * s;
        if constexpr (MC == 1) tma2d_mc(dst + rank * (G::A_BYTES / 2), mapA, kb * G::BK, m0 + rank * 64, bar, 3);
        else { tma2d(dst, mapA, kb * G::BK, m0, bar); tma2d(dst + G::A_BYTES / 2, mapA, kb * G::BK, m0 + 64, bar); }
    };
    constexpr int PRE = STAGES < KB ? STAGES : KB;
#define F1_LAG 2
    constexpr int LAG = F1_LAG;
    auto prologue_loads = [&]() {
        if (elect_one()) {
#pragma unroll
            for (int kb = 0; kb < PRE; kb++) { mbar_expect_tx(bar_full + 8 * kb, STAGE_TX); loadB(kb, kb); }
        }
        if (!prm.wait_in_epilogue) pdl_wait();
        if (elect_one()) {
#pragma unroll
            for (int kb = 0; kb < PRE; kb++) loadA(kb, kb);
        }
    };
    if (!INLINE_PROD && warp == 8) {
        prologue_loads();
        int s = PRE % STAGES, ph = (PRE / STAGES) & 1;
#pragma unroll 1
        for (int kb = PRE; kb < KB; kb++) {
            mbar_wait(bar_empty + 8 * s, ph ^ 1);
            if (elect_one()) {
                mbar_expect_tx(bar_full + 8 * s, STAGE_TX);
                loadB(kb, s);
                loadA(kb, s);
            }
            if (++s == STAGES) { s = 0; ph ^= 1; }
        }
        if constexpr (EPI == EPI_RES) {
            mbar_wait(bar_empty + 8 * s, ph ^ 1);
            if (elect_one()) {
                mbar_expect_tx(bar_full + 8 * s, 16384);
                tma2d(sbase + s * SM::STAGE, mapR, n0, m0, bar_full + 8 * s);
                tma2d(sbase + s * SM::STAGE + 8192, mapR, n0, m0 + 64, bar_full + 8 * s);
            }
        }
    } else {
        if (INLINE_PROD && warp == 0) prologue_loads();
        const int wg = warp >> 2, g = lane >> 2, c = lane & 3;
        const int rloc = wg * 64 + (warp & 3) * 16 + g;
        const int row0 = m0 + rloc;
        float mean0 = 0.f, rstd0 = 1.f, mean1 = 0.f, rstd1 = 1.f;
        RowStatRaw raw;
        float csv = 0.f;
        auto ln_inputs = [&]() {
            pdl_wait();
            if constexpr (EPI != EPI_RES) {
                raw = load_row_stats(prm.stats_in, row0, c);
                const float* cs = EPI == EPI_FFN1 ? g_cs_1 + n0 : g_cs_q + n0;
                if (tid < TN) csv = cs[tid];
            }
        };
        if (!prm.wait_in_epilogue) ln_inputs();
        float acc[BN / 2];
        const uint64_t dA0 = mkdesc(sbase + wg * (G::A_BYTES / 2), 16, G::A_SBO, G::A_SWZ);
        const uint64_t dB0 = mkdesc(sbase + G::A_BYTES, G::B_LBO, G::B_SBO, G::B_SWZ);
        int s = 0, ph = 0;
#pragma unroll 1
        for (int kb = 0; kb < KB; kb++) {
            mbar_wait(bar_full + 8 * s, ph);
            const uint64_t dA = dA0 + (uint64_t)(s * (SM::STAGE >> 4)), dB = dB0 + (uint64_t)(s * (SM::STAGE >> 4));
            wg_fence();
#pragma unroll
            for (int k = 0; k < G::BK / 16; k++) wgmma_ss_tb<BN>(acc, dA + (uint64_t)(k * 2), dB + (uint64_t)(k * (G::B_KSTEP >> 4)), (kb | k) != 0);
            wg_commit();
            if constexpr (EPI == EPI_RES) {
                wg_wait<0>();
                if ((warp & 3) == 0 && elect_one()) {
                    if (MC) { mbar_arrive_remote(bar_empty + 8 * s, 0); mbar_arrive_remote(bar_empty + 8 * s, 1); }
                    else mbar_arrive(bar_empty + 8 * s);
                }
            } else if (kb > 0) {
                wg_wait<1>();
                const int sp = s == 0 ? STAGES - 1 : s - 1;
                if ((warp & 3) == 0 && elect_one()) {
                    if (MC) { mbar_arrive_remote(bar_empty + 8 * sp, 0); mbar_arrive_remote(bar_empty + 8 * sp, 1); }
                    else mbar_arrive(bar_empty + 8 * sp);
                }
                if (INLINE_PROD && warp == 0 && kb >= LAG && kb - LAG + STAGES < KB) {
                    const int sq = LAG == 1 ? sp : (sp == 0 ? STAGES - 1 : sp - 1);
                    mbar_wait(bar_empty + 8 * sq, ((kb - LAG) / STAGES) & 1);
                    if (elect_one()) {
                        mbar_expect_tx(bar_full + 8 * sq, STAGE_TX);
                        loadB(kb - LAG + STAGES, sq);
                        loadA(kb - LAG + STAGES, sq);
                    }
                }
            }
            if (++s == STAGES) { s = 0; ph ^= 1; }
        }
        if (prm.wait_in_epilogue) ln_inputs();
        if constexpr (EPI != EPI_RES) {
            finish_row_stats(raw, mean0, rstd0, mean1, rstd1);
            if (tid < TN) s_cs[tid] = csv;
        }
        wg_wait<0>();
        fence_regs(acc);
        if (tid == 0) TL(prm.tk, 2);
        if constexpr (EPI != EPI_RES) named_bar(1, 256);

        if constexpr (XKV) {
            {
                const float* acx = &acc[32];
                const float rm0 = rstd0 * mean0, rm1 = rstd1 * mean1;
                float n0s = 0.f, n1s = 0.f, vmax = 0.f;
#pragma unroll
                for (int j = 0; j < 2; j++) {
                    const float2 cs2 = *(const float2*)(g_cs_kv + tile_n * 16 + 8 * j + 2 * c);
                    const uint32_t u0 = pack_bf16(acx[4 * j] * rstd0 - rm0 * cs2.x, acx[4 * j + 1] * rstd0 - rm0 * cs2.y);
                    const uint32_t u1 = pack_bf16(acx[4 * j + 2] * rstd1 - rm1 * cs2.x, acx[4 * j + 3] * rstd1 - rm1 * cs2.y);
                    n0s += bf_lo(u0) * bf_lo(u0) + bf_hi(u0) * bf_hi(u0);
                    n1s += bf_lo(u1) * bf_lo(u1) + bf_hi(u1) * bf_hi(u1);
                    vmax = fmaxf(vmax, fmaxf(fmaxf(fabsf(bf_lo(u0)), fabsf(bf_hi(u0))), fmaxf(fabsf(bf_lo(u1)), fabsf(bf_hi(u1)))));
                    if (tile_n == 0) {
                        *(uint32_t*)(g_kimg + (row0 >> 3) * 256 + j * 128 + g * 16 + c * 4) = u0;
                        *(uint32_t*)(g_kimg + ((row0 + 8) >> 3) * 256 + j * 128 + g * 16 + c * 4) = u1;
                    } else {
                        uint8_t* vb = g_vimg + (row0 >> 4) * 768 + j * 256 + g * 16 + c * 4;
                        *(uint32_t*)(vb) = u0;
                        *(uint32_t*)(vb + 128) = u1;
                    }
                }
                if (tile_n == 1) {
                    uint8_t* vb = g_vimg + (row0 >> 4) * 768 + 512 + g * 16 + c * 4;
                    const uint32_t one = c == 0 ? 0x00003F80u : 0u;
                    *(uint32_t*)(vb) = one;
                    *(uint32_t*)(vb + 128) = one;
                }
                n0s += __shfl_xor_sync(0xffffffffu, n0s, 1); n0s += __shfl_xor_sync(0xffffffffu, n0s, 2);
                n1s += __shfl_xor_sync(0xffffffffu, n1s, 1); n1s += __shfl_xor_sync(0xffffffffu, n1s, 2);
                float km = tile_n == 0 ? fmaxf(n0s, n1s) : vmax;
                if (!(n0s + n1s < INFINITY)) km = INFINITY;
#pragma unroll
                for (int o = 1; o < 32; o <<= 1) km = fmaxf(km, __shfl_xor_sync(0xffffffffu, km, o));
                if (lane == 0) s_red[warp] = km;
                named_bar(1, 256);
                if (tid == 0) {
                    float a = 0.f;
                    for (int i = 0; i < 8; i++) a = fmaxf(a, s_red[i]);
                    g_kvmax[tile_n * 16 + tile_m] = a;
                }
            }
        }
        if constexpr (EPI != EPI_FFN1) {
            const uint32_t stile = sbase + (EPI == EPI_RES ? s * SM::STAGE : 0);
            const int mrow = wg * 64 + (warp & 3) * 16 + (lane & 7) + ((lane >> 3) & 1) * 8;
            const uint32_t rbase = stile + mrow * 128;
            if constexpr (EPI == EPI_RES) {
                mbar_wait(bar_full + 8 * s, ph);
                float s0 = 0.f, s1 = 0.f;
#pragma unroll
                for (int jj = 0; jj < 4; jj++) {
                    uint32_t r0, r1, r2, r3;
                    const uint32_t addr = rbase + (((2 * jj + (lane >> 4)) ^ (mrow & 7)) << 4);
                    ldsm_x4(r0, r1, r2, r3, addr);
                    const uint32_t u0 = pack_bf16(acc[8 * jj] + bf_lo(r0), acc[8 * jj + 1] + bf_hi(r0));
                    const uint32_t u1 = pack_bf16(acc[8 * jj + 2] + bf_lo(r1), acc[8 * jj + 3] + bf_hi(r1));
                    const uint32_t u2 = pack_bf16(acc[8 * jj + 4] + bf_lo(r2), acc[8 * jj + 5] + bf_hi(r2));
                    const uint32_t u3 = pack_bf16(acc[8 * jj + 6] + bf_lo(r3), acc[8 * jj + 7] + bf_hi(r3));
                    stsm_x4(addr, u0, u1, u2, u3);
                    acc[8 * jj] = bf_lo(u0); acc[8 * jj + 1] = bf_hi(u0); acc[8 * jj + 4] = bf_lo(u2); acc[8 * jj + 5] = bf_hi(u2);
                    acc[8 * jj + 2] = bf_lo(u1); acc[8 * jj + 3] = bf_hi(u1); acc[8 * jj + 6] = bf_lo(u3); acc[8 * jj + 7] = bf_hi(u3);
                    s0 += (acc[8 * jj] + acc[8 * jj + 1]) + (acc[8 * jj + 4] + acc[8 * jj + 5]);
                    s1 += (acc[8 * jj + 2] + acc[8 * jj + 3]) + (acc[8 * jj + 6] + acc[8 * jj + 7]);
                }
                fence_async_smem();
                named_bar(2 + wg, 128);
                if ((warp & 3) == 0 && elect_one()) { tma2d_store(mapC, stile + wg * 8192, n0, m0 + wg * 64); bulk_commit(); }
                if (prm.stats_out) {
                    s0 += __shfl_xor_sync(0xffffffffu, s0, 1); s0 += __shfl_xor_sync(0xffffffffu, s0, 2);
                    s1 += __shfl_xor_sync(0xffffffffu, s1, 1); s1 += __shfl_xor_sync(0xffffffffu, s1, 2);
                    const float mu0 = s0 * (1.f / 64.f), mu1 = s1 * (1.f / 64.f);
                    float q0 = 0.f, q1 = 0.f;
#pragma unroll
                    for (int j = 0; j < 8; j++) {
                        float d;
                        d = acc[4 * j] - mu0; q0 += d * d; d = acc[4 * j + 1] - mu0; q0 += d * d;
                        d = acc[4 * j + 2] - mu1; q1 += d * d; d = acc[4 * j + 3] - mu1; q1 += d * d;
                    }
                    q0 += __shfl_xor_sync(0xffffffffu, q0, 1); q0 += __shfl_xor_sync(0xffffffffu, q0, 2);
                    q1 += __shfl_xor_sync(0xffffffffu, q1, 1); q1 += __shfl_xor_sync(0xffffffffu, q1, 2);
                    if (c == 0) {
                        prm.stats_out[tile_n * S_ + row0] = make_float2(mu0, q0);
                        prm.stats_out[tile_n * S_ + row0 + 8] = make_float2(mu1, q1);
                    }
                }
            } else {
                const float sc = 0.25f * 1.4426950408889634f;
                const float a0 = rstd0 * sc, a1 = rstd1 * sc, rm0 = a0 * mean0, rm1 = a1 * mean1;
#pragma unroll
                for (int jj = 0; jj < 4; jj++) {
                    const float2 ca = *(const float2*)(s_cs + 16 * jj + 2 * c), cb = *(const float2*)(s_cs + 16 * jj + 8 + 2 * c);
                    const uint32_t u0 = pack_bf16(acc[8 * jj] * a0 - rm0 * ca.x, acc[8 * jj + 1] * a0 - rm0 * ca.y);
                    const uint32_t u1 = pack_bf16(acc[8 * jj + 2] * a1 - rm1 * ca.x, acc[8 * jj + 3] * a1 - rm1 * ca.y);
                    const uint32_t u2 = pack_bf16(acc[8 * jj + 4] * a0 - rm0 * cb.x, acc[8 * jj + 5] * a0 - rm0 * cb.y);
                    const uint32_t u3 = pack_bf16(acc[8 * jj + 6] * a1 - rm1 * cb.x, acc[8 * jj + 7] * a1 - rm1 * cb.y);
                    stsm_x4(rbase + (((2 * jj + (lane >> 4)) ^ (mrow & 7)) << 4), u0, u1, u2, u3);
                }
                fence_async_smem();
                named_bar(2 + wg, 128);
                if ((warp & 3) == 0 && elect_one()) { tma2d_store(mapC, stile + wg * 8192, n0, m0 + wg * 64); bulk_commit(); }
            }
            if ((warp & 3) == 0) bulk_wait_read();
        } else {
            const uint32_t stile = sbase + wg * (7 * 4096);
            const int mrow = (warp & 3) * 16 + (lane & 7) + ((lane >> 3) & 1) * 8;
            const float a0 = 0.5f * rstd0, a1 = 0.5f * rstd1, rm0 = a0 * mean0, rm1 = a1 * mean1;
#pragma unroll
            for (int jj = 0; jj < 14; jj++) {
                const float2 ca = *(const float2*)(s_cs + 16 * jj + 2 * c), cb = *(const float2*)(s_cs + 16 * jj + 8 + 2 * c);
                float y[8] = {acc[8 * jj] * a0 - rm0 * ca.x,     acc[8 * jj + 1] * a0 - rm0 * ca.y,
                              acc[8 * jj + 2] * a1 - rm1 * ca.x, acc[8 * jj + 3] * a1 - rm1 * ca.y,
                              acc[8 * jj + 4] * a0 - rm0 * cb.x, acc[8 * jj + 5] * a0 - rm0 * cb.y,
                              acc[8 * jj + 6] * a1 - rm1 * cb.x, acc[8 * jj + 7] * a1 - rm1 * cb.y};
#pragma unroll
                for (int i = 0; i < 8; i++) {
                    float t;
                    asm("tanh.approx.f32 %0, %1;" : "=f"(t) : "f"(y[i]));
                    y[i] = fmaf(y[i], t, y[i]);
                }
                const int chunk = (2 * jj + (lane >> 4)) & 3, blk = jj >> 1;
                stsm_x4(stile + blk * 4096 + mrow * 64 + ((chunk ^ ((mrow >> 1) & 3)) << 4),
                        pack_bf16(y[0], y[1]), pack_bf16(y[2], y[3]), pack_bf16(y[4], y[5]), pack_bf16(y[6], y[7]));
                if (jj & 1) {
                    fence_async_smem();
                    __syncwarp();
                    if (elect_one()) {
                        tma2d_store(mapC, stile + blk * 4096 + (warp & 3) * 1024, n0 + blk * 32, m0 + wg * 64 + (warp & 3) * 16);
                        bulk_commit();
                    }
                }
            }
            bulk_wait_read();
        }
    }
    if (tid == 0) TL(prm.tk, 3);
    if (MC) cluster_sync();
}

#define WO_ST 5
#define F2_ST 5
#define F1_ST 4
constexpr int QKV_STAGES = 7, WO_STAGES = WO_ST, FFN2_STAGES = F2_ST, FFN1_STAGES = F1_ST;
__global__ void __launch_bounds__(288) qkv_kernel(const __grid_constant__ CUtensorMap mapA, const __grid_constant__ CUtensorMap mapWq,
                                                  const __grid_constant__ CUtensorMap mapWk, const __grid_constant__ CUtensorMap mapWv,
                                                  const __grid_constant__ CUtensorMap mapQ, const GemmParams prm) {
    extern __shared__ __align__(1024) uint8_t smem_raw[];
    uint32_t pad[64];
#pragma unroll
    for (int i = 0; i < 64; i++) asm volatile("mov.u32 %0, %%clock;" : "=r"(pad[i]));
    const int tn = blockIdx.x & 7;
    if (tn < 2) gemm_body<80, 16, QKV_STAGES, EPI_QKV, 1>(&mapA, &mapWq, tn == 0 ? &mapWk : &mapWv, &mapA, &mapQ, prm, blockIdx.x >> 3, tn, smem_raw);
    else gemm_body<64, 16, QKV_STAGES, EPI_QKV, 1>(&mapA, &mapWq, &mapWq, &mapA, &mapQ, prm, blockIdx.x >> 3, tn, smem_raw);
    if (prm.stats_in == nullptr) {
#pragma unroll
        for (int i = 0; i < 64; i++) asm volatile("st.volatile.global.u32 [%0], %1;" ::"l"(g_kimg + 4 * i), "r"(pad[i]) : "memory");
    }
}
template <int KB, int STAGES>
__global__ void __launch_bounds__(288) res_gemm_kernel(const __grid_constant__ CUtensorMap mapA, const __grid_constant__ CUtensorMap mapW,
                                                       const __grid_constant__ CUtensorMap mapR, const __grid_constant__ CUtensorMap mapC, const GemmParams prm) {
    extern __shared__ __align__(1024) uint8_t smem_raw[];
    gemm_body<64, KB, STAGES, EPI_RES, 1>(&mapA, &mapW, &mapW, &mapR, &mapC, prm, blockIdx.x >> 3, blockIdx.x & 7, smem_raw);
}
__global__ void __launch_bounds__(256) ffn1_kernel(const __grid_constant__ CUtensorMap mapA, const __grid_constant__ CUtensorMap mapW4,
                                                   const __grid_constant__ CUtensorMap mapW3, const __grid_constant__ CUtensorMap mapH, const GemmParams prm) {
    extern __shared__ __align__(1024) uint8_t smem_raw[];
    const int pair = blockIdx.x >> 1, tile_n = pair & 7, tile_m = (pair >> 3) * 2 + (blockIdx.x & 1);
    gemm_body<224, 16, FFN1_STAGES, EPI_FFN1, 2>(&mapA, &mapW4, &mapW3, &mapA, &mapH, prm, tile_m, tile_n, smem_raw);
}

constexpr int NPOLY = 10;
__host__ __device__ constexpr bool is_mufu(int i) { return ((i + 1) * (16 - NPOLY)) / 16 != (i * (16 - NPOLY)) / 16; }

__device__ __forceinline__ float ex2(float x) { float r; asm("ex2.approx.ftz.f32 %0, %1;" : "=f"(r) : "f"(x)); return r; }
__device__ __forceinline__ uint32_t exp_pair_mufu(float a, float b) { return pack_bf16(ex2(a), ex2(b)); }
__device__ __forceinline__ uint32_t exp_pair_fma(float a, float b, uint32_t c3f) {
    constexpr float MAGIC = 98430.4140625f;
    const float ta = a + MAGIC, tb = b + (MAGIC - 143.5f);
    uint32_t y, m, r;
    asm("mad.lo.u32 %0, %1, 65536, %2;" : "=r"(y) : "r"(__float_as_uint(tb)), "r"(__float_as_uint(ta)));
    asm("lop3.b32 %0, %1, 0x007F007F, %2, 0xEA;" : "=r"(m) : "r"(y), "r"(c3f));
    const uint32_t e = y & 0xFF80FF80u;
    asm("fma.rn.bf16x2 %0, %1, %2, %3;" : "=r"(r) : "r"(y), "r"(m), "r"(e));
    return r;
}

constexpr int KCH = 256, NCH = S_ / KCH;
constexpr int K_BYTES = S_ * 32, V_BYTES = (S_ / 16) * 768;
constexpr int ATT_SMEM = K_BYTES + V_BYTES;

__global__ void __launch_bounds__(512, 1) attn_kernel(int tk) {
    extern __shared__ __align__(1024) uint8_t smem[];
    __shared__ uint64_t bars[NCH];
    __shared__ int s_slow;
    const int tid = threadIdx.x, wg = tid >> 7, warp = (tid >> 5) & 3, lane = tid & 31;
    const uint32_t sK = smem_u32(smem), sV = sK + K_BYTES;
    if (tid == 0) TL(tk, 0);
    if (tid == 0) {
        for (int i = 0; i < NCH; i++) mbar_init(smem_u32(&bars[i]), 1);
        s_slow = 0;
        fence_mbar_init();
    }
    __syncthreads();
    pdl_launch();
    pdl_wait();
    if (tid == 0) TL(tk, 1);
    if (__shfl_sync(0xffffffffu, tid >> 5, 0) == 0 && elect_one()) {
#pragma unroll
        for (int i = 0; i < NCH; i++) {
            mbar_expect_tx(smem_u32(&bars[i]), KCH * 32 + (KCH / 16) * 768);
            bulk_load(sK + i * KCH * 32, g_kimg + i * KCH * 32, KCH * 32, smem_u32(&bars[i]));
            bulk_load(sV + i * (KCH / 16) * 768, g_vimg + i * (KCH / 16) * 768, (KCH / 16) * 768, smem_u32(&bars[i]));
        }
    }
    const int tb = blockIdx.x >> 3, hg = blockIdx.x & 7;
    const int head = hg * 4 + wg;
    const int g = lane >> 2, c = lane & 3;
    uint32_t qa[2][4];
    float qn = 0.f;
#pragma unroll
    for (int m = 0; m < 2; m++) {
        const int row = tb * 128 + m * 64 + warp * 16 + g;
        const uint32_t* p0 = (const uint32_t*)(g_q + (size_t)row * D_ + head * 16);
        const uint32_t* p1 = (const uint32_t*)(g_q + (size_t)(row + 8) * D_ + head * 16);
        qa[m][0] = p0[c]; qa[m][1] = p1[c]; qa[m][2] = p0[c + 4]; qa[m][3] = p1[c + 4];
        float n0 = bf_lo(qa[m][0]) * bf_lo(qa[m][0]) + bf_hi(qa[m][0]) * bf_hi(qa[m][0]) + bf_lo(qa[m][2]) * bf_lo(qa[m][2]) + bf_hi(qa[m][2]) * bf_hi(qa[m][2]);
        float n1 = bf_lo(qa[m][1]) * bf_lo(qa[m][1]) + bf_hi(qa[m][1]) * bf_hi(qa[m][1]) + bf_lo(qa[m][3]) * bf_lo(qa[m][3]) + bf_hi(qa[m][3]) * bf_hi(qa[m][3]);
        n0 += __shfl_xor_sync(0xffffffffu, n0, 1); n0 += __shfl_xor_sync(0xffffffffu, n0, 2);
        n1 += __shfl_xor_sync(0xffffffffu, n1, 1); n1 += __shfl_xor_sync(0xffffffffu, n1, 2);
        if (!(n0 == n0) || !(n1 == n1)) n0 = __int_as_float(0x7f800000);
        qn = fmaxf(qn, fmaxf(n0, n1));
    }
    {
        float km = 0.f, vm = 0.f;
#pragma unroll
        for (int i = 0; i < 16; i++) { km = fmaxf(km, g_kvmax[i]); vm = fmaxf(vm, g_kvmax[16 + i]); }
        const bool ok = (qn * km <= 10000.f) && (vm <= 16384.f);
        if (!ok) s_slow = 1;
    }
    float oacc[2][12];
#pragma unroll
    for (int m = 0; m < 2; m++)
#pragma unroll
        for (int i = 0; i < 12; i++) oacc[m][i] = 0.f;
    __syncthreads();
    const bool slow = s_slow != 0;

    const uint64_t dK0 = mkdesc(sK, 128, 256, 0);
    const uint64_t dV0 = mkdesc(sV, 128, 256, 0);
    uint32_t c3f;
    asm volatile("mov.b32 %0, 0x3F003F00;" : "=r"(c3f));
    if (!slow) {
#pragma unroll 1
        for (int t = 0; t < S_ / 64; t++) {
            if ((t & 3) == 0) mbar_wait(smem_u32(&bars[t >> 2]), 0);
            const uint64_t dK = dK0 + (uint64_t)(t * 64 * 32 / 16);
            const uint64_t dV = dV0 + (uint64_t)(t * 4 * 768 / 16);
#pragma unroll
            for (int m = 0; m < 2; m++) {
                float s[32];
                wg_fence();
                wgmma_rs_n64_z(s, qa[m][0], qa[m][1], qa[m][2], qa[m][3], dK);
                wg_commit();
                wg_wait<0>();
                fence_regs(s);
                uint32_t p[16];
#pragma unroll
                for (int i = 0; i < 16; i++) p[i] = is_mufu(i) ? exp_pair_mufu(s[2 * i], s[2 * i + 1]) : exp_pair_fma(s[2 * i], s[2 * i + 1], c3f);
                wg_fence();
#pragma unroll
                for (int kk = 0; kk < 4; kk++)
                    wgmma_rs_n24_tb(oacc[m], p[4 * kk], p[4 * kk + 1], p[4 * kk + 2], p[4 * kk + 3], dV + (uint64_t)(kk * 768 / 16));
                wg_commit();
            }
        }
        wg_wait<0>();
    } else {
        float mx[2][2] = {{-INFINITY, -INFINITY}, {-INFINITY, -INFINITY}};
#pragma unroll 1
        for (int t = 0; t < S_ / 64; t++) {
            if ((t & 3) == 0) mbar_wait(smem_u32(&bars[t >> 2]), 0);
            const uint64_t dK = dK0 + (uint64_t)(t * 64 * 32 / 16);
            const uint64_t dV = dV0 + (uint64_t)(t * 4 * 768 / 16);
#pragma unroll
            for (int m = 0; m < 2; m++) {
                float s[32];
                wg_fence();
                wgmma_rs_n64_z(s, qa[m][0], qa[m][1], qa[m][2], qa[m][3], dK);
                wg_commit();
                wg_wait<0>();
                fence_regs(s);
                fence_regs(oacc[m]);
                float r0 = mx[m][0], r1 = mx[m][1];
#pragma unroll
                for (int j = 0; j < 8; j++) {
                    r0 = fmaxf(r0, fmaxf(s[4 * j], s[4 * j + 1]));
                    r1 = fmaxf(r1, fmaxf(s[4 * j + 2], s[4 * j + 3]));
                }
                r0 = fmaxf(r0, __shfl_xor_sync(0xffffffffu, r0, 1)); r0 = fmaxf(r0, __shfl_xor_sync(0xffffffffu, r0, 2));
                r1 = fmaxf(r1, __shfl_xor_sync(0xffffffffu, r1, 1)); r1 = fmaxf(r1, __shfl_xor_sync(0xffffffffu, r1, 2));
                const float al0 = ex2(mx[m][0] - r0), al1 = ex2(mx[m][1] - r1);
                mx[m][0] = r0; mx[m][1] = r1;
#pragma unroll
                for (int j = 0; j < 3; j++) {
                    oacc[m][4 * j] *= al0; oacc[m][4 * j + 1] *= al0;
                    oacc[m][4 * j + 2] *= al1; oacc[m][4 * j + 3] *= al1;
                }
                uint32_t p[16];
#pragma unroll
                for (int j = 0; j < 8; j++) {
                    p[2 * j] = pack_bf16(ex2(s[4 * j] - r0), ex2(s[4 * j + 1] - r0));
                    p[2 * j + 1] = pack_bf16(ex2(s[4 * j + 2] - r1), ex2(s[4 * j + 3] - r1));
                }
                fence_regs(oacc[m]);
                wg_fence();
#pragma unroll
                for (int kk = 0; kk < 4; kk++)
                    wgmma_rs_n24_tb(oacc[m], p[4 * kk], p[4 * kk + 1], p[4 * kk + 2], p[4 * kk + 3], dV + (uint64_t)(kk * 768 / 16));
                wg_commit();
                wg_wait<0>();
            }
        }
    }
    fence_regs(oacc[0]); fence_regs(oacc[1]);
    if (tid == 0) TL(tk, 2);
#pragma unroll
    for (int m = 0; m < 2; m++) {
        const float l0 = __shfl_sync(0xffffffffu, oacc[m][8], lane & ~3);
        const float l1 = __shfl_sync(0xffffffffu, oacc[m][10], lane & ~3);
        const float r0 = 1.0f / l0, r1 = 1.0f / l1;
        const int row = tb * 128 + m * 64 + warp * 16 + g;
        uint32_t* p0 = (uint32_t*)(g_o + (size_t)row * D_ + head * 16);
        uint32_t* p1 = (uint32_t*)(g_o + (size_t)(row + 8) * D_ + head * 16);
        p0[c] = pack_bf16(oacc[m][0] * r0, oacc[m][1] * r0);
        p1[c] = pack_bf16(oacc[m][2] * r1, oacc[m][3] * r1);
        p0[c + 4] = pack_bf16(oacc[m][4] * r0, oacc[m][5] * r0);
        p1[c + 4] = pack_bf16(oacc[m][6] * r1, oacc[m][7] * r1);
    }
    if (tid == 0) TL(tk, 3);
}

typedef CUresult (*EncodeFn)(CUtensorMap*, CUtensorMapDataType, cuuint32_t, void*, const cuuint64_t*, const cuuint64_t*, const cuuint32_t*,
                             const cuuint32_t*, CUtensorMapInterleave, CUtensorMapSwizzle, CUtensorMapL2promotion, CUtensorMapFloatOOBfill);

EncodeFn get_encode() {
    static EncodeFn fn = nullptr;
    if (!fn) {
        void* p = nullptr;
        cudaDriverEntryPointQueryResult qr;
        cudaGetDriverEntryPoint("cuTensorMapEncodeTiled", &p, cudaEnableDefault, &qr);
        fn = (EncodeFn)p;
    }
    return fn;
}
CUtensorMap map2d(const void* ptr, uint64_t cols, uint64_t rows, uint32_t bc, uint32_t br, CUtensorMapSwizzle sw) {
    CUtensorMap m;
    cuuint64_t gd[2] = {cols, rows}, gs[1] = {cols * 2};
    cuuint32_t bx[2] = {bc, br}, es[2] = {1, 1};
    get_encode()(&m, CU_TENSOR_MAP_DATA_TYPE_BFLOAT16, 2, (void*)ptr, gd, gs, bx, es, CU_TENSOR_MAP_INTERLEAVE_NONE, sw,
                 CU_TENSOR_MAP_L2_PROMOTION_L2_128B, CU_TENSOR_MAP_FLOAT_OOB_FILL_NONE);
    return m;
}
CUtensorMap map3d32(const void* ptr, uint64_t cols, uint64_t rows, uint32_t br, uint32_t nb) {
    CUtensorMap m;
    cuuint64_t gd[3] = {32, rows, cols / 32}, gs[2] = {cols * 2, 64};
    cuuint32_t bx[3] = {32, br, nb}, es[3] = {1, 1, 1};
    get_encode()(&m, CU_TENSOR_MAP_DATA_TYPE_BFLOAT16, 3, (void*)ptr, gd, gs, bx, es, CU_TENSOR_MAP_INTERLEAVE_NONE, CU_TENSOR_MAP_SWIZZLE_64B,
                 CU_TENSOR_MAP_L2_PROMOTION_L2_128B, CU_TENSOR_MAP_FLOAT_OOB_FILL_NONE);
    return m;
}

template <typename... KArgs, typename... Args>
void launch(void (*kern)(KArgs...), int grid, int block, int smem, int cluster, bool pdl, Args... args) {
    cudaLaunchConfig_t cfg = {};
    cfg.gridDim = dim3(grid);
    cfg.blockDim = dim3(block);
    cfg.dynamicSmemBytes = smem;
    cfg.stream = cudaStreamPerThread;
    cudaLaunchAttribute at[2];
    int n = 0;
    if (cluster > 1) { at[n].id = cudaLaunchAttributeClusterDimension; at[n].val.clusterDim.x = cluster; at[n].val.clusterDim.y = 1; at[n].val.clusterDim.z = 1; n++; }
    if (pdl) { at[n].id = cudaLaunchAttributeProgrammaticStreamSerialization; at[n].val.programmaticStreamSerializationAllowed = 1; n++; }
    cfg.attrs = at;
    cfg.numAttrs = n;
    cudaLaunchKernelEx(&cfg, kern, KArgs(args)...);
}

template <typename T> void* sym(const T& s) { void* p = nullptr; cudaGetSymbolAddress(&p, s); return p; }

}

extern "C" void kernel_launch(void* const* d_in, const int* in_sizes, int n_in, void* d_out, int out_size) {
    const __nv_bfloat16* x = (const __nv_bfloat16*)d_in[0];
    const __nv_bfloat16* wq = (const __nv_bfloat16*)d_in[1];
    const __nv_bfloat16* wk = (const __nv_bfloat16*)d_in[2];
    const __nv_bfloat16* wv = (const __nv_bfloat16*)d_in[3];
    const __nv_bfloat16* wo = (const __nv_bfloat16*)d_in[4];
    const __nv_bfloat16* w1 = (const __nv_bfloat16*)d_in[6];
    const __nv_bfloat16* w2 = (const __nv_bfloat16*)d_in[7];

    constexpr int SM_QKV = GemmSmem<QKV_STAGES, EPI_QKV>::TOTAL;
    constexpr int HALF_PLUS = 116736;
    constexpr int SM_WO = GemmSmem<WO_STAGES, EPI_RES>::TOTAL > HALF_PLUS ? GemmSmem<WO_STAGES, EPI_RES>::TOTAL : HALF_PLUS;
    constexpr int SM_FFN2 = GemmSmem<FFN2_STAGES, EPI_RES>::TOTAL > HALF_PLUS ? GemmSmem<FFN2_STAGES, EPI_RES>::TOTAL : HALF_PLUS;
    constexpr int SM_FFN1 = GemmSmem<FFN1_STAGES, EPI_FFN1>::TOTAL;
    cudaFuncSetAttribute(qkv_kernel, cudaFuncAttributeMaxDynamicSharedMemorySize, SM_QKV);
    cudaFuncSetAttribute(res_gemm_kernel<8, WO_STAGES>, cudaFuncAttributeMaxDynamicSharedMemorySize, SM_WO);
    cudaFuncSetAttribute(ffn1_kernel, cudaFuncAttributeMaxDynamicSharedMemorySize, SM_FFN1);
    cudaFuncSetAttribute(res_gemm_kernel<28, FFN2_STAGES>, cudaFuncAttributeMaxDynamicSharedMemorySize, SM_FFN2);
    cudaFuncSetAttribute(attn_kernel, cudaFuncAttributeMaxDynamicSharedMemorySize, ATT_SMEM);
    cudaFuncSetAttribute(prep_kernel, cudaFuncAttributePreferredSharedMemoryCarveout, 100);
    cudaFuncSetAttribute(qkv_kernel, cudaFuncAttributePreferredSharedMemoryCarveout, 100);
    cudaFuncSetAttribute(res_gemm_kernel<8, WO_STAGES>, cudaFuncAttributePreferredSharedMemoryCarveout, 100);
    cudaFuncSetAttribute(ffn1_kernel, cudaFuncAttributePreferredSharedMemoryCarveout, 100);
    cudaFuncSetAttribute(res_gemm_kernel<28, FFN2_STAGES>, cudaFuncAttributePreferredSharedMemoryCarveout, 100);
    cudaFuncSetAttribute(attn_kernel, cudaFuncAttributePreferredSharedMemoryCarveout, 100);

    void *q = sym(g_q), *o = sym(g_o), *x1 = sym(g_x1), *x2 = sym(g_x2), *x3 = sym(g_x3), *h = sym(g_h);
    float2* stats = (float2*)sym(g_stats);
    const void* xs[5] = {x, x1, x2, x3, d_out};

    const CUtensorMapSwizzle SW128 = CU_TENSOR_MAP_SWIZZLE_128B, SW64 = CU_TENSOR_MAP_SWIZZLE_64B;
    const CUtensorMap mWq = map3d32(wq, D_, D_, 32, 2);
    const CUtensorMap mWk = map2d(wk, 16, D_, 32, 32, SW64);
    const CUtensorMap mWv = map2d(wv, 16, D_, 32, 32, SW64);
    const CUtensorMap mWo = map2d(wo, D_, D_, 64, 64, SW128);
    const CUtensorMap mW1a = map3d32(w1, F_, D_, 32, 4), mW1b = map3d32(w1, F_, D_, 32, 3);
    const CUtensorMap mW2 = map2d(w2, D_, F_, 64, 64, SW128);
    const CUtensorMap mQ = map2d(q, D_, S_, 64, 64, SW128);
    const CUtensorMap mO = map2d(o, D_, S_, 64, 64, SW128);
    const CUtensorMap mHst = map2d(h, F_, S_, 32, 16, SW64);
    const CUtensorMap mHld = map2d(h, F_, S_, 64, 64, SW128);
    CUtensorMap mX[5], mX32[4];
    for (int i = 0; i < 5; i++) mX[i] = map2d(xs[i], D_, S_, 64, 64, SW128);
    for (int i = 0; i < 4; i++) mX32[i] = map2d(xs[i], D_, S_, 32, 64, SW64);

    launch(prep_kernel, PREP_CS_CTAS + PREP_STAT_CTAS, 256, 0, 1, false, x, wq, wk, wv, wo, w1, w2);
    for (int layer = 0; layer < 2; layer++) {
        const int xi = layer * 2;
        GemmParams p;
        p.stats_in = stats + (size_t)xi * 8 * S_; p.stats_out = nullptr; p.wait_in_epilogue = layer == 0; p.tk = 1 + 5 * layer;
        launch(qkv_kernel, 128, 288, SM_QKV, 2, true, mX32[xi], mWq, mWk, mWv, mQ, p);
        launch(attn_kernel, 128, 512, ATT_SMEM, 1, true, 2 + 5 * layer);
        p.stats_in = nullptr; p.stats_out = stats + (size_t)(xi + 1) * 8 * S_; p.wait_in_epilogue = 0; p.tk = 3 + 5 * layer;
        launch(res_gemm_kernel<8, WO_STAGES>, 128, 288, SM_WO, 2, true, mO, mWo, mX[xi], mX[xi + 1], p);
        p.stats_in = stats + (size_t)(xi + 1) * 8 * S_; p.stats_out = nullptr; p.tk = 4 + 5 * layer;
        launch(ffn1_kernel, 128, 256, SM_FFN1, 2, true, mX32[xi + 1], mW1a, mW1b, mHst, p);
        p.stats_in = nullptr; p.stats_out = layer == 0 ? stats + (size_t)2 * 8 * S_ : nullptr; p.tk = 5 + 5 * layer;
        launch(res_gemm_kernel<28, FFN2_STAGES>, 128, 288, SM_FFN2, 2, true, mHld, mW2, mX[xi + 1], mX[xi + 2], p);
    }
}
```

```cpp
#include <cuda_runtime.h>
#include <cuda_bf16.h>
#include <cuda.h>
#include <stdint.h>

#define F1_INLINE 0
#define QKV_MC 0
#define WO_MC 0
#define F2_MC 0
#define F1_MC 0
#define PREB 2
#define RES_WAIT0 0

namespace {

constexpr int S_ = 2048, D_ = 512, H_ = 32, F_ = 1792;

__device__ __align__(1024) __nv_bfloat16 g_q[S_ * D_];
__device__ __align__(1024) __nv_bfloat16 g_o[S_ * D_];
__device__ __align__(1024) __nv_bfloat16 g_x1[S_ * D_];
__device__ __align__(1024) __nv_bfloat16 g_x2[S_ * D_];
__device__ __align__(1024) __nv_bfloat16 g_x3[S_ * D_];
__device__ __align__(1024) __nv_bfloat16 g_h[S_ * F_];
__device__ __align__(1024) uint8_t g_kimg[S_ * 32];
__device__ __align__(1024) uint8_t g_vimg[(S_ / 16) * 768];
__device__ __align__(1024) float2 g_stats[4][8 * S_];
__device__ __align__(16) float g_cs_q[D_];
__device__ __align__(16) float g_cs_kv[32];
__device__ __align__(16) float g_cs_1[F_];
__device__ __align__(16) float g_kvmax[32];

#define TL(k, slot)

__device__ __forceinline__ uint32_t smem_u32(const void* p) { return (uint32_t)__cvta_generic_to_shared(p); }
__device__ __forceinline__ void mbar_init(uint32_t bar, uint32_t cnt) {
    asm volatile("mbarrier.init.shared::cta.b64 [%0], %1;" ::"r"(bar), "r"(cnt));
}
__device__ __forceinline__ void mbar_expect_tx(uint32_t bar, uint32_t bytes) {
    asm volatile("mbarrier.arrive.expect_tx.shared::cta.b64 _, [%0], %1;" ::"r"(bar), "r"(bytes) : "memory");
}
__device__ __forceinline__ void mbar_arrive(uint32_t bar) {
    asm volatile("mbarrier.arrive.shared::cta.b64 _, [%0];" ::"r"(bar) : "memory");
}
__device__ __forceinline__ void mbar_arrive_remote(uint32_t bar, uint32_t cta) {
    asm volatile("{\n.reg .b32 ra;\nmapa.shared::cluster.u32 ra, %0, %1;\nmbarrier.arrive.shared::cluster.b64 _, [ra];\n}" ::"r"(bar), "r"(cta) : "memory");
}
__device__ __forceinline__ void mbar_wait(uint32_t bar, uint32_t parity) {
    asm volatile("{\n.reg .pred p;\nWAIT_%=:\nmbarrier.try_wait.parity.shared::cta.b64 p, [%0], %1;\n@p bra DONE_%=;\nbra WAIT_%=;\nDONE_%=:\n}" ::"r"(bar), "r"(parity) : "memory");
}
__device__ __forceinline__ void bulk_load(uint32_t dst, const void* src, uint32_t bytes, uint32_t bar) {
    asm volatile("cp.async.bulk.shared::cluster.global.mbarrier::complete_tx::bytes [%0], [%1], %2, [%3];" ::"r"(dst), "l"(src), "r"(bytes), "r"(bar) : "memory");
}
__device__ __forceinline__ void tma2d(uint32_t dst, const CUtensorMap* m, int c0, int c1, uint32_t bar) {
    asm volatile("cp.async.bulk.tensor.2d.shared::cluster.global.mbarrier::complete_tx::bytes [%0], [%1, {%3, %4}], [%2];" ::"r"(dst), "l"(m), "r"(bar), "r"(c0), "r"(c1) : "memory");
}
__device__ __forceinline__ void tma2d_mc(uint32_t dst, const CUtensorMap* m, int c0, int c1, uint32_t bar, uint16_t mask) {
    asm volatile("cp.async.bulk.tensor.2d.shared::cluster.global.mbarrier::complete_tx::bytes.multicast::cluster [%0], [%1, {%3, %4}], [%2], %5;" ::"r"(dst), "l"(m), "r"(bar), "r"(c0), "r"(c1), "h"(mask) : "memory");
}
__device__ __forceinline__ void tma3d(uint32_t dst, const CUtensorMap* m, int c0, int c1, int c2, uint32_t bar) {
    asm volatile("cp.async.bulk.tensor.3d.shared::cluster.global.mbarrier::complete_tx::bytes [%0], [%1, {%3, %4, %5}], [%2];" ::"r"(dst), "l"(m), "r"(bar), "r"(c0), "r"(c1), "r"(c2) : "memory");
}
__device__ __forceinline__ void tma3d_mc(uint32_t dst, const CUtensorMap* m, int c0, int c1, int c2, uint32_t bar, uint16_t mask) {
    asm volatile("cp.async.bulk.tensor.3d.shared::cluster.global.mbarrier::complete_tx::bytes.multicast::cluster [%0], [%1, {%3, %4, %5}], [%2], %6;" ::"r"(dst), "l"(m), "r"(bar), "r"(c0), "r"(c1), "r"(c2), "h"(mask) : "memory");
}
__device__ __forceinline__ void tma2d_store(const CUtensorMap* m, uint32_t src, int c0, int c1) {
    asm volatile("cp.async.bulk.tensor.2d.global.shared::cta.bulk_group [%0, {%2, %3}], [%1];" ::"l"(m), "r"(src), "r"(c0), "r"(c1) : "memory");
}
__device__ __forceinline__ void tma3d_store(const CUtensorMap* m, uint32_t src, int c0, int c1, int c2) {
    asm volatile("cp.async.bulk.tensor.3d.global.shared::cta.bulk_group [%0, {%2, %3, %4}], [%1];" ::"l"(m), "r"(src), "r"(c0), "r"(c1), "r"(c2) : "memory");
}
__device__ __forceinline__ void bulk_commit() { asm volatile("cp.async.bulk.commit_group;" ::: "memory"); }
__device__ __forceinline__ void bulk_wait_read() { asm volatile("cp.async.bulk.wait_group.read 0;" ::: "memory"); }
__device__ __forceinline__ void prefetch_tmap(const CUtensorMap* m) { asm volatile("prefetch.tensormap [%0];" ::"l"(m) : "memory"); }
__device__ __forceinline__ void fence_async_smem() { asm volatile("fence.proxy.async.shared::cta;" ::: "memory"); }
__device__ __forceinline__ void fence_mbar_init() { asm volatile("fence.mbarrier_init.release.cluster;" ::: "memory"); }
__device__ __forceinline__ void cluster_sync() { asm volatile("barrier.cluster.arrive.release.aligned;\nbarrier.cluster.wait.acquire.aligned;" ::: "memory"); }
__device__ __forceinline__ uint32_t cluster_rank() { uint32_t r; asm volatile("mov.u32 %0, %%cluster_ctarank;" : "=r"(r)); return r; }
__device__ __forceinline__ void pdl_wait() { asm volatile("griddepcontrol.wait;" ::: "memory"); }
__device__ __forceinline__ void pdl_launch() { asm volatile("griddepcontrol.launch_dependents;" ::: "memory"); }
__device__ __forceinline__ bool elect_one() {
    uint32_t p;
    asm volatile("{\n.reg .pred p;\nelect.sync _|p, 0xffffffff;\nselp.b32 %0, 1, 0, p;\n}" : "=r"(p));
    return p != 0;
}
__device__ __forceinline__ void named_bar(int id, int n) { asm volatile("bar.sync %0, %1;" ::"r"(id), "r"(n) : "memory"); }

__device__ __forceinline__ void wg_fence() { asm volatile("wgmma.fence.sync.aligned;" ::: "memory"); }
__device__ __forceinline__ void wg_commit() { asm volatile("wgmma.commit_group.sync.aligned;" ::: "memory"); }
template <int N> __device__ __forceinline__ void wg_wait() { asm volatile("wgmma.wait_group.sync.aligned %0;" ::"n"(N) : "memory"); }
template <int N> __device__ __forceinline__ void fence_regs(float (&d)[N]) {
#pragma unroll
    for (int i = 0; i < N; i++) asm volatile("" : "+f"(d[i])::"memory");
}
__device__ __forceinline__ uint64_t mkdesc(uint32_t addr, uint32_t lbo, uint32_t sbo, uint32_t swz) {
    uint64_t d = 0;
    d |= (uint64_t)((addr & 0x3FFFF) >> 4);
    d |= (uint64_t)((lbo & 0x3FFFF) >> 4) << 16;
    d |= (uint64_t)((sbo & 0x3FFFF) >> 4) << 32;
    d |= (uint64_t)swz << 62;
    return d;
}
__device__ __forceinline__ void ldsm_x4(uint32_t& r0, uint32_t& r1, uint32_t& r2, uint32_t& r3, uint32_t addr) {
    asm volatile("ldmatrix.sync.aligned.m8n8.x4.shared.b16 {%0,%1,%2,%3}, [%4];" : "=r"(r0), "=r"(r1), "=r"(r2), "=r"(r3) : "r"(addr) : "memory");
}
__device__ __forceinline__ void stsm_x4(uint32_t addr, uint32_t r0, uint32_t r1, uint32_t r2, uint32_t r3) {
    asm volatile("stmatrix.sync.aligned.m8n8.x4.shared.b16 [%0], {%1,%2,%3,%4};" ::"r"(addr), "r"(r0), "r"(r1), "r"(r2), "r"(r3) : "memory");
}
__device__ __forceinline__ uint32_t pack_bf16(float lo, float hi) {
    uint32_t r;
    asm("cvt.rn.bf16x2.f32 %0, %1, %2;" : "=r"(r) : "f"(hi), "f"(lo));
    return r;
}
__device__ __forceinline__ float bf_lo(uint32_t v) { return __uint_as_float(v << 16); }
__device__ __forceinline__ float bf_hi(uint32_t v) { return __uint_as_float(v & 0xFFFF0000u); }

#define WG_REGS_4(o) "+f"(d[o]), "+f"(d[o + 1]), "+f"(d[o + 2]), "+f"(d[o + 3])
#define WG_REGS_8(o) WG_REGS_4(o), WG_REGS_4(o + 4)
#define WG_REGS_16(o) WG_REGS_8(o), WG_REGS_8(o + 8)
#define WG_REGS_32(o) WG_REGS_16(o), WG_REGS_16(o + 16)

__device__ __forceinline__ void wgmma_ss_n80_tb(float (&d)[40], uint64_t dA, uint64_t dB, int sc) {
    asm volatile("{\n.reg .pred p;\nsetp.ne.b32 p, %42, 0;\n"
                 "wgmma.mma_async.sync.aligned.m64n80k16.f32.bf16.bf16 "
                 "{%0,%1,%2,%3,%4,%5,%6,%7,%8,%9,%10,%11,%12,%13,%14,%15,%16,%17,%18,%19,%20,%21,%22,%23,%24,%25,%26,%27,%28,%29,%30,%31,"
                 "%32,%33,%34,%35,%36,%37,%38,%39}, %40, %41, p, 1, 1, 0, 1;\n}\n"
                 : WG_REGS_32(0), WG_REGS_8(32) : "l"(dA), "l"(dB), "r"(sc));
}
__device__ __forceinline__ void wgmma_ss_n64_tb(float (&d)[32], uint64_t dA, uint64_t dB, int sc) {
    asm volatile("{\n.reg .pred p;\nsetp.ne.b32 p, %34, 0;\n"
                 "wgmma.mma_async.sync.aligned.m64n64k16.f32.bf16.bf16 "
                 "{%0,%1,%2,%3,%4,%5,%6,%7,%8,%9,%10,%11,%12,%13,%14,%15,%16,%17,%18,%19,%20,%21,%22,%23,%24,%25,%26,%27,%28,%29,%30,%31}, "
                 "%32, %33, p, 1, 1, 0, 1;\n}\n"
                 : WG_REGS_32(0) : "l"(dA), "l"(dB), "r"(sc));
}
__device__ __forceinline__ void wgmma_ss_n224_tb(float (&d)[112], uint64_t dA, uint64_t dB, int sc) {
    asm volatile("{\n.reg .pred p;\nsetp.ne.b32 p, %114, 0;\n"
                 "wgmma.mma_async.sync.aligned.m64n224k16.f32.bf16.bf16 "
                 "{%0,%1,%2,%3,%4,%5,%6,%7,%8,%9,%10,%11,%12,%13,%14,%15,%16,%17,%18,%19,%20,%21,%22,%23,%24,%25,%26,%27,%28,%29,%30,%31,"
                 "%32,%33,%34,%35,%36,%37,%38,%39,%40,%41,%42,%43,%44,%45,%46,%47,%48,%49,%50,%51,%52,%53,%54,%55,%56,%57,%58,%59,%60,%61,%62,%63,"
                 "%64,%65,%66,%67,%68,%69,%70,%71,%72,%73,%74,%75,%76,%77,%78,%79,%80,%81,%82,%83,%84,%85,%86,%87,%88,%89,%90,%91,%92,%93,%94,%95,"
                 "%96,%97,%98,%99,%100,%101,%102,%103,%104,%105,%106,%107,%108,%109,%110,%111}, "
                 "%112, %113, p, 1, 1, 0, 1;\n}\n"
                 : WG_REGS_32(0), WG_REGS_32(32), WG_REGS_32(64), WG_REGS_16(96) : "l"(dA), "l"(dB), "r"(sc));
}
template <int BN> __device__ __forceinline__ void wgmma_ss_tb(float (&d)[BN / 2], uint64_t dA, uint64_t dB, int sc) {
    if constexpr (BN == 64) wgmma_ss_n64_tb(d, dA, dB, sc);
    else if constexpr (BN == 80) wgmma_ss_n80_tb(d, dA, dB, sc);
    else wgmma_ss_n224_tb(d, dA, dB, sc);
}
__device__ __forceinline__ void wgmma_rs_n64_z(float (&d)[32], uint32_t a0, uint32_t a1, uint32_t a2, uint32_t a3, uint64_t dB) {
    asm volatile("{\n.reg .pred p;\nsetp.ne.b32 p, 0, 0;\n"
                 "wgmma.mma_async.sync.aligned.m64n64k16.f32.bf16.bf16 "
                 "{%0,%1,%2,%3,%4,%5,%6,%7,%8,%9,%10,%11,%12,%13,%14,%15,%16,%17,%18,%19,%20,%21,%22,%23,%24,%25,%26,%27,%28,%29,%30,%31}, "
                 "{%32,%33,%34,%35}, %36, p, 1, 1, 0;\n}\n"
                 : "=f"(d[0]), "=f"(d[1]), "=f"(d[2]), "=f"(d[3]), "=f"(d[4]), "=f"(d[5]), "=f"(d[6]), "=f"(d[7]),
                   "=f"(d[8]), "=f"(d[9]), "=f"(d[10]), "=f"(d[11]), "=f"(d[12]), "=f"(d[13]), "=f"(d[14]), "=f"(d[15]),
                   "=f"(d[16]), "=f"(d[17]), "=f"(d[18]), "=f"(d[19]), "=f"(d[20]), "=f"(d[21]), "=f"(d[22]), "=f"(d[23]),
                   "=f"(d[24]), "=f"(d[25]), "=f"(d[26]), "=f"(d[27]), "=f"(d[28]), "=f"(d[29]), "=f"(d[30]), "=f"(d[31])
                 : "r"(a0), "r"(a1), "r"(a2), "r"(a3), "l"(dB));
}
__device__ __forceinline__ void wgmma_rs_n24_tb(float (&d)[12], uint32_t a0, uint32_t a1, uint32_t a2, uint32_t a3, uint64_t dB) {
    asm volatile("{\n.reg .pred p;\nsetp.eq.b32 p, 0, 0;\n"
                 "wgmma.mma_async.sync.aligned.m64n24k16.f32.bf16.bf16 "
                 "{%0,%1,%2,%3,%4,%5,%6,%7,%8,%9,%10,%11}, {%12,%13,%14,%15}, %16, p, 1, 1, 1;\n}\n"
                 : WG_REGS_8(0), WG_REGS_4(8) : "r"(a0), "r"(a1), "r"(a2), "r"(a3), "l"(dB));
}

constexpr int PREP_STAT_CTAS = S_ / 8;
constexpr int PREP_CS_CTAS = 8 + 1 + F_ / 64;

__global__ void __launch_bounds__(256) prep_kernel(const __nv_bfloat16* __restrict__ x, const __nv_bfloat16* __restrict__ wq,
                                                   const __nv_bfloat16* __restrict__ wk, const __nv_bfloat16* __restrict__ wv,
                                                   const __nv_bfloat16* __restrict__ wo, const __nv_bfloat16* __restrict__ w1,
                                                   const __nv_bfloat16* __restrict__ w2) {
    pdl_launch();
    const int tid = threadIdx.x;
    if (tid == 0) { TL(0, 0); TL(0, 1); }
    if (blockIdx.x < PREP_CS_CTAS) {
        __shared__ float red[32][65];
        const int b = blockIdx.x;
        const int rg = tid >> 3, c8 = tid & 7;
        float acc[8];
#pragma unroll
        for (int i = 0; i < 8; i++) acc[i] = 0.f;
        const __nv_bfloat16* base;
        int ld;
        bool active = true;
        if (b < 8) { base = wq + b * 64 + c8 * 8; ld = D_; }
        else if (b == 8) { base = (c8 < 2 ? wk + c8 * 8 : wv + (c8 - 2) * 8); ld = 16; active = c8 < 4; }
        else { base = w1 + (b - 9) * 64 + c8 * 8; ld = F_; }
        if (active) {
            uint4 v[16];
#pragma unroll
            for (int i = 0; i < 16; i++) v[i] = __ldg((const uint4*)(base + (size_t)(rg + 32 * i) * ld));
#pragma unroll
            for (int i = 0; i < 16; i++) {
                acc[0] += bf_lo(v[i].x); acc[1] += bf_hi(v[i].x); acc[2] += bf_lo(v[i].y); acc[3] += bf_hi(v[i].y);
                acc[4] += bf_lo(v[i].z); acc[5] += bf_hi(v[i].z); acc[6] += bf_lo(v[i].w); acc[7] += bf_hi(v[i].w);
            }
        }
#pragma unroll
        for (int i = 0; i < 8; i++) red[rg][c8 * 8 + i] = acc[i];
        __syncthreads();
        if (tid < 64) {
            float s = 0.f;
#pragma unroll
            for (int i = 0; i < 32; i++) s += red[i][tid];
            if (b < 8) g_cs_q[b * 64 + tid] = s;
            else if (b == 8) { if (tid < 32) g_cs_kv[tid] = s; }
            else g_cs_1[(b - 9) * 64 + tid] = s;
        }
    } else {
        const int cb = blockIdx.x - PREP_CS_CTAS;
        if (tid < 72) {
            const int line = cb * 72 + tid;
            const char* p = line < 4096 ? (const char*)wo + (size_t)line * 128 : (const char*)w2 + (size_t)(line - 4096) * 128;
            asm volatile("prefetch.global.L2 [%0];" ::"l"(p));
        }
        const int warp = tid >> 5, lane = tid & 31;
        const int row = cb * 8 + warp;
        const uint4* p = (const uint4*)(x + (size_t)row * D_ + lane * 16);
        const uint4 a = __ldg(p), b = __ldg(p + 1);
        float v[16] = {bf_lo(a.x), bf_hi(a.x), bf_lo(a.y), bf_hi(a.y), bf_lo(a.z), bf_hi(a.z), bf_lo(a.w), bf_hi(a.w),
                       bf_lo(b.x), bf_hi(b.x), bf_lo(b.y), bf_hi(b.y), bf_lo(b.z), bf_hi(b.z), bf_lo(b.w), bf_hi(b.w)};
        float s = 0.f;
#pragma unroll
        for (int i = 0; i < 16; i++) s += v[i];
        s += __shfl_xor_sync(0xffffffffu, s, 1);
        s += __shfl_xor_sync(0xffffffffu, s, 2);
        const float mean = s * (1.f / 64.f);
        float m2 = 0.f;
#pragma unroll
        for (int i = 0; i < 16; i++) { const float d = v[i] - mean; m2 += d * d; }
        m2 += __shfl_xor_sync(0xffffffffu, m2, 1);
        m2 += __shfl_xor_sync(0xffffffffu, m2, 2);
        if ((lane & 3) == 0) g_stats[0][(lane >> 2) * S_ + row] = make_float2(mean, m2);
    }
    if (tid == 0) { TL(0, 2); TL(0, 3); }
}

enum { EPI_QKV = 0, EPI_RES = 1, EPI_FFN1 = 2 };

struct GemmParams {
    const float2* stats_in;
    float2* stats_out;
    int wait_in_epilogue;
    int tk;
};

template <int BK_, int NBLK> struct Geo {
    static constexpr int BK = BK_, A_BYTES = 128 * BK * 2, A_SWZ = BK == 64 ? 1 : 2, A_SBO = BK * 16;
    static constexpr int BLK = BK * 64;
    static constexpr int B_BYTES = NBLK * BLK, B_SWZ = 2, B_LBO = BLK, B_SBO = 512, B_KSTEP = 1024;
};
template <> struct Geo<64, 0> {
    static constexpr int BK = 64, A_BYTES = 128 * 128, A_SWZ = 1, A_SBO = 1024, BLK = 8192;
    static constexpr int B_BYTES = 64 * 128, B_SWZ = 1, B_LBO = 8192, B_SBO = 1024, B_KSTEP = 2048;
};
#define F1_BK 64
template <int EPI> struct EpiGeo;
template <> struct EpiGeo<EPI_QKV> { using G = Geo<64, 3>; };
template <> struct EpiGeo<EPI_RES> { using G = Geo<64, 0>; };
template <> struct EpiGeo<EPI_FFN1> { using G = Geo<F1_BK, 7>; };

template <int STAGES, int EPI> struct GemmSmem {
    using G = typename EpiGeo<EPI>::G;
    static constexpr int STAGE = G::A_BYTES + G::B_BYTES;
    static constexpr int AUX_OFF = STAGES * STAGE;
    static constexpr int TOTAL = AUX_OFF + 1152;
};

struct RowStatRaw { float2 a0, a1, b0, b1; };
__device__ __forceinline__ RowStatRaw load_row_stats(const float2* __restrict__ st, int row0, int c) {
    RowStatRaw r;
    r.a0 = st[(2 * c) * S_ + row0]; r.a1 = st[(2 * c + 1) * S_ + row0];
    r.b0 = st[(2 * c) * S_ + row0 + 8]; r.b1 = st[(2 * c + 1) * S_ + row0 + 8];
    return r;
}
__device__ __forceinline__ void finish_row_stats(const RowStatRaw& r, float& mean0, float& rstd0, float& mean1, float& rstd1) {
    float sa = r.a0.x + r.a1.x, sb = r.b0.x + r.b1.x;
    sa += __shfl_xor_sync(0xffffffffu, sa, 1); sa += __shfl_xor_sync(0xffffffffu, sa, 2);
    sb += __shfl_xor_sync(0xffffffffu, sb, 1); sb += __shfl_xor_sync(0xffffffffu, sb, 2);
    mean0 = sa * 0.125f; mean1 = sb * 0.125f;
    float ma = r.a0.y + r.a1.y + 64.f * ((r.a0.x - mean0) * (r.a0.x - mean0) + (r.a1.x - mean0) * (r.a1.x - mean0));
    float mb = r.b0.y + r.b1.y + 64.f * ((r.b0.x - mean1) * (r.b0.x - mean1) + (r.b1.x - mean1) * (r.b1.x - mean1));
    ma += __shfl_xor_sync(0xffffffffu, ma, 1); ma += __shfl_xor_sync(0xffffffffu, ma, 2);
    mb += __shfl_xor_sync(0xffffffffu, mb, 1); mb += __shfl_xor_sync(0xffffffffu, mb, 2);
    rstd0 = 1.0f / sqrtf(ma * (1.f / 512.f) + 1e-5f);
    rstd1 = 1.0f / sqrtf(mb * (1.f / 512.f) + 1e-5f);
}

template <int BN, int KB, int STAGES, int EPI, int MC>
__device__ __forceinline__ void gemm_body(const CUtensorMap* mapA, const CUtensorMap* mapB, const CUtensorMap* mapB2, const CUtensorMap* mapR,
                                          const CUtensorMap* mapC, const GemmParams& prm, int tile_m, int tile_n, uint8_t* smem_raw) {
    using SM = GemmSmem<STAGES, EPI>;
    using G = typename SM::G;
    constexpr bool XKV = BN == 80;
    constexpr int TN = EPI == EPI_QKV ? 64 : BN;
    pdl_launch();
    const uint32_t sbase = smem_u32(smem_raw);
    if (sbase & 1023) __trap();
    uint8_t* sgen = smem_raw;
    const uint32_t bar_full = sbase + SM::AUX_OFF, bar_empty = bar_full + 8 * STAGES;
    float* s_cs = (float*)(sgen + SM::AUX_OFF + 256);
    float* s_red = (float*)(sgen + SM::AUX_OFF + 768);
    const int tid = threadIdx.x, lane = tid & 31;
    const int warp = __shfl_sync(0xffffffffu, tid >> 5, 0);
    const uint32_t rank = MC ? cluster_rank() : 0;
    if (tid == 0) TL(prm.tk, 0);

    constexpr bool INLINE_PROD = EPI == EPI_FFN1 && F1_INLINE;
    constexpr int PWARP = INLINE_PROD ? 0 : 8;
    if (warp == PWARP && elect_one()) {
        prefetch_tmap(mapB); prefetch_tmap(mapA); prefetch_tmap(mapC);
        for (int s = 0; s < STAGES; s++) { mbar_init(bar_full + 8 * s, 1); mbar_init(bar_empty + 8 * s, MC ? 4 : 2); }
        fence_mbar_init();
    }
    __syncthreads();
    if (MC) cluster_sync();

    const int m0 = tile_m * 128, n0 = tile_n * TN;
    constexpr uint32_t STAGE_TX = G::A_BYTES + (EPI == EPI_QKV ? (XKV ? 3 : 2) * G::BLK : G::B_BYTES);
    auto loadB = [&](int kb, int s) {
        const uint32_t dst = sbase + s * SM::STAGE + G::A_BYTES, bar = bar_full + 8 * s;
        if constexpr (EPI == EPI_RES) {
            tma2d(dst, mapB, n0, kb * 64, bar);
        } else if constexpr (EPI == EPI_QKV) {
            tma3d(dst, mapB, 0, kb * G::BK, tile_n * 2, bar);
            if constexpr (XKV) tma2d(dst + 2 * G::BLK, mapB2, 0, kb * G::BK, bar);
        } else {
            if constexpr (MC == 2) {
                if (rank == 0) tma3d_mc(dst, mapB, 0, kb * G::BK, tile_n * 7, bar, 3);
                else tma3d_mc(dst + 4 * G::BLK, mapB2, 0, kb * G::BK, tile_n * 7 + 4, bar, 3);
            } else {
                tma3d(dst, mapB, 0, kb * G::BK, tile_n * 7, bar);
                tma3d(dst + 4 * G::BLK, mapB2, 0, kb * G::BK, tile_n * 7 + 4, bar);
            }
        }
    };
    auto loadA = [&](int kb, int s) {
        const uint32_t dst = sbase + s * SM::STAGE, bar = bar_full + 8 * s;
        if constexpr (MC == 1) tma2d_mc(dst + rank * (G::A_BYTES / 2), mapA, kb * G::BK, m0 + rank * 64, bar, 3);
        else tma2d(dst, mapA, kb * G::BK, m0, bar);
    };
    constexpr int PRE = STAGES < KB ? STAGES : KB;
#define F1_LAG 2
    constexpr int LAG = F1_LAG;
    constexpr int PRE_B = PRE < PREB ? PRE : PREB;
    auto prologue_loads = [&]() {
        if (elect_one()) {
#pragma unroll
            for (int kb = 0; kb < PRE; kb++) mbar_expect_tx(bar_full + 8 * kb, STAGE_TX);
#pragma unroll
            for (int kb = 0; kb < PRE_B; kb++) loadB(kb, kb);
        }
        if (!prm.wait_in_epilogue) pdl_wait();
        if (elect_one()) {
#pragma unroll
            for (int kb = 0; kb < PRE; kb++) {
                loadA(kb, kb);
                if (kb + PRE_B < PRE) loadB(kb + PRE_B, kb + PRE_B);
            }
            if constexpr (EPI == EPI_RES && KB < STAGES) {
                mbar_expect_tx(bar_full + 8 * KB, 16384);
                tma2d(sbase + KB * SM::STAGE, mapR, n0, m0, bar_full + 8 * KB);
            }
        }
    };
    if (!INLINE_PROD && warp == 8) {
        prologue_loads();
        int s = PRE % STAGES, ph = (PRE / STAGES) & 1;
#pragma unroll 1
        for (int kb = PRE; kb < KB; kb++) {
            mbar_wait(bar_empty + 8 * s, ph ^ 1);
            if (elect_one()) {
                mbar_expect_tx(bar_full + 8 * s, STAGE_TX);
                loadB(kb, s);
                loadA(kb, s);
            }
            if (++s == STAGES) { s = 0; ph ^= 1; }
        }
        if constexpr (EPI == EPI_RES && KB >= STAGES) {
            mbar_wait(bar_empty + 8 * s, ph ^ 1);
            if (elect_one()) {
                mbar_expect_tx(bar_full + 8 * s, 16384);
                tma2d(sbase + s * SM::STAGE, mapR, n0, m0, bar_full + 8 * s);
            }
        }
    } else {
        if (INLINE_PROD && warp == 0) prologue_loads();
        const int wg = warp >> 2, g = lane >> 2, c = lane & 3;
        const int rloc = wg * 64 + (warp & 3) * 16 + g;
        const int row0 = m0 + rloc;
        float mean0 = 0.f, rstd0 = 1.f, mean1 = 0.f, rstd1 = 1.f;
        RowStatRaw raw;
        float csv = 0.f;
        auto ln_inputs = [&]() {
            pdl_wait();
            if constexpr (EPI != EPI_RES) {
                raw = load_row_stats(prm.stats_in, row0, c);
                const float* cs = EPI == EPI_FFN1 ? g_cs_1 + n0 : g_cs_q + n0;
                if (tid < TN) csv = cs[tid];
            }
        };
        if (!prm.wait_in_epilogue) ln_inputs();
        float acc[BN / 2];
        const uint64_t dA0 = mkdesc(sbase + wg * (G::A_BYTES / 2), 16, G::A_SBO, G::A_SWZ);
        const uint64_t dB0 = mkdesc(sbase + G::A_BYTES, G::B_LBO, G::B_SBO, G::B_SWZ);
        int s = 0, ph = 0;
#pragma unroll 1
        for (int kb = 0; kb < KB; kb++) {
            mbar_wait(bar_full + 8 * s, ph);
            const uint64_t dA = dA0 + (uint64_t)(s * (SM::STAGE >> 4)), dB = dB0 + (uint64_t)(s * (SM::STAGE >> 4));
            wg_fence();
#pragma unroll
            for (int k = 0; k < G::BK / 16; k++) wgmma_ss_tb<BN>(acc, dA + (uint64_t)(k * 2), dB + (uint64_t)(k * (G::B_KSTEP >> 4)), (kb | k) != 0);
            wg_commit();
            if constexpr (EPI == EPI_RES && RES_WAIT0) {
                wg_wait<0>();
                if ((warp & 3) == 0 && elect_one()) {
                    if (MC) { mbar_arrive_remote(bar_empty + 8 * s, 0); mbar_arrive_remote(bar_empty + 8 * s, 1); }
                    else mbar_arrive(bar_empty + 8 * s);
                }
            } else if (kb > 0) {
                wg_wait<1>();
                const int sp = s == 0 ? STAGES - 1 : s - 1;
                if ((warp & 3) == 0 && elect_one()) {
                    if (MC) { mbar_arrive_remote(bar_empty + 8 * sp, 0); mbar_arrive_remote(bar_empty + 8 * sp, 1); }
                    else mbar_arrive(bar_empty + 8 * sp);
                }
                if (INLINE_PROD && warp == 0 && kb >= LAG && kb - LAG + STAGES < KB) {
                    const int sq = LAG == 1 ? sp : (sp == 0 ? STAGES - 1 : sp - 1);
                    mbar_wait(bar_empty + 8 * sq, ((kb - LAG) / STAGES) & 1);
                    if (elect_one()) {
                        mbar_expect_tx(bar_full + 8 * sq, STAGE_TX);
                        loadB(kb - LAG + STAGES, sq);
                        loadA(kb - LAG + STAGES, sq);
                    }
                }
            }
            if (++s == STAGES) { s = 0; ph ^= 1; }
        }
        if (prm.wait_in_epilogue) ln_inputs();
        if constexpr (EPI != EPI_RES) {
            finish_row_stats(raw, mean0, rstd0, mean1, rstd1);
            if (tid < TN) s_cs[tid] = csv;
        }
        wg_wait<0>();
        fence_regs(acc);
        if (tid == 0) TL(prm.tk, 2);
        if constexpr (EPI != EPI_RES) named_bar(1, 256);

        if constexpr (XKV) {
            {
                const float* acx = &acc[32];
                const float rm0 = rstd0 * mean0, rm1 = rstd1 * mean1;
                float n0s = 0.f, n1s = 0.f, vmax = 0.f;
#pragma unroll
                for (int j = 0; j < 2; j++) {
                    const float2 cs2 = *(const float2*)(g_cs_kv + tile_n * 16 + 8 * j + 2 * c);
                    const uint32_t u0 = pack_bf16(acx[4 * j] * rstd0 - rm0 * cs2.x, acx[4 * j + 1] * rstd0 - rm0 * cs2.y);
                    const uint32_t u1 = pack_bf16(acx[4 * j + 2] * rstd1 - rm1 * cs2.x, acx[4 * j + 3] * rstd1 - rm1 * cs2.y);
                    n0s += bf_lo(u0) * bf_lo(u0) + bf_hi(u0) * bf_hi(u0);
                    n1s += bf_lo(u1) * bf_lo(u1) + bf_hi(u1) * bf_hi(u1);
                    vmax = fmaxf(vmax, fmaxf(fmaxf(fabsf(bf_lo(u0)), fabsf(bf_hi(u0))), fmaxf(fabsf(bf_lo(u1)), fabsf(bf_hi(u1)))));
                    if (tile_n == 0) {
                        *(uint32_t*)(g_kimg + (row0 >> 3) * 256 + j * 128 + g * 16 + c * 4) = u0;
                        *(uint32_t*)(g_kimg + ((row0 + 8) >> 3) * 256 + j * 128 + g * 16 + c * 4) = u1;
                    } else {
                        uint8_t* vb = g_vimg + (row0 >> 4) * 768 + j * 256 + g * 16 + c * 4;
                        *(uint32_t*)(vb) = u0;
                        *(uint32_t*)(vb + 128) = u1;
                    }
                }
                if (tile_n == 1) {
                    uint8_t* vb = g_vimg + (row0 >> 4) * 768 + 512 + g * 16 + c * 4;
                    const uint32_t one = c == 0 ? 0x00003F80u : 0u;
                    *(uint32_t*)(vb) = one;
                    *(uint32_t*)(vb + 128) = one;
                }
                n0s += __shfl_xor_sync(0xffffffffu, n0s, 1); n0s += __shfl_xor_sync(0xffffffffu, n0s, 2);
                n1s += __shfl_xor_sync(0xffffffffu, n1s, 1); n1s += __shfl_xor_sync(0xffffffffu, n1s, 2);
                float km = tile_n == 0 ? fmaxf(n0s, n1s) : vmax;
                if (!(n0s + n1s < INFINITY)) km = INFINITY;
#pragma unroll
                for (int o = 1; o < 32; o <<= 1) km = fmaxf(km, __shfl_xor_sync(0xffffffffu, km, o));
                if (lane == 0) s_red[warp] = km;
                named_bar(1, 256);
                if (tid == 0) {
                    float a = 0.f;
                    for (int i = 0; i < 8; i++) a = fmaxf(a, s_red[i]);
                    g_kvmax[tile_n * 16 + tile_m] = a;
                }
            }
        }
        if constexpr (EPI != EPI_FFN1) {
            const uint32_t stile = sbase + (EPI == EPI_RES ? s * SM::STAGE : 0);
            const int mrow = wg * 64 + (warp & 3) * 16 + (lane & 7) + ((lane >> 3) & 1) * 8;
            const uint32_t rbase = stile + mrow * 128;
            if constexpr (EPI == EPI_RES) {
                mbar_wait(bar_full + 8 * s, ph);
                float s0 = 0.f, s1 = 0.f;
#pragma unroll
                for (int jj = 0; jj < 4; jj++) {
                    uint32_t r0, r1, r2, r3;
                    const uint32_t addr = rbase + (((2 * jj + (lane >> 4)) ^ (mrow & 7)) << 4);
                    ldsm_x4(r0, r1, r2, r3, addr);
                    const uint32_t u0 = pack_bf16(acc[8 * jj] + bf_lo(r0), acc[8 * jj + 1] + bf_hi(r0));
                    const uint32_t u1 = pack_bf16(acc[8 * jj + 2] + bf_lo(r1), acc[8 * jj + 3] + bf_hi(r1));
                    const uint32_t u2 = pack_bf16(acc[8 * jj + 4] + bf_lo(r2), acc[8 * jj + 5] + bf_hi(r2));
                    const uint32_t u3 = pack_bf16(acc[8 * jj + 6] + bf_lo(r3), acc[8 * jj + 7] + bf_hi(r3));
                    stsm_x4(addr, u0, u1, u2, u3);
                    acc[8 * jj] = bf_lo(u0); acc[8 * jj + 1] = bf_hi(u0); acc[8 * jj + 4] = bf_lo(u2); acc[8 * jj + 5] = bf_hi(u2);
                    acc[8 * jj + 2] = bf_lo(u1); acc[8 * jj + 3] = bf_hi(u1); acc[8 * jj + 6] = bf_lo(u3); acc[8 * jj + 7] = bf_hi(u3);
                    s0 += (acc[8 * jj] + acc[8 * jj + 1]) + (acc[8 * jj + 4] + acc[8 * jj + 5]);
                    s1 += (acc[8 * jj + 2] + acc[8 * jj + 3]) + (acc[8 * jj + 6] + acc[8 * jj + 7]);
                }
                fence_async_smem();
                named_bar(2 + wg, 128);
                if ((warp & 3) == 0 && elect_one()) { tma2d_store(mapC, stile + wg * 8192, n0, m0 + wg * 64); bulk_commit(); }
                if (prm.stats_out) {
                    s0 += __shfl_xor_sync(0xffffffffu, s0, 1); s0 += __shfl_xor_sync(0xffffffffu, s0, 2);
                    s1 += __shfl_xor_sync(0xffffffffu, s1, 1); s1 += __shfl_xor_sync(0xffffffffu, s1, 2);
                    const float mu0 = s0 * (1.f / 64.f), mu1 = s1 * (1.f / 64.f);
                    float q0 = 0.f, q1 = 0.f;
#pragma unroll
                    for (int j = 0; j < 8; j++) {
                        float d;
                        d = acc[4 * j] - mu0; q0 += d * d; d = acc[4 * j + 1] - mu0; q0 += d * d;
                        d = acc[4 * j + 2] - mu1; q1 += d * d; d = acc[4 * j + 3] - mu1; q1 += d * d;
                    }
                    q0 += __shfl_xor_sync(0xffffffffu, q0, 1); q0 += __shfl_xor_sync(0xffffffffu, q0, 2);
                    q1 += __shfl_xor_sync(0xffffffffu, q1, 1); q1 += __shfl_xor_sync(0xffffffffu, q1, 2);
                    if (c == 0) {
                        prm.stats_out[tile_n * S_ + row0] = make_float2(mu0, q0);
                        prm.stats_out[tile_n * S_ + row0 + 8] = make_float2(mu1, q1);
                    }
                }
            } else {
                const float sc = 0.25f * 1.4426950408889634f;
                const float a0 = rstd0 * sc, a1 = rstd1 * sc, rm0 = a0 * mean0, rm1 = a1 * mean1;
#pragma unroll
                for (int jj = 0; jj < 4; jj++) {
                    const float2 ca = *(const float2*)(s_cs + 16 * jj + 2 * c), cb = *(const float2*)(s_cs + 16 * jj + 8 + 2 * c);
                    const uint32_t u0 = pack_bf16(acc[8 * jj] * a0 - rm0 * ca.x, acc[8 * jj + 1] * a0 - rm0 * ca.y);
                    const uint32_t u1 = pack_bf16(acc[8 * jj + 2] * a1 - rm1 * ca.x, acc[8 * jj + 3] * a1 - rm1 * ca.y);
                    const uint32_t u2 = pack_bf16(acc[8 * jj + 4] * a0 - rm0 * cb.x, acc[8 * jj + 5] * a0 - rm0 * cb.y);
                    const uint32_t u3 = pack_bf16(acc[8 * jj + 6] * a1 - rm1 * cb.x, acc[8 * jj + 7] * a1 - rm1 * cb.y);
                    stsm_x4(rbase + (((2 * jj + (lane >> 4)) ^ (mrow & 7)) << 4), u0, u1, u2, u3);
                }
                fence_async_smem();
                named_bar(2 + wg, 128);
                if ((warp & 3) == 0 && elect_one()) { tma2d_store(mapC, stile + wg * 8192, n0, m0 + wg * 64); bulk_commit(); }
            }
            if ((warp & 3) == 0) bulk_wait_read();
        } else {
            const uint32_t stile = sbase + wg * (7 * 4096);
            const int mrow = (warp & 3) * 16 + (lane & 7) + ((lane >> 3) & 1) * 8;
            const float a0 = 0.5f * rstd0, a1 = 0.5f * rstd1, rm0 = a0 * mean0, rm1 = a1 * mean1;
#pragma unroll
            for (int jj = 0; jj < 14; jj++) {
                const float2 ca = *(const float2*)(s_cs + 16 * jj + 2 * c), cb = *(const float2*)(s_cs + 16 * jj + 8 + 2 * c);
                float y[8] = {acc[8 * jj] * a0 - rm0 * ca.x,     acc[8 * jj + 1] * a0 - rm0 * ca.y,
                              acc[8 * jj + 2] * a1 - rm1 * ca.x, acc[8 * jj + 3] * a1 - rm1 * ca.y,
                              acc[8 * jj + 4] * a0 - rm0 * cb.x, acc[8 * jj + 5] * a0 - rm0 * cb.y,
                              acc[8 * jj + 6] * a1 - rm1 * cb.x, acc[8 * jj + 7] * a1 - rm1 * cb.y};
#pragma unroll
                for (int i = 0; i < 8; i++) {
                    float t;
                    asm("tanh.approx.f32 %0, %1;" : "=f"(t) : "f"(y[i]));
                    y[i] = fmaf(y[i], t, y[i]);
                }
                const int chunk = (2 * jj + (lane >> 4)) & 3, blk = jj >> 1;
                stsm_x4(stile + blk * 4096 + mrow * 64 + ((chunk ^ ((mrow >> 1) & 3)) << 4),
                        pack_bf16(y[0], y[1]), pack_bf16(y[2], y[3]), pack_bf16(y[4], y[5]), pack_bf16(y[6], y[7]));
                if (jj & 1) {
                    fence_async_smem();
                    __syncwarp();
                    if (elect_one()) {
                        tma2d_store(mapC, stile + blk * 4096 + (warp & 3) * 1024, n0 + blk * 32, m0 + wg * 64 + (warp & 3) * 16);
                        bulk_commit();
                    }
                }
            }
            bulk_wait_read();
        }
    }
    if (tid == 0) TL(prm.tk, 3);
    if (MC) cluster_sync();
}

#define WO_ST 9
#define F2_ST 8
#define F1_ST (F1_BK == 64 ? 5 : 9)
#define QKV_ST 8
constexpr int QKV_STAGES = QKV_ST, WO_STAGES = WO_ST, FFN2_STAGES = F2_ST, FFN1_STAGES = F1_ST;
__global__ void __launch_bounds__(288) qkv_kernel(const __grid_constant__ CUtensorMap mapA, const __grid_constant__ CUtensorMap mapWq,
                                                  const __grid_constant__ CUtensorMap mapWk, const __grid_constant__ CUtensorMap mapWv,
                                                  const __grid_constant__ CUtensorMap mapQ, const GemmParams prm) {
    extern __shared__ __align__(1024) uint8_t smem_raw[];
    const int tn = blockIdx.x & 7;
    if (tn < 2) gemm_body<80, 8, QKV_STAGES, EPI_QKV, QKV_MC>(&mapA, &mapWq, tn == 0 ? &mapWk : &mapWv, &mapA, &mapQ, prm, blockIdx.x >> 3, tn, smem_raw);
    else gemm_body<64, 8, QKV_STAGES, EPI_QKV, QKV_MC>(&mapA, &mapWq, &mapWq, &mapA, &mapQ, prm, blockIdx.x >> 3, tn, smem_raw);
}
template <int KB, int STAGES>
__global__ void __launch_bounds__(288) res_gemm_kernel(const __grid_constant__ CUtensorMap mapA, const __grid_constant__ CUtensorMap mapW,
                                                       const __grid_constant__ CUtensorMap mapR, const __grid_constant__ CUtensorMap mapC, const GemmParams prm) {
    extern __shared__ __align__(1024) uint8_t smem_raw[];
    gemm_body<64, KB, STAGES, EPI_RES, (KB == 8 ? WO_MC : F2_MC)>(&mapA, &mapW, &mapW, &mapR, &mapC, prm, blockIdx.x >> 3, blockIdx.x & 7, smem_raw);
}
__global__ void __launch_bounds__(F1_INLINE ? 256 : 288) ffn1_kernel(const __grid_constant__ CUtensorMap mapA, const __grid_constant__ CUtensorMap mapW4,
                                                   const __grid_constant__ CUtensorMap mapW3, const __grid_constant__ CUtensorMap mapH, const GemmParams prm) {
    extern __shared__ __align__(1024) uint8_t smem_raw[];
    const int pair = blockIdx.x >> 1, tile_n = pair & 7, tile_m = (pair >> 3) * 2 + (blockIdx.x & 1);
    gemm_body<224, 512 / F1_BK, FFN1_STAGES, EPI_FFN1, F1_MC>(&mapA, &mapW4, &mapW3, &mapA, &mapH, prm, tile_m, tile_n, smem_raw);
}

constexpr int NPOLY = 10;
__host__ __device__ constexpr bool is_mufu(int i) { return ((i + 1) * (16 - NPOLY)) / 16 != (i * (16 - NPOLY)) / 16; }

__device__ __forceinline__ float ex2(float x) { float r; asm("ex2.approx.ftz.f32 %0, %1;" : "=f"(r) : "f"(x)); return r; }
__device__ __forceinline__ uint32_t exp_pair_mufu(float a, float b) { return pack_bf16(ex2(a), ex2(b)); }
__device__ __forceinline__ uint32_t exp_pair_fma(float a, float b, uint32_t c3f) {
    constexpr float MAGIC = 98430.4140625f;
    const float ta = a + MAGIC, tb = b + (MAGIC - 143.5f);
    uint32_t y, m, r;
    asm("mad.lo.u32 %0, %1, 65536, %2;" : "=r"(y) : "r"(__float_as_uint(tb)), "r"(__float_as_uint(ta)));
    asm("lop3.b32 %0, %1, 0x007F007F, %2, 0xEA;" : "=r"(m) : "r"(y), "r"(c3f));
    const uint32_t e = y & 0xFF80FF80u;
    asm("fma.rn.bf16x2 %0, %1, %2, %3;" : "=r"(r) : "r"(y), "r"(m), "r"(e));
    return r;
}

constexpr int KCH = 256, NCH = S_ / KCH;
constexpr int K_BYTES = S_ * 32, V_BYTES = (S_ / 16) * 768;
constexpr int ATT_SMEM = K_BYTES + V_BYTES;

__global__ void __launch_bounds__(512, 1) attn_kernel(int tk) {
    extern __shared__ __align__(1024) uint8_t smem[];
    __shared__ uint64_t bars[NCH];
    __shared__ int s_slow;
    const int tid = threadIdx.x, wg = tid >> 7, warp = (tid >> 5) & 3, lane = tid & 31;
    const uint32_t sK = smem_u32(smem), sV = sK + K_BYTES;
    if (tid == 0) TL(tk, 0);
    if (tid == 0) {
        for (int i = 0; i < NCH; i++) mbar_init(smem_u32(&bars[i]), 1);
        s_slow = 0;
        fence_mbar_init();
    }
    __syncthreads();
    pdl_launch();
    pdl_wait();
    if (tid == 0) TL(tk, 1);
    if (__shfl_sync(0xffffffffu, tid >> 5, 0) == 0 && elect_one()) {
#pragma unroll
        for (int i = 0; i < NCH; i++) {
            mbar_expect_tx(smem_u32(&bars[i]), KCH * 32 + (KCH / 16) * 768);
            bulk_load(sK + i * KCH * 32, g_kimg + i * KCH * 32, KCH * 32, smem_u32(&bars[i]));
            bulk_load(sV + i * (KCH / 16) * 768, g_vimg + i * (KCH / 16) * 768, (KCH / 16) * 768, smem_u32(&bars[i]));
        }
    }
    const int tb = blockIdx.x >> 3, hg = blockIdx.x & 7;
    const int head = hg * 4 + wg;
    const int g = lane >> 2, c = lane & 3;
    uint32_t qa[2][4];
    float qn = 0.f;
#pragma unroll
    for (int m = 0; m < 2; m++) {
        const int row = tb * 128 + m * 64 + warp * 16 + g;
        const uint32_t* p0 = (const uint32_t*)(g_q + (size_t)row * D_ + head * 16);
        const uint32_t* p1 = (const uint32_t*)(g_q + (size_t)(row + 8) * D_ + head * 16);
        qa[m][0] = p0[c]; qa[m][1] = p1[c]; qa[m][2] = p0[c + 4]; qa[m][3] = p1[c + 4];
        float n0 = bf_lo(qa[m][0]) * bf_lo(qa[m][0]) + bf_hi(qa[m][0]) * bf_hi(qa[m][0]) + bf_lo(qa[m][2]) * bf_lo(qa[m][2]) + bf_hi(qa[m][2]) * bf_hi(qa[m][2]);
        float n1 = bf_lo(qa[m][1]) * bf_lo(qa[m][1]) + bf_hi(qa[m][1]) * bf_hi(qa[m][1]) + bf_lo(qa[m][3]) * bf_lo(qa[m][3]) + bf_hi(qa[m][3]) * bf_hi(qa[m][3]);
        n0 += __shfl_xor_sync(0xffffffffu, n0, 1); n0 += __shfl_xor_sync(0xffffffffu, n0, 2);
        n1 += __shfl_xor_sync(0xffffffffu, n1, 1); n1 += __shfl_xor_sync(0xffffffffu, n1, 2);
        if (!(n0 == n0) || !(n1 == n1)) n0 = __int_as_float(0x7f800000);
        qn = fmaxf(qn, fmaxf(n0, n1));
    }
    {
        float km = 0.f, vm = 0.f;
#pragma unroll
        for (int i = 0; i < 16; i++) { km = fmaxf(km, g_kvmax[i]); vm = fmaxf(vm, g_kvmax[16 + i]); }
        const bool ok = (qn * km <= 10000.f) && (vm <= 16384.f);
        if (!ok) s_slow = 1;
    }
    float oacc[2][12];
#pragma unroll
    for (int m = 0; m < 2; m++)
#pragma unroll
        for (int i = 0; i < 12; i++) oacc[m][i] = 0.f;
    __syncthreads();
    const bool slow = s_slow != 0;

    const uint64_t dK0 = mkdesc(sK, 128, 256, 0);
    const uint64_t dV0 = mkdesc(sV, 128, 256, 0);
    uint32_t c3f;
    asm volatile("mov.b32 %0, 0x3F003F00;" : "=r"(c3f));
    if (!slow) {
#pragma unroll 1
        for (int t = 0; t < S_ / 64; t++) {
            if ((t & 3) == 0) mbar_wait(smem_u32(&bars[t >> 2]), 0);
            const uint64_t dK = dK0 + (uint64_t)(t * 64 * 32 / 16);
            const uint64_t dV = dV0 + (uint64_t)(t * 4 * 768 / 16);
#pragma unroll
            for (int m = 0; m < 2; m++) {
                float s[32];
                wg_fence();
                wgmma_rs_n64_z(s, qa[m][0], qa[m][1], qa[m][2], qa[m][3], dK);
                wg_commit();
                wg_wait<0>();
                fence_regs(s);
                uint32_t p[16];
#pragma unroll
                for (int i = 0; i < 16; i++) p[i] = is_mufu(i) ? exp_pair_mufu(s[2 * i], s[2 * i + 1]) : exp_pair_fma(s[2 * i], s[2 * i + 1], c3f);
                wg_fence();
#pragma unroll
                for (int kk = 0; kk < 4; kk++)
                    wgmma_rs_n24_tb(oacc[m], p[4 * kk], p[4 * kk + 1], p[4 * kk + 2], p[4 * kk + 3], dV + (uint64_t)(kk * 768 / 16));
                wg_commit();
            }
        }
        wg_wait<0>();
    } else {
        float mx[2][2] = {{-INFINITY, -INFINITY}, {-INFINITY, -INFINITY}};
#pragma unroll 1
        for (int t = 0; t < S_ / 64; t++) {
            if ((t & 3) == 0) mbar_wait(smem_u32(&bars[t >> 2]), 0);
            const uint64_t dK = dK0 + (uint64_t)(t * 64 * 32 / 16);
            const uint64_t dV = dV0 + (uint64_t)(t * 4 * 768 / 16);
#pragma unroll
            for (int m = 0; m < 2; m++) {
                float s[32];
                wg_fence();
                wgmma_rs_n64_z(s, qa[m][0], qa[m][1], qa[m][2], qa[m][3], dK);
                wg_commit();
                wg_wait<0>();
                fence_regs(s);
                fence_regs(oacc[m]);
                float r0 = mx[m][0], r1 = mx[m][1];
#pragma unroll
                for (int j = 0; j < 8; j++) {
                    r0 = fmaxf(r0, fmaxf(s[4 * j], s[4 * j + 1]));
                    r1 = fmaxf(r1, fmaxf(s[4 * j + 2], s[4 * j + 3]));
                }
                r0 = fmaxf(r0, __shfl_xor_sync(0xffffffffu, r0, 1)); r0 = fmaxf(r0, __shfl_xor_sync(0xffffffffu, r0, 2));
                r1 = fmaxf(r1, __shfl_xor_sync(0xffffffffu, r1, 1)); r1 = fmaxf(r1, __shfl_xor_sync(0xffffffffu, r1, 2));
                const float al0 = ex2(mx[m][0] - r0), al1 = ex2(mx[m][1] - r1);
                mx[m][0] = r0; mx[m][1] = r1;
#pragma unroll
                for (int j = 0; j < 3; j++) {
                    oacc[m][4 * j] *= al0; oacc[m][4 * j + 1] *= al0;
                    oacc[m][4 * j + 2] *= al1; oacc[m][4 * j + 3] *= al1;
                }
                uint32_t p[16];
#pragma unroll
                for (int j = 0; j < 8; j++) {
                    p[2 * j] = pack_bf16(ex2(s[4 * j] - r0), ex2(s[4 * j + 1] - r0));
                    p[2 * j + 1] = pack_bf16(ex2(s[4 * j + 2] - r1), ex2(s[4 * j + 3] - r1));
                }
                fence_regs(oacc[m]);
                wg_fence();
#pragma unroll
                for (int kk = 0; kk < 4; kk++)
                    wgmma_rs_n24_tb(oacc[m], p[4 * kk], p[4 * kk + 1], p[4 * kk + 2], p[4 * kk + 3], dV + (uint64_t)(kk * 768 / 16));
                wg_commit();
                wg_wait<0>();
            }
        }
    }
    fence_regs(oacc[0]); fence_regs(oacc[1]);
    if (tid == 0) TL(tk, 2);
#pragma unroll
    for (int m = 0; m < 2; m++) {
        const float l0 = __shfl_sync(0xffffffffu, oacc[m][8], lane & ~3);
        const float l1 = __shfl_sync(0xffffffffu, oacc[m][10], lane & ~3);
        const float r0 = 1.0f / l0, r1 = 1.0f / l1;
        const int row = tb * 128 + m * 64 + warp * 16 + g;
        uint32_t* p0 = (uint32_t*)(g_o + (size_t)row * D_ + head * 16);
        uint32_t* p1 = (uint32_t*)(g_o + (size_t)(row + 8) * D_ + head * 16);
        p0[c] = pack_bf16(oacc[m][0] * r0, oacc[m][1] * r0);
        p1[c] = pack_bf16(oacc[m][2] * r1, oacc[m][3] * r1);
        p0[c + 4] = pack_bf16(oacc[m][4] * r0, oacc[m][5] * r0);
        p1[c + 4] = pack_bf16(oacc[m][6] * r1, oacc[m][7] * r1);
    }
    if (tid == 0) TL(tk, 3);
}

typedef CUresult (*EncodeFn)(CUtensorMap*, CUtensorMapDataType, cuuint32_t, void*, const cuuint64_t*, const cuuint64_t*, const cuuint32_t*,
                             const cuuint32_t*, CUtensorMapInterleave, CUtensorMapSwizzle, CUtensorMapL2promotion, CUtensorMapFloatOOBfill);

EncodeFn get_encode() {
    static EncodeFn fn = nullptr;
    if (!fn) {
        void* p = nullptr;
        cudaDriverEntryPointQueryResult qr;
        cudaGetDriverEntryPoint("cuTensorMapEncodeTiled", &p, cudaEnableDefault, &qr);
        fn = (EncodeFn)p;
    }
    return fn;
}
CUtensorMap map2d(const void* ptr, uint64_t cols, uint64_t rows, uint32_t bc, uint32_t br, CUtensorMapSwizzle sw) {
    CUtensorMap m;
    cuuint64_t gd[2] = {cols, rows}, gs[1] = {cols * 2};
    cuuint32_t bx[2] = {bc, br}, es[2] = {1, 1};
    get_encode()(&m, CU_TENSOR_MAP_DATA_TYPE_BFLOAT16, 2, (void*)ptr, gd, gs, bx, es, CU_TENSOR_MAP_INTERLEAVE_NONE, sw,
                 CU_TENSOR_MAP_L2_PROMOTION_L2_128B, CU_TENSOR_MAP_FLOAT_OOB_FILL_NONE);
    return m;
}
CUtensorMap map3d32(const void* ptr, uint64_t cols, uint64_t rows, uint32_t br, uint32_t nb) {
    CUtensorMap m;
    cuuint64_t gd[3] = {32, rows, cols / 32}, gs[2] = {cols * 2, 64};
    cuuint32_t bx[3] = {32, br, nb}, es[3] = {1, 1, 1};
    get_encode()(&m, CU_TENSOR_MAP_DATA_TYPE_BFLOAT16, 3, (void*)ptr, gd, gs, bx, es, CU_TENSOR_MAP_INTERLEAVE_NONE, CU_TENSOR_MAP_SWIZZLE_64B,
                 CU_TENSOR_MAP_L2_PROMOTION_L2_128B, CU_TENSOR_MAP_FLOAT_OOB_FILL_NONE);
    return m;
}

template <typename... KArgs, typename... Args>
void launch(void (*kern)(KArgs...), int grid, int block, int smem, int cluster, bool pdl, Args... args) {
    cudaLaunchConfig_t cfg = {};
    cfg.gridDim = dim3(grid);
    cfg.blockDim = dim3(block);
    cfg.dynamicSmemBytes = smem;
    cfg.stream = cudaStreamPerThread;
    cudaLaunchAttribute at[2];
    int n = 0;
    if (cluster > 1) { at[n].id = cudaLaunchAttributeClusterDimension; at[n].val.clusterDim.x = cluster; at[n].val.clusterDim.y = 1; at[n].val.clusterDim.z = 1; n++; }
    if (pdl) { at[n].id = cudaLaunchAttributeProgrammaticStreamSerialization; at[n].val.programmaticStreamSerializationAllowed = 1; n++; }
    cfg.attrs = at;
    cfg.numAttrs = n;
    cudaLaunchKernelEx(&cfg, kern, KArgs(args)...);
}

template <typename T> void* sym(const T& s) { void* p = nullptr; cudaGetSymbolAddress(&p, s); return p; }

}

extern "C" void kernel_launch(void* const* d_in, const int* in_sizes, int n_in, void* d_out, int out_size) {
    const __nv_bfloat16* x = (const __nv_bfloat16*)d_in[0];
    const __nv_bfloat16* wq = (const __nv_bfloat16*)d_in[1];
    const __nv_bfloat16* wk = (const __nv_bfloat16*)d_in[2];
    const __nv_bfloat16* wv = (const __nv_bfloat16*)d_in[3];
    const __nv_bfloat16* wo = (const __nv_bfloat16*)d_in[4];
    const __nv_bfloat16* w1 = (const __nv_bfloat16*)d_in[6];
    const __nv_bfloat16* w2 = (const __nv_bfloat16*)d_in[7];

    constexpr int SM_QKV = GemmSmem<QKV_STAGES, EPI_QKV>::TOTAL;
    constexpr int HALF_PLUS = 116736;
    constexpr int SM_WO = GemmSmem<WO_STAGES, EPI_RES>::TOTAL > HALF_PLUS ? GemmSmem<WO_STAGES, EPI_RES>::TOTAL : HALF_PLUS;
    constexpr int SM_FFN2 = GemmSmem<FFN2_STAGES, EPI_RES>::TOTAL > HALF_PLUS ? GemmSmem<FFN2_STAGES, EPI_RES>::TOTAL : HALF_PLUS;
    constexpr int SM_FFN1 = GemmSmem<FFN1_STAGES, EPI_FFN1>::TOTAL;
    cudaFuncSetAttribute(qkv_kernel, cudaFuncAttributeMaxDynamicSharedMemorySize, SM_QKV);
    cudaFuncSetAttribute(res_gemm_kernel<8, WO_STAGES>, cudaFuncAttributeMaxDynamicSharedMemorySize, SM_WO);
    cudaFuncSetAttribute(ffn1_kernel, cudaFuncAttributeMaxDynamicSharedMemorySize, SM_FFN1);
    cudaFuncSetAttribute(res_gemm_kernel<28, FFN2_STAGES>, cudaFuncAttributeMaxDynamicSharedMemorySize, SM_FFN2);
    cudaFuncSetAttribute(attn_kernel, cudaFuncAttributeMaxDynamicSharedMemorySize, ATT_SMEM);
    cudaFuncSetAttribute(prep_kernel, cudaFuncAttributePreferredSharedMemoryCarveout, 100);
    cudaFuncSetAttribute(qkv_kernel, cudaFuncAttributePreferredSharedMemoryCarveout, 100);
    cudaFuncSetAttribute(res_gemm_kernel<8, WO_STAGES>, cudaFuncAttributePreferredSharedMemoryCarveout, 100);
    cudaFuncSetAttribute(ffn1_kernel, cudaFuncAttributePreferredSharedMemoryCarveout, 100);
    cudaFuncSetAttribute(res_gemm_kernel<28, FFN2_STAGES>, cudaFuncAttributePreferredSharedMemoryCarveout, 100);
    cudaFuncSetAttribute(attn_kernel, cudaFuncAttributePreferredSharedMemoryCarveout, 100);

    void *q = sym(g_q), *o = sym(g_o), *x1 = sym(g_x1), *x2 = sym(g_x2), *x3 = sym(g_x3), *h = sym(g_h);
    float2* stats = (float2*)sym(g_stats);
    const void* xs[5] = {x, x1, x2, x3, d_out};

    const CUtensorMapSwizzle SW128 = CU_TENSOR_MAP_SWIZZLE_128B, SW64 = CU_TENSOR_MAP_SWIZZLE_64B;
    const CUtensorMap mWq = map3d32(wq, D_, D_, 64, 2);
    const CUtensorMap mWk = map2d(wk, 16, D_, 32, 64, SW64);
    const CUtensorMap mWv = map2d(wv, 16, D_, 32, 64, SW64);
    const CUtensorMap mWo = map2d(wo, D_, D_, 64, 64, SW128);
    const CUtensorMap mW1a = map3d32(w1, F_, D_, F1_BK, 4), mW1b = map3d32(w1, F_, D_, F1_BK, 3);
    const CUtensorMap mW2 = map2d(w2, D_, F_, 64, 64, SW128);
    const CUtensorMap mQ = map2d(q, D_, S_, 64, 64, SW128);
    const CUtensorMap mHst = map2d(h, F_, S_, 32, 16, SW64);
    CUtensorMap mXa[4], mXf[4], mXr[4], mXs[5];
    for (int i = 0; i < 4; i++) {
        mXa[i] = map2d(xs[i], D_, S_, 64, QKV_MC ? 64 : 128, SW128);
        mXf[i] = F1_BK == 64 ? map2d(xs[i], D_, S_, 64, 128, SW128) : map2d(xs[i], D_, S_, 32, 128, SW64);
        mXr[i] = map2d(xs[i], D_, S_, 64, 128, SW128);
    }
    for (int i = 0; i < 5; i++) mXs[i] = map2d(xs[i], D_, S_, 64, 64, SW128);
    const CUtensorMap mOa = map2d(o, D_, S_, 64, WO_MC ? 64 : 128, SW128);
    const CUtensorMap mHa = map2d(h, F_, S_, 64, F2_MC ? 64 : 128, SW128);

    launch(prep_kernel, PREP_CS_CTAS + PREP_STAT_CTAS, 256, 0, 1, false, x, wq, wk, wv, wo, w1, w2);
    for (int layer = 0; layer < 2; layer++) {
        const int xi = layer * 2;
        GemmParams p;
        p.stats_in = stats + (size_t)xi * 8 * S_; p.stats_out = nullptr; p.wait_in_epilogue = layer == 0; p.tk = 1 + 5 * layer;
        launch(qkv_kernel, 128, 288, SM_QKV, QKV_MC ? 2 : 1, true, mXa[xi], mWq, mWk, mWv, mQ, p);
        launch(attn_kernel, 128, 512, ATT_SMEM, 1, true, 2 + 5 * layer);
        p.stats_in = nullptr; p.stats_out = stats + (size_t)(xi + 1) * 8 * S_; p.wait_in_epilogue = 0; p.tk = 3 + 5 * layer;
        launch(res_gemm_kernel<8, WO_STAGES>, 128, 288, SM_WO, WO_MC ? 2 : 1, true, mOa, mWo, mXr[xi], mXs[xi + 1], p);
        p.stats_in = stats + (size_t)(xi + 1) * 8 * S_; p.stats_out = nullptr; p.tk = 4 + 5 * layer;
        launch(ffn1_kernel, 128, F1_INLINE ? 256 : 288, SM_FFN1, F1_MC ? 2 : 1, true, mXf[xi + 1], mW1a, mW1b, mHst, p);
        p.stats_in = nullptr; p.stats_out = layer == 0 ? stats + (size_t)2 * 8 * S_ : nullptr; p.tk = 5 + 5 * layer;
        launch(res_gemm_kernel<28, FFN2_STAGES>, 128, 288, SM_FFN2, F2_MC ? 2 : 1, true, mHa, mW2, mXr[xi + 1], mXs[xi + 2], p);
    }
}
```

```cpp
#include <cuda_runtime.h>
#include <cuda_bf16.h>
#include <cuda.h>
#include <stdint.h>

#define F1_INLINE 0
#define QKV_MC 0
#define WO_MC 0
#define F2_MC 0
#define F1_MC 2
#define PREB 2
#define RES_WAIT0 0

namespace {

constexpr int S_ = 2048, D_ = 512, H_ = 32, F_ = 1792;

__device__ __align__(1024) __nv_bfloat16 g_q[S_ * D_];
__device__ __align__(1024) __nv_bfloat16 g_o[S_ * D_];
__device__ __align__(1024) __nv_bfloat16 g_x1[S_ * D_];
__device__ __align__(1024) __nv_bfloat16 g_x2[S_ * D_];
__device__ __align__(1024) __nv_bfloat16 g_x3[S_ * D_];
__device__ __align__(1024) __nv_bfloat16 g_h[S_ * F_];
__device__ __align__(1024) uint8_t g_kimg[S_ * 32];
__device__ __align__(1024) uint8_t g_vimg[(S_ / 16) * 768];
__device__ __align__(1024) float2 g_stats[4][8 * S_];
__device__ __align__(16) float g_cs_q[D_];
__device__ __align__(16) float g_cs_kv[32];
__device__ __align__(16) float g_cs_1[F_];
__device__ __align__(16) float g_kvmax[32];

#define TL(k, slot)

__device__ __forceinline__ uint32_t smem_u32(const void* p) { return (uint32_t)__cvta_generic_to_shared(p); }
__device__ __forceinline__ void mbar_init(uint32_t bar, uint32_t cnt) {
    asm volatile("mbarrier.init.shared::cta.b64 [%0], %1;" ::"r"(bar), "r"(cnt));
}
__device__ __forceinline__ void mbar_expect_tx(uint32_t bar, uint32_t bytes) {
    asm volatile("mbarrier.arrive.expect_tx.shared::cta.b64 _, [%0], %1;" ::"r"(bar), "r"(bytes) : "memory");
}
__device__ __forceinline__ void mbar_arrive(uint32_t bar) {
    asm volatile("mbarrier.arrive.shared::cta.b64 _, [%0];" ::"r"(bar) : "memory");
}
__device__ __forceinline__ void mbar_arrive_remote(uint32_t bar, uint32_t cta) {
    asm volatile("{\n.reg .b32 ra;\nmapa.shared::cluster.u32 ra, %0, %1;\nmbarrier.arrive.shared::cluster.b64 _, [ra];\n}" ::"r"(bar), "r"(cta) : "memory");
}
__device__ __forceinline__ void mbar_wait(uint32_t bar, uint32_t parity) {
    asm volatile("{\n.reg .pred p;\nWAIT_%=:\nmbarrier.try_wait.parity.shared::cta.b64 p, [%0], %1;\n@p bra DONE_%=;\nbra WAIT_%=;\nDONE_%=:\n}" ::"r"(bar), "r"(parity) : "memory");
}
__device__ __forceinline__ void bulk_load(uint32_t dst, const void* src, uint32_t bytes, uint32_t bar) {
    asm volatile("cp.async.bulk.shared::cluster.global.mbarrier::complete_tx::bytes [%0], [%1], %2, [%3];" ::"r"(dst), "l"(src), "r"(bytes), "r"(bar) : "memory");
}
__device__ __forceinline__ void tma2d(uint32_t dst, const CUtensorMap* m, int c0, int c1, uint32_t bar) {
    asm volatile("cp.async.bulk.tensor.2d.shared::cluster.global.mbarrier::complete_tx::bytes [%0], [%1, {%3, %4}], [%2];" ::"r"(dst), "l"(m), "r"(bar), "r"(c0), "r"(c1) : "memory");
}
__device__ __forceinline__ void tma2d_mc(uint32_t dst, const CUtensorMap* m, int c0, int c1, uint32_t bar, uint16_t mask) {
    asm volatile("cp.async.bulk.tensor.2d.shared::cluster.global.mbarrier::complete_tx::bytes.multicast::cluster [%0], [%1, {%3, %4}], [%2], %5;" ::"r"(dst), "l"(m), "r"(bar), "r"(c0), "r"(c1), "h"(mask) : "memory");
}
__device__ __forceinline__ void tma3d(uint32_t dst, const CUtensorMap* m, int c0, int c1, int c2, uint32_t bar) {
    asm volatile("cp.async.bulk.tensor.3d.shared::cluster.global.mbarrier::complete_tx::bytes [%0], [%1, {%3, %4, %5}], [%2];" ::"r"(dst), "l"(m), "r"(bar), "r"(c0), "r"(c1), "r"(c2) : "memory");
}
__device__ __forceinline__ void tma3d_mc(uint32_t dst, const CUtensorMap* m, int c0, int c1, int c2, uint32_t bar, uint16_t mask) {
    asm volatile("cp.async.bulk.tensor.3d.shared::cluster.global.mbarrier::complete_tx::bytes.multicast::cluster [%0], [%1, {%3, %4, %5}], [%2], %6;" ::"r"(dst), "l"(m), "r"(bar), "r"(c0), "r"(c1), "r"(c2), "h"(mask) : "memory");
}
__device__ __forceinline__ void tma2d_store(const CUtensorMap* m, uint32_t src, int c0, int c1) {
    asm volatile("cp.async.bulk.tensor.2d.global.shared::cta.bulk_group [%0, {%2, %3}], [%1];" ::"l"(m), "r"(src), "r"(c0), "r"(c1) : "memory");
}
__device__ __forceinline__ void tma3d_store(const CUtensorMap* m, uint32_t src, int c0, int c1, int c2) {
    asm volatile("cp.async.bulk.tensor.3d.global.shared::cta.bulk_group [%0, {%2, %3, %4}], [%1];" ::"l"(m), "r"(src), "r"(c0), "r"(c1), "r"(c2) : "memory");
}
__device__ __forceinline__ void bulk_commit() { asm volatile("cp.async.bulk.commit_group;" ::: "memory"); }
__device__ __forceinline__ void bulk_wait_read() { asm volatile("cp.async.bulk.wait_group.read 0;" ::: "memory"); }
__device__ __forceinline__ void prefetch_tmap(const CUtensorMap* m) { asm volatile("prefetch.tensormap [%0];" ::"l"(m) : "memory"); }
__device__ __forceinline__ void fence_async_smem() { asm volatile("fence.proxy.async.shared::cta;" ::: "memory"); }
__device__ __forceinline__ void fence_mbar_init() { asm volatile("fence.mbarrier_init.release.cluster;" ::: "memory"); }
__device__ __forceinline__ void cluster_sync() { asm volatile("barrier.cluster.arrive.release.aligned;\nbarrier.cluster.wait.acquire.aligned;" ::: "memory"); }
__device__ __forceinline__ uint32_t cluster_rank() { uint32_t r; asm volatile("mov.u32 %0, %%cluster_ctarank;" : "=r"(r)); return r; }
__device__ __forceinline__ void pdl_wait() { asm volatile("griddepcontrol.wait;" ::: "memory"); }
__device__ __forceinline__ void pdl_launch() { asm volatile("griddepcontrol.launch_dependents;" ::: "memory"); }
__device__ __forceinline__ bool elect_one() {
    uint32_t p;
    asm volatile("{\n.reg .pred p;\nelect.sync _|p, 0xffffffff;\nselp.b32 %0, 1, 0, p;\n}" : "=r"(p));
    return p != 0;
}
__device__ __forceinline__ void named_bar(int id, int n) { asm volatile("bar.sync %0, %1;" ::"r"(id), "r"(n) : "memory"); }

__device__ __forceinline__ void wg_fence() { asm volatile("wgmma.fence.sync.aligned;" ::: "memory"); }
__device__ __forceinline__ void wg_commit() { asm volatile("wgmma.commit_group.sync.aligned;" ::: "memory"); }
template <int N> __device__ __forceinline__ void wg_wait() { asm volatile("wgmma.wait_group.sync.aligned %0;" ::"n"(N) : "memory"); }
template <int N> __device__ __forceinline__ void fence_regs(float (&d)[N]) {
#pragma unroll
    for (int i = 0; i < N; i++) asm volatile("" : "+f"(d[i])::"memory");
}
__device__ __forceinline__ uint64_t mkdesc(uint32_t addr, uint32_t lbo, uint32_t sbo, uint32_t swz) {
    uint64_t d = 0;
    d |= (uint64_t)((addr & 0x3FFFF) >> 4);
    d |= (uint64_t)((lbo & 0x3FFFF) >> 4) << 16;
    d |= (uint64_t)((sbo & 0x3FFFF) >> 4) << 32;
    d |= (uint64_t)swz << 62;
    return d;
}
__device__ __forceinline__ void ldsm_x4(uint32_t& r0, uint32_t& r1, uint32_t& r2, uint32_t& r3, uint32_t addr) {
    asm volatile("ldmatrix.sync.aligned.m8n8.x4.shared.b16 {%0,%1,%2,%3}, [%4];" : "=r"(r0), "=r"(r1), "=r"(r2), "=r"(r3) : "r"(addr) : "memory");
}
__device__ __forceinline__ void stsm_x4(uint32_t addr, uint32_t r0, uint32_t r1, uint32_t r2, uint32_t r3) {
    asm volatile("stmatrix.sync.aligned.m8n8.x4.shared.b16 [%0], {%1,%2,%3,%4};" ::"r"(addr), "r"(r0), "r"(r1), "r"(r2), "r"(r3) : "memory");
}
__device__ __forceinline__ uint32_t pack_bf16(float lo, float hi) {
    uint32_t r;
    asm("cvt.rn.bf16x2.f32 %0, %1, %2;" : "=r"(r) : "f"(hi), "f"(lo));
    return r;
}
__device__ __forceinline__ float bf_lo(uint32_t v) { return __uint_as_float(v << 16); }
__device__ __forceinline__ float bf_hi(uint32_t v) { return __uint_as_float(v & 0xFFFF0000u); }

#define WG_REGS_4(o) "+f"(d[o]), "+f"(d[o + 1]), "+f"(d[o + 2]), "+f"(d[o + 3])
#define WG_REGS_8(o) WG_REGS_4(o), WG_REGS_4(o + 4)
#define WG_REGS_16(o) WG_REGS_8(o), WG_REGS_8(o + 8)
#define WG_REGS_32(o) WG_REGS_16(o), WG_REGS_16(o + 16)

__device__ __forceinline__ void wgmma_ss_n80_tb(float (&d)[40], uint64_t dA, uint64_t dB, int sc) {
    asm volatile("{\n.reg .pred p;\nsetp.ne.b32 p, %42, 0;\n"
                 "wgmma.mma_async.sync.aligned.m64n80k16.f32.bf16.bf16 "
                 "{%0,%1,%2,%3,%4,%5,%6,%7,%8,%9,%10,%11,%12,%13,%14,%15,%16,%17,%18,%19,%20,%21,%22,%23,%24,%25,%26,%27,%28,%29,%30,%31,"
                 "%32,%33,%34,%35,%36,%37,%38,%39}, %40, %41, p, 1, 1, 0, 1;\n}\n"
                 : WG_REGS_32(0), WG_REGS_8(32) : "l"(dA), "l"(dB), "r"(sc));
}
__device__ __forceinline__ void wgmma_ss_n64_tb(float (&d)[32], uint64_t dA, uint64_t dB, int sc) {
    asm volatile("{\n.reg .pred p;\nsetp.ne.b32 p, %34, 0;\n"
                 "wgmma.mma_async.sync.aligned.m64n64k16.f32.bf16.bf16 "
                 "{%0,%1,%2,%3,%4,%5,%6,%7,%8,%9,%10,%11,%12,%13,%14,%15,%16,%17,%18,%19,%20,%21,%22,%23,%24,%25,%26,%27,%28,%29,%30,%31}, "
                 "%32, %33, p, 1, 1, 0, 1;\n}\n"
                 : WG_REGS_32(0) : "l"(dA), "l"(dB), "r"(sc));
}
__device__ __forceinline__ void wgmma_ss_n224_tb(float (&d)[112], uint64_t dA, uint64_t dB, int sc) {
    asm volatile("{\n.reg .pred p;\nsetp.ne.b32 p, %114, 0;\n"
                 "wgmma.mma_async.sync.aligned.m64n224k16.f32.bf16.bf16 "
                 "{%0,%1,%2,%3,%4,%5,%6,%7,%8,%9,%10,%11,%12,%13,%14,%15,%16,%17,%18,%19,%20,%21,%22,%23,%24,%25,%26,%27,%28,%29,%30,%31,"
                 "%32,%33,%34,%35,%36,%37,%38,%39,%40,%41,%42,%43,%44,%45,%46,%47,%48,%49,%50,%51,%52,%53,%54,%55,%56,%57,%58,%59,%60,%61,%62,%63,"
                 "%64,%65,%66,%67,%68,%69,%70,%71,%72,%73,%74,%75,%76,%77,%78,%79,%80,%81,%82,%83,%84,%85,%86,%87,%88,%89,%90,%91,%92,%93,%94,%95,"
                 "%96,%97,%98,%99,%100,%101,%102,%103,%104,%105,%106,%107,%108,%109,%110,%111}, "
                 "%112, %113, p, 1, 1, 0, 1;\n}\n"
                 : WG_REGS_32(0), WG_REGS_32(32), WG_REGS_32(64), WG_REGS_16(96) : "l"(dA), "l"(dB), "r"(sc));
}
template <int BN> __device__ __forceinline__ void wgmma_ss_tb(float (&d)[BN / 2], uint64_t dA, uint64_t dB, int sc) {
    if constexpr (BN == 64) wgmma_ss_n64_tb(d, dA, dB, sc);
    else if constexpr (BN == 80) wgmma_ss_n80_tb(d, dA, dB, sc);
    else wgmma_ss_n224_tb(d, dA, dB, sc);
}
__device__ __forceinline__ void wgmma_rs_n64_z(float (&d)[32], uint32_t a0, uint32_t a1, uint32_t a2, uint32_t a3, uint64_t dB) {
    asm volatile("{\n.reg .pred p;\nsetp.ne.b32 p, 0, 0;\n"
                 "wgmma.mma_async.sync.aligned.m64n64k16.f32.bf16.bf16 "
                 "{%0,%1,%2,%3,%4,%5,%6,%7,%8,%9,%10,%11,%12,%13,%14,%15,%16,%17,%18,%19,%20,%21,%22,%23,%24,%25,%26,%27,%28,%29,%30,%31}, "
                 "{%32,%33,%34,%35}, %36, p, 1, 1, 0;\n}\n"
                 : "=f"(d[0]), "=f"(d[1]), "=f"(d[2]), "=f"(d[3]), "=f"(d[4]), "=f"(d[5]), "=f"(d[6]), "=f"(d[7]),
                   "=f"(d[8]), "=f"(d[9]), "=f"(d[10]), "=f"(d[11]), "=f"(d[12]), "=f"(d[13]), "=f"(d[14]), "=f"(d[15]),
                   "=f"(d[16]), "=f"(d[17]), "=f"(d[18]), "=f"(d[19]), "=f"(d[20]), "=f"(d[21]), "=f"(d[22]), "=f"(d[23]),
                   "=f"(d[24]), "=f"(d[25]), "=f"(d[26]), "=f"(d[27]), "=f"(d[28]), "=f"(d[29]), "=f"(d[30]), "=f"(d[31])
                 : "r"(a0), "r"(a1), "r"(a2), "r"(a3), "l"(dB));
}
__device__ __forceinline__ void wgmma_rs_n24_tb(float (&d)[12], uint32_t a0, uint32_t a1, uint32_t a2, uint32_t a3, uint64_t dB) {
    asm volatile("{\n.reg .pred p;\nsetp.eq.b32 p, 0, 0;\n"
                 "wgmma.mma_async.sync.aligned.m64n24k16.f32.bf16.bf16 "
                 "{%0,%1,%2,%3,%4,%5,%6,%7,%8,%9,%10,%11}, {%12,%13,%14,%15}, %16, p, 1, 1, 1;\n}\n"
                 : WG_REGS_8(0), WG_REGS_4(8) : "r"(a0), "r"(a1), "r"(a2), "r"(a3), "l"(dB));
}

constexpr int PREP_STAT_CTAS = S_ / 32;
constexpr int PREP_CS_CTAS = 8 + 1 + F_ / 64;

__global__ void __launch_bounds__(256) prep_kernel(const __nv_bfloat16* __restrict__ x, const __nv_bfloat16* __restrict__ wq,
                                                   const __nv_bfloat16* __restrict__ wk, const __nv_bfloat16* __restrict__ wv,
                                                   const __nv_bfloat16* __restrict__ wo, const __nv_bfloat16* __restrict__ w1,
                                                   const __nv_bfloat16* __restrict__ w2) {
    pdl_launch();
    const int tid = threadIdx.x, warp = tid >> 5, lane = tid & 31;
    if (tid == 0) { TL(0, 0); TL(0, 1); }
    if (blockIdx.x >= PREP_STAT_CTAS) {
        __shared__ float red[8][64];
        const int b = blockIdx.x - PREP_STAT_CTAS;
        const int rg = lane >> 3, c8 = lane & 7;
        float acc[8];
#pragma unroll
        for (int i = 0; i < 8; i++) acc[i] = 0.f;
        const __nv_bfloat16* base;
        int ld;
        bool active = true;
        if (b < 8) { base = wq + b * 64 + c8 * 8; ld = D_; }
        else if (b == 8) { base = (c8 < 2 ? wk + c8 * 8 : wv + (c8 - 2) * 8); ld = 16; active = c8 < 4; }
        else { base = w1 + (b - 9) * 64 + c8 * 8; ld = F_; }
        if (active) {
            uint4 v[16];
#pragma unroll
            for (int i = 0; i < 16; i++) v[i] = __ldg((const uint4*)(base + (size_t)(warp * 64 + rg + 4 * i) * ld));
#pragma unroll
            for (int i = 0; i < 16; i++) {
                acc[0] += bf_lo(v[i].x); acc[1] += bf_hi(v[i].x); acc[2] += bf_lo(v[i].y); acc[3] += bf_hi(v[i].y);
                acc[4] += bf_lo(v[i].z); acc[5] += bf_hi(v[i].z); acc[6] += bf_lo(v[i].w); acc[7] += bf_hi(v[i].w);
            }
        }
#pragma unroll
        for (int i = 0; i < 8; i++) {
            acc[i] += __shfl_xor_sync(0xffffffffu, acc[i], 8);
            acc[i] += __shfl_xor_sync(0xffffffffu, acc[i], 16);
        }
        if (rg == 0) {
#pragma unroll
            for (int i = 0; i < 8; i++) red[warp][c8 * 8 + i] = acc[i];
        }
        __syncthreads();
        if (tid < 64) {
            float s = 0.f;
#pragma unroll
            for (int i = 0; i < 8; i++) s += red[i][tid];
            if (b < 8) g_cs_q[b * 64 + tid] = s;
            else if (b == 8) { if (tid < 32) g_cs_kv[tid] = s; }
            else g_cs_1[(b - 9) * 64 + tid] = s;
        }
    } else {
        const int cb = blockIdx.x;
        const int row0 = cb * 32 + warp * 4;
        uint4 a[4], b[4];
#pragma unroll
        for (int r = 0; r < 4; r++) {
            const uint4* p = (const uint4*)(x + (size_t)(row0 + r) * D_ + lane * 16);
            a[r] = __ldg(p); b[r] = __ldg(p + 1);
        }
        for (int i = tid; i < 288; i += 256) {
            const int line = cb * 288 + i;
            const char* p = line < 4096 ? (const char*)wo + (size_t)line * 128 : (const char*)w2 + (size_t)(line - 4096) * 128;
            asm volatile("prefetch.global.L2 [%0];" ::"l"(p));
        }
#pragma unroll
        for (int r = 0; r < 4; r++) {
            const float v[16] = {bf_lo(a[r].x), bf_hi(a[r].x), bf_lo(a[r].y), bf_hi(a[r].y), bf_lo(a[r].z), bf_hi(a[r].z), bf_lo(a[r].w), bf_hi(a[r].w),
                                 bf_lo(b[r].x), bf_hi(b[r].x), bf_lo(b[r].y), bf_hi(b[r].y), bf_lo(b[r].z), bf_hi(b[r].z), bf_lo(b[r].w), bf_hi(b[r].w)};
            float s = 0.f;
#pragma unroll
            for (int i = 0; i < 16; i++) s += v[i];
            s += __shfl_xor_sync(0xffffffffu, s, 1);
            s += __shfl_xor_sync(0xffffffffu, s, 2);
            const float mean = s * (1.f / 64.f);
            float m2 = 0.f;
#pragma unroll
            for (int i = 0; i < 16; i++) { const float d = v[i] - mean; m2 += d * d; }
            m2 += __shfl_xor_sync(0xffffffffu, m2, 1);
            m2 += __shfl_xor_sync(0xffffffffu, m2, 2);
            if ((lane & 3) == 0) g_stats[0][(lane >> 2) * S_ + row0 + r] = make_float2(mean, m2);
        }
    }
    if (tid == 0) { TL(0, 2); TL(0, 3); }
}

enum { EPI_QKV = 0, EPI_RES = 1, EPI_FFN1 = 2 };

struct GemmParams {
    const float2* stats_in;
    float2* stats_out;
    int wait_in_epilogue;
    int tk;
};

template <int BK_, int NBLK> struct Geo {
    static constexpr int BK = BK_, A_BYTES = 128 * BK * 2, A_SWZ = BK == 64 ? 1 : 2, A_SBO = BK * 16;
    static constexpr int BLK = BK * 64;
    static constexpr int B_BYTES = NBLK * BLK, B_SWZ = 2, B_LBO = BLK, B_SBO = 512, B_KSTEP = 1024;
};
template <> struct Geo<64, 0> {
    static constexpr int BK = 64, A_BYTES = 128 * 128, A_SWZ = 1, A_SBO = 1024, BLK = 8192;
    static constexpr int B_BYTES = 64 * 128, B_SWZ = 1, B_LBO = 8192, B_SBO = 1024, B_KSTEP = 2048;
};
#define F1_BK 32
template <int EPI> struct EpiGeo;
template <> struct EpiGeo<EPI_QKV> { using G = Geo<64, 3>; };
template <> struct EpiGeo<EPI_RES> { using G = Geo<64, 0>; };
template <> struct EpiGeo<EPI_FFN1> { using G = Geo<F1_BK, 7>; };

template <int STAGES, int EPI> struct GemmSmem {
    using G = typename EpiGeo<EPI>::G;
    static constexpr int STAGE = G::A_BYTES + G::B_BYTES;
    static constexpr int AUX_OFF = STAGES * STAGE;
    static constexpr int TOTAL = AUX_OFF + 1152;
};

struct RowStatRaw { float2 a0, a1, b0, b1; };
__device__ __forceinline__ RowStatRaw load_row_stats(const float2* __restrict__ st, int row0, int c) {
    RowStatRaw r;
    r.a0 = st[(2 * c) * S_ + row0]; r.a1 = st[(2 * c + 1) * S_ + row0];
    r.b0 = st[(2 * c) * S_ + row0 + 8]; r.b1 = st[(2 * c + 1) * S_ + row0 + 8];
    return r;
}
__device__ __forceinline__ void finish_row_stats(const RowStatRaw& r, float& mean0, float& rstd0, float& mean1, float& rstd1) {
    float sa = r.a0.x + r.a1.x, sb = r.b0.x + r.b1.x;
    sa += __shfl_xor_sync(0xffffffffu, sa, 1); sa += __shfl_xor_sync(0xffffffffu, sa, 2);
    sb += __shfl_xor_sync(0xffffffffu, sb, 1); sb += __shfl_xor_sync(0xffffffffu, sb, 2);
    mean0 = sa * 0.125f; mean1 = sb * 0.125f;
    float ma = r.a0.y + r.a1.y + 64.f * ((r.a0.x - mean0) * (r.a0.x - mean0) + (r.a1.x - mean0) * (r.a1.x - mean0));
    float mb = r.b0.y + r.b1.y + 64.f * ((r.b0.x - mean1) * (r.b0.x - mean1) + (r.b1.x - mean1) * (r.b1.x - mean1));
    ma += __shfl_xor_sync(0xffffffffu, ma, 1); ma += __shfl_xor_sync(0xffffffffu, ma, 2);
    mb += __shfl_xor_sync(0xffffffffu, mb, 1); mb += __shfl_xor_sync(0xffffffffu, mb, 2);
    rstd0 = 1.0f / sqrtf(ma * (1.f / 512.f) + 1e-5f);
    rstd1 = 1.0f / sqrtf(mb * (1.f / 512.f) + 1e-5f);
}

template <int BN, int KB, int STAGES, int EPI, int MC>
__device__ __forceinline__ void gemm_body(const CUtensorMap* mapA, const CUtensorMap* mapB, const CUtensorMap* mapB2, const CUtensorMap* mapR,
                                          const CUtensorMap* mapC, const GemmParams& prm, int tile_m, int tile_n, uint8_t* smem_raw) {
    using SM = GemmSmem<STAGES, EPI>;
    using G = typename SM::G;
    constexpr bool XKV = BN == 80;
    constexpr int TN = EPI == EPI_QKV ? 64 : BN;
    pdl_launch();
    const uint32_t sbase = smem_u32(smem_raw);
    if (sbase & 1023) __trap();
    uint8_t* sgen = smem_raw;
    const uint32_t bar_full = sbase + SM::AUX_OFF, bar_empty = bar_full + 8 * STAGES;
    float* s_cs = (float*)(sgen + SM::AUX_OFF + 256);
    float* s_red = (float*)(sgen + SM::AUX_OFF + 768);
    const int tid = threadIdx.x, lane = tid & 31;
    const int warp = __shfl_sync(0xffffffffu, tid >> 5, 0);
    const uint32_t rank = MC ? cluster_rank() : 0;
    if (tid == 0) TL(prm.tk, 0);

    constexpr bool INLINE_PROD = EPI == EPI_FFN1 && F1_INLINE;
    constexpr int PWARP = INLINE_PROD ? 0 : 8;
    if (warp == PWARP && elect_one()) {
        prefetch_tmap(mapB); prefetch_tmap(mapA); prefetch_tmap(mapC);
        for (int s = 0; s < STAGES; s++) { mbar_init(bar_full + 8 * s, 1); mbar_init(bar_empty + 8 * s, MC ? 4 : 2); }
        fence_mbar_init();
    }
    __syncthreads();
    if (MC) cluster_sync();

    const int m0 = tile_m * 128, n0 = tile_n * TN;
    constexpr uint32_t STAGE_TX = G::A_BYTES + (EPI == EPI_QKV ? (XKV ? 3 : 2) * G::BLK : G::B_BYTES);
    auto loadB = [&](int kb, int s) {
        const uint32_t dst = sbase + s * SM::STAGE + G::A_BYTES, bar = bar_full + 8 * s;
        if constexpr (EPI == EPI_RES) {
            tma2d(dst, mapB, n0, kb * 64, bar);
        } else if constexpr (EPI == EPI_QKV) {
            tma3d(dst, mapB, 0, kb * G::BK, tile_n * 2, bar);
            if constexpr (XKV) tma2d(dst + 2 * G::BLK, mapB2, 0, kb * G::BK, bar);
        } else {
            if constexpr (MC == 2) {
                if (rank == 0) tma3d_mc(dst, mapB, 0, kb * G::BK, tile_n * 7, bar, 3);
                else tma3d_mc(dst + 4 * G::BLK, mapB2, 0, kb * G::BK, tile_n * 7 + 4, bar, 3);
            } else {
                tma3d(dst, mapB, 0, kb * G::BK, tile_n * 7, bar);
                tma3d(dst + 4 * G::BLK, mapB2, 0, kb * G::BK, tile_n * 7 + 4, bar);
            }
        }
    };
    auto loadA = [&](int kb, int s) {
        const uint32_t dst = sbase + s * SM::STAGE, bar = bar_full + 8 * s;
        if constexpr (MC == 1) tma2d_mc(dst + rank * (G::A_BYTES / 2), mapA, kb * G::BK, m0 + rank * 64, bar, 3);
        else tma2d(dst, mapA, kb * G::BK, m0, bar);
    };
    constexpr int PRE = STAGES < KB ? STAGES : KB;
#define F1_LAG 2
    constexpr int LAG = F1_LAG;
    constexpr int PRE_B = PRE < PREB ? PRE : PREB;
    auto prologue_loads = [&]() {
        if (elect_one()) {
#pragma unroll
            for (int kb = 0; kb < PRE; kb++) mbar_expect_tx(bar_full + 8 * kb, STAGE_TX);
#pragma unroll
            for (int kb = 0; kb < PRE_B; kb++) loadB(kb, kb);
        }
        if (!prm.wait_in_epilogue) pdl_wait();
        if (elect_one()) {
#pragma unroll
            for (int kb = 0; kb < PRE; kb++) {
                loadA(kb, kb);
                if (kb + PRE_B < PRE) loadB(kb + PRE_B, kb + PRE_B);
            }
            if constexpr (EPI == EPI_RES && KB < STAGES) {
                mbar_expect_tx(bar_full + 8 * KB, 16384);
                tma2d(sbase + KB * SM::STAGE, mapR, n0, m0, bar_full + 8 * KB);
            }
        }
    };
    if (!INLINE_PROD && warp == 8) {
        prologue_loads();
        int s = PRE % STAGES, ph = (PRE / STAGES) & 1;
#pragma unroll 1
        for (int kb = PRE; kb < KB; kb++) {
            mbar_wait(bar_empty + 8 * s, ph ^ 1);
            if (elect_one()) {
                mbar_expect_tx(bar_full + 8 * s, STAGE_TX);
                loadB(kb, s);
                loadA(kb, s);
            }
            if (++s == STAGES) { s = 0; ph ^= 1; }
        }
        if constexpr (EPI == EPI_RES && KB >= STAGES) {
            mbar_wait(bar_empty + 8 * s, ph ^ 1);
            if (elect_one()) {
                mbar_expect_tx(bar_full + 8 * s, 16384);
                tma2d(sbase + s * SM::STAGE, mapR, n0, m0, bar_full + 8 * s);
            }
        }
    } else {
        if (INLINE_PROD && warp == 0) prologue_loads();
        const int wg = warp >> 2, g = lane >> 2, c = lane & 3;
        const int rloc = wg * 64 + (warp & 3) * 16 + g;
        const int row0 = m0 + rloc;
        float mean0 = 0.f, rstd0 = 1.f, mean1 = 0.f, rstd1 = 1.f;
        RowStatRaw raw;
        float csv = 0.f;
        float2 cskv[2] = {make_float2(0.f, 0.f), make_float2(0.f, 0.f)};
        auto ln_inputs = [&]() {
            pdl_wait();
            if constexpr (EPI != EPI_RES) {
                raw = load_row_stats(prm.stats_in, row0, c);
                const float* cs = EPI == EPI_FFN1 ? g_cs_1 + n0 : g_cs_q + n0;
                if (tid < TN) csv = cs[tid];
                if constexpr (XKV) {
                    cskv[0] = *(const float2*)(g_cs_kv + tile_n * 16 + 2 * c);
                    cskv[1] = *(const float2*)(g_cs_kv + tile_n * 16 + 8 + 2 * c);
                }
            }
        };
        if (!prm.wait_in_epilogue) ln_inputs();
        float acc[BN / 2];
        const uint64_t dA0 = mkdesc(sbase + wg * (G::A_BYTES / 2), 16, G::A_SBO, G::A_SWZ);
        const uint64_t dB0 = mkdesc(sbase + G::A_BYTES, G::B_LBO, G::B_SBO, G::B_SWZ);
        int s = 0, ph = 0;
#pragma unroll 1
        for (int kb = 0; kb < KB; kb++) {
            mbar_wait(bar_full + 8 * s, ph);
            const uint64_t dA = dA0 + (uint64_t)(s * (SM::STAGE >> 4)), dB = dB0 + (uint64_t)(s * (SM::STAGE >> 4));
            wg_fence();
#pragma unroll
            for (int k = 0; k < G::BK / 16; k++) wgmma_ss_tb<BN>(acc, dA + (uint64_t)(k * 2), dB + (uint64_t)(k * (G::B_KSTEP >> 4)), (kb | k) != 0);
            wg_commit();
            if constexpr (EPI == EPI_RES && RES_WAIT0) {
                wg_wait<0>();
                if ((warp & 3) == 0 && elect_one()) {
                    if (MC) { mbar_arrive_remote(bar_empty + 8 * s, 0); mbar_arrive_remote(bar_empty + 8 * s, 1); }
                    else mbar_arrive(bar_empty + 8 * s);
                }
            } else if (kb > 0) {
                wg_wait<1>();
                const int sp = s == 0 ? STAGES - 1 : s - 1;
                if ((warp & 3) == 0 && elect_one()) {
                    if (MC) { mbar_arrive_remote(bar_empty + 8 * sp, 0); mbar_arrive_remote(bar_empty + 8 * sp, 1); }
                    else mbar_arrive(bar_empty + 8 * sp);
                }
                if (INLINE_PROD && warp == 0 && kb >= LAG && kb - LAG + STAGES < KB) {
                    const int sq = LAG == 1 ? sp : (sp == 0 ? STAGES - 1 : sp - 1);
                    mbar_wait(bar_empty + 8 * sq, ((kb - LAG) / STAGES) & 1);
                    if (elect_one()) {
                        mbar_expect_tx(bar_full + 8 * sq, STAGE_TX);
                        loadB(kb - LAG + STAGES, sq);
                        loadA(kb - LAG + STAGES, sq);
                    }
                }
            }
            if (++s == STAGES) { s = 0; ph ^= 1; }
        }
        if (prm.wait_in_epilogue) ln_inputs();
        if constexpr (EPI != EPI_RES) {
            finish_row_stats(raw, mean0, rstd0, mean1, rstd1);
            if (tid < TN) s_cs[tid] = csv;
        }
        wg_wait<0>();
        fence_regs(acc);
        if (tid == 0) TL(prm.tk, 2);
        if constexpr (EPI != EPI_RES) named_bar(1, 256);

        if constexpr (EPI != EPI_FFN1) {
            const uint32_t stile = sbase + (EPI == EPI_RES ? s * SM::STAGE : 0);
            const int mrow = wg * 64 + (warp & 3) * 16 + (lane & 7) + ((lane >> 3) & 1) * 8;
            const uint32_t rbase = stile + mrow * 128;
            if constexpr (EPI == EPI_RES) {
                mbar_wait(bar_full + 8 * s, ph);
                float s0 = 0.f, s1 = 0.f;
#pragma unroll
                for (int jj = 0; jj < 4; jj++) {
                    uint32_t r0, r1, r2, r3;
                    const uint32_t addr = rbase + (((2 * jj + (lane >> 4)) ^ (mrow & 7)) << 4);
                    ldsm_x4(r0, r1, r2, r3, addr);
                    const uint32_t u0 = pack_bf16(acc[8 * jj] + bf_lo(r0), acc[8 * jj + 1] + bf_hi(r0));
                    const uint32_t u1 = pack_bf16(acc[8 * jj + 2] + bf_lo(r1), acc[8 * jj + 3] + bf_hi(r1));
                    const uint32_t u2 = pack_bf16(acc[8 * jj + 4] + bf_lo(r2), acc[8 * jj + 5] + bf_hi(r2));
                    const uint32_t u3 = pack_bf16(acc[8 * jj + 6] + bf_lo(r3), acc[8 * jj + 7] + bf_hi(r3));
                    stsm_x4(addr, u0, u1, u2, u3);
                    acc[8 * jj] = bf_lo(u0); acc[8 * jj + 1] = bf_hi(u0); acc[8 * jj + 4] = bf_lo(u2); acc[8 * jj + 5] = bf_hi(u2);
                    acc[8 * jj + 2] = bf_lo(u1); acc[8 * jj + 3] = bf_hi(u1); acc[8 * jj + 6] = bf_lo(u3); acc[8 * jj + 7] = bf_hi(u3);
                    s0 += (acc[8 * jj] + acc[8 * jj + 1]) + (acc[8 * jj + 4] + acc[8 * jj + 5]);
                    s1 += (acc[8 * jj + 2] + acc[8 * jj + 3]) + (acc[8 * jj + 6] + acc[8 * jj + 7]);
                }
                fence_async_smem();
                named_bar(2 + wg, 128);
                if ((warp & 3) == 0 && elect_one()) { tma2d_store(mapC, stile + wg * 8192, n0, m0 + wg * 64); bulk_commit(); }
                if (prm.stats_out) {
                    s0 += __shfl_xor_sync(0xffffffffu, s0, 1); s0 += __shfl_xor_sync(0xffffffffu, s0, 2);
                    s1 += __shfl_xor_sync(0xffffffffu, s1, 1); s1 += __shfl_xor_sync(0xffffffffu, s1, 2);
                    const float mu0 = s0 * (1.f / 64.f), mu1 = s1 * (1.f / 64.f);
                    float q0 = 0.f, q1 = 0.f;
#pragma unroll
                    for (int j = 0; j < 8; j++) {
                        float d;
                        d = acc[4 * j] - mu0; q0 += d * d; d = acc[4 * j + 1] - mu0; q0 += d * d;
                        d = acc[4 * j + 2] - mu1; q1 += d * d; d = acc[4 * j + 3] - mu1; q1 += d * d;
                    }
                    q0 += __shfl_xor_sync(0xffffffffu, q0, 1); q0 += __shfl_xor_sync(0xffffffffu, q0, 2);
                    q1 += __shfl_xor_sync(0xffffffffu, q1, 1); q1 += __shfl_xor_sync(0xffffffffu, q1, 2);
                    if (c == 0) {
                        prm.stats_out[tile_n * S_ + row0] = make_float2(mu0, q0);
                        prm.stats_out[tile_n * S_ + row0 + 8] = make_float2(mu1, q1);
                    }
                }
            } else {
                const float sc = 0.25f * 1.4426950408889634f;
                const float a0 = rstd0 * sc, a1 = rstd1 * sc, rm0 = a0 * mean0, rm1 = a1 * mean1;
#pragma unroll
                for (int jj = 0; jj < 4; jj++) {
                    const float2 ca = *(const float2*)(s_cs + 16 * jj + 2 * c), cb = *(const float2*)(s_cs + 16 * jj + 8 + 2 * c);
                    const uint32_t u0 = pack_bf16(acc[8 * jj] * a0 - rm0 * ca.x, acc[8 * jj + 1] * a0 - rm0 * ca.y);
                    const uint32_t u1 = pack_bf16(acc[8 * jj + 2] * a1 - rm1 * ca.x, acc[8 * jj + 3] * a1 - rm1 * ca.y);
                    const uint32_t u2 = pack_bf16(acc[8 * jj + 4] * a0 - rm0 * cb.x, acc[8 * jj + 5] * a0 - rm0 * cb.y);
                    const uint32_t u3 = pack_bf16(acc[8 * jj + 6] * a1 - rm1 * cb.x, acc[8 * jj + 7] * a1 - rm1 * cb.y);
                    stsm_x4(rbase + (((2 * jj + (lane >> 4)) ^ (mrow & 7)) << 4), u0, u1, u2, u3);
                }
                fence_async_smem();
                named_bar(2 + wg, 128);
                if ((warp & 3) == 0 && elect_one()) { tma2d_store(mapC, stile + wg * 8192, n0, m0 + wg * 64); bulk_commit(); }
            }
            if constexpr (XKV) {
                {
                    const float* acx = &acc[32];
                    const float rm0 = rstd0 * mean0, rm1 = rstd1 * mean1;
                    float n0s = 0.f, n1s = 0.f, vmax = 0.f;
#pragma unroll
                    for (int j = 0; j < 2; j++) {
                        const float2 cs2 = cskv[j];
                        const uint32_t u0 = pack_bf16(acx[4 * j] * rstd0 - rm0 * cs2.x, acx[4 * j + 1] * rstd0 - rm0 * cs2.y);
                        const uint32_t u1 = pack_bf16(acx[4 * j + 2] * rstd1 - rm1 * cs2.x, acx[4 * j + 3] * rstd1 - rm1 * cs2.y);
                        n0s += bf_lo(u0) * bf_lo(u0) + bf_hi(u0) * bf_hi(u0);
                        n1s += bf_lo(u1) * bf_lo(u1) + bf_hi(u1) * bf_hi(u1);
                        vmax = fmaxf(vmax, fmaxf(fmaxf(fabsf(bf_lo(u0)), fabsf(bf_hi(u0))), fmaxf(fabsf(bf_lo(u1)), fabsf(bf_hi(u1)))));
                        if (tile_n == 0) {
                            *(uint32_t*)(g_kimg + (row0 >> 3) * 256 + j * 128 + g * 16 + c * 4) = u0;
                            *(uint32_t*)(g_kimg + ((row0 + 8) >> 3) * 256 + j * 128 + g * 16 + c * 4) = u1;
                        } else {
                            uint8_t* vb = g_vimg + (row0 >> 4) * 768 + j * 256 + g * 16 + c * 4;
                            *(uint32_t*)(vb) = u0;
                            *(uint32_t*)(vb + 128) = u1;
                        }
                    }
                    if (tile_n == 1) {
                        uint8_t* vb = g_vimg + (row0 >> 4) * 768 + 512 + g * 16 + c * 4;
                        const uint32_t one = c == 0 ? 0x00003F80u : 0u;
                        *(uint32_t*)(vb) = one;
                        *(uint32_t*)(vb + 128) = one;
                    }
                    n0s += __shfl_xor_sync(0xffffffffu, n0s, 1); n0s += __shfl_xor_sync(0xffffffffu, n0s, 2);
                    n1s += __shfl_xor_sync(0xffffffffu, n1s, 1); n1s += __shfl_xor_sync(0xffffffffu, n1s, 2);
                    float km = tile_n == 0 ? fmaxf(n0s, n1s) : vmax;
                    if (!(n0s + n1s < INFINITY)) km = INFINITY;
#pragma unroll
                    for (int o = 1; o < 32; o <<= 1) km = fmaxf(km, __shfl_xor_sync(0xffffffffu, km, o));
                    if (lane == 0) s_red[warp] = km;
                    named_bar(1, 256);
                    if (tid == 0) {
                        float a = 0.f;
                        for (int i = 0; i < 8; i++) a = fmaxf(a, s_red[i]);
                        g_kvmax[tile_n * 16 + tile_m] = a;
                    }
                }
            }
            if ((warp & 3) == 0) bulk_wait_read();
        } else {
            const uint32_t stile = sbase + wg * (7 * 4096);
            const int mrow = (warp & 3) * 16 + (lane & 7) + ((lane >> 3) & 1) * 8;
            const float a0 = 0.5f * rstd0, a1 = 0.5f * rstd1, rm0 = a0 * mean0, rm1 = a1 * mean1;
#pragma unroll
            for (int jj = 0; jj < 14; jj++) {
                const float2 ca = *(const float2*)(s_cs + 16 * jj + 2 * c), cb = *(const float2*)(s_cs + 16 * jj + 8 + 2 * c);
                float y[8] = {acc[8 * jj] * a0 - rm0 * ca.x,     acc[8 * jj + 1] * a0 - rm0 * ca.y,
                              acc[8 * jj + 2] * a1 - rm1 * ca.x, acc[8 * jj + 3] * a1 - rm1 * ca.y,
                              acc[8 * jj + 4] * a0 - rm0 * cb.x, acc[8 * jj + 5] * a0 - rm0 * cb.y,
                              acc[8 * jj + 6] * a1 - rm1 * cb.x, acc[8 * jj + 7] * a1 - rm1 * cb.y};
#pragma unroll
                for (int i = 0; i < 8; i++) {
                    float t;
                    asm("tanh.approx.f32 %0, %1;" : "=f"(t) : "f"(y[i]));
                    y[i] = fmaf(y[i], t, y[i]);
                }
                const int chunk = (2 * jj + (lane >> 4)) & 3, blk = jj >> 1;
                stsm_x4(stile + blk * 4096 + mrow * 64 + ((chunk ^ ((mrow >> 1) & 3)) << 4),
                        pack_bf16(y[0], y[1]), pack_bf16(y[2], y[3]), pack_bf16(y[4], y[5]), pack_bf16(y[6], y[7]));
                if (jj & 1) {
                    fence_async_smem();
                    __syncwarp();
                    if (elect_one()) {
                        tma2d_store(mapC, stile + blk * 4096 + (warp & 3) * 1024, n0 + blk * 32, m0 + wg * 64 + (warp & 3) * 16);
                        bulk_commit();
                    }
                }
            }
            bulk_wait_read();
        }
    }
    if (tid == 0) TL(prm.tk, 3);
    if (MC) cluster_sync();
}

#define WO_ST 9
#define F2_ST 6
#define F1_ST (F1_BK == 64 ? 5 : 9)
#define QKV_ST 8
constexpr int QKV_STAGES = QKV_ST, QKV_STAGES0 = 7  , WO_STAGES = WO_ST, FFN2_STAGES = F2_ST, FFN1_STAGES = F1_ST;
template <int STAGES>
__global__ void __launch_bounds__(288) qkv_kernel(const __grid_constant__ CUtensorMap mapA, const __grid_constant__ CUtensorMap mapWq,
                                                  const __grid_constant__ CUtensorMap mapWk, const __grid_constant__ CUtensorMap mapWv,
                                                  const __grid_constant__ CUtensorMap mapQ, const GemmParams prm) {
    extern __shared__ __align__(1024) uint8_t smem_raw[];
    const int tn = blockIdx.x & 7;
    if (tn < 2) gemm_body<80, 8, STAGES, EPI_QKV, QKV_MC>(&mapA, &mapWq, tn == 0 ? &mapWk : &mapWv, &mapA, &mapQ, prm, blockIdx.x >> 3, tn, smem_raw);
    else gemm_body<64, 8, STAGES, EPI_QKV, QKV_MC>(&mapA, &mapWq, &mapWq, &mapA, &mapQ, prm, blockIdx.x >> 3, tn, smem_raw);
}
template <int KB, int STAGES>
__global__ void __launch_bounds__(288) res_gemm_kernel(const __grid_constant__ CUtensorMap mapA, const __grid_constant__ CUtensorMap mapW,
                                                       const __grid_constant__ CUtensorMap mapR, const __grid_constant__ CUtensorMap mapC, const GemmParams prm) {
    extern __shared__ __align__(1024) uint8_t smem_raw[];
    gemm_body<64, KB, STAGES, EPI_RES, (KB == 8 ? WO_MC : F2_MC)>(&mapA, &mapW, &mapW, &mapR, &mapC, prm, blockIdx.x >> 3, blockIdx.x & 7, smem_raw);
}
__global__ void __launch_bounds__(F1_INLINE ? 256 : 288) ffn1_kernel(const __grid_constant__ CUtensorMap mapA, const __grid_constant__ CUtensorMap mapW4,
                                                   const __grid_constant__ CUtensorMap mapW3, const __grid_constant__ CUtensorMap mapH, const GemmParams prm) {
    extern __shared__ __align__(1024) uint8_t smem_raw[];
    const int pair = blockIdx.x >> 1, tile_n = pair & 7, tile_m = (pair >> 3) * 2 + (blockIdx.x & 1);
    gemm_body<224, 512 / F1_BK, FFN1_STAGES, EPI_FFN1, F1_MC>(&mapA, &mapW4, &mapW3, &mapA, &mapH, prm, tile_m, tile_n, smem_raw);
}

constexpr int NPOLY = 10;
__host__ __device__ constexpr bool is_mufu(int i) { return ((i + 1) * (16 - NPOLY)) / 16 != (i * (16 - NPOLY)) / 16; }

__device__ __forceinline__ float ex2(float x) { float r; asm("ex2.approx.ftz.f32 %0, %1;" : "=f"(r) : "f"(x)); return r; }
__device__ __forceinline__ uint32_t exp_pair_mufu(float a, float b) { return pack_bf16(ex2(a), ex2(b)); }
__device__ __forceinline__ uint32_t exp_pair_fma(float a, float b, uint32_t c3f) {
    constexpr float MAGIC = 98430.4140625f;
    const float ta = a + MAGIC, tb = b + (MAGIC - 143.5f);
    uint32_t y, m, r;
    asm("mad.lo.u32 %0, %1, 65536, %2;" : "=r"(y) : "r"(__float_as_uint(tb)), "r"(__float_as_uint(ta)));
    asm("lop3.b32 %0, %1, 0x007F007F, %2, 0xEA;" : "=r"(m) : "r"(y), "r"(c3f));
    const uint32_t e = y & 0xFF80FF80u;
    asm("fma.rn.bf16x2 %0, %1, %2, %3;" : "=r"(r) : "r"(y), "r"(m), "r"(e));
    return r;
}

constexpr int KCH = 256, NCH = S_ / KCH;
constexpr int K_BYTES = S_ * 32, V_BYTES = (S_ / 16) * 768;
constexpr int ATT_SMEM = K_BYTES + V_BYTES;

__global__ void __launch_bounds__(512, 1) attn_kernel(int tk) {
    extern __shared__ __align__(1024) uint8_t smem[];
    __shared__ uint64_t bars[NCH];
    __shared__ int s_slow;
    const int tid = threadIdx.x, wg = tid >> 7, warp = (tid >> 5) & 3, lane = tid & 31;
    const uint32_t sK = smem_u32(smem), sV = sK + K_BYTES;
    if (tid == 0) TL(tk, 0);
    if (tid == 0) {
        for (int i = 0; i < NCH; i++) mbar_init(smem_u32(&bars[i]), 1);
        s_slow = 0;
        fence_mbar_init();
    }
    __syncthreads();
    pdl_launch();
    pdl_wait();
    if (tid == 0) TL(tk, 1);
    if (__shfl_sync(0xffffffffu, tid >> 5, 0) == 0 && elect_one()) {
#pragma unroll
        for (int i = 0; i < NCH; i++) {
            mbar_expect_tx(smem_u32(&bars[i]), KCH * 32 + (KCH / 16) * 768);
            bulk_load(sK + i * KCH * 32, g_kimg + i * KCH * 32, KCH * 32, smem_u32(&bars[i]));
            bulk_load(sV + i * (KCH / 16) * 768, g_vimg + i * (KCH / 16) * 768, (KCH / 16) * 768, smem_u32(&bars[i]));
        }
    }
    const int tb = blockIdx.x >> 3, hg = blockIdx.x & 7;
    const int head = hg * 4 + wg;
    const int g = lane >> 2, c = lane & 3;
    uint32_t qa[2][4];
    float qn = 0.f;
#pragma unroll
    for (int m = 0; m < 2; m++) {
        const int row = tb * 128 + m * 64 + warp * 16 + g;
        const uint32_t* p0 = (const uint32_t*)(g_q + (size_t)row * D_ + head * 16);
        const uint32_t* p1 = (const uint32_t*)(g_q + (size_t)(row + 8) * D_ + head * 16);
        qa[m][0] = p0[c]; qa[m][1] = p1[c]; qa[m][2] = p0[c + 4]; qa[m][3] = p1[c + 4];
        float n0 = bf_lo(qa[m][0]) * bf_lo(qa[m][0]) + bf_hi(qa[m][0]) * bf_hi(qa[m][0]) + bf_lo(qa[m][2]) * bf_lo(qa[m][2]) + bf_hi(qa[m][2]) * bf_hi(qa[m][2]);
        float n1 = bf_lo(qa[m][1]) * bf_lo(qa[m][1]) + bf_hi(qa[m][1]) * bf_hi(qa[m][1]) + bf_lo(qa[m][3]) * bf_lo(qa[m][3]) + bf_hi(qa[m][3]) * bf_hi(qa[m][3]);
        n0 += __shfl_xor_sync(0xffffffffu, n0, 1); n0 += __shfl_xor_sync(0xffffffffu, n0, 2);
        n1 += __shfl_xor_sync(0xffffffffu, n1, 1); n1 += __shfl_xor_sync(0xffffffffu, n1, 2);
        if (!(n0 == n0) || !(n1 == n1)) n0 = __int_as_float(0x7f800000);
        qn = fmaxf(qn, fmaxf(n0, n1));
    }
    {
        float km = 0.f, vm = 0.f;
#pragma unroll
        for (int i = 0; i < 16; i++) { km = fmaxf(km, g_kvmax[i]); vm = fmaxf(vm, g_kvmax[16 + i]); }
        const bool ok = (qn * km <= 10000.f) && (vm <= 16384.f);
        if (!ok) s_slow = 1;
    }
    float oacc[2][12];
#pragma unroll
    for (int m = 0; m < 2; m++)
#pragma unroll
        for (int i = 0; i < 12; i++) oacc[m][i] = 0.f;
    __syncthreads();
    const bool slow = s_slow != 0;

    const uint64_t dK0 = mkdesc(sK, 128, 256, 0);
    const uint64_t dV0 = mkdesc(sV, 128, 256, 0);
    uint32_t c3f;
    asm volatile("mov.b32 %0, 0x3F003F00;" : "=r"(c3f));
    if (!slow) {
#pragma unroll 1
        for (int t = 0; t < S_ / 64; t++) {
            if ((t & 3) == 0) mbar_wait(smem_u32(&bars[t >> 2]), 0);
            const uint64_t dK = dK0 + (uint64_t)(t * 64 * 32 / 16);
            const uint64_t dV = dV0 + (uint64_t)(t * 4 * 768 / 16);
#pragma unroll
            for (int m = 0; m < 2; m++) {
                float s[32];
                wg_fence();
                wgmma_rs_n64_z(s, qa[m][0], qa[m][1], qa[m][2], qa[m][3], dK);
                wg_commit();
                wg_wait<0>();
                fence_regs(s);
                uint32_t p[16];
#pragma unroll
                for (int i = 0; i < 16; i++) p[i] = is_mufu(i) ? exp_pair_mufu(s[2 * i], s[2 * i + 1]) : exp_pair_fma(s[2 * i], s[2 * i + 1], c3f);
                wg_fence();
#pragma unroll
                for (int kk = 0; kk < 4; kk++)
                    wgmma_rs_n24_tb(oacc[m], p[4 * kk], p[4 * kk + 1], p[4 * kk + 2], p[4 * kk + 3], dV + (uint64_t)(kk * 768 / 16));
                wg_commit();
            }
        }
        wg_wait<0>();
    } else {
        float mx[2][2] = {{-INFINITY, -INFINITY}, {-INFINITY, -INFINITY}};
#pragma unroll 1
        for (int t = 0; t < S_ / 64; t++) {
            if ((t & 3) == 0) mbar_wait(smem_u32(&bars[t >> 2]), 0);
            const uint64_t dK = dK0 + (uint64_t)(t * 64 * 32 / 16);
            const uint64_t dV = dV0 + (uint64_t)(t * 4 * 768 / 16);
#pragma unroll
            for (int m = 0; m < 2; m++) {
                float s[32];
                wg_fence();
                wgmma_rs_n64_z(s, qa[m][0], qa[m][1], qa[m][2], qa[m][3], dK);
                wg_commit();
                wg_wait<0>();
                fence_regs(s);
                fence_regs(oacc[m]);
                float r0 = mx[m][0], r1 = mx[m][1];
#pragma unroll
                for (int j = 0; j < 8; j++) {
                    r0 = fmaxf(r0, fmaxf(s[4 * j], s[4 * j + 1]));
                    r1 = fmaxf(r1, fmaxf(s[4 * j + 2], s[4 * j + 3]));
                }
                r0 = fmaxf(r0, __shfl_xor_sync(0xffffffffu, r0, 1)); r0 = fmaxf(r0, __shfl_xor_sync(0xffffffffu, r0, 2));
                r1 = fmaxf(r1, __shfl_xor_sync(0xffffffffu, r1, 1)); r1 = fmaxf(r1, __shfl_xor_sync(0xffffffffu, r1, 2));
                const float al0 = ex2(mx[m][0] - r0), al1 = ex2(mx[m][1] - r1);
                mx[m][0] = r0; mx[m][1] = r1;
#pragma unroll
                for (int j = 0; j < 3; j++) {
                    oacc[m][4 * j] *= al0; oacc[m][4 * j + 1] *= al0;
                    oacc[m][4 * j + 2] *= al1; oacc[m][4 * j + 3] *= al1;
                }
                uint32_t p[16];
#pragma unroll
                for (int j = 0; j < 8; j++) {
                    p[2 * j] = pack_bf16(ex2(s[4 * j] - r0), ex2(s[4 * j + 1] - r0));
                    p[2 * j + 1] = pack_bf16(ex2(s[4 * j + 2] - r1), ex2(s[4 * j + 3] - r1));
                }
                fence_regs(oacc[m]);
                wg_fence();
#pragma unroll
                for (int kk = 0; kk < 4; kk++)
                    wgmma_rs_n24_tb(oacc[m], p[4 * kk], p[4 * kk + 1], p[4 * kk + 2], p[4 * kk + 3], dV + (uint64_t)(kk * 768 / 16));
                wg_commit();
                wg_wait<0>();
            }
        }
    }
    fence_regs(oacc[0]); fence_regs(oacc[1]);
    if (tid == 0) TL(tk, 2);
#pragma unroll
    for (int m = 0; m < 2; m++) {
        const float l0 = __shfl_sync(0xffffffffu, oacc[m][8], lane & ~3);
        const float l1 = __shfl_sync(0xffffffffu, oacc[m][10], lane & ~3);
        const float r0 = 1.0f / l0, r1 = 1.0f / l1;
        const int row = tb * 128 + m * 64 + warp * 16 + g;
        uint32_t* p0 = (uint32_t*)(g_o + (size_t)row * D_ + head * 16);
        uint32_t* p1 = (uint32_t*)(g_o + (size_t)(row + 8) * D_ + head * 16);
        p0[c] = pack_bf16(oacc[m][0] * r0, oacc[m][1] * r0);
        p1[c] = pack_bf16(oacc[m][2] * r1, oacc[m][3] * r1);
        p0[c + 4] = pack_bf16(oacc[m][4] * r0, oacc[m][5] * r0);
        p1[c + 4] = pack_bf16(oacc[m][6] * r1, oacc[m][7] * r1);
    }
    if (tid == 0) TL(tk, 3);
}

typedef CUresult (*EncodeFn)(CUtensorMap*, CUtensorMapDataType, cuuint32_t, void*, const cuuint64_t*, const cuuint64_t*, const cuuint32_t*,
                             const cuuint32_t*, CUtensorMapInterleave, CUtensorMapSwizzle, CUtensorMapL2promotion, CUtensorMapFloatOOBfill);

EncodeFn get_encode() {
    static EncodeFn fn = nullptr;
    if (!fn) {
        void* p = nullptr;
        cudaDriverEntryPointQueryResult qr;
        cudaGetDriverEntryPoint("cuTensorMapEncodeTiled", &p, cudaEnableDefault, &qr);
        fn = (EncodeFn)p;
    }
    return fn;
}
CUtensorMap map2d(const void* ptr, uint64_t cols, uint64_t rows, uint32_t bc, uint32_t br, CUtensorMapSwizzle sw) {
    CUtensorMap m;
    cuuint64_t gd[2] = {cols, rows}, gs[1] = {cols * 2};
    cuuint32_t bx[2] = {bc, br}, es[2] = {1, 1};
    get_encode()(&m, CU_TENSOR_MAP_DATA_TYPE_BFLOAT16, 2, (void*)ptr, gd, gs, bx, es, CU_TENSOR_MAP_INTERLEAVE_NONE, sw,
                 CU_TENSOR_MAP_L2_PROMOTION_L2_128B, CU_TENSOR_MAP_FLOAT_OOB_FILL_NONE);
    return m;
}
CUtensorMap map3d32(const void* ptr, uint64_t cols, uint64_t rows, uint32_t br, uint32_t nb) {
    CUtensorMap m;
    cuuint64_t gd[3] = {32, rows, cols / 32}, gs[2] = {cols * 2, 64};
    cuuint32_t bx[3] = {32, br, nb}, es[3] = {1, 1, 1};
    get_encode()(&m, CU_TENSOR_MAP_DATA_TYPE_BFLOAT16, 3, (void*)ptr, gd, gs, bx, es, CU_TENSOR_MAP_INTERLEAVE_NONE, CU_TENSOR_MAP_SWIZZLE_64B,
                 CU_TENSOR_MAP_L2_PROMOTION_L2_128B, CU_TENSOR_MAP_FLOAT_OOB_FILL_NONE);
    return m;
}

template <typename... KArgs, typename... Args>
void launch(void (*kern)(KArgs...), int grid, int block, int smem, int cluster, bool pdl, Args... args) {
    cudaLaunchConfig_t cfg = {};
    cfg.gridDim = dim3(grid);
    cfg.blockDim = dim3(block);
    cfg.dynamicSmemBytes = smem;
    cfg.stream = cudaStreamPerThread;
    cudaLaunchAttribute at[2];
    int n = 0;
    if (cluster > 1) { at[n].id = cudaLaunchAttributeClusterDimension; at[n].val.clusterDim.x = cluster; at[n].val.clusterDim.y = 1; at[n].val.clusterDim.z = 1; n++; }
    if (pdl) { at[n].id = cudaLaunchAttributeProgrammaticStreamSerialization; at[n].val.programmaticStreamSerializationAllowed = 1; n++; }
    cfg.attrs = at;
    cfg.numAttrs = n;
    cudaLaunchKernelEx(&cfg, kern, KArgs(args)...);
}

template <typename T> void* sym(const T& s) { void* p = nullptr; cudaGetSymbolAddress(&p, s); return p; }

}

extern "C" void kernel_launch(void* const* d_in, const int* in_sizes, int n_in, void* d_out, int out_size) {
    const __nv_bfloat16* x = (const __nv_bfloat16*)d_in[0];
    const __nv_bfloat16* wq = (const __nv_bfloat16*)d_in[1];
    const __nv_bfloat16* wk = (const __nv_bfloat16*)d_in[2];
    const __nv_bfloat16* wv = (const __nv_bfloat16*)d_in[3];
    const __nv_bfloat16* wo = (const __nv_bfloat16*)d_in[4];
    const __nv_bfloat16* w1 = (const __nv_bfloat16*)d_in[6];
    const __nv_bfloat16* w2 = (const __nv_bfloat16*)d_in[7];

    constexpr int SM_QKV = GemmSmem<QKV_STAGES, EPI_QKV>::TOTAL, SM_QKV0 = GemmSmem<QKV_STAGES0, EPI_QKV>::TOTAL;
    constexpr int HALF_PLUS = 116736;
    constexpr int SM_WO = GemmSmem<WO_STAGES, EPI_RES>::TOTAL > HALF_PLUS ? GemmSmem<WO_STAGES, EPI_RES>::TOTAL : HALF_PLUS;
    constexpr int SM_FFN2 = GemmSmem<FFN2_STAGES, EPI_RES>::TOTAL > HALF_PLUS ? GemmSmem<FFN2_STAGES, EPI_RES>::TOTAL : HALF_PLUS;
    constexpr int SM_FFN1 = GemmSmem<FFN1_STAGES, EPI_FFN1>::TOTAL;
    cudaFuncSetAttribute(qkv_kernel<QKV_STAGES>, cudaFuncAttributeMaxDynamicSharedMemorySize, SM_QKV);
    cudaFuncSetAttribute(qkv_kernel<QKV_STAGES0>, cudaFuncAttributeMaxDynamicSharedMemorySize, SM_QKV0);
    cudaFuncSetAttribute(res_gemm_kernel<8, WO_STAGES>, cudaFuncAttributeMaxDynamicSharedMemorySize, SM_WO);
    cudaFuncSetAttribute(ffn1_kernel, cudaFuncAttributeMaxDynamicSharedMemorySize, SM_FFN1);
    cudaFuncSetAttribute(res_gemm_kernel<28, FFN2_STAGES>, cudaFuncAttributeMaxDynamicSharedMemorySize, SM_FFN2);
    cudaFuncSetAttribute(attn_kernel, cudaFuncAttributeMaxDynamicSharedMemorySize, ATT_SMEM);
    cudaFuncSetAttribute(prep_kernel, cudaFuncAttributePreferredSharedMemoryCarveout, 100);
    cudaFuncSetAttribute(qkv_kernel<QKV_STAGES>, cudaFuncAttributePreferredSharedMemoryCarveout, 100);
    cudaFuncSetAttribute(qkv_kernel<QKV_STAGES0>, cudaFuncAttributePreferredSharedMemoryCarveout, 100);
    cudaFuncSetAttribute(res_gemm_kernel<8, WO_STAGES>, cudaFuncAttributePreferredSharedMemoryCarveout, 100);
    cudaFuncSetAttribute(ffn1_kernel, cudaFuncAttributePreferredSharedMemoryCarveout, 100);
    cudaFuncSetAttribute(res_gemm_kernel<28, FFN2_STAGES>, cudaFuncAttributePreferredSharedMemoryCarveout, 100);
    cudaFuncSetAttribute(attn_kernel, cudaFuncAttributePreferredSharedMemoryCarveout, 100);

    void *q = sym(g_q), *o = sym(g_o), *x1 = sym(g_x1), *x2 = sym(g_x2), *x3 = sym(g_x3), *h = sym(g_h);
    float2* stats = (float2*)sym(g_stats);
    const void* xs[5] = {x, x1, x2, x3, d_out};

    const CUtensorMapSwizzle SW128 = CU_TENSOR_MAP_SWIZZLE_128B, SW64 = CU_TENSOR_MAP_SWIZZLE_64B;
    const CUtensorMap mWq = map3d32(wq, D_, D_, 64, 2);
    const CUtensorMap mWk = map2d(wk, 16, D_, 32, 64, SW64);
    const CUtensorMap mWv = map2d(wv, 16, D_, 32, 64, SW64);
    const CUtensorMap mWo = map2d(wo, D_, D_, 64, 64, SW128);
    const CUtensorMap mW1a = map3d32(w1, F_, D_, F1_BK, 4), mW1b = map3d32(w1, F_, D_, F1_BK, 3);
    const CUtensorMap mW2 = map2d(w2, D_, F_, 64, 64, SW128);
    const CUtensorMap mQ = map2d(q, D_, S_, 64, 64, SW128);
    const CUtensorMap mHst = map2d(h, F_, S_, 32, 16, SW64);
    CUtensorMap mXa[4], mXf[4], mXr[4], mXs[5];
    for (int i = 0; i < 4; i++) {
        mXa[i] = map2d(xs[i], D_, S_, 64, QKV_MC ? 64 : 128, SW128);
        mXf[i] = F1_BK == 64 ? map2d(xs[i], D_, S_, 64, 128, SW128) : map2d(xs[i], D_, S_, 32, 128, SW64);
        mXr[i] = map2d(xs[i], D_, S_, 64, 128, SW128);
    }
    for (int i = 0; i < 5; i++) mXs[i] = map2d(xs[i], D_, S_, 64, 64, SW128);
    const CUtensorMap mOa = map2d(o, D_, S_, 64, WO_MC ? 64 : 128, SW128);
    const CUtensorMap mHa = map2d(h, F_, S_, 64, F2_MC ? 64 : 128, SW128);

    launch(prep_kernel, PREP_STAT_CTAS + PREP_CS_CTAS, 256, 0, 1, false, x, wq, wk, wv, wo, w1, w2);
    for (int layer = 0; layer < 2; layer++) {
        const int xi = layer * 2;
        GemmParams p;
        p.stats_in = stats + (size_t)xi * 8 * S_; p.stats_out = nullptr; p.wait_in_epilogue = layer == 0; p.tk = 1 + 5 * layer;
        if (layer == 0) launch(qkv_kernel<QKV_STAGES0>, 128, 288, SM_QKV0, QKV_MC ? 2 : 1, true, mXa[xi], mWq, mWk, mWv, mQ, p);
        else launch(qkv_kernel<QKV_STAGES>, 128, 288, SM_QKV, QKV_MC ? 2 : 1, true, mXa[xi], mWq, mWk, mWv, mQ, p);
        launch(attn_kernel, 128, 512, ATT_SMEM, 1, true, 2 + 5 * layer);
        p.stats_in = nullptr; p.stats_out = stats + (size_t)(xi + 1) * 8 * S_; p.wait_in_epilogue = 0; p.tk = 3 + 5 * layer;
        launch(res_gemm_kernel<8, WO_STAGES>, 128, 288, SM_WO, WO_MC ? 2 : 1, true, mOa, mWo, mXr[xi], mXs[xi + 1], p);
        p.stats_in = stats + (size_t)(xi + 1) * 8 * S_; p.stats_out = nullptr; p.tk = 4 + 5 * layer;
        launch(ffn1_kernel, 128, F1_INLINE ? 256 : 288, SM_FFN1, F1_MC ? 2 : 1, true, mXf[xi + 1], mW1a, mW1b, mHst, p);
        p.stats_in = nullptr; p.stats_out = layer == 0 ? stats + (size_t)2 * 8 * S_ : nullptr; p.tk = 5 + 5 * layer;
        launch(res_gemm_kernel<28, FFN2_STAGES>, 128, 288, SM_FFN2, F2_MC ? 2 : 1, true, mHa, mW2, mXr[xi + 1], mXs[xi + 2], p);
    }
}
```

```cpp
#include <cuda_runtime.h>
#include <cuda_bf16.h>
#include <cuda.h>
#include <stdint.h>

#define F1_INLINE 0
#define QKV_MC 0
#define WO_MC 0
#define F2_MC 0
#define F1_MC 2
#define PREB 2
#define RES_WAIT0 0

namespace {

constexpr int S_ = 2048, D_ = 512, H_ = 32, F_ = 1792;

__device__ __align__(1024) __nv_bfloat16 g_q[S_ * D_];
__device__ __align__(1024) __nv_bfloat16 g_o[S_ * D_];
__device__ __align__(1024) __nv_bfloat16 g_x1[S_ * D_];
__device__ __align__(1024) __nv_bfloat16 g_x2[S_ * D_];
__device__ __align__(1024) __nv_bfloat16 g_x3[S_ * D_];
__device__ __align__(1024) __nv_bfloat16 g_h[S_ * F_];
__device__ __align__(1024) uint8_t g_kimg[S_ * 32];
__device__ __align__(1024) uint8_t g_vimg[(S_ / 16) * 768];
__device__ __align__(1024) float2 g_stats[4][8 * S_];
__device__ __align__(16) float g_cs_q[D_];
__device__ __align__(16) float g_cs_kv[32];
__device__ __align__(16) float g_cs_1[F_];
__device__ __align__(16) float g_kvmax[32];

#define TL(k, slot)

__device__ __forceinline__ uint32_t smem_u32(const void* p) { return (uint32_t)__cvta_generic_to_shared(p); }
__device__ __forceinline__ void mbar_init(uint32_t bar, uint32_t cnt) {
    asm volatile("mbarrier.init.shared::cta.b64 [%0], %1;" ::"r"(bar), "r"(cnt));
}
__device__ __forceinline__ void mbar_expect_tx(uint32_t bar, uint32_t bytes) {
    asm volatile("mbarrier.arrive.expect_tx.shared::cta.b64 _, [%0], %1;" ::"r"(bar), "r"(bytes) : "memory");
}
__device__ __forceinline__ void mbar_arrive(uint32_t bar) {
    asm volatile("mbarrier.arrive.shared::cta.b64 _, [%0];" ::"r"(bar) : "memory");
}
__device__ __forceinline__ void mbar_arrive_remote(uint32_t bar, uint32_t cta) {
    asm volatile("{\n.reg .b32 ra;\nmapa.shared::cluster.u32 ra, %0, %1;\nmbarrier.arrive.shared::cluster.b64 _, [ra];\n}" ::"r"(bar), "r"(cta) : "memory");
}
__device__ __forceinline__ void mbar_wait(uint32_t bar, uint32_t parity) {
    asm volatile("{\n.reg .pred p;\nWAIT_%=:\nmbarrier.try_wait.parity.shared::cta.b64 p, [%0], %1;\n@p bra DONE_%=;\nbra WAIT_%=;\nDONE_%=:\n}" ::"r"(bar), "r"(parity) : "memory");
}
__device__ __forceinline__ void bulk_load(uint32_t dst, const void* src, uint32_t bytes, uint32_t bar) {
    asm volatile("cp.async.bulk.shared::cluster.global.mbarrier::complete_tx::bytes [%0], [%1], %2, [%3];" ::"r"(dst), "l"(src), "r"(bytes), "r"(bar) : "memory");
}
__device__ __forceinline__ void tma2d(uint32_t dst, const CUtensorMap* m, int c0, int c1, uint32_t bar) {
    asm volatile("cp.async.bulk.tensor.2d.shared::cluster.global.mbarrier::complete_tx::bytes [%0], [%1, {%3, %4}], [%2];" ::"r"(dst), "l"(m), "r"(bar), "r"(c0), "r"(c1) : "memory");
}
__device__ __forceinline__ void tma2d_mc(uint32_t dst, const CUtensorMap* m, int c0, int c1, uint32_t bar, uint16_t mask) {
    asm volatile("cp.async.bulk.tensor.2d.shared::cluster.global.mbarrier::complete_tx::bytes.multicast::cluster [%0], [%1, {%3, %4}], [%2], %5;" ::"r"(dst), "l"(m), "r"(bar), "r"(c0), "r"(c1), "h"(mask) : "memory");
}
__device__ __forceinline__ void tma3d(uint32_t dst, const CUtensorMap* m, int c0, int c1, int c2, uint32_t bar) {
    asm volatile("cp.async.bulk.tensor.3d.shared::cluster.global.mbarrier::complete_tx::bytes [%0], [%1, {%3, %4, %5}], [%2];" ::"r"(dst), "l"(m), "r"(bar), "r"(c0), "r"(c1), "r"(c2) : "memory");
}
__device__ __forceinline__ void tma3d_mc(uint32_t dst, const CUtensorMap* m, int c0, int c1, int c2, uint32_t bar, uint16_t mask) {
    asm volatile("cp.async.bulk.tensor.3d.shared::cluster.global.mbarrier::complete_tx::bytes.multicast::cluster [%0], [%1, {%3, %4, %5}], [%2], %6;" ::"r"(dst), "l"(m), "r"(bar), "r"(c0), "r"(c1), "r"(c2), "h"(mask) : "memory");
}
__device__ __forceinline__ void tma2d_store(const CUtensorMap* m, uint32_t src, int c0, int c1) {
    asm volatile("cp.async.bulk.tensor.2d.global.shared::cta.bulk_group [%0, {%2, %3}], [%1];" ::"l"(m), "r"(src), "r"(c0), "r"(c1) : "memory");
}
__device__ __forceinline__ void tma3d_store(const CUtensorMap* m, uint32_t src, int c0, int c1, int c2) {
    asm volatile("cp.async.bulk.tensor.3d.global.shared::cta.bulk_group [%0, {%2, %3, %4}], [%1];" ::"l"(m), "r"(src), "r"(c0), "r"(c1), "r"(c2) : "memory");
}
__device__ __forceinline__ void bulk_commit() { asm volatile("cp.async.bulk.commit_group;" ::: "memory"); }
__device__ __forceinline__ void bulk_wait_read() { asm volatile("cp.async.bulk.wait_group.read 0;" ::: "memory"); }
__device__ __forceinline__ void prefetch_tmap(const CUtensorMap* m) { asm volatile("prefetch.tensormap [%0];" ::"l"(m) : "memory"); }
__device__ __forceinline__ void fence_async_smem() { asm volatile("fence.proxy.async.shared::cta;" ::: "memory"); }
__device__ __forceinline__ void fence_mbar_init() { asm volatile("fence.mbarrier_init.release.cluster;" ::: "memory"); }
__device__ __forceinline__ void cluster_sync() { asm volatile("barrier.cluster.arrive.release.aligned;\nbarrier.cluster.wait.acquire.aligned;" ::: "memory"); }
__device__ __forceinline__ uint32_t cluster_rank() { uint32_t r; asm volatile("mov.u32 %0, %%cluster_ctarank;" : "=r"(r)); return r; }
__device__ __forceinline__ void pdl_wait() { asm volatile("griddepcontrol.wait;" ::: "memory"); }
__device__ __forceinline__ void pdl_launch() { asm volatile("griddepcontrol.launch_dependents;" ::: "memory"); }
__device__ __forceinline__ bool elect_one() {
    uint32_t p;
    asm volatile("{\n.reg .pred p;\nelect.sync _|p, 0xffffffff;\nselp.b32 %0, 1, 0, p;\n}" : "=r"(p));
    return p != 0;
}
__device__ __forceinline__ void named_bar(int id, int n) { asm volatile("bar.sync %0, %1;" ::"r"(id), "r"(n) : "memory"); }

__device__ __forceinline__ void wg_fence() { asm volatile("wgmma.fence.sync.aligned;" ::: "memory"); }
__device__ __forceinline__ void wg_commit() { asm volatile("wgmma.commit_group.sync.aligned;" ::: "memory"); }
template <int N> __device__ __forceinline__ void wg_wait() { asm volatile("wgmma.wait_group.sync.aligned %0;" ::"n"(N) : "memory"); }
template <int N> __device__ __forceinline__ void fence_regs(float (&d)[N]) {
#pragma unroll
    for (int i = 0; i < N; i++) asm volatile("" : "+f"(d[i])::"memory");
}
__device__ __forceinline__ uint64_t mkdesc(uint32_t addr, uint32_t lbo, uint32_t sbo, uint32_t swz) {
    uint64_t d = 0;
    d |= (uint64_t)((addr & 0x3FFFF) >> 4);
    d |= (uint64_t)((lbo & 0x3FFFF) >> 4) << 16;
    d |= (uint64_t)((sbo & 0x3FFFF) >> 4) << 32;
    d |= (uint64_t)swz << 62;
    return d;
}
__device__ __forceinline__ void ldsm_x4(uint32_t& r0, uint32_t& r1, uint32_t& r2, uint32_t& r3, uint32_t addr) {
    asm volatile("ldmatrix.sync.aligned.m8n8.x4.shared.b16 {%0,%1,%2,%3}, [%4];" : "=r"(r0), "=r"(r1), "=r"(r2), "=r"(r3) : "r"(addr) : "memory");
}
__device__ __forceinline__ void stsm_x4(uint32_t addr, uint32_t r0, uint32_t r1, uint32_t r2, uint32_t r3) {
    asm volatile("stmatrix.sync.aligned.m8n8.x4.shared.b16 [%0], {%1,%2,%3,%4};" ::"r"(addr), "r"(r0), "r"(r1), "r"(r2), "r"(r3) : "memory");
}
__device__ __forceinline__ uint32_t pack_bf16(float lo, float hi) {
    uint32_t r;
    asm("cvt.rn.bf16x2.f32 %0, %1, %2;" : "=r"(r) : "f"(hi), "f"(lo));
    return r;
}
__device__ __forceinline__ float bf_lo(uint32_t v) { return __uint_as_float(v << 16); }
__device__ __forceinline__ float bf_hi(uint32_t v) { return __uint_as_float(v & 0xFFFF0000u); }

#define WG_REGS_4(o) "+f"(d[o]), "+f"(d[o + 1]), "+f"(d[o + 2]), "+f"(d[o + 3])
#define WG_REGS_8(o) WG_REGS_4(o), WG_REGS_4(o + 4)
#define WG_REGS_16(o) WG_REGS_8(o), WG_REGS_8(o + 8)
#define WG_REGS_32(o) WG_REGS_16(o), WG_REGS_16(o + 16)

__device__ __forceinline__ void wgmma_ss_n80_tb(float (&d)[40], uint64_t dA, uint64_t dB, int sc) {
    asm volatile("{\n.reg .pred p;\nsetp.ne.b32 p, %42, 0;\n"
                 "wgmma.mma_async.sync.aligned.m64n80k16.f32.bf16.bf16 "
                 "{%0,%1,%2,%3,%4,%5,%6,%7,%8,%9,%10,%11,%12,%13,%14,%15,%16,%17,%18,%19,%20,%21,%22,%23,%24,%25,%26,%27,%28,%29,%30,%31,"
                 "%32,%33,%34,%35,%36,%37,%38,%39}, %40, %41, p, 1, 1, 0, 1;\n}\n"
                 : WG_REGS_32(0), WG_REGS_8(32) : "l"(dA), "l"(dB), "r"(sc));
}
__device__ __forceinline__ void wgmma_ss_n64_tb(float (&d)[32], uint64_t dA, uint64_t dB, int sc) {
    asm volatile("{\n.reg .pred p;\nsetp.ne.b32 p, %34, 0;\n"
                 "wgmma.mma_async.sync.aligned.m64n64k16.f32.bf16.bf16 "
                 "{%0,%1,%2,%3,%4,%5,%6,%7,%8,%9,%10,%11,%12,%13,%14,%15,%16,%17,%18,%19,%20,%21,%22,%23,%24,%25,%26,%27,%28,%29,%30,%31}, "
                 "%32, %33, p, 1, 1, 0, 1;\n}\n"
                 : WG_REGS_32(0) : "l"(dA), "l"(dB), "r"(sc));
}
__device__ __forceinline__ void wgmma_ss_n224_tb(float (&d)[112], uint64_t dA, uint64_t dB, int sc) {
    asm volatile("{\n.reg .pred p;\nsetp.ne.b32 p, %114, 0;\n"
                 "wgmma.mma_async.sync.aligned.m64n224k16.f32.bf16.bf16 "
                 "{%0,%1,%2,%3,%4,%5,%6,%7,%8,%9,%10,%11,%12,%13,%14,%15,%16,%17,%18,%19,%20,%21,%22,%23,%24,%25,%26,%27,%28,%29,%30,%31,"
                 "%32,%33,%34,%35,%36,%37,%38,%39,%40,%41,%42,%43,%44,%45,%46,%47,%48,%49,%50,%51,%52,%53,%54,%55,%56,%57,%58,%59,%60,%61,%62,%63,"
                 "%64,%65,%66,%67,%68,%69,%70,%71,%72,%73,%74,%75,%76,%77,%78,%79,%80,%81,%82,%83,%84,%85,%86,%87,%88,%89,%90,%91,%92,%93,%94,%95,"
                 "%96,%97,%98,%99,%100,%101,%102,%103,%104,%105,%106,%107,%108,%109,%110,%111}, "
                 "%112, %113, p, 1, 1, 0, 1;\n}\n"
                 : WG_REGS_32(0), WG_REGS_32(32), WG_REGS_32(64), WG_REGS_16(96) : "l"(dA), "l"(dB), "r"(sc));
}
template <int BN> __device__ __forceinline__ void wgmma_ss_tb(float (&d)[BN / 2], uint64_t dA, uint64_t dB, int sc) {
    if constexpr (BN == 64) wgmma_ss_n64_tb(d, dA, dB, sc);
    else if constexpr (BN == 80) wgmma_ss_n80_tb(d, dA, dB, sc);
    else wgmma_ss_n224_tb(d, dA, dB, sc);
}
__device__ __forceinline__ void wgmma_rs_n64_z(float (&d)[32], uint32_t a0, uint32_t a1, uint32_t a2, uint32_t a3, uint64_t dB) {
    asm volatile("{\n.reg .pred p;\nsetp.ne.b32 p, 0, 0;\n"
                 "wgmma.mma_async.sync.aligned.m64n64k16.f32.bf16.bf16 "
                 "{%0,%1,%2,%3,%4,%5,%6,%7,%8,%9,%10,%11,%12,%13,%14,%15,%16,%17,%18,%19,%20,%21,%22,%23,%24,%25,%26,%27,%28,%29,%30,%31}, "
                 "{%32,%33,%34,%35}, %36, p, 1, 1, 0;\n}\n"
                 : "=f"(d[0]), "=f"(d[1]), "=f"(d[2]), "=f"(d[3]), "=f"(d[4]), "=f"(d[5]), "=f"(d[6]), "=f"(d[7]),
                   "=f"(d[8]), "=f"(d[9]), "=f"(d[10]), "=f"(d[11]), "=f"(d[12]), "=f"(d[13]), "=f"(d[14]), "=f"(d[15]),
                   "=f"(d[16]), "=f"(d[17]), "=f"(d[18]), "=f"(d[19]), "=f"(d[20]), "=f"(d[21]), "=f"(d[22]), "=f"(d[23]),
                   "=f"(d[24]), "=f"(d[25]), "=f"(d[26]), "=f"(d[27]), "=f"(d[28]), "=f"(d[29]), "=f"(d[30]), "=f"(d[31])
                 : "r"(a0), "r"(a1), "r"(a2), "r"(a3), "l"(dB));
}
__device__ __forceinline__ void wgmma_rs_n24_tb(float (&d)[12], uint32_t a0, uint32_t a1, uint32_t a2, uint32_t a3, uint64_t dB) {
    asm volatile("{\n.reg .pred p;\nsetp.eq.b32 p, 0, 0;\n"
                 "wgmma.mma_async.sync.aligned.m64n24k16.f32.bf16.bf16 "
                 "{%0,%1,%2,%3,%4,%5,%6,%7,%8,%9,%10,%11}, {%12,%13,%14,%15}, %16, p, 1, 1, 1;\n}\n"
                 : WG_REGS_8(0), WG_REGS_4(8) : "r"(a0), "r"(a1), "r"(a2), "r"(a3), "l"(dB));
}

constexpr int SIDE_CTAS = 4;
__device__ __forceinline__ void side_job(int cta, float* red  , const __nv_bfloat16* __restrict__ wo,
                                         const __nv_bfloat16* __restrict__ w1, const __nv_bfloat16* __restrict__ w2) {
    const int tid = threadIdx.x, warp = tid >> 5, lane = tid & 31;
    for (int line = cta * 512 + tid; line < 18432; line += SIDE_CTAS * 512) {
        const char* p = line < 4096 ? (const char*)wo + (size_t)line * 128 : (const char*)w2 + (size_t)(line - 4096) * 128;
        asm volatile("prefetch.global.L2 [%0];" ::"l"(p));
    }
    const int rg = lane >> 3, c8 = lane & 7;
    for (int slab = cta; slab < F_ / 64; slab += SIDE_CTAS) {
        const __nv_bfloat16* base = w1 + slab * 64 + c8 * 8;
        uint4 v[8];
#pragma unroll
        for (int i = 0; i < 8; i++) v[i] = __ldg((const uint4*)(base + (size_t)(warp * 32 + rg + 4 * i) * F_));
        float acc[8];
#pragma unroll
        for (int i = 0; i < 8; i++) acc[i] = 0.f;
#pragma unroll
        for (int i = 0; i < 8; i++) {
            acc[0] += bf_lo(v[i].x); acc[1] += bf_hi(v[i].x); acc[2] += bf_lo(v[i].y); acc[3] += bf_hi(v[i].y);
            acc[4] += bf_lo(v[i].z); acc[5] += bf_hi(v[i].z); acc[6] += bf_lo(v[i].w); acc[7] += bf_hi(v[i].w);
        }
#pragma unroll
        for (int i = 0; i < 8; i++) {
            acc[i] += __shfl_xor_sync(0xffffffffu, acc[i], 8);
            acc[i] += __shfl_xor_sync(0xffffffffu, acc[i], 16);
        }
        if (rg == 0) {
#pragma unroll
            for (int i = 0; i < 8; i++) red[warp * 64 + c8 * 8 + i] = acc[i];
        }
        __syncthreads();
        if (tid < 64) {
            float s = 0.f;
#pragma unroll
            for (int i = 0; i < 16; i++) s += red[i * 64 + tid];
            g_cs_1[slab * 64 + tid] = s;
        }
        __syncthreads();
    }
}

enum { EPI_QKV = 0, EPI_RES = 1, EPI_FFN1 = 2 };

struct GemmParams {
    const float2* stats_in;
    float2* stats_out;
    int tk;
};

template <int BK_, int NBLK> struct Geo {
    static constexpr int BK = BK_, A_BYTES = 128 * BK * 2, A_SWZ = BK == 64 ? 1 : 2, A_SBO = BK * 16;
    static constexpr int BLK = BK * 64;
    static constexpr int B_BYTES = NBLK * BLK, B_SWZ = 2, B_LBO = BLK, B_SBO = 512, B_KSTEP = 1024;
};
template <> struct Geo<64, 0> {
    static constexpr int BK = 64, A_BYTES = 128 * 128, A_SWZ = 1, A_SBO = 1024, BLK = 8192;
    static constexpr int B_BYTES = 64 * 128, B_SWZ = 1, B_LBO = 8192, B_SBO = 1024, B_KSTEP = 2048;
};
#define F1_BK 32
template <int EPI> struct EpiGeo;
template <> struct EpiGeo<EPI_QKV> { using G = Geo<64, 3>; };
template <> struct EpiGeo<EPI_RES> { using G = Geo<64, 0>; };
template <> struct EpiGeo<EPI_FFN1> { using G = Geo<F1_BK, 7>; };

template <int STAGES, int EPI> struct GemmSmem {
    using G = typename EpiGeo<EPI>::G;
    static constexpr int STAGE = G::A_BYTES + G::B_BYTES;
    static constexpr int AUX_OFF = STAGES * STAGE;
    static constexpr int TOTAL = AUX_OFF + 1152;
};

struct RowStatRaw { float2 a0, a1, b0, b1; };
__device__ __forceinline__ RowStatRaw load_row_stats(const float2* __restrict__ st, int row0, int c) {
    RowStatRaw r;
    r.a0 = st[(2 * c) * S_ + row0]; r.a1 = st[(2 * c + 1) * S_ + row0];
    r.b0 = st[(2 * c) * S_ + row0 + 8]; r.b1 = st[(2 * c + 1) * S_ + row0 + 8];
    return r;
}
__device__ __forceinline__ void finish_row_stats(const RowStatRaw& r, float& mean0, float& rstd0, float& mean1, float& rstd1) {
    float sa = r.a0.x + r.a1.x, sb = r.b0.x + r.b1.x;
    sa += __shfl_xor_sync(0xffffffffu, sa, 1); sa += __shfl_xor_sync(0xffffffffu, sa, 2);
    sb += __shfl_xor_sync(0xffffffffu, sb, 1); sb += __shfl_xor_sync(0xffffffffu, sb, 2);
    mean0 = sa * 0.125f; mean1 = sb * 0.125f;
    float ma = r.a0.y + r.a1.y + 64.f * ((r.a0.x - mean0) * (r.a0.x - mean0) + (r.a1.x - mean0) * (r.a1.x - mean0));
    float mb = r.b0.y + r.b1.y + 64.f * ((r.b0.x - mean1) * (r.b0.x - mean1) + (r.b1.x - mean1) * (r.b1.x - mean1));
    ma += __shfl_xor_sync(0xffffffffu, ma, 1); ma += __shfl_xor_sync(0xffffffffu, ma, 2);
    mb += __shfl_xor_sync(0xffffffffu, mb, 1); mb += __shfl_xor_sync(0xffffffffu, mb, 2);
    rstd0 = 1.0f / sqrtf(ma * (1.f / 512.f) + 1e-5f);
    rstd1 = 1.0f / sqrtf(mb * (1.f / 512.f) + 1e-5f);
}

template <int BN, int KB, int STAGES, int EPI, int MC, bool SELF = false>
__device__ __forceinline__ void gemm_body(const CUtensorMap* mapA, const CUtensorMap* mapB, const CUtensorMap* mapB2, const CUtensorMap* mapR,
                                          const CUtensorMap* mapC, const GemmParams& prm, int tile_m, int tile_n, uint8_t* smem_raw) {
    using SM = GemmSmem<STAGES, EPI>;
    using G = typename SM::G;
    constexpr bool XKV = BN == 80;
    constexpr int TN = EPI == EPI_QKV ? 64 : BN;
    pdl_launch();
    const uint32_t sbase = smem_u32(smem_raw);
    if (sbase & 1023) __trap();
    uint8_t* sgen = smem_raw;
    const uint32_t bar_full = sbase + SM::AUX_OFF, bar_empty = bar_full + 8 * STAGES;
    float* s_cs = (float*)(sgen + SM::AUX_OFF + 256);
    float* s_red = (float*)(sgen + SM::AUX_OFF + 768);
    const int tid = threadIdx.x, lane = tid & 31;
    const int warp = __shfl_sync(0xffffffffu, tid >> 5, 0);
    const uint32_t rank = MC ? cluster_rank() : 0;
    if (tid == 0) TL(prm.tk, 0);

    constexpr bool INLINE_PROD = EPI == EPI_FFN1 && F1_INLINE;
    constexpr int PWARP = INLINE_PROD ? 0 : 8;
    if (warp == PWARP && elect_one()) {
        prefetch_tmap(mapB); prefetch_tmap(mapA); prefetch_tmap(mapC);
        for (int s = 0; s < STAGES; s++) { mbar_init(bar_full + 8 * s, 1); mbar_init(bar_empty + 8 * s, MC ? 4 : 2); }
        fence_mbar_init();
    }
    __syncthreads();
    if (MC) cluster_sync();

    const int m0 = tile_m * 128, n0 = tile_n * TN;
    constexpr uint32_t STAGE_TX = G::A_BYTES + (EPI == EPI_QKV ? (XKV ? 3 : 2) * G::BLK : G::B_BYTES);
    auto loadB = [&](int kb, int s) {
        const uint32_t dst = sbase + s * SM::STAGE + G::A_BYTES, bar = bar_full + 8 * s;
        if constexpr (EPI == EPI_RES) {
            tma2d(dst, mapB, n0, kb * 64, bar);
        } else if constexpr (EPI == EPI_QKV) {
            tma3d(dst, mapB, 0, kb * G::BK, tile_n * 2, bar);
            if constexpr (XKV) tma2d(dst + 2 * G::BLK, mapB2, 0, kb * G::BK, bar);
        } else {
            if constexpr (MC == 2) {
                if (rank == 0) tma3d_mc(dst, mapB, 0, kb * G::BK, tile_n * 7, bar, 3);
                else tma3d_mc(dst + 4 * G::BLK, mapB2, 0, kb * G::BK, tile_n * 7 + 4, bar, 3);
            } else {
                tma3d(dst, mapB, 0, kb * G::BK, tile_n * 7, bar);
                tma3d(dst + 4 * G::BLK, mapB2, 0, kb * G::BK, tile_n * 7 + 4, bar);
            }
        }
    };
    auto loadA = [&](int kb, int s) {
        const uint32_t dst = sbase + s * SM::STAGE, bar = bar_full + 8 * s;
        if constexpr (MC == 1) tma2d_mc(dst + rank * (G::A_BYTES / 2), mapA, kb * G::BK, m0 + rank * 64, bar, 3);
        else tma2d(dst, mapA, kb * G::BK, m0, bar);
    };
    constexpr int PRE = STAGES < KB ? STAGES : KB;
#define F1_LAG 2
    constexpr int LAG = F1_LAG;
    constexpr int PRE_B = PRE < PREB ? PRE : PREB;
    auto prologue_loads = [&]() {
        if (elect_one()) {
#pragma unroll
            for (int kb = 0; kb < PRE; kb++) mbar_expect_tx(bar_full + 8 * kb, STAGE_TX);
#pragma unroll
            for (int kb = 0; kb < PRE_B; kb++) loadB(kb, kb);
        }
        if (!SELF) pdl_wait();
        if (elect_one()) {
#pragma unroll
            for (int kb = 0; kb < PRE; kb++) {
                loadA(kb, kb);
                if (kb + PRE_B < PRE) loadB(kb + PRE_B, kb + PRE_B);
            }
            if constexpr (EPI == EPI_RES && KB < STAGES) {
                mbar_expect_tx(bar_full + 8 * KB, 16384);
                tma2d(sbase + KB * SM::STAGE, mapR, n0, m0, bar_full + 8 * KB);
            }
        }
    };
    if (!INLINE_PROD && warp == 8) {
        prologue_loads();
        int s = PRE % STAGES, ph = (PRE / STAGES) & 1;
#pragma unroll 1
        for (int kb = PRE; kb < KB; kb++) {
            mbar_wait(bar_empty + 8 * s, ph ^ 1);
            if (elect_one()) {
                mbar_expect_tx(bar_full + 8 * s, STAGE_TX);
                loadB(kb, s);
                loadA(kb, s);
            }
            if (++s == STAGES) { s = 0; ph ^= 1; }
        }
        if constexpr (EPI == EPI_RES && KB >= STAGES) {
            mbar_wait(bar_empty + 8 * s, ph ^ 1);
            if (elect_one()) {
                mbar_expect_tx(bar_full + 8 * s, 16384);
                tma2d(sbase + s * SM::STAGE, mapR, n0, m0, bar_full + 8 * s);
            }
        }
    } else {
        if (INLINE_PROD && warp == 0) prologue_loads();
        const int wg = warp >> 2, g = lane >> 2, c = lane & 3;
        const int rloc = wg * 64 + (warp & 3) * 16 + g;
        const int row0 = m0 + rloc;
        float mean0 = 0.f, rstd0 = 1.f, mean1 = 0.f, rstd1 = 1.f;
        RowStatRaw raw;
        float csv = 0.f;
        float2 cskv[2] = {make_float2(0.f, 0.f), make_float2(0.f, 0.f)};
        auto ln_inputs = [&]() {
            pdl_wait();
            if constexpr (EPI != EPI_RES) {
                raw = load_row_stats(prm.stats_in, row0, c);
                const float* cs = EPI == EPI_FFN1 ? g_cs_1 + n0 : g_cs_q + n0;
                if (tid < TN) csv = cs[tid];
                if constexpr (XKV) {
                    cskv[0] = *(const float2*)(g_cs_kv + tile_n * 16 + 2 * c);
                    cskv[1] = *(const float2*)(g_cs_kv + tile_n * 16 + 8 + 2 * c);
                }
            }
        };
        if (!SELF) ln_inputs();
        float st_p = 0.f, st_s = 0.f, st_q = 0.f, cs_acc[8], cs_x[8];
#pragma unroll
        for (int i = 0; i < 8; i++) { cs_acc[i] = 0.f; cs_x[i] = 0.f; }
        float acc[BN / 2];
        const uint64_t dA0 = mkdesc(sbase + wg * (G::A_BYTES / 2), 16, G::A_SBO, G::A_SWZ);
        const uint64_t dB0 = mkdesc(sbase + G::A_BYTES, G::B_LBO, G::B_SBO, G::B_SWZ);
        int s = 0, ph = 0;
#pragma unroll 1
        for (int kb = 0; kb < KB; kb++) {
            mbar_wait(bar_full + 8 * s, ph);
            const uint64_t dA = dA0 + (uint64_t)(s * (SM::STAGE >> 4)), dB = dB0 + (uint64_t)(s * (SM::STAGE >> 4));
            wg_fence();
#pragma unroll
            for (int k = 0; k < G::BK / 16; k++) wgmma_ss_tb<BN>(acc, dA + (uint64_t)(k * 2), dB + (uint64_t)(k * (G::B_KSTEP >> 4)), (kb | k) != 0);
            wg_commit();
            if constexpr (SELF) {
                static_assert(!SELF || (STAGES >= KB && EPI == EPI_QKV), "SELF needs every k block resident");
                const uint32_t arow = sbase + s * SM::STAGE + (tid >> 1) * 128;
                if (kb == 0) {
                    uint32_t w; asm volatile("ld.shared.u32 %0, [%1];" : "=r"(w) : "r"(arow));
                    st_p = bf_lo(w);
                }
#pragma unroll
                for (int j = 0; j < 4; j++) {
                    uint32_t w0, w1_, w2_, w3;
                    asm volatile("ld.shared.v4.u32 {%0,%1,%2,%3}, [%4];" : "=r"(w0), "=r"(w1_), "=r"(w2_), "=r"(w3)
                                 : "r"(arow + (((2 * j + (tid & 1) + 2 * ((tid >> 1) & 3)) & 7) << 4)));
                    const float v[8] = {bf_lo(w0) - st_p, bf_hi(w0) - st_p, bf_lo(w1_) - st_p, bf_hi(w1_) - st_p,
                                        bf_lo(w2_) - st_p, bf_hi(w2_) - st_p, bf_lo(w3) - st_p, bf_hi(w3) - st_p};
#pragma unroll
                    for (int i = 0; i < 8; i++) { st_s += v[i]; st_q = fmaf(v[i], v[i], st_q); }
                }
                const uint32_t bblk = sbase + s * SM::STAGE + G::A_BYTES;
#pragma unroll
                for (int r = 0; r < 2; r++) {
                    const int krow = (tid >> 3) * 2 + r, ch = tid & 7;
                    uint32_t w0, w1_, w2_, w3;
                    asm volatile("ld.shared.v4.u32 {%0,%1,%2,%3}, [%4];" : "=r"(w0), "=r"(w1_), "=r"(w2_), "=r"(w3)
                                 : "r"(bblk + (ch >> 2) * G::BLK + krow * 64 + (((ch & 3) ^ ((krow >> 1) & 3)) << 4)));
                    cs_acc[0] += bf_lo(w0); cs_acc[1] += bf_hi(w0); cs_acc[2] += bf_lo(w1_); cs_acc[3] += bf_hi(w1_);
                    cs_acc[4] += bf_lo(w2_); cs_acc[5] += bf_hi(w2_); cs_acc[6] += bf_lo(w3); cs_acc[7] += bf_hi(w3);
                }
                if constexpr (XKV) {
                    if (tid < 128) {
                        const int krow = tid >> 1, ch = tid & 1;
                        uint32_t w0, w1_, w2_, w3;
                        asm volatile("ld.shared.v4.u32 {%0,%1,%2,%3}, [%4];" : "=r"(w0), "=r"(w1_), "=r"(w2_), "=r"(w3)
                                     : "r"(bblk + 2 * G::BLK + krow * 64 + ((ch ^ ((krow >> 1) & 3)) << 4)));
                        cs_x[0] += bf_lo(w0); cs_x[1] += bf_hi(w0); cs_x[2] += bf_lo(w1_); cs_x[3] += bf_hi(w1_);
                        cs_x[4] += bf_lo(w2_); cs_x[5] += bf_hi(w2_); cs_x[6] += bf_lo(w3); cs_x[7] += bf_hi(w3);
                    }
                }
            }
            if constexpr (EPI == EPI_RES && RES_WAIT0) {
                wg_wait<0>();
                if ((warp & 3) == 0 && elect_one()) {
                    if (MC) { mbar_arrive_remote(bar_empty + 8 * s, 0); mbar_arrive_remote(bar_empty + 8 * s, 1); }
                    else mbar_arrive(bar_empty + 8 * s);
                }
            } else if (kb > 0) {
                wg_wait<1>();
                const int sp = s == 0 ? STAGES - 1 : s - 1;
                if ((warp & 3) == 0 && elect_one()) {
                    if (MC) { mbar_arrive_remote(bar_empty + 8 * sp, 0); mbar_arrive_remote(bar_empty + 8 * sp, 1); }
                    else mbar_arrive(bar_empty + 8 * sp);
                }
                if (INLINE_PROD && warp == 0 && kb >= LAG && kb - LAG + STAGES < KB) {
                    const int sq = LAG == 1 ? sp : (sp == 0 ? STAGES - 1 : sp - 1);
                    mbar_wait(bar_empty + 8 * sq, ((kb - LAG) / STAGES) & 1);
                    if (elect_one()) {
                        mbar_expect_tx(bar_full + 8 * sq, STAGE_TX);
                        loadB(kb - LAG + STAGES, sq);
                        loadA(kb - LAG + STAGES, sq);
                    }
                }
            }
            if (++s == STAGES) { s = 0; ph ^= 1; }
        }
        if constexpr (SELF) {
            wg_wait<0>();
            named_bar(1, 256);
            float* sc = (float*)(sgen + (STAGES - 1) * SM::STAGE + G::A_BYTES);
            float ss = st_s + __shfl_xor_sync(0xffffffffu, st_s, 1), qq = st_q + __shfl_xor_sync(0xffffffffu, st_q, 1);
            const float piv = __shfl_sync(0xffffffffu, st_p, lane & ~1);
            if ((tid & 1) == 0) {
                const float md = ss * (1.f / 512.f);
                const float var = fmaxf(qq * (1.f / 512.f) - md * md, 0.f);
                sc[tid] = piv + md;
                sc[tid + 1] = 1.0f / sqrtf(var + 1e-5f);
            }
#pragma unroll
            for (int i = 0; i < 8; i++) {
                cs_acc[i] += __shfl_xor_sync(0xffffffffu, cs_acc[i], 8);
                cs_acc[i] += __shfl_xor_sync(0xffffffffu, cs_acc[i], 16);
                if constexpr (XKV) {
                    cs_x[i] += __shfl_xor_sync(0xffffffffu, cs_x[i], 2); cs_x[i] += __shfl_xor_sync(0xffffffffu, cs_x[i], 4);
                    cs_x[i] += __shfl_xor_sync(0xffffffffu, cs_x[i], 8); cs_x[i] += __shfl_xor_sync(0xffffffffu, cs_x[i], 16);
                }
            }
            if (lane < 8) {
#pragma unroll
                for (int i = 0; i < 8; i++) sc[256 + warp * 64 + lane * 8 + i] = cs_acc[i];
            }
            if (XKV && lane < 2 && warp < 4) {
#pragma unroll
                for (int i = 0; i < 8; i++) sc[768 + warp * 16 + lane * 8 + i] = cs_x[i];
            }
            named_bar(1, 256);
            mean0 = sc[2 * rloc]; rstd0 = sc[2 * rloc + 1]; mean1 = sc[2 * rloc + 16]; rstd1 = sc[2 * rloc + 17];
            if (tid < 64) {
                float t = 0.f;
#pragma unroll
                for (int w = 0; w < 8; w++) t += sc[256 + w * 64 + tid];
                s_cs[tid] = t;
                if (tile_m == 0) g_cs_q[n0 + tid] = t;
            }
            if constexpr (XKV) {
#pragma unroll
                for (int j = 0; j < 2; j++) {
                    float tx = 0.f, ty = 0.f;
#pragma unroll
                    for (int w = 0; w < 4; w++) { tx += sc[768 + w * 16 + 8 * j + 2 * c]; ty += sc[768 + w * 16 + 8 * j + 2 * c + 1]; }
                    cskv[j] = make_float2(tx, ty);
                }
                if (tile_m == 0 && warp == 0 && g == 0) {
                    *(float2*)(g_cs_kv + tile_n * 16 + 2 * c) = cskv[0];
                    *(float2*)(g_cs_kv + tile_n * 16 + 8 + 2 * c) = cskv[1];
                }
            }
        } else if constexpr (EPI != EPI_RES) {
            finish_row_stats(raw, mean0, rstd0, mean1, rstd1);
            if (tid < TN) s_cs[tid] = csv;
        }
        wg_wait<0>();
        fence_regs(acc);
        if (tid == 0) TL(prm.tk, 2);
        if constexpr (EPI != EPI_RES) named_bar(1, 256);

        if constexpr (EPI != EPI_FFN1) {
            const uint32_t stile = sbase + (EPI == EPI_RES ? s * SM::STAGE : 0);
            const int mrow = wg * 64 + (warp & 3) * 16 + (lane & 7) + ((lane >> 3) & 1) * 8;
            const uint32_t rbase = stile + mrow * 128;
            if constexpr (EPI == EPI_RES) {
                mbar_wait(bar_full + 8 * s, ph);
                float s0 = 0.f, s1 = 0.f;
#pragma unroll
                for (int jj = 0; jj < 4; jj++) {
                    uint32_t r0, r1, r2, r3;
                    const uint32_t addr = rbase + (((2 * jj + (lane >> 4)) ^ (mrow & 7)) << 4);
                    ldsm_x4(r0, r1, r2, r3, addr);
                    const uint32_t u0 = pack_bf16(acc[8 * jj] + bf_lo(r0), acc[8 * jj + 1] + bf_hi(r0));
                    const uint32_t u1 = pack_bf16(acc[8 * jj + 2] + bf_lo(r1), acc[8 * jj + 3] + bf_hi(r1));
                    const uint32_t u2 = pack_bf16(acc[8 * jj + 4] + bf_lo(r2), acc[8 * jj + 5] + bf_hi(r2));
                    const uint32_t u3 = pack_bf16(acc[8 * jj + 6] + bf_lo(r3), acc[8 * jj + 7] + bf_hi(r3));
                    stsm_x4(addr, u0, u1, u2, u3);
                    acc[8 * jj] = bf_lo(u0); acc[8 * jj + 1] = bf_hi(u0); acc[8 * jj + 4] = bf_lo(u2); acc[8 * jj + 5] = bf_hi(u2);
                    acc[8 * jj + 2] = bf_lo(u1); acc[8 * jj + 3] = bf_hi(u1); acc[8 * jj + 6] = bf_lo(u3); acc[8 * jj + 7] = bf_hi(u3);
                    s0 += (acc[8 * jj] + acc[8 * jj + 1]) + (acc[8 * jj + 4] + acc[8 * jj + 5]);
                    s1 += (acc[8 * jj + 2] + acc[8 * jj + 3]) + (acc[8 * jj + 6] + acc[8 * jj + 7]);
                }
                fence_async_smem();
                named_bar(2 + wg, 128);
                if ((warp & 3) == 0 && elect_one()) { tma2d_store(mapC, stile + wg * 8192, n0, m0 + wg * 64); bulk_commit(); }
                if (prm.stats_out) {
                    s0 += __shfl_xor_sync(0xffffffffu, s0, 1); s0 += __shfl_xor_sync(0xffffffffu, s0, 2);
                    s1 += __shfl_xor_sync(0xffffffffu, s1, 1); s1 += __shfl_xor_sync(0xffffffffu, s1, 2);
                    const float mu0 = s0 * (1.f / 64.f), mu1 = s1 * (1.f / 64.f);
                    float q0 = 0.f, q1 = 0.f;
#pragma unroll
                    for (int j = 0; j < 8; j++) {
                        float d;
                        d = acc[4 * j] - mu0; q0 += d * d; d = acc[4 * j + 1] - mu0; q0 += d * d;
                        d = acc[4 * j + 2] - mu1; q1 += d * d; d = acc[4 * j + 3] - mu1; q1 += d * d;
                    }
                    q0 += __shfl_xor_sync(0xffffffffu, q0, 1); q0 += __shfl_xor_sync(0xffffffffu, q0, 2);
                    q1 += __shfl_xor_sync(0xffffffffu, q1, 1); q1 += __shfl_xor_sync(0xffffffffu, q1, 2);
                    if (c == 0) {
                        prm.stats_out[tile_n * S_ + row0] = make_float2(mu0, q0);
                        prm.stats_out[tile_n * S_ + row0 + 8] = make_float2(mu1, q1);
                    }
                }
            } else {
                const float sc = 0.25f * 1.4426950408889634f;
                const float a0 = rstd0 * sc, a1 = rstd1 * sc, rm0 = a0 * mean0, rm1 = a1 * mean1;
#pragma unroll
                for (int jj = 0; jj < 4; jj++) {
                    const float2 ca = *(const float2*)(s_cs + 16 * jj + 2 * c), cb = *(const float2*)(s_cs + 16 * jj + 8 + 2 * c);
                    const uint32_t u0 = pack_bf16(acc[8 * jj] * a0 - rm0 * ca.x, acc[8 * jj + 1] * a0 - rm0 * ca.y);
                    const uint32_t u1 = pack_bf16(acc[8 * jj + 2] * a1 - rm1 * ca.x, acc[8 * jj + 3] * a1 - rm1 * ca.y);
                    const uint32_t u2 = pack_bf16(acc[8 * jj + 4] * a0 - rm0 * cb.x, acc[8 * jj + 5] * a0 - rm0 * cb.y);
                    const uint32_t u3 = pack_bf16(acc[8 * jj + 6] * a1 - rm1 * cb.x, acc[8 * jj + 7] * a1 - rm1 * cb.y);
                    stsm_x4(rbase + (((2 * jj + (lane >> 4)) ^ (mrow & 7)) << 4), u0, u1, u2, u3);
                }
                fence_async_smem();
                named_bar(2 + wg, 128);
                if ((warp & 3) == 0 && elect_one()) { tma2d_store(mapC, stile + wg * 8192, n0, m0 + wg * 64); bulk_commit(); }
            }
            if constexpr (XKV) {
                {
                    const float* acx = &acc[32];
                    const float rm0 = rstd0 * mean0, rm1 = rstd1 * mean1;
                    float n0s = 0.f, n1s = 0.f, vmax = 0.f;
#pragma unroll
                    for (int j = 0; j < 2; j++) {
                        const float2 cs2 = cskv[j];
                        const uint32_t u0 = pack_bf16(acx[4 * j] * rstd0 - rm0 * cs2.x, acx[4 * j + 1] * rstd0 - rm0 * cs2.y);
                        const uint32_t u1 = pack_bf16(acx[4 * j + 2] * rstd1 - rm1 * cs2.x, acx[4 * j + 3] * rstd1 - rm1 * cs2.y);
                        n0s += bf_lo(u0) * bf_lo(u0) + bf_hi(u0) * bf_hi(u0);
                        n1s += bf_lo(u1) * bf_lo(u1) + bf_hi(u1) * bf_hi(u1);
                        vmax = fmaxf(vmax, fmaxf(fmaxf(fabsf(bf_lo(u0)), fabsf(bf_hi(u0))), fmaxf(fabsf(bf_lo(u1)), fabsf(bf_hi(u1)))));
                        if (tile_n == 0) {
                            *(uint32_t*)(g_kimg + (row0 >> 3) * 256 + j * 128 + g * 16 + c * 4) = u0;
                            *(uint32_t*)(g_kimg + ((row0 + 8) >> 3) * 256 + j * 128 + g * 16 + c * 4) = u1;
                        } else {
                            uint8_t* vb = g_vimg + (row0 >> 4) * 768 + j * 256 + g * 16 + c * 4;
                            *(uint32_t*)(vb) = u0;
                            *(uint32_t*)(vb + 128) = u1;
                        }
                    }
                    if (tile_n == 1) {
                        uint8_t* vb = g_vimg + (row0 >> 4) * 768 + 512 + g * 16 + c * 4;
                        const uint32_t one = c == 0 ? 0x00003F80u : 0u;
                        *(uint32_t*)(vb) = one;
                        *(uint32_t*)(vb + 128) = one;
                    }
                    n0s += __shfl_xor_sync(0xffffffffu, n0s, 1); n0s += __shfl_xor_sync(0xffffffffu, n0s, 2);
                    n1s += __shfl_xor_sync(0xffffffffu, n1s, 1); n1s += __shfl_xor_sync(0xffffffffu, n1s, 2);
                    float km = tile_n == 0 ? fmaxf(n0s, n1s) : vmax;
                    if (!(n0s + n1s < INFINITY)) km = INFINITY;
#pragma unroll
                    for (int o = 1; o < 32; o <<= 1) km = fmaxf(km, __shfl_xor_sync(0xffffffffu, km, o));
                    if (lane == 0) s_red[warp] = km;
                    named_bar(1, 256);
                    if (tid == 0) {
                        float a = 0.f;
                        for (int i = 0; i < 8; i++) a = fmaxf(a, s_red[i]);
                        g_kvmax[tile_n * 16 + tile_m] = a;
                    }
                }
            }
            if ((warp & 3) == 0) bulk_wait_read();
        } else {
            const uint32_t stile = sbase + wg * (7 * 4096);
            const int mrow = (warp & 3) * 16 + (lane & 7) + ((lane >> 3) & 1) * 8;
            const float a0 = 0.5f * rstd0, a1 = 0.5f * rstd1, rm0 = a0 * mean0, rm1 = a1 * mean1;
#pragma unroll
            for (int jj = 0; jj < 14; jj++) {
                const float2 ca = *(const float2*)(s_cs + 16 * jj + 2 * c), cb = *(const float2*)(s_cs + 16 * jj + 8 + 2 * c);
                float y[8] = {acc[8 * jj] * a0 - rm0 * ca.x,     acc[8 * jj + 1] * a0 - rm0 * ca.y,
                              acc[8 * jj + 2] * a1 - rm1 * ca.x, acc[8 * jj + 3] * a1 - rm1 * ca.y,
                              acc[8 * jj + 4] * a0 - rm0 * cb.x, acc[8 * jj + 5] * a0 - rm0 * cb.y,
                              acc[8 * jj + 6] * a1 - rm1 * cb.x, acc[8 * jj + 7] * a1 - rm1 * cb.y};
#pragma unroll
                for (int i = 0; i < 8; i++) {
                    float t;
                    asm("tanh.approx.f32 %0, %1;" : "=f"(t) : "f"(y[i]));
                    y[i] = fmaf(y[i], t, y[i]);
                }
                const int chunk = (2 * jj + (lane >> 4)) & 3, blk = jj >> 1;
                stsm_x4(stile + blk * 4096 + mrow * 64 + ((chunk ^ ((mrow >> 1) & 3)) << 4),
                        pack_bf16(y[0], y[1]), pack_bf16(y[2], y[3]), pack_bf16(y[4], y[5]), pack_bf16(y[6], y[7]));
                if (jj & 1) {
                    fence_async_smem();
                    __syncwarp();
                    if (elect_one()) {
                        tma2d_store(mapC, stile + blk * 4096 + (warp & 3) * 1024, n0 + blk * 32, m0 + wg * 64 + (warp & 3) * 16);
                        bulk_commit();
                    }
                }
            }
            bulk_wait_read();
        }
    }
    if (tid == 0) TL(prm.tk, 3);
    if (MC) cluster_sync();
}

#define WO_ST 9
#define F2_ST 6
#define F1_ST (F1_BK == 64 ? 5 : 9)
#define QKV_ST 8
constexpr int QKV_STAGES = QKV_ST, WO_STAGES = WO_ST, FFN2_STAGES = F2_ST, FFN1_STAGES = F1_ST;
template <bool SELF>
__global__ void __launch_bounds__(288) qkv_kernel(const __grid_constant__ CUtensorMap mapA, const __grid_constant__ CUtensorMap mapWq,
                                                  const __grid_constant__ CUtensorMap mapWk, const __grid_constant__ CUtensorMap mapWv,
                                                  const __grid_constant__ CUtensorMap mapQ, const GemmParams prm) {
    extern __shared__ __align__(1024) uint8_t smem_raw[];
    const int tn = blockIdx.x & 7;
    if (tn < 2) gemm_body<80, 8, QKV_STAGES, EPI_QKV, QKV_MC, SELF>(&mapA, &mapWq, tn == 0 ? &mapWk : &mapWv, &mapA, &mapQ, prm, blockIdx.x >> 3, tn, smem_raw);
    else gemm_body<64, 8, QKV_STAGES, EPI_QKV, QKV_MC, SELF>(&mapA, &mapWq, &mapWq, &mapA, &mapQ, prm, blockIdx.x >> 3, tn, smem_raw);
}
template <int KB, int STAGES>
__global__ void __launch_bounds__(288) res_gemm_kernel(const __grid_constant__ CUtensorMap mapA, const __grid_constant__ CUtensorMap mapW,
                                                       const __grid_constant__ CUtensorMap mapR, const __grid_constant__ CUtensorMap mapC, const GemmParams prm) {
    extern __shared__ __align__(1024) uint8_t smem_raw[];
    gemm_body<64, KB, STAGES, EPI_RES, (KB == 8 ? WO_MC : F2_MC)>(&mapA, &mapW, &mapW, &mapR, &mapC, prm, blockIdx.x >> 3, blockIdx.x & 7, smem_raw);
}
__global__ void __launch_bounds__(F1_INLINE ? 256 : 288) ffn1_kernel(const __grid_constant__ CUtensorMap mapA, const __grid_constant__ CUtensorMap mapW4,
                                                   const __grid_constant__ CUtensorMap mapW3, const __grid_constant__ CUtensorMap mapH, const GemmParams prm) {
    extern __shared__ __align__(1024) uint8_t smem_raw[];
    const int pair = blockIdx.x >> 1, tile_n = pair & 7, tile_m = (pair >> 3) * 2 + (blockIdx.x & 1);
    gemm_body<224, 512 / F1_BK, FFN1_STAGES, EPI_FFN1, F1_MC>(&mapA, &mapW4, &mapW3, &mapA, &mapH, prm, tile_m, tile_n, smem_raw);
}

constexpr int NPOLY = 10;
__host__ __device__ constexpr bool is_mufu(int i) { return ((i + 1) * (16 - NPOLY)) / 16 != (i * (16 - NPOLY)) / 16; }

__device__ __forceinline__ float ex2(float x) { float r; asm("ex2.approx.ftz.f32 %0, %1;" : "=f"(r) : "f"(x)); return r; }
__device__ __forceinline__ uint32_t exp_pair_mufu(float a, float b) { return pack_bf16(ex2(a), ex2(b)); }
__device__ __forceinline__ uint32_t exp_pair_fma(float a, float b, uint32_t c3f) {
    constexpr float MAGIC = 98430.4140625f;
    const float ta = a + MAGIC, tb = b + (MAGIC - 143.5f);
    uint32_t y, m, r;
    asm("mad.lo.u32 %0, %1, 65536, %2;" : "=r"(y) : "r"(__float_as_uint(tb)), "r"(__float_as_uint(ta)));
    asm("lop3.b32 %0, %1, 0x007F007F, %2, 0xEA;" : "=r"(m) : "r"(y), "r"(c3f));
    const uint32_t e = y & 0xFF80FF80u;
    asm("fma.rn.bf16x2 %0, %1, %2, %3;" : "=r"(r) : "r"(y), "r"(m), "r"(e));
    return r;
}

constexpr int KCH = 256, NCH = S_ / KCH;
constexpr int K_BYTES = S_ * 32, V_BYTES = (S_ / 16) * 768;
constexpr int ATT_SMEM = K_BYTES + V_BYTES;

__global__ void __launch_bounds__(512, 1) attn_kernel(const __nv_bfloat16* __restrict__ wo, const __nv_bfloat16* __restrict__ w1,
                                                       const __nv_bfloat16* __restrict__ w2, int tk) {
    extern __shared__ __align__(1024) uint8_t smem[];
    __shared__ uint64_t bars[NCH];
    __shared__ int s_slow;
    const int tid = threadIdx.x, wg = tid >> 7, warp = (tid >> 5) & 3, lane = tid & 31;
    const uint32_t sK = smem_u32(smem), sV = sK + K_BYTES;
    if (blockIdx.x >= 128) {
        pdl_launch();
        side_job(blockIdx.x - 128, (float*)smem, wo, w1, w2);
        return;
    }
    if (tid == 0) TL(tk, 0);
    if (tid == 0) {
        for (int i = 0; i < NCH; i++) mbar_init(smem_u32(&bars[i]), 1);
        s_slow = 0;
        fence_mbar_init();
    }
    __syncthreads();
    pdl_launch();
    pdl_wait();
    if (tid == 0) TL(tk, 1);
    if (__shfl_sync(0xffffffffu, tid >> 5, 0) == 0 && elect_one()) {
#pragma unroll
        for (int i = 0; i < NCH; i++) {
            mbar_expect_tx(smem_u32(&bars[i]), KCH * 32 + (KCH / 16) * 768);
            bulk_load(sK + i * KCH * 32, g_kimg + i * KCH * 32, KCH * 32, smem_u32(&bars[i]));
            bulk_load(sV + i * (KCH / 16) * 768, g_vimg + i * (KCH / 16) * 768, (KCH / 16) * 768, smem_u32(&bars[i]));
        }
    }
    const int tb = blockIdx.x >> 3, hg = blockIdx.x & 7;
    const int head = hg * 4 + wg;
    const int g = lane >> 2, c = lane & 3;
    uint32_t qa[2][4];
    float qn = 0.f;
#pragma unroll
    for (int m = 0; m < 2; m++) {
        const int row = tb * 128 + m * 64 + warp * 16 + g;
        const uint32_t* p0 = (const uint32_t*)(g_q + (size_t)row * D_ + head * 16);
        const uint32_t* p1 = (const uint32_t*)(g_q + (size_t)(row + 8) * D_ + head * 16);
        qa[m][0] = p0[c]; qa[m][1] = p1[c]; qa[m][2] = p0[c + 4]; qa[m][3] = p1[c + 4];
        float n0 = bf_lo(qa[m][0]) * bf_lo(qa[m][0]) + bf_hi(qa[m][0]) * bf_hi(qa[m][0]) + bf_lo(qa[m][2]) * bf_lo(qa[m][2]) + bf_hi(qa[m][2]) * bf_hi(qa[m][2]);
        float n1 = bf_lo(qa[m][1]) * bf_lo(qa[m][1]) + bf_hi(qa[m][1]) * bf_hi(qa[m][1]) + bf_lo(qa[m][3]) * bf_lo(qa[m][3]) + bf_hi(qa[m][3]) * bf_hi(qa[m][3]);
        n0 += __shfl_xor_sync(0xffffffffu, n0, 1); n0 += __shfl_xor_sync(0xffffffffu, n0, 2);
        n1 += __shfl_xor_sync(0xffffffffu, n1, 1); n1 += __shfl_xor_sync(0xffffffffu, n1, 2);
        if (!(n0 == n0) || !(n1 == n1)) n0 = __int_as_float(0x7f800000);
        qn = fmaxf(qn, fmaxf(n0, n1));
    }
    {
        float km = 0.f, vm = 0.f;
#pragma unroll
        for (int i = 0; i < 16; i++) { km = fmaxf(km, g_kvmax[i]); vm = fmaxf(vm, g_kvmax[16 + i]); }
        const bool ok = (qn * km <= 10000.f) && (vm <= 16384.f);
        if (!ok) s_slow = 1;
    }
    float oacc[2][12];
#pragma unroll
    for (int m = 0; m < 2; m++)
#pragma unroll
        for (int i = 0; i < 12; i++) oacc[m][i] = 0.f;
    __syncthreads();
    const bool slow = s_slow != 0;

    const uint64_t dK0 = mkdesc(sK, 128, 256, 0);
    const uint64_t dV0 = mkdesc(sV, 128, 256, 0);
    uint32_t c3f;
    asm volatile("mov.b32 %0, 0x3F003F00;" : "=r"(c3f));
    if (!slow) {
#pragma unroll 1
        for (int t = 0; t < S_ / 64; t++) {
            if ((t & 3) == 0) mbar_wait(smem_u32(&bars[t >> 2]), 0);
            const uint64_t dK = dK0 + (uint64_t)(t * 64 * 32 / 16);
            const uint64_t dV = dV0 + (uint64_t)(t * 4 * 768 / 16);
#pragma unroll
            for (int m = 0; m < 2; m++) {
                float s[32];
                wg_fence();
                wgmma_rs_n64_z(s, qa[m][0], qa[m][1], qa[m][2], qa[m][3], dK);
                wg_commit();
                wg_wait<0>();
                fence_regs(s);
                uint32_t p[16];
#pragma unroll
                for (int i = 0; i < 16; i++) p[i] = is_mufu(i) ? exp_pair_mufu(s[2 * i], s[2 * i + 1]) : exp_pair_fma(s[2 * i], s[2 * i + 1], c3f);
                wg_fence();
#pragma unroll
                for (int kk = 0; kk < 4; kk++)
                    wgmma_rs_n24_tb(oacc[m], p[4 * kk], p[4 * kk + 1], p[4 * kk + 2], p[4 * kk + 3], dV + (uint64_t)(kk * 768 / 16));
                wg_commit();
            }
        }
        wg_wait<0>();
    } else {
        float mx[2][2] = {{-INFINITY, -INFINITY}, {-INFINITY, -INFINITY}};
#pragma unroll 1
        for (int t = 0; t < S_ / 64; t++) {
            if ((t & 3) == 0) mbar_wait(smem_u32(&bars[t >> 2]), 0);
            const uint64_t dK = dK0 + (uint64_t)(t * 64 * 32 / 16);
            const uint64_t dV = dV0 + (uint64_t)(t * 4 * 768 / 16);
#pragma unroll
            for (int m = 0; m < 2; m++) {
                float s[32];
                wg_fence();
                wgmma_rs_n64_z(s, qa[m][0], qa[m][1], qa[m][2], qa[m][3], dK);
                wg_commit();
                wg_wait<0>();
                fence_regs(s);
                fence_regs(oacc[m]);
                float r0 = mx[m][0], r1 = mx[m][1];
#pragma unroll
                for (int j = 0; j < 8; j++) {
                    r0 = fmaxf(r0, fmaxf(s[4 * j], s[4 * j + 1]));
                    r1 = fmaxf(r1, fmaxf(s[4 * j + 2], s[4 * j + 3]));
                }
                r0 = fmaxf(r0, __shfl_xor_sync(0xffffffffu, r0, 1)); r0 = fmaxf(r0, __shfl_xor_sync(0xffffffffu, r0, 2));
                r1 = fmaxf(r1, __shfl_xor_sync(0xffffffffu, r1, 1)); r1 = fmaxf(r1, __shfl_xor_sync(0xffffffffu, r1, 2));
                const float al0 = ex2(mx[m][0] - r0), al1 = ex2(mx[m][1] - r1);
                mx[m][0] = r0; mx[m][1] = r1;
#pragma unroll
                for (int j = 0; j < 3; j++) {
                    oacc[m][4 * j] *= al0; oacc[m][4 * j + 1] *= al0;
                    oacc[m][4 * j + 2] *= al1; oacc[m][4 * j + 3] *= al1;
                }
                uint32_t p[16];
#pragma unroll
                for (int j = 0; j < 8; j++) {
                    p[2 * j] = pack_bf16(ex2(s[4 * j] - r0), ex2(s[4 * j + 1] - r0));
                    p[2 * j + 1] = pack_bf16(ex2(s[4 * j + 2] - r1), ex2(s[4 * j + 3] - r1));
                }
                fence_regs(oacc[m]);
                wg_fence();
#pragma unroll
                for (int kk = 0; kk < 4; kk++)
                    wgmma_rs_n24_tb(oacc[m], p[4 * kk], p[4 * kk + 1], p[4 * kk + 2], p[4 * kk + 3], dV + (uint64_t)(kk * 768 / 16));
                wg_commit();
                wg_wait<0>();
            }
        }
    }
    fence_regs(oacc[0]); fence_regs(oacc[1]);
    if (tid == 0) TL(tk, 2);
#pragma unroll
    for (int m = 0; m < 2; m++) {
        const float l0 = __shfl_sync(0xffffffffu, oacc[m][8], lane & ~3);
        const float l1 = __shfl_sync(0xffffffffu, oacc[m][10], lane & ~3);
        const float r0 = 1.0f / l0, r1 = 1.0f / l1;
        const int row = tb * 128 + m * 64 + warp * 16 + g;
        uint32_t* p0 = (uint32_t*)(g_o + (size_t)row * D_ + head * 16);
        uint32_t* p1 = (uint32_t*)(g_o + (size_t)(row + 8) * D_ + head * 16);
        p0[c] = pack_bf16(oacc[m][0] * r0, oacc[m][1] * r0);
        p1[c] = pack_bf16(oacc[m][2] * r1, oacc[m][3] * r1);
        p0[c + 4] = pack_bf16(oacc[m][4] * r0, oacc[m][5] * r0);
        p1[c + 4] = pack_bf16(oacc[m][6] * r1, oacc[m][7] * r1);
    }
    if (tid == 0) TL(tk, 3);
}

typedef CUresult (*EncodeFn)(CUtensorMap*, CUtensorMapDataType, cuuint32_t, void*, const cuuint64_t*, const cuuint64_t*, const cuuint32_t*,
                             const cuuint32_t*, CUtensorMapInterleave, CUtensorMapSwizzle, CUtensorMapL2promotion, CUtensorMapFloatOOBfill);

EncodeFn get_encode() {
    static EncodeFn fn = nullptr;
    if (!fn) {
        void* p = nullptr;
        cudaDriverEntryPointQueryResult qr;
        cudaGetDriverEntryPoint("cuTensorMapEncodeTiled", &p, cudaEnableDefault, &qr);
        fn = (EncodeFn)p;
    }
    return fn;
}
CUtensorMap map2d(const void* ptr, uint64_t cols, uint64_t rows, uint32_t bc, uint32_t br, CUtensorMapSwizzle sw) {
    CUtensorMap m;
    cuuint64_t gd[2] = {cols, rows}, gs[1] = {cols * 2};
    cuuint32_t bx[2] = {bc, br}, es[2] = {1, 1};
    get_encode()(&m, CU_TENSOR_MAP_DATA_TYPE_BFLOAT16, 2, (void*)ptr, gd, gs, bx, es, CU_TENSOR_MAP_INTERLEAVE_NONE, sw,
                 CU_TENSOR_MAP_L2_PROMOTION_L2_128B, CU_TENSOR_MAP_FLOAT_OOB_FILL_NONE);
    return m;
}
CUtensorMap map3d32(const void* ptr, uint64_t cols, uint64_t rows, uint32_t br, uint32_t nb) {
    CUtensorMap m;
    cuuint64_t gd[3] = {32, rows, cols / 32}, gs[2] = {cols * 2, 64};
    cuuint32_t bx[3] = {32, br, nb}, es[3] = {1, 1, 1};
    get_encode()(&m, CU_TENSOR_MAP_DATA_TYPE_BFLOAT16, 3, (void*)ptr, gd, gs, bx, es, CU_TENSOR_MAP_INTERLEAVE_NONE, CU_TENSOR_MAP_SWIZZLE_64B,
                 CU_TENSOR_MAP_L2_PROMOTION_L2_128B, CU_TENSOR_MAP_FLOAT_OOB_FILL_NONE);
    return m;
}

template <typename... KArgs, typename... Args>
void launch(void (*kern)(KArgs...), int grid, int block, int smem, int cluster, bool pdl, Args... args) {
    cudaLaunchConfig_t cfg = {};
    cfg.gridDim = dim3(grid);
    cfg.blockDim = dim3(block);
    cfg.dynamicSmemBytes = smem;
    cfg.stream = cudaStreamPerThread;
    cudaLaunchAttribute at[2];
    int n = 0;
    if (cluster > 1) { at[n].id = cudaLaunchAttributeClusterDimension; at[n].val.clusterDim.x = cluster; at[n].val.clusterDim.y = 1; at[n].val.clusterDim.z = 1; n++; }
    if (pdl) { at[n].id = cudaLaunchAttributeProgrammaticStreamSerialization; at[n].val.programmaticStreamSerializationAllowed = 1; n++; }
    cfg.attrs = at;
    cfg.numAttrs = n;
    cudaLaunchKernelEx(&cfg, kern, KArgs(args)...);
}

template <typename T> void* sym(const T& s) { void* p = nullptr; cudaGetSymbolAddress(&p, s); return p; }

}

extern "C" void kernel_launch(void* const* d_in, const int* in_sizes, int n_in, void* d_out, int out_size) {
    const __nv_bfloat16* x = (const __nv_bfloat16*)d_in[0];
    const __nv_bfloat16* wq = (const __nv_bfloat16*)d_in[1];
    const __nv_bfloat16* wk = (const __nv_bfloat16*)d_in[2];
    const __nv_bfloat16* wv = (const __nv_bfloat16*)d_in[3];
    const __nv_bfloat16* wo = (const __nv_bfloat16*)d_in[4];
    const __nv_bfloat16* w1 = (const __nv_bfloat16*)d_in[6];
    const __nv_bfloat16* w2 = (const __nv_bfloat16*)d_in[7];

    constexpr int SM_QKV = GemmSmem<QKV_STAGES, EPI_QKV>::TOTAL;
    constexpr int HALF_PLUS = 116736;
    constexpr int SM_WO = GemmSmem<WO_STAGES, EPI_RES>::TOTAL > HALF_PLUS ? GemmSmem<WO_STAGES, EPI_RES>::TOTAL : HALF_PLUS;
    constexpr int SM_FFN2 = GemmSmem<FFN2_STAGES, EPI_RES>::TOTAL > HALF_PLUS ? GemmSmem<FFN2_STAGES, EPI_RES>::TOTAL : HALF_PLUS;
    constexpr int SM_FFN1 = GemmSmem<FFN1_STAGES, EPI_FFN1>::TOTAL;
    cudaFuncSetAttribute(qkv_kernel<false>, cudaFuncAttributeMaxDynamicSharedMemorySize, SM_QKV);
    cudaFuncSetAttribute(qkv_kernel<true>, cudaFuncAttributeMaxDynamicSharedMemorySize, SM_QKV);
    cudaFuncSetAttribute(res_gemm_kernel<8, WO_STAGES>, cudaFuncAttributeMaxDynamicSharedMemorySize, SM_WO);
    cudaFuncSetAttribute(ffn1_kernel, cudaFuncAttributeMaxDynamicSharedMemorySize, SM_FFN1);
    cudaFuncSetAttribute(res_gemm_kernel<28, FFN2_STAGES>, cudaFuncAttributeMaxDynamicSharedMemorySize, SM_FFN2);
    cudaFuncSetAttribute(attn_kernel, cudaFuncAttributeMaxDynamicSharedMemorySize, ATT_SMEM);
    cudaFuncSetAttribute(qkv_kernel<false>, cudaFuncAttributePreferredSharedMemoryCarveout, 100);
    cudaFuncSetAttribute(qkv_kernel<true>, cudaFuncAttributePreferredSharedMemoryCarveout, 100);
    cudaFuncSetAttribute(res_gemm_kernel<8, WO_STAGES>, cudaFuncAttributePreferredSharedMemoryCarveout, 100);
    cudaFuncSetAttribute(ffn1_kernel, cudaFuncAttributePreferredSharedMemoryCarveout, 100);
    cudaFuncSetAttribute(res_gemm_kernel<28, FFN2_STAGES>, cudaFuncAttributePreferredSharedMemoryCarveout, 100);
    cudaFuncSetAttribute(attn_kernel, cudaFuncAttributePreferredSharedMemoryCarveout, 100);

    void *q = sym(g_q), *o = sym(g_o), *x1 = sym(g_x1), *x2 = sym(g_x2), *x3 = sym(g_x3), *h = sym(g_h);
    float2* stats = (float2*)sym(g_stats);
    const void* xs[5] = {x, x1, x2, x3, d_out};

    const CUtensorMapSwizzle SW128 = CU_TENSOR_MAP_SWIZZLE_128B, SW64 = CU_TENSOR_MAP_SWIZZLE_64B;
    const CUtensorMap mWq = map3d32(wq, D_, D_, 64, 2);
    const CUtensorMap mWk = map2d(wk, 16, D_, 32, 64, SW64);
    const CUtensorMap mWv = map2d(wv, 16, D_, 32, 64, SW64);
    const CUtensorMap mWo = map2d(wo, D_, D_, 64, 64, SW128);
    const CUtensorMap mW1a = map3d32(w1, F_, D_, F1_BK, 4), mW1b = map3d32(w1, F_, D_, F1_BK, 3);
    const CUtensorMap mW2 = map2d(w2, D_, F_, 64, 64, SW128);
    const CUtensorMap mQ = map2d(q, D_, S_, 64, 64, SW128);
    const CUtensorMap mHst = map2d(h, F_, S_, 32, 16, SW64);
    CUtensorMap mXa[4], mXf[4], mXr[4], mXs[5];
    for (int i = 0; i < 4; i++) {
        mXa[i] = map2d(xs[i], D_, S_, 64, QKV_MC ? 64 : 128, SW128);
        mXf[i] = F1_BK == 64 ? map2d(xs[i], D_, S_, 64, 128, SW128) : map2d(xs[i], D_, S_, 32, 128, SW64);
        mXr[i] = map2d(xs[i], D_, S_, 64, 128, SW128);
    }
    for (int i = 0; i < 5; i++) mXs[i] = map2d(xs[i], D_, S_, 64, 64, SW128);
    const CUtensorMap mOa = map2d(o, D_, S_, 64, WO_MC ? 64 : 128, SW128);
    const CUtensorMap mHa = map2d(h, F_, S_, 64, F2_MC ? 64 : 128, SW128);

    for (int layer = 0; layer < 2; layer++) {
        const int xi = layer * 2;
        GemmParams p;
        p.stats_in = stats + (size_t)xi * 8 * S_; p.stats_out = nullptr; p.tk = 1 + 5 * layer;
        if (layer == 0) launch(qkv_kernel<true>, 128, 288, SM_QKV, QKV_MC ? 2 : 1, false, mXa[xi], mWq, mWk, mWv, mQ, p);
        else launch(qkv_kernel<false>, 128, 288, SM_QKV, QKV_MC ? 2 : 1, true, mXa[xi], mWq, mWk, mWv, mQ, p);
        launch(attn_kernel, layer == 0 ? 128 + SIDE_CTAS : 128, 512, ATT_SMEM, 1, true, wo, w1, w2, 2 + 5 * layer);
        p.stats_in = nullptr; p.stats_out = stats + (size_t)(xi + 1) * 8 * S_; p.tk = 3 + 5 * layer;
        launch(res_gemm_kernel<8, WO_STAGES>, 128, 288, SM_WO, WO_MC ? 2 : 1, true, mOa, mWo, mXr[xi], mXs[xi + 1], p);
        p.stats_in = stats + (size_t)(xi + 1) * 8 * S_; p.stats_out = nullptr; p.tk = 4 + 5 * layer;
        launch(ffn1_kernel, 128, F1_INLINE ? 256 : 288, SM_FFN1, F1_MC ? 2 : 1, true, mXf[xi + 1], mW1a, mW1b, mHst, p);
        p.stats_in = nullptr; p.stats_out = layer == 0 ? stats + (size_t)2 * 8 * S_ : nullptr; p.tk = 5 + 5 * layer;
        launch(res_gemm_kernel<28, FFN2_STAGES>, 128, 288, SM_FFN2, F2_MC ? 2 : 1, true, mHa, mW2, mXr[xi + 1], mXs[xi + 2], p);
    }
}
```

```cpp
#include <cuda_runtime.h>
#include <cuda_bf16.h>
#include <cuda.h>
#include <stdint.h>

#define F1_INLINE 0
#define QKV_MC 0
#define WO_MC 0
#define F2_MC 0
#define F1_MC 2
#define PREB 2
#define RES_WAIT0 0

namespace {

constexpr int S_ = 2048, D_ = 512, H_ = 32, F_ = 1792;

__device__ __align__(1024) __nv_bfloat16 g_q[S_ * D_];
__device__ __align__(1024) __nv_bfloat16 g_o[S_ * D_];
__device__ __align__(1024) __nv_bfloat16 g_x1[S_ * D_];
__device__ __align__(1024) __nv_bfloat16 g_x2[S_ * D_];
__device__ __align__(1024) __nv_bfloat16 g_x3[S_ * D_];
__device__ __align__(1024) __nv_bfloat16 g_h[S_ * F_];
__device__ __align__(1024) uint8_t g_kimg[S_ * 32];
__device__ __align__(1024) uint8_t g_vimg[(S_ / 16) * 768];
__device__ __align__(1024) float2 g_stats[4][8 * S_];
__device__ __align__(16) float g_cs_q[D_];
__device__ __align__(16) float g_cs_kv[32];
__device__ __align__(16) float g_cs_1[F_];
__device__ __align__(16) float g_kvmax[32];

#define TL(k, slot)

__device__ __forceinline__ uint32_t smem_u32(const void* p) { return (uint32_t)__cvta_generic_to_shared(p); }
__device__ __forceinline__ void mbar_init(uint32_t bar, uint32_t cnt) {
    asm volatile("mbarrier.init.shared::cta.b64 [%0], %1;" ::"r"(bar), "r"(cnt));
}
__device__ __forceinline__ void mbar_expect_tx(uint32_t bar, uint32_t bytes) {
    asm volatile("mbarrier.arrive.expect_tx.shared::cta.b64 _, [%0], %1;" ::"r"(bar), "r"(bytes) : "memory");
}
__device__ __forceinline__ void mbar_arrive(uint32_t bar) {
    asm volatile("mbarrier.arrive.shared::cta.b64 _, [%0];" ::"r"(bar) : "memory");
}
__device__ __forceinline__ void mbar_arrive_remote(uint32_t bar, uint32_t cta) {
    asm volatile("{\n.reg .b32 ra;\nmapa.shared::cluster.u32 ra, %0, %1;\nmbarrier.arrive.shared::cluster.b64 _, [ra];\n}" ::"r"(bar), "r"(cta) : "memory");
}
__device__ __forceinline__ void mbar_wait(uint32_t bar, uint32_t parity) {
    asm volatile("{\n.reg .pred p;\nWAIT_%=:\nmbarrier.try_wait.parity.shared::cta.b64 p, [%0], %1;\n@p bra DONE_%=;\nbra WAIT_%=;\nDONE_%=:\n}" ::"r"(bar), "r"(parity) : "memory");
}
__device__ __forceinline__ void bulk_load(uint32_t dst, const void* src, uint32_t bytes, uint32_t bar) {
    asm volatile("cp.async.bulk.shared::cluster.global.mbarrier::complete_tx::bytes [%0], [%1], %2, [%3];" ::"r"(dst), "l"(src), "r"(bytes), "r"(bar) : "memory");
}
__device__ __forceinline__ void tma2d(uint32_t dst, const CUtensorMap* m, int c0, int c1, uint32_t bar) {
    asm volatile("cp.async.bulk.tensor.2d.shared::cluster.global.mbarrier::complete_tx::bytes [%0], [%1, {%3, %4}], [%2];" ::"r"(dst), "l"(m), "r"(bar), "r"(c0), "r"(c1) : "memory");
}
__device__ __forceinline__ void tma2d_mc(uint32_t dst, const CUtensorMap* m, int c0, int c1, uint32_t bar, uint16_t mask) {
    asm volatile("cp.async.bulk.tensor.2d.shared::cluster.global.mbarrier::complete_tx::bytes.multicast::cluster [%0], [%1, {%3, %4}], [%2], %5;" ::"r"(dst), "l"(m), "r"(bar), "r"(c0), "r"(c1), "h"(mask) : "memory");
}
__device__ __forceinline__ void tma3d(uint32_t dst, const CUtensorMap* m, int c0, int c1, int c2, uint32_t bar) {
    asm volatile("cp.async.bulk.tensor.3d.shared::cluster.global.mbarrier::complete_tx::bytes [%0], [%1, {%3, %4, %5}], [%2];" ::"r"(dst), "l"(m), "r"(bar), "r"(c0), "r"(c1), "r"(c2) : "memory");
}
__device__ __forceinline__ void tma3d_mc(uint32_t dst, const CUtensorMap* m, int c0, int c1, int c2, uint32_t bar, uint16_t mask) {
    asm volatile("cp.async.bulk.tensor.3d.shared::cluster.global.mbarrier::complete_tx::bytes.multicast::cluster [%0], [%1, {%3, %4, %5}], [%2], %6;" ::"r"(dst), "l"(m), "r"(bar), "r"(c0), "r"(c1), "r"(c2), "h"(mask) : "memory");
}
__device__ __forceinline__ void tma2d_store(const CUtensorMap* m, uint32_t src, int c0, int c1) {
    asm volatile("cp.async.bulk.tensor.2d.global.shared::cta.bulk_group [%0, {%2, %3}], [%1];" ::"l"(m), "r"(src), "r"(c0), "r"(c1) : "memory");
}
__device__ __forceinline__ void tma3d_store(const CUtensorMap* m, uint32_t src, int c0, int c1, int c2) {
    asm volatile("cp.async.bulk.tensor.3d.global.shared::cta.bulk_group [%0, {%2, %3, %4}], [%1];" ::"l"(m), "r"(src), "r"(c0), "r"(c1), "r"(c2) : "memory");
}
__device__ __forceinline__ void bulk_commit() { asm volatile("cp.async.bulk.commit_group;" ::: "memory"); }
__device__ __forceinline__ void bulk_wait_read() { asm volatile("cp.async.bulk.wait_group.read 0;" ::: "memory"); }
__device__ __forceinline__ void prefetch_tmap(const CUtensorMap* m) { asm volatile("prefetch.tensormap [%0];" ::"l"(m) : "memory"); }
__device__ __forceinline__ void fence_async_smem() { asm volatile("fence.proxy.async.shared::cta;" ::: "memory"); }
__device__ __forceinline__ void fence_mbar_init() { asm volatile("fence.mbarrier_init.release.cluster;" ::: "memory"); }
__device__ __forceinline__ void cluster_sync() { asm volatile("barrier.cluster.arrive.release.aligned;\nbarrier.cluster.wait.acquire.aligned;" ::: "memory"); }
__device__ __forceinline__ uint32_t cluster_rank() { uint32_t r; asm volatile("mov.u32 %0, %%cluster_ctarank;" : "=r"(r)); return r; }
__device__ __forceinline__ void pdl_wait() { asm volatile("griddepcontrol.wait;" ::: "memory"); }
__device__ __forceinline__ void pdl_launch() { asm volatile("griddepcontrol.launch_dependents;" ::: "memory"); }
__device__ __forceinline__ bool elect_one() {
    uint32_t p;
    asm volatile("{\n.reg .pred p;\nelect.sync _|p, 0xffffffff;\nselp.b32 %0, 1, 0, p;\n}" : "=r"(p));
    return p != 0;
}
__device__ __forceinline__ void named_bar(int id, int n) { asm volatile("bar.sync %0, %1;" ::"r"(id), "r"(n) : "memory"); }

__device__ __forceinline__ void wg_fence() { asm volatile("wgmma.fence.sync.aligned;" ::: "memory"); }
__device__ __forceinline__ void wg_commit() { asm volatile("wgmma.commit_group.sync.aligned;" ::: "memory"); }
template <int N> __device__ __forceinline__ void wg_wait() { asm volatile("wgmma.wait_group.sync.aligned %0;" ::"n"(N) : "memory"); }
template <int N> __device__ __forceinline__ void fence_regs(float (&d)[N]) {
#pragma unroll
    for (int i = 0; i < N; i++) asm volatile("" : "+f"(d[i])::"memory");
}
__device__ __forceinline__ uint64_t mkdesc(uint32_t addr, uint32_t lbo, uint32_t sbo, uint32_t swz) {
    uint64_t d = 0;
    d |= (uint64_t)((addr & 0x3FFFF) >> 4);
    d |= (uint64_t)((lbo & 0x3FFFF) >> 4) << 16;
    d |= (uint64_t)((sbo & 0x3FFFF) >> 4) << 32;
    d |= (uint64_t)swz << 62;
    return d;
}
__device__ __forceinline__ void ldsm_x4(uint32_t& r0, uint32_t& r1, uint32_t& r2, uint32_t& r3, uint32_t addr) {
    asm volatile("ldmatrix.sync.aligned.m8n8.x4.shared.b16 {%0,%1,%2,%3}, [%4];" : "=r"(r0), "=r"(r1), "=r"(r2), "=r"(r3) : "r"(addr) : "memory");
}
__device__ __forceinline__ void stsm_x4(uint32_t addr, uint32_t r0, uint32_t r1, uint32_t r2, uint32_t r3) {
    asm volatile("stmatrix.sync.aligned.m8n8.x4.shared.b16 [%0], {%1,%2,%3,%4};" ::"r"(addr), "r"(r0), "r"(r1), "r"(r2), "r"(r3) : "memory");
}
__device__ __forceinline__ uint32_t pack_bf16(float lo, float hi) {
    uint32_t r;
    asm("cvt.rn.bf16x2.f32 %0, %1, %2;" : "=r"(r) : "f"(hi), "f"(lo));
    return r;
}
__device__ __forceinline__ float bf_lo(uint32_t v) { return __uint_as_float(v << 16); }
__device__ __forceinline__ float bf_hi(uint32_t v) { return __uint_as_float(v & 0xFFFF0000u); }

#define WG_REGS_4(o) "+f"(d[o]), "+f"(d[o + 1]), "+f"(d[o + 2]), "+f"(d[o + 3])
#define WG_REGS_8(o) WG_REGS_4(o), WG_REGS_4(o + 4)
#define WG_REGS_16(o) WG_REGS_8(o), WG_REGS_8(o + 8)
#define WG_REGS_32(o) WG_REGS_16(o), WG_REGS_16(o + 16)

__device__ __forceinline__ void wgmma_ss_n80_tb(float (&d)[40], uint64_t dA, uint64_t dB, int sc) {
    asm volatile("{\n.reg .pred p;\nsetp.ne.b32 p, %42, 0;\n"
                 "wgmma.mma_async.sync.aligned.m64n80k16.f32.bf16.bf16 "
                 "{%0,%1,%2,%3,%4,%5,%6,%7,%8,%9,%10,%11,%12,%13,%14,%15,%16,%17,%18,%19,%20,%21,%22,%23,%24,%25,%26,%27,%28,%29,%30,%31,"
                 "%32,%33,%34,%35,%36,%37,%38,%39}, %40, %41, p, 1, 1, 0, 1;\n}\n"
                 : WG_REGS_32(0), WG_REGS_8(32) : "l"(dA), "l"(dB), "r"(sc));
}
__device__ __forceinline__ void wgmma_ss_n64_tb(float (&d)[32], uint64_t dA, uint64_t dB, int sc) {
    asm volatile("{\n.reg .pred p;\nsetp.ne.b32 p, %34, 0;\n"
                 "wgmma.mma_async.sync.aligned.m64n64k16.f32.bf16.bf16 "
                 "{%0,%1,%2,%3,%4,%5,%6,%7,%8,%9,%10,%11,%12,%13,%14,%15,%16,%17,%18,%19,%20,%21,%22,%23,%24,%25,%26,%27,%28,%29,%30,%31}, "
                 "%32, %33, p, 1, 1, 0, 1;\n}\n"
                 : WG_REGS_32(0) : "l"(dA), "l"(dB), "r"(sc));
}
__device__ __forceinline__ void wgmma_ss_n224_tb(float (&d)[112], uint64_t dA, uint64_t dB, int sc) {
    asm volatile("{\n.reg .pred p;\nsetp.ne.b32 p, %114, 0;\n"
                 "wgmma.mma_async.sync.aligned.m64n224k16.f32.bf16.bf16 "
                 "{%0,%1,%2,%3,%4,%5,%6,%7,%8,%9,%10,%11,%12,%13,%14,%15,%16,%17,%18,%19,%20,%21,%22,%23,%24,%25,%26,%27,%28,%29,%30,%31,"
                 "%32,%33,%34,%35,%36,%37,%38,%39,%40,%41,%42,%43,%44,%45,%46,%47,%48,%49,%50,%51,%52,%53,%54,%55,%56,%57,%58,%59,%60,%61,%62,%63,"
                 "%64,%65,%66,%67,%68,%69,%70,%71,%72,%73,%74,%75,%76,%77,%78,%79,%80,%81,%82,%83,%84,%85,%86,%87,%88,%89,%90,%91,%92,%93,%94,%95,"
                 "%96,%97,%98,%99,%100,%101,%102,%103,%104,%105,%106,%107,%108,%109,%110,%111}, "
                 "%112, %113, p, 1, 1, 0, 1;\n}\n"
                 : WG_REGS_32(0), WG_REGS_32(32), WG_REGS_32(64), WG_REGS_16(96) : "l"(dA), "l"(dB), "r"(sc));
}
template <int BN> __device__ __forceinline__ void wgmma_ss_tb(float (&d)[BN / 2], uint64_t dA, uint64_t dB, int sc) {
    if constexpr (BN == 64) wgmma_ss_n64_tb(d, dA, dB, sc);
    else if constexpr (BN == 80) wgmma_ss_n80_tb(d, dA, dB, sc);
    else wgmma_ss_n224_tb(d, dA, dB, sc);
}
__device__ __forceinline__ void wgmma_rs_n64_z(float (&d)[32], uint32_t a0, uint32_t a1, uint32_t a2, uint32_t a3, uint64_t dB) {
    asm volatile("{\n.reg .pred p;\nsetp.ne.b32 p, 0, 0;\n"
                 "wgmma.mma_async.sync.aligned.m64n64k16.f32.bf16.bf16 "
                 "{%0,%1,%2,%3,%4,%5,%6,%7,%8,%9,%10,%11,%12,%13,%14,%15,%16,%17,%18,%19,%20,%21,%22,%23,%24,%25,%26,%27,%28,%29,%30,%31}, "
                 "{%32,%33,%34,%35}, %36, p, 1, 1, 0;\n}\n"
                 : "=f"(d[0]), "=f"(d[1]), "=f"(d[2]), "=f"(d[3]), "=f"(d[4]), "=f"(d[5]), "=f"(d[6]), "=f"(d[7]),
                   "=f"(d[8]), "=f"(d[9]), "=f"(d[10]), "=f"(d[11]), "=f"(d[12]), "=f"(d[13]), "=f"(d[14]), "=f"(d[15]),
                   "=f"(d[16]), "=f"(d[17]), "=f"(d[18]), "=f"(d[19]), "=f"(d[20]), "=f"(d[21]), "=f"(d[22]), "=f"(d[23]),
                   "=f"(d[24]), "=f"(d[25]), "=f"(d[26]), "=f"(d[27]), "=f"(d[28]), "=f"(d[29]), "=f"(d[30]), "=f"(d[31])
                 : "r"(a0), "r"(a1), "r"(a2), "r"(a3), "l"(dB));
}
__device__ __forceinline__ void wgmma_rs_n24_tb(float (&d)[12], uint32_t a0, uint32_t a1, uint32_t a2, uint32_t a3, uint64_t dB) {
    asm volatile("{\n.reg .pred p;\nsetp.eq.b32 p, 0, 0;\n"
                 "wgmma.mma_async.sync.aligned.m64n24k16.f32.bf16.bf16 "
                 "{%0,%1,%2,%3,%4,%5,%6,%7,%8,%9,%10,%11}, {%12,%13,%14,%15}, %16, p, 1, 1, 1;\n}\n"
                 : WG_REGS_8(0), WG_REGS_4(8) : "r"(a0), "r"(a1), "r"(a2), "r"(a3), "l"(dB));
}

constexpr int SIDE_CTAS = 4;
__device__ __forceinline__ void side_job(int cta, float* red  , const __nv_bfloat16* __restrict__ wo,
                                         const __nv_bfloat16* __restrict__ w1, const __nv_bfloat16* __restrict__ w2) {
    const int tid = threadIdx.x, warp = tid >> 5, lane = tid & 31;
    for (int line = cta * 512 + tid; line < 18432; line += SIDE_CTAS * 512) {
        const char* p = line < 4096 ? (const char*)wo + (size_t)line * 128 : (const char*)w2 + (size_t)(line - 4096) * 128;
        asm volatile("prefetch.global.L2 [%0];" ::"l"(p));
    }
    const int rg = lane >> 3, c8 = lane & 7;
    for (int slab = cta; slab < F_ / 64; slab += SIDE_CTAS) {
        const __nv_bfloat16* base = w1 + slab * 64 + c8 * 8;
        uint4 v[8];
#pragma unroll
        for (int i = 0; i < 8; i++) v[i] = __ldg((const uint4*)(base + (size_t)(warp * 32 + rg + 4 * i) * F_));
        float acc[8];
#pragma unroll
        for (int i = 0; i < 8; i++) acc[i] = 0.f;
#pragma unroll
        for (int i = 0; i < 8; i++) {
            acc[0] += bf_lo(v[i].x); acc[1] += bf_hi(v[i].x); acc[2] += bf_lo(v[i].y); acc[3] += bf_hi(v[i].y);
            acc[4] += bf_lo(v[i].z); acc[5] += bf_hi(v[i].z); acc[6] += bf_lo(v[i].w); acc[7] += bf_hi(v[i].w);
        }
#pragma unroll
        for (int i = 0; i < 8; i++) {
            acc[i] += __shfl_xor_sync(0xffffffffu, acc[i], 8);
            acc[i] += __shfl_xor_sync(0xffffffffu, acc[i], 16);
        }
        if (rg == 0) {
#pragma unroll
            for (int i = 0; i < 8; i++) red[warp * 64 + c8 * 8 + i] = acc[i];
        }
        __syncthreads();
        if (tid < 64) {
            float s = 0.f;
#pragma unroll
            for (int i = 0; i < 16; i++) s += red[i * 64 + tid];
            g_cs_1[slab * 64 + tid] = s;
        }
        __syncthreads();
    }
}

enum { EPI_QKV = 0, EPI_RES = 1, EPI_FFN1 = 2 };

struct GemmParams {
    const float2* stats_in;
    float2* stats_out;
    int tk;
};

template <int BK_, int NBLK> struct Geo {
    static constexpr int BK = BK_, A_BYTES = 128 * BK * 2, A_SWZ = BK == 64 ? 1 : 2, A_SBO = BK * 16;
    static constexpr int BLK = BK * 64;
    static constexpr int B_BYTES = NBLK * BLK, B_SWZ = 2, B_LBO = BLK, B_SBO = 512, B_KSTEP = 1024;
};
template <> struct Geo<64, 0> {
    static constexpr int BK = 64, A_BYTES = 128 * 128, A_SWZ = 1, A_SBO = 1024, BLK = 8192;
    static constexpr int B_BYTES = 64 * 128, B_SWZ = 1, B_LBO = 8192, B_SBO = 1024, B_KSTEP = 2048;
};
#define F1_BK 32
template <int EPI> struct EpiGeo;
template <> struct EpiGeo<EPI_QKV> { using G = Geo<64, 3>; };
template <> struct EpiGeo<EPI_RES> { using G = Geo<64, 0>; };
template <> struct EpiGeo<EPI_FFN1> { using G = Geo<F1_BK, 7>; };

template <int STAGES, int EPI> struct GemmSmem {
    using G = typename EpiGeo<EPI>::G;
    static constexpr int STAGE = G::A_BYTES + G::B_BYTES;
    static constexpr int AUX_OFF = STAGES * STAGE;
    static constexpr int TOTAL = AUX_OFF + 1152;
};

struct RowStatRaw { float2 a0, a1, b0, b1; };
__device__ __forceinline__ RowStatRaw load_row_stats(const float2* __restrict__ st, int row0, int c) {
    RowStatRaw r;
    r.a0 = st[(2 * c) * S_ + row0]; r.a1 = st[(2 * c + 1) * S_ + row0];
    r.b0 = st[(2 * c) * S_ + row0 + 8]; r.b1 = st[(2 * c + 1) * S_ + row0 + 8];
    return r;
}
__device__ __forceinline__ void finish_row_stats(const RowStatRaw& r, float& mean0, float& rstd0, float& mean1, float& rstd1) {
    float sa = r.a0.x + r.a1.x, sb = r.b0.x + r.b1.x;
    sa += __shfl_xor_sync(0xffffffffu, sa, 1); sa += __shfl_xor_sync(0xffffffffu, sa, 2);
    sb += __shfl_xor_sync(0xffffffffu, sb, 1); sb += __shfl_xor_sync(0xffffffffu, sb, 2);
    mean0 = sa * 0.125f; mean1 = sb * 0.125f;
    float ma = r.a0.y + r.a1.y + 64.f * ((r.a0.x - mean0) * (r.a0.x - mean0) + (r.a1.x - mean0) * (r.a1.x - mean0));
    float mb = r.b0.y + r.b1.y + 64.f * ((r.b0.x - mean1) * (r.b0.x - mean1) + (r.b1.x - mean1) * (r.b1.x - mean1));
    ma += __shfl_xor_sync(0xffffffffu, ma, 1); ma += __shfl_xor_sync(0xffffffffu, ma, 2);
    mb += __shfl_xor_sync(0xffffffffu, mb, 1); mb += __shfl_xor_sync(0xffffffffu, mb, 2);
    rstd0 = 1.0f / sqrtf(ma * (1.f / 512.f) + 1e-5f);
    rstd1 = 1.0f / sqrtf(mb * (1.f / 512.f) + 1e-5f);
}

template <int BN, int KB, int STAGES, int EPI, int MC, bool SELF = false>
__device__ __forceinline__ void gemm_body(const CUtensorMap* mapA, const CUtensorMap* mapB, const CUtensorMap* mapB2, const CUtensorMap* mapR,
                                          const CUtensorMap* mapC, const GemmParams& prm, int tile_m, int tile_n, uint8_t* smem_raw) {
    using SM = GemmSmem<STAGES, EPI>;
    using G = typename SM::G;
    constexpr bool XKV = BN == 80;
    constexpr int TN = EPI == EPI_QKV ? 64 : BN;
    pdl_launch();
    const uint32_t sbase = smem_u32(smem_raw);
    if (sbase & 1023) __trap();
    uint8_t* sgen = smem_raw;
    const uint32_t bar_full = sbase + SM::AUX_OFF, bar_empty = bar_full + 8 * STAGES;
    float* s_cs = (float*)(sgen + SM::AUX_OFF + 256);
    float* s_red = (float*)(sgen + SM::AUX_OFF + 768);
    const int tid = threadIdx.x, lane = tid & 31;
    const int warp = __shfl_sync(0xffffffffu, tid >> 5, 0);
    const uint32_t rank = MC ? cluster_rank() : 0;
    if (tid == 0) TL(prm.tk, 0);

    constexpr bool INLINE_PROD = EPI == EPI_FFN1 && F1_INLINE;
    constexpr int PWARP = INLINE_PROD ? 0 : 8;
    if (warp == PWARP && elect_one()) {
        prefetch_tmap(mapB); prefetch_tmap(mapA); prefetch_tmap(mapC);
        for (int s = 0; s < STAGES; s++) { mbar_init(bar_full + 8 * s, 1); mbar_init(bar_empty + 8 * s, MC ? 4 : 2); }
        fence_mbar_init();
    }
    __syncthreads();
    if (MC) cluster_sync();

    const int m0 = tile_m * 128, n0 = tile_n * TN;
    constexpr uint32_t STAGE_TX = G::A_BYTES + (EPI == EPI_QKV ? (XKV ? 3 : 2) * G::BLK : G::B_BYTES);
    auto loadB = [&](int kb, int s) {
        const uint32_t dst = sbase + s * SM::STAGE + G::A_BYTES, bar = bar_full + 8 * s;
        if constexpr (EPI == EPI_RES) {
            tma2d(dst, mapB, n0, kb * 64, bar);
        } else if constexpr (EPI == EPI_QKV) {
            tma3d(dst, mapB, 0, kb * G::BK, tile_n * 2, bar);
            if constexpr (XKV) tma2d(dst + 2 * G::BLK, mapB2, 0, kb * G::BK, bar);
        } else {
            if constexpr (MC == 2) {
                if (rank == 0) tma3d_mc(dst, mapB, 0, kb * G::BK, tile_n * 7, bar, 3);
                else tma3d_mc(dst + 4 * G::BLK, mapB2, 0, kb * G::BK, tile_n * 7 + 4, bar, 3);
            } else {
                tma3d(dst, mapB, 0, kb * G::BK, tile_n * 7, bar);
                tma3d(dst + 4 * G::BLK, mapB2, 0, kb * G::BK, tile_n * 7 + 4, bar);
            }
        }
    };
    auto loadA = [&](int kb, int s) {
        const uint32_t dst = sbase + s * SM::STAGE, bar = bar_full + 8 * s;
        if constexpr (MC == 1) tma2d_mc(dst + rank * (G::A_BYTES / 2), mapA, kb * G::BK, m0 + rank * 64, bar, 3);
        else tma2d(dst, mapA, kb * G::BK, m0, bar);
    };
    constexpr int PRE = STAGES < KB ? STAGES : KB;
#define F1_LAG 2
    constexpr int LAG = F1_LAG;
    constexpr int PRE_B = PRE < PREB ? PRE : PREB;
    auto prologue_loads = [&]() {
        if (elect_one()) {
#pragma unroll
            for (int kb = 0; kb < PRE; kb++) mbar_expect_tx(bar_full + 8 * kb, STAGE_TX);
#pragma unroll
            for (int kb = 0; kb < PRE_B; kb++) loadB(kb, kb);
        }
        if (!SELF) pdl_wait();
        if (elect_one()) {
#pragma unroll
            for (int kb = 0; kb < PRE; kb++) {
                loadA(kb, kb);
                if (kb + PRE_B < PRE) loadB(kb + PRE_B, kb + PRE_B);
            }
            if constexpr (EPI == EPI_RES && KB < STAGES) {
                mbar_expect_tx(bar_full + 8 * KB, 16384);
                tma2d(sbase + KB * SM::STAGE, mapR, n0, m0, bar_full + 8 * KB);
            }
        }
    };
    if (!INLINE_PROD && warp == 8) {
        prologue_loads();
        int s = PRE % STAGES, ph = (PRE / STAGES) & 1;
#pragma unroll 1
        for (int kb = PRE; kb < KB; kb++) {
            mbar_wait(bar_empty + 8 * s, ph ^ 1);
            if (elect_one()) {
                mbar_expect_tx(bar_full + 8 * s, STAGE_TX);
                loadB(kb, s);
                loadA(kb, s);
            }
            if (++s == STAGES) { s = 0; ph ^= 1; }
        }
        if constexpr (EPI == EPI_RES && KB >= STAGES) {
            mbar_wait(bar_empty + 8 * s, ph ^ 1);
            if (elect_one()) {
                mbar_expect_tx(bar_full + 8 * s, 16384);
                tma2d(sbase + s * SM::STAGE, mapR, n0, m0, bar_full + 8 * s);
            }
        }
    } else {
        if (INLINE_PROD && warp == 0) prologue_loads();
        const int wg = warp >> 2, g = lane >> 2, c = lane & 3;
        const int rloc = wg * 64 + (warp & 3) * 16 + g;
        const int row0 = m0 + rloc;
        float mean0 = 0.f, rstd0 = 1.f, mean1 = 0.f, rstd1 = 1.f;
        RowStatRaw raw;
        float csv = 0.f;
        float2 cskv[2] = {make_float2(0.f, 0.f), make_float2(0.f, 0.f)};
        auto ln_inputs = [&]() {
            pdl_wait();
            if constexpr (EPI != EPI_RES) {
                raw = load_row_stats(prm.stats_in, row0, c);
                const float* cs = EPI == EPI_FFN1 ? g_cs_1 + n0 : g_cs_q + n0;
                if (tid < TN) csv = cs[tid];
                if constexpr (XKV) {
                    cskv[0] = *(const float2*)(g_cs_kv + tile_n * 16 + 2 * c);
                    cskv[1] = *(const float2*)(g_cs_kv + tile_n * 16 + 8 + 2 * c);
                }
            }
        };
        if (!SELF) ln_inputs();
        float st_s[4] = {0.f, 0.f, 0.f, 0.f}, st_q[4] = {0.f, 0.f, 0.f, 0.f}, cs_acc[8], cs_x[8];
#pragma unroll
        for (int i = 0; i < 8; i++) { cs_acc[i] = 0.f; cs_x[i] = 0.f; }
        float acc[BN / 2];
        const uint64_t dA0 = mkdesc(sbase + wg * (G::A_BYTES / 2), 16, G::A_SBO, G::A_SWZ);
        const uint64_t dB0 = mkdesc(sbase + G::A_BYTES, G::B_LBO, G::B_SBO, G::B_SWZ);
        int s = 0, ph = 0;
#pragma unroll 1
        for (int kb = 0; kb < KB; kb++) {
            mbar_wait(bar_full + 8 * s, ph);
            const uint64_t dA = dA0 + (uint64_t)(s * (SM::STAGE >> 4)), dB = dB0 + (uint64_t)(s * (SM::STAGE >> 4));
            wg_fence();
#pragma unroll
            for (int k = 0; k < G::BK / 16; k++) wgmma_ss_tb<BN>(acc, dA + (uint64_t)(k * 2), dB + (uint64_t)(k * (G::B_KSTEP >> 4)), (kb | k) != 0);
            wg_commit();
            if constexpr (SELF) {
                static_assert(!SELF || (STAGES >= KB && EPI == EPI_QKV), "SELF needs every k block resident");
                const uint32_t arow = sbase + s * SM::STAGE + (tid >> 1) * 128;
#pragma unroll
                for (int j = 0; j < 4; j++) {
                    uint32_t w[4];
                    asm volatile("ld.shared.v4.u32 {%0,%1,%2,%3}, [%4];" : "=r"(w[0]), "=r"(w[1]), "=r"(w[2]), "=r"(w[3])
                                 : "r"(arow + (((2 * j + (tid & 1) + 2 * ((tid >> 1) & 3)) & 7) << 4)));
#pragma unroll
                    for (int i = 0; i < 4; i++) {
                        const float lo = bf_lo(w[i]), hi = bf_hi(w[i]);
                        st_s[i] += lo + hi;
                        st_q[i] = fmaf(lo, lo, fmaf(hi, hi, st_q[i]));
                    }
                }
                const uint32_t bblk = sbase + s * SM::STAGE + G::A_BYTES;
#pragma unroll
                for (int r = 0; r < 2; r++) {
                    const int krow = (tid >> 3) * 2 + r, ch = tid & 7;
                    uint32_t w0, w1_, w2_, w3;
                    asm volatile("ld.shared.v4.u32 {%0,%1,%2,%3}, [%4];" : "=r"(w0), "=r"(w1_), "=r"(w2_), "=r"(w3)
                                 : "r"(bblk + (ch >> 2) * G::BLK + krow * 64 + (((ch & 3) ^ ((krow >> 1) & 3)) << 4)));
                    cs_acc[0] += bf_lo(w0); cs_acc[1] += bf_hi(w0); cs_acc[2] += bf_lo(w1_); cs_acc[3] += bf_hi(w1_);
                    cs_acc[4] += bf_lo(w2_); cs_acc[5] += bf_hi(w2_); cs_acc[6] += bf_lo(w3); cs_acc[7] += bf_hi(w3);
                }
                if constexpr (XKV) {
                    if (tid < 128) {
                        const int krow = tid >> 1, ch = tid & 1;
                        uint32_t w0, w1_, w2_, w3;
                        asm volatile("ld.shared.v4.u32 {%0,%1,%2,%3}, [%4];" : "=r"(w0), "=r"(w1_), "=r"(w2_), "=r"(w3)
                                     : "r"(bblk + 2 * G::BLK + krow * 64 + ((ch ^ ((krow >> 1) & 3)) << 4)));
                        cs_x[0] += bf_lo(w0); cs_x[1] += bf_hi(w0); cs_x[2] += bf_lo(w1_); cs_x[3] += bf_hi(w1_);
                        cs_x[4] += bf_lo(w2_); cs_x[5] += bf_hi(w2_); cs_x[6] += bf_lo(w3); cs_x[7] += bf_hi(w3);
                    }
                }
            }
            if constexpr (EPI == EPI_RES && RES_WAIT0) {
                wg_wait<0>();
                if ((warp & 3) == 0 && elect_one()) {
                    if (MC) { mbar_arrive_remote(bar_empty + 8 * s, 0); mbar_arrive_remote(bar_empty + 8 * s, 1); }
                    else mbar_arrive(bar_empty + 8 * s);
                }
            } else if (kb > 0) {
                wg_wait<1>();
                const int sp = s == 0 ? STAGES - 1 : s - 1;
                if ((warp & 3) == 0 && elect_one()) {
                    if (MC) { mbar_arrive_remote(bar_empty + 8 * sp, 0); mbar_arrive_remote(bar_empty + 8 * sp, 1); }
                    else mbar_arrive(bar_empty + 8 * sp);
                }
                if (INLINE_PROD && warp == 0 && kb >= LAG && kb - LAG + STAGES < KB) {
                    const int sq = LAG == 1 ? sp : (sp == 0 ? STAGES - 1 : sp - 1);
                    mbar_wait(bar_empty + 8 * sq, ((kb - LAG) / STAGES) & 1);
                    if (elect_one()) {
                        mbar_expect_tx(bar_full + 8 * sq, STAGE_TX);
                        loadB(kb - LAG + STAGES, sq);
                        loadA(kb - LAG + STAGES, sq);
                    }
                }
            }
            if (++s == STAGES) { s = 0; ph ^= 1; }
        }
        if constexpr (SELF) {
            wg_wait<0>();
            named_bar(1, 256);
            float* sc = (float*)(sgen + (STAGES - 1) * SM::STAGE + G::A_BYTES);
            float ss = (st_s[0] + st_s[1]) + (st_s[2] + st_s[3]), qq = (st_q[0] + st_q[1]) + (st_q[2] + st_q[3]);
            ss += __shfl_xor_sync(0xffffffffu, ss, 1);
            qq += __shfl_xor_sync(0xffffffffu, qq, 1);
            if ((tid & 1) == 0) {
                const float md = ss * (1.f / 512.f);
                const float var = fmaxf(qq * (1.f / 512.f) - md * md, 0.f);
                sc[tid] = md;
                sc[tid + 1] = 1.0f / sqrtf(var + 1e-5f);
            }
#pragma unroll
            for (int i = 0; i < 8; i++) {
                cs_acc[i] += __shfl_xor_sync(0xffffffffu, cs_acc[i], 8);
                cs_acc[i] += __shfl_xor_sync(0xffffffffu, cs_acc[i], 16);
                if constexpr (XKV) {
                    cs_x[i] += __shfl_xor_sync(0xffffffffu, cs_x[i], 2); cs_x[i] += __shfl_xor_sync(0xffffffffu, cs_x[i], 4);
                    cs_x[i] += __shfl_xor_sync(0xffffffffu, cs_x[i], 8); cs_x[i] += __shfl_xor_sync(0xffffffffu, cs_x[i], 16);
                }
            }
            if (lane < 8) {
#pragma unroll
                for (int i = 0; i < 8; i++) sc[256 + warp * 64 + lane * 8 + i] = cs_acc[i];
            }
            if (XKV && lane < 2 && warp < 4) {
#pragma unroll
                for (int i = 0; i < 8; i++) sc[768 + warp * 16 + lane * 8 + i] = cs_x[i];
            }
            named_bar(1, 256);
            mean0 = sc[2 * rloc]; rstd0 = sc[2 * rloc + 1]; mean1 = sc[2 * rloc + 16]; rstd1 = sc[2 * rloc + 17];
            if (tid < 64) {
                float t = 0.f;
#pragma unroll
                for (int w = 0; w < 8; w++) t += sc[256 + w * 64 + tid];
                s_cs[tid] = t;
                if (tile_m == 0) g_cs_q[n0 + tid] = t;
            }
            if constexpr (XKV) {
#pragma unroll
                for (int j = 0; j < 2; j++) {
                    float tx = 0.f, ty = 0.f;
#pragma unroll
                    for (int w = 0; w < 4; w++) { tx += sc[768 + w * 16 + 8 * j + 2 * c]; ty += sc[768 + w * 16 + 8 * j + 2 * c + 1]; }
                    cskv[j] = make_float2(tx, ty);
                }
                if (tile_m == 0 && warp == 0 && g == 0) {
                    *(float2*)(g_cs_kv + tile_n * 16 + 2 * c) = cskv[0];
                    *(float2*)(g_cs_kv + tile_n * 16 + 8 + 2 * c) = cskv[1];
                }
            }
        } else if constexpr (EPI != EPI_RES) {
            finish_row_stats(raw, mean0, rstd0, mean1, rstd1);
            if (tid < TN) s_cs[tid] = csv;
        }
        wg_wait<0>();
        fence_regs(acc);
        if (tid == 0) TL(prm.tk, 2);
        if constexpr (EPI != EPI_RES) named_bar(1, 256);

        if constexpr (EPI != EPI_FFN1) {
            const uint32_t stile = sbase + (EPI == EPI_RES ? s * SM::STAGE : 0);
            const int mrow = wg * 64 + (warp & 3) * 16 + (lane & 7) + ((lane >> 3) & 1) * 8;
            const uint32_t rbase = stile + mrow * 128;
            if constexpr (EPI == EPI_RES) {
                mbar_wait(bar_full + 8 * s, ph);
                float s0 = 0.f, s1 = 0.f;
#pragma unroll
                for (int jj = 0; jj < 4; jj++) {
                    uint32_t r0, r1, r2, r3;
                    const uint32_t addr = rbase + (((2 * jj + (lane >> 4)) ^ (mrow & 7)) << 4);
                    ldsm_x4(r0, r1, r2, r3, addr);
                    const uint32_t u0 = pack_bf16(acc[8 * jj] + bf_lo(r0), acc[8 * jj + 1] + bf_hi(r0));
                    const uint32_t u1 = pack_bf16(acc[8 * jj + 2] + bf_lo(r1), acc[8 * jj + 3] + bf_hi(r1));
                    const uint32_t u2 = pack_bf16(acc[8 * jj + 4] + bf_lo(r2), acc[8 * jj + 5] + bf_hi(r2));
                    const uint32_t u3 = pack_bf16(acc[8 * jj + 6] + bf_lo(r3), acc[8 * jj + 7] + bf_hi(r3));
                    stsm_x4(addr, u0, u1, u2, u3);
                    acc[8 * jj] = bf_lo(u0); acc[8 * jj + 1] = bf_hi(u0); acc[8 * jj + 4] = bf_lo(u2); acc[8 * jj + 5] = bf_hi(u2);
                    acc[8 * jj + 2] = bf_lo(u1); acc[8 * jj + 3] = bf_hi(u1); acc[8 * jj + 6] = bf_lo(u3); acc[8 * jj + 7] = bf_hi(u3);
                    s0 += (acc[8 * jj] + acc[8 * jj + 1]) + (acc[8 * jj + 4] + acc[8 * jj + 5]);
                    s1 += (acc[8 * jj + 2] + acc[8 * jj + 3]) + (acc[8 * jj + 6] + acc[8 * jj + 7]);
                }
                fence_async_smem();
                named_bar(2 + wg, 128);
                if ((warp & 3) == 0 && elect_one()) { tma2d_store(mapC, stile + wg * 8192, n0, m0 + wg * 64); bulk_commit(); }
                if (prm.stats_out) {
                    s0 += __shfl_xor_sync(0xffffffffu, s0, 1); s0 += __shfl_xor_sync(0xffffffffu, s0, 2);
                    s1 += __shfl_xor_sync(0xffffffffu, s1, 1); s1 += __shfl_xor_sync(0xffffffffu, s1, 2);
                    const float mu0 = s0 * (1.f / 64.f), mu1 = s1 * (1.f / 64.f);
                    float q0 = 0.f, q1 = 0.f;
#pragma unroll
                    for (int j = 0; j < 8; j++) {
                        float d;
                        d = acc[4 * j] - mu0; q0 += d * d; d = acc[4 * j + 1] - mu0; q0 += d * d;
                        d = acc[4 * j + 2] - mu1; q1 += d * d; d = acc[4 * j + 3] - mu1; q1 += d * d;
                    }
                    q0 += __shfl_xor_sync(0xffffffffu, q0, 1); q0 += __shfl_xor_sync(0xffffffffu, q0, 2);
                    q1 += __shfl_xor_sync(0xffffffffu, q1, 1); q1 += __shfl_xor_sync(0xffffffffu, q1, 2);
                    if (c == 0) {
                        prm.stats_out[tile_n * S_ + row0] = make_float2(mu0, q0);
                        prm.stats_out[tile_n * S_ + row0 + 8] = make_float2(mu1, q1);
                    }
                }
            } else {
                const float sc = 0.25f * 1.4426950408889634f;
                const float a0 = rstd0 * sc, a1 = rstd1 * sc, rm0 = a0 * mean0, rm1 = a1 * mean1;
#pragma unroll
                for (int jj = 0; jj < 4; jj++) {
                    const float2 ca = *(const float2*)(s_cs + 16 * jj + 2 * c), cb = *(const float2*)(s_cs + 16 * jj + 8 + 2 * c);
                    const uint32_t u0 = pack_bf16(acc[8 * jj] * a0 - rm0 * ca.x, acc[8 * jj + 1] * a0 - rm0 * ca.y);
                    const uint32_t u1 = pack_bf16(acc[8 * jj + 2] * a1 - rm1 * ca.x, acc[8 * jj + 3] * a1 - rm1 * ca.y);
                    const uint32_t u2 = pack_bf16(acc[8 * jj + 4] * a0 - rm0 * cb.x, acc[8 * jj + 5] * a0 - rm0 * cb.y);
                    const uint32_t u3 = pack_bf16(acc[8 * jj + 6] * a1 - rm1 * cb.x, acc[8 * jj + 7] * a1 - rm1 * cb.y);
                    stsm_x4(rbase + (((2 * jj + (lane >> 4)) ^ (mrow & 7)) << 4), u0, u1, u2, u3);
                }
                fence_async_smem();
                named_bar(2 + wg, 128);
                if ((warp & 3) == 0 && elect_one()) { tma2d_store(mapC, stile + wg * 8192, n0, m0 + wg * 64); bulk_commit(); }
            }
            if constexpr (XKV) {
                {
                    const float* acx = &acc[32];
                    const float rm0 = rstd0 * mean0, rm1 = rstd1 * mean1;
                    float n0s = 0.f, n1s = 0.f, vmax = 0.f;
#pragma unroll
                    for (int j = 0; j < 2; j++) {
                        const float2 cs2 = cskv[j];
                        const uint32_t u0 = pack_bf16(acx[4 * j] * rstd0 - rm0 * cs2.x, acx[4 * j + 1] * rstd0 - rm0 * cs2.y);
                        const uint32_t u1 = pack_bf16(acx[4 * j + 2] * rstd1 - rm1 * cs2.x, acx[4 * j + 3] * rstd1 - rm1 * cs2.y);
                        n0s += bf_lo(u0) * bf_lo(u0) + bf_hi(u0) * bf_hi(u0);
                        n1s += bf_lo(u1) * bf_lo(u1) + bf_hi(u1) * bf_hi(u1);
                        vmax = fmaxf(vmax, fmaxf(fmaxf(fabsf(bf_lo(u0)), fabsf(bf_hi(u0))), fmaxf(fabsf(bf_lo(u1)), fabsf(bf_hi(u1)))));
                        if (tile_n == 0) {
                            *(uint32_t*)(g_kimg + (row0 >> 3) * 256 + j * 128 + g * 16 + c * 4) = u0;
                            *(uint32_t*)(g_kimg + ((row0 + 8) >> 3) * 256 + j * 128 + g * 16 + c * 4) = u1;
                        } else {
                            uint8_t* vb = g_vimg + (row0 >> 4) * 768 + j * 256 + g * 16 + c * 4;
                            *(uint32_t*)(vb) = u0;
                            *(uint32_t*)(vb + 128) = u1;
                        }
                    }
                    if (tile_n == 1) {
                        uint8_t* vb = g_vimg + (row0 >> 4) * 768 + 512 + g * 16 + c * 4;
                        const uint32_t one = c == 0 ? 0x00003F80u : 0u;
                        *(uint32_t*)(vb) = one;
                        *(uint32_t*)(vb + 128) = one;
                    }
                    n0s += __shfl_xor_sync(0xffffffffu, n0s, 1); n0s += __shfl_xor_sync(0xffffffffu, n0s, 2);
                    n1s += __shfl_xor_sync(0xffffffffu, n1s, 1); n1s += __shfl_xor_sync(0xffffffffu, n1s, 2);
                    float km = tile_n == 0 ? fmaxf(n0s, n1s) : vmax;
                    if (!(n0s + n1s < INFINITY)) km = INFINITY;
#pragma unroll
                    for (int o = 1; o < 32; o <<= 1) km = fmaxf(km, __shfl_xor_sync(0xffffffffu, km, o));
                    if (lane == 0) s_red[warp] = km;
                    named_bar(1, 256);
                    if (tid == 0) {
                        float a = 0.f;
                        for (int i = 0; i < 8; i++) a = fmaxf(a, s_red[i]);
                        g_kvmax[tile_n * 16 + tile_m] = a;
                    }
                }
            }
            if ((warp & 3) == 0) bulk_wait_read();
        } else {
            const uint32_t stile = sbase + wg * (7 * 4096);
            const int mrow = (warp & 3) * 16 + (lane & 7) + ((lane >> 3) & 1) * 8;
            const float a0 = 0.5f * rstd0, a1 = 0.5f * rstd1, rm0 = a0 * mean0, rm1 = a1 * mean1;
#pragma unroll
            for (int jj = 0; jj < 14; jj++) {
                const float2 ca = *(const float2*)(s_cs + 16 * jj + 2 * c), cb = *(const float2*)(s_cs + 16 * jj + 8 + 2 * c);
                float y[8] = {acc[8 * jj] * a0 - rm0 * ca.x,     acc[8 * jj + 1] * a0 - rm0 * ca.y,
                              acc[8 * jj + 2] * a1 - rm1 * ca.x, acc[8 * jj + 3] * a1 - rm1 * ca.y,
                              acc[8 * jj + 4] * a0 - rm0 * cb.x, acc[8 * jj + 5] * a0 - rm0 * cb.y,
                              acc[8 * jj + 6] * a1 - rm1 * cb.x, acc[8 * jj + 7] * a1 - rm1 * cb.y};
#pragma unroll
                for (int i = 0; i < 8; i++) {
                    float t;
                    asm("tanh.approx.f32 %0, %1;" : "=f"(t) : "f"(y[i]));
                    y[i] = fmaf(y[i], t, y[i]);
                }
                const int chunk = (2 * jj + (lane >> 4)) & 3, blk = jj >> 1;
                stsm_x4(stile + blk * 4096 + mrow * 64 + ((chunk ^ ((mrow >> 1) & 3)) << 4),
                        pack_bf16(y[0], y[1]), pack_bf16(y[2], y[3]), pack_bf16(y[4], y[5]), pack_bf16(y[6], y[7]));
                if (jj & 1) {
                    fence_async_smem();
                    __syncwarp();
                    if (elect_one()) {
                        tma2d_store(mapC, stile + blk * 4096 + (warp & 3) * 1024, n0 + blk * 32, m0 + wg * 64 + (warp & 3) * 16);
                        bulk_commit();
                    }
                }
            }
            bulk_wait_read();
        }
    }
    if (tid == 0) TL(prm.tk, 3);
    if (MC) cluster_sync();
}

#define WO_ST 9
#define F2_ST 6
#define F1_ST (F1_BK == 64 ? 5 : 9)
#define QKV_ST 8
constexpr int QKV_STAGES = QKV_ST, WO_STAGES = WO_ST, FFN2_STAGES = F2_ST, FFN1_STAGES = F1_ST;
template <bool SELF>
__global__ void __launch_bounds__(288) qkv_kernel(const __grid_constant__ CUtensorMap mapA, const __grid_constant__ CUtensorMap mapWq,
                                                  const __grid_constant__ CUtensorMap mapWk, const __grid_constant__ CUtensorMap mapWv,
                                                  const __grid_constant__ CUtensorMap mapQ, const GemmParams prm) {
    extern __shared__ __align__(1024) uint8_t smem_raw[];
    const int tn = blockIdx.x & 7;
    if (tn < 2) gemm_body<80, 8, QKV_STAGES, EPI_QKV, QKV_MC, SELF>(&mapA, &mapWq, tn == 0 ? &mapWk : &mapWv, &mapA, &mapQ, prm, blockIdx.x >> 3, tn, smem_raw);
    else gemm_body<64, 8, QKV_STAGES, EPI_QKV, QKV_MC, SELF>(&mapA, &mapWq, &mapWq, &mapA, &mapQ, prm, blockIdx.x >> 3, tn, smem_raw);
}
template <int KB, int STAGES>
__global__ void __launch_bounds__(288) res_gemm_kernel(const __grid_constant__ CUtensorMap mapA, const __grid_constant__ CUtensorMap mapW,
                                                       const __grid_constant__ CUtensorMap mapR, const __grid_constant__ CUtensorMap mapC, const GemmParams prm) {
    extern __shared__ __align__(1024) uint8_t smem_raw[];
    gemm_body<64, KB, STAGES, EPI_RES, (KB == 8 ? WO_MC : F2_MC)>(&mapA, &mapW, &mapW, &mapR, &mapC, prm, blockIdx.x >> 3, blockIdx.x & 7, smem_raw);
}
__global__ void __launch_bounds__(F1_INLINE ? 256 : 288) ffn1_kernel(const __grid_constant__ CUtensorMap mapA, const __grid_constant__ CUtensorMap mapW4,
                                                   const __grid_constant__ CUtensorMap mapW3, const __grid_constant__ CUtensorMap mapH, const GemmParams prm) {
    extern __shared__ __align__(1024) uint8_t smem_raw[];
    const int pair = blockIdx.x >> 1, tile_n = pair & 7, tile_m = (pair >> 3) * 2 + (blockIdx.x & 1);
    gemm_body<224, 512 / F1_BK, FFN1_STAGES, EPI_FFN1, F1_MC>(&mapA, &mapW4, &mapW3, &mapA, &mapH, prm, tile_m, tile_n, smem_raw);
}

constexpr int NPOLY = 10;
__host__ __device__ constexpr bool is_mufu(int i) { return ((i + 1) * (16 - NPOLY)) / 16 != (i * (16 - NPOLY)) / 16; }

__device__ __forceinline__ float ex2(float x) { float r; asm("ex2.approx.ftz.f32 %0, %1;" : "=f"(r) : "f"(x)); return r; }
__device__ __forceinline__ uint32_t exp_pair_mufu(float a, float b) { return pack_bf16(ex2(a), ex2(b)); }
__device__ __forceinline__ uint32_t exp_pair_fma(float a, float b, uint32_t c3f) {
    constexpr float MAGIC = 98430.4140625f;
    const float ta = a + MAGIC, tb = b + (MAGIC - 143.5f);
    uint32_t y, m, r;
    asm("mad.lo.u32 %0, %1, 65536, %2;" : "=r"(y) : "r"(__float_as_uint(tb)), "r"(__float_as_uint(ta)));
    asm("lop3.b32 %0, %1, 0x007F007F, %2, 0xEA;" : "=r"(m) : "r"(y), "r"(c3f));
    const uint32_t e = y & 0xFF80FF80u;
    asm("fma.rn.bf16x2 %0, %1, %2, %3;" : "=r"(r) : "r"(y), "r"(m), "r"(e));
    return r;
}

constexpr int KCH = 256, NCH = S_ / KCH;
constexpr int K_BYTES = S_ * 32, V_BYTES = (S_ / 16) * 768;
constexpr int ATT_SMEM = K_BYTES + V_BYTES;

__global__ void __launch_bounds__(512, 1) attn_kernel(const __nv_bfloat16* __restrict__ wo, const __nv_bfloat16* __restrict__ w1,
                                                       const __nv_bfloat16* __restrict__ w2, int tk) {
    extern __shared__ __align__(1024) uint8_t smem[];
    __shared__ uint64_t bars[NCH];
    __shared__ int s_slow;
    const int tid = threadIdx.x, wg = tid >> 7, warp = (tid >> 5) & 3, lane = tid & 31;
    const uint32_t sK = smem_u32(smem), sV = sK + K_BYTES;
    if (blockIdx.x >= 128) {
        pdl_launch();
        side_job(blockIdx.x - 128, (float*)smem, wo, w1, w2);
        return;
    }
    if (tid == 0) TL(tk, 0);
    if (tid == 0) {
        for (int i = 0; i < NCH; i++) mbar_init(smem_u32(&bars[i]), 1);
        s_slow = 0;
        fence_mbar_init();
    }
    __syncthreads();
    pdl_launch();
    pdl_wait();
    if (tid == 0) TL(tk, 1);
    if (__shfl_sync(0xffffffffu, tid >> 5, 0) == 0 && elect_one()) {
#pragma unroll
        for (int i = 0; i < NCH; i++) {
            mbar_expect_tx(smem_u32(&bars[i]), KCH * 32 + (KCH / 16) * 768);
            bulk_load(sK + i * KCH * 32, g_kimg + i * KCH * 32, KCH * 32, smem_u32(&bars[i]));
            bulk_load(sV + i * (KCH / 16) * 768, g_vimg + i * (KCH / 16) * 768, (KCH / 16) * 768, smem_u32(&bars[i]));
        }
    }
    const int tb = blockIdx.x >> 3, hg = blockIdx.x & 7;
    const int head = hg * 4 + wg;
    const int g = lane >> 2, c = lane & 3;
    uint32_t qa[2][4];
    float qn = 0.f;
#pragma unroll
    for (int m = 0; m < 2; m++) {
        const int row = tb * 128 + m * 64 + warp * 16 + g;
        const uint32_t* p0 = (const uint32_t*)(g_q + (size_t)row * D_ + head * 16);
        const uint32_t* p1 = (const uint32_t*)(g_q + (size_t)(row + 8) * D_ + head * 16);
        qa[m][0] = p0[c]; qa[m][1] = p1[c]; qa[m][2] = p0[c + 4]; qa[m][3] = p1[c + 4];
        float n0 = bf_lo(qa[m][0]) * bf_lo(qa[m][0]) + bf_hi(qa[m][0]) * bf_hi(qa[m][0]) + bf_lo(qa[m][2]) * bf_lo(qa[m][2]) + bf_hi(qa[m][2]) * bf_hi(qa[m][2]);
        float n1 = bf_lo(qa[m][1]) * bf_lo(qa[m][1]) + bf_hi(qa[m][1]) * bf_hi(qa[m][1]) + bf_lo(qa[m][3]) * bf_lo(qa[m][3]) + bf_hi(qa[m][3]) * bf_hi(qa[m][3]);
        n0 += __shfl_xor_sync(0xffffffffu, n0, 1); n0 += __shfl_xor_sync(0xffffffffu, n0, 2);
        n1 += __shfl_xor_sync(0xffffffffu, n1, 1); n1 += __shfl_xor_sync(0xffffffffu, n1, 2);
        if (!(n0 == n0) || !(n1 == n1)) n0 = __int_as_float(0x7f800000);
        qn = fmaxf(qn, fmaxf(n0, n1));
    }
    {
        float km = 0.f, vm = 0.f;
#pragma unroll
        for (int i = 0; i < 16; i++) { km = fmaxf(km, g_kvmax[i]); vm = fmaxf(vm, g_kvmax[16 + i]); }
        const bool ok = (qn * km <= 10000.f) && (vm <= 16384.f);
        if (!ok) s_slow = 1;
    }
    float oacc[2][12];
#pragma unroll
    for (int m = 0; m < 2; m++)
#pragma unroll
        for (int i = 0; i < 12; i++) oacc[m][i] = 0.f;
    __syncthreads();
    const bool slow = s_slow != 0;

    const uint64_t dK0 = mkdesc(sK, 128, 256, 0);
    const uint64_t dV0 = mkdesc(sV, 128, 256, 0);
    uint32_t c3f;
    asm volatile("mov.b32 %0, 0x3F003F00;" : "=r"(c3f));
    if (!slow) {
#pragma unroll 1
        for (int t = 0; t < S_ / 64; t++) {
            if ((t & 3) == 0) mbar_wait(smem_u32(&bars[t >> 2]), 0);
            const uint64_t dK = dK0 + (uint64_t)(t * 64 * 32 / 16);
            const uint64_t dV = dV0 + (uint64_t)(t * 4 * 768 / 16);
#pragma unroll
            for (int m = 0; m < 2; m++) {
                float s[32];
                wg_fence();
                wgmma_rs_n64_z(s, qa[m][0], qa[m][1], qa[m][2], qa[m][3], dK);
                wg_commit();
                wg_wait<0>();
                fence_regs(s);
                uint32_t p[16];
#pragma unroll
                for (int i = 0; i < 16; i++) p[i] = is_mufu(i) ? exp_pair_mufu(s[2 * i], s[2 * i + 1]) : exp_pair_fma(s[2 * i], s[2 * i + 1], c3f);
                wg_fence();
#pragma unroll
                for (int kk = 0; kk < 4; kk++)
                    wgmma_rs_n24_tb(oacc[m], p[4 * kk], p[4 * kk + 1], p[4 * kk + 2], p[4 * kk + 3], dV + (uint64_t)(kk * 768 / 16));
                wg_commit();
            }
        }
        wg_wait<0>();
    } else {
        float mx[2][2] = {{-INFINITY, -INFINITY}, {-INFINITY, -INFINITY}};
#pragma unroll 1
        for (int t = 0; t < S_ / 64; t++) {
            if ((t & 3) == 0) mbar_wait(smem_u32(&bars[t >> 2]), 0);
            const uint64_t dK = dK0 + (uint64_t)(t * 64 * 32 / 16);
            const uint64_t dV = dV0 + (uint64_t)(t * 4 * 768 / 16);
#pragma unroll
            for (int m = 0; m < 2; m++) {
                float s[32];
                wg_fence();
                wgmma_rs_n64_z(s, qa[m][0], qa[m][1], qa[m][2], qa[m][3], dK);
                wg_commit();
                wg_wait<0>();
                fence_regs(s);
                fence_regs(oacc[m]);
                float r0 = mx[m][0], r1 = mx[m][1];
#pragma unroll
                for (int j = 0; j < 8; j++) {
                    r0 = fmaxf(r0, fmaxf(s[4 * j], s[4 * j + 1]));
                    r1 = fmaxf(r1, fmaxf(s[4 * j + 2], s[4 * j + 3]));
                }
                r0 = fmaxf(r0, __shfl_xor_sync(0xffffffffu, r0, 1)); r0 = fmaxf(r0, __shfl_xor_sync(0xffffffffu, r0, 2));
                r1 = fmaxf(r1, __shfl_xor_sync(0xffffffffu, r1, 1)); r1 = fmaxf(r1, __shfl_xor_sync(0xffffffffu, r1, 2));
                const float al0 = ex2(mx[m][0] - r0), al1 = ex2(mx[m][1] - r1);
                mx[m][0] = r0; mx[m][1] = r1;
#pragma unroll
                for (int j = 0; j < 3; j++) {
                    oacc[m][4 * j] *= al0; oacc[m][4 * j + 1] *= al0;
                    oacc[m][4 * j + 2] *= al1; oacc[m][4 * j + 3] *= al1;
                }
                uint32_t p[16];
#pragma unroll
                for (int j = 0; j < 8; j++) {
                    p[2 * j] = pack_bf16(ex2(s[4 * j] - r0), ex2(s[4 * j + 1] - r0));
                    p[2 * j + 1] = pack_bf16(ex2(s[4 * j + 2] - r1), ex2(s[4 * j + 3] - r1));
                }
                fence_regs(oacc[m]);
                wg_fence();
#pragma unroll
                for (int kk = 0; kk < 4; kk++)
                    wgmma_rs_n24_tb(oacc[m], p[4 * kk], p[4 * kk + 1], p[4 * kk + 2], p[4 * kk + 3], dV + (uint64_t)(kk * 768 / 16));
                wg_commit();
                wg_wait<0>();
            }
        }
    }
    fence_regs(oacc[0]); fence_regs(oacc[1]);
    if (tid == 0) TL(tk, 2);
#pragma unroll
    for (int m = 0; m < 2; m++) {
        const float l0 = __shfl_sync(0xffffffffu, oacc[m][8], lane & ~3);
        const float l1 = __shfl_sync(0xffffffffu, oacc[m][10], lane & ~3);
        const float r0 = 1.0f / l0, r1 = 1.0f / l1;
        const int row = tb * 128 + m * 64 + warp * 16 + g;
        uint32_t* p0 = (uint32_t*)(g_o + (size_t)row * D_ + head * 16);
        uint32_t* p1 = (uint32_t*)(g_o + (size_t)(row + 8) * D_ + head * 16);
        p0[c] = pack_bf16(oacc[m][0] * r0, oacc[m][1] * r0);
        p1[c] = pack_bf16(oacc[m][2] * r1, oacc[m][3] * r1);
        p0[c + 4] = pack_bf16(oacc[m][4] * r0, oacc[m][5] * r0);
        p1[c + 4] = pack_bf16(oacc[m][6] * r1, oacc[m][7] * r1);
    }
    if (tid == 0) TL(tk, 3);
}

typedef CUresult (*EncodeFn)(CUtensorMap*, CUtensorMapDataType, cuuint32_t, void*, const cuuint64_t*, const cuuint64_t*, const cuuint32_t*,
                             const cuuint32_t*, CUtensorMapInterleave, CUtensorMapSwizzle, CUtensorMapL2promotion, CUtensorMapFloatOOBfill);

EncodeFn get_encode() {
    static EncodeFn fn = nullptr;
    if (!fn) {
        void* p = nullptr;
        cudaDriverEntryPointQueryResult qr;
        cudaGetDriverEntryPoint("cuTensorMapEncodeTiled", &p, cudaEnableDefault, &qr);
        fn = (EncodeFn)p;
    }
    return fn;
}
CUtensorMap map2d(const void* ptr, uint64_t cols, uint64_t rows, uint32_t bc, uint32_t br, CUtensorMapSwizzle sw) {
    CUtensorMap m;
    cuuint64_t gd[2] = {cols, rows}, gs[1] = {cols * 2};
    cuuint32_t bx[2] = {bc, br}, es[2] = {1, 1};
    get_encode()(&m, CU_TENSOR_MAP_DATA_TYPE_BFLOAT16, 2, (void*)ptr, gd, gs, bx, es, CU_TENSOR_MAP_INTERLEAVE_NONE, sw,
                 CU_TENSOR_MAP_L2_PROMOTION_L2_128B, CU_TENSOR_MAP_FLOAT_OOB_FILL_NONE);
    return m;
}
CUtensorMap map3d32(const void* ptr, uint64_t cols, uint64_t rows, uint32_t br, uint32_t nb) {
    CUtensorMap m;
    cuuint64_t gd[3] = {32, rows, cols / 32}, gs[2] = {cols * 2, 64};
    cuuint32_t bx[3] = {32, br, nb}, es[3] = {1, 1, 1};
    get_encode()(&m, CU_TENSOR_MAP_DATA_TYPE_BFLOAT16, 3, (void*)ptr, gd, gs, bx, es, CU_TENSOR_MAP_INTERLEAVE_NONE, CU_TENSOR_MAP_SWIZZLE_64B,
                 CU_TENSOR_MAP_L2_PROMOTION_L2_128B, CU_TENSOR_MAP_FLOAT_OOB_FILL_NONE);
    return m;
}

template <typename... KArgs, typename... Args>
void launch(void (*kern)(KArgs...), int grid, int block, int smem, int cluster, bool pdl, Args... args) {
    cudaLaunchConfig_t cfg = {};
    cfg.gridDim = dim3(grid);
    cfg.blockDim = dim3(block);
    cfg.dynamicSmemBytes = smem;
    cfg.stream = cudaStreamPerThread;
    cudaLaunchAttribute at[2];
    int n = 0;
    if (cluster > 1) { at[n].id = cudaLaunchAttributeClusterDimension; at[n].val.clusterDim.x = cluster; at[n].val.clusterDim.y = 1; at[n].val.clusterDim.z = 1; n++; }
    if (pdl) { at[n].id = cudaLaunchAttributeProgrammaticStreamSerialization; at[n].val.programmaticStreamSerializationAllowed = 1; n++; }
    cfg.attrs = at;
    cfg.numAttrs = n;
    cudaLaunchKernelEx(&cfg, kern, KArgs(args)...);
}

template <typename T> void* sym(const T& s) { void* p = nullptr; cudaGetSymbolAddress(&p, s); return p; }

}

extern "C" void kernel_launch(void* const* d_in, const int* in_sizes, int n_in, void* d_out, int out_size) {
    const __nv_bfloat16* x = (const __nv_bfloat16*)d_in[0];
    const __nv_bfloat16* wq = (const __nv_bfloat16*)d_in[1];
    const __nv_bfloat16* wk = (const __nv_bfloat16*)d_in[2];
    const __nv_bfloat16* wv = (const __nv_bfloat16*)d_in[3];
    const __nv_bfloat16* wo = (const __nv_bfloat16*)d_in[4];
    const __nv_bfloat16* w1 = (const __nv_bfloat16*)d_in[6];
    const __nv_bfloat16* w2 = (const __nv_bfloat16*)d_in[7];

    constexpr int SM_QKV = GemmSmem<QKV_STAGES, EPI_QKV>::TOTAL;
    constexpr int HALF_PLUS = 116736;
    constexpr int SM_WO = GemmSmem<WO_STAGES, EPI_RES>::TOTAL > HALF_PLUS ? GemmSmem<WO_STAGES, EPI_RES>::TOTAL : HALF_PLUS;
    constexpr int SM_FFN2 = GemmSmem<FFN2_STAGES, EPI_RES>::TOTAL > HALF_PLUS ? GemmSmem<FFN2_STAGES, EPI_RES>::TOTAL : HALF_PLUS;
    constexpr int SM_FFN1 = GemmSmem<FFN1_STAGES, EPI_FFN1>::TOTAL;
    cudaFuncSetAttribute(qkv_kernel<false>, cudaFuncAttributeMaxDynamicSharedMemorySize, SM_QKV);
    cudaFuncSetAttribute(qkv_kernel<true>, cudaFuncAttributeMaxDynamicSharedMemorySize, SM_QKV);
    cudaFuncSetAttribute(res_gemm_kernel<8, WO_STAGES>, cudaFuncAttributeMaxDynamicSharedMemorySize, SM_WO);
    cudaFuncSetAttribute(ffn1_kernel, cudaFuncAttributeMaxDynamicSharedMemorySize, SM_FFN1);
    cudaFuncSetAttribute(res_gemm_kernel<28, FFN2_STAGES>, cudaFuncAttributeMaxDynamicSharedMemorySize, SM_FFN2);
    cudaFuncSetAttribute(attn_kernel, cudaFuncAttributeMaxDynamicSharedMemorySize, ATT_SMEM);
    cudaFuncSetAttribute(qkv_kernel<false>, cudaFuncAttributePreferredSharedMemoryCarveout, 100);
    cudaFuncSetAttribute(qkv_kernel<true>, cudaFuncAttributePreferredSharedMemoryCarveout, 100);
    cudaFuncSetAttribute(res_gemm_kernel<8, WO_STAGES>, cudaFuncAttributePreferredSharedMemoryCarveout, 100);
    cudaFuncSetAttribute(ffn1_kernel, cudaFuncAttributePreferredSharedMemoryCarveout, 100);
    cudaFuncSetAttribute(res_gemm_kernel<28, FFN2_STAGES>, cudaFuncAttributePreferredSharedMemoryCarveout, 100);
    cudaFuncSetAttribute(attn_kernel, cudaFuncAttributePreferredSharedMemoryCarveout, 100);

    void *q = sym(g_q), *o = sym(g_o), *x1 = sym(g_x1), *x2 = sym(g_x2), *x3 = sym(g_x3), *h = sym(g_h);
    float2* stats = (float2*)sym(g_stats);
    const void* xs[5] = {x, x1, x2, x3, d_out};

    const CUtensorMapSwizzle SW128 = CU_TENSOR_MAP_SWIZZLE_128B, SW64 = CU_TENSOR_MAP_SWIZZLE_64B;
    const CUtensorMap mWq = map3d32(wq, D_, D_, 64, 2);
    const CUtensorMap mWk = map2d(wk, 16, D_, 32, 64, SW64);
    const CUtensorMap mWv = map2d(wv, 16, D_, 32, 64, SW64);
    const CUtensorMap mWo = map2d(wo, D_, D_, 64, 64, SW128);
    const CUtensorMap mW1a = map3d32(w1, F_, D_, F1_BK, 4), mW1b = map3d32(w1, F_, D_, F1_BK, 3);
    const CUtensorMap mW2 = map2d(w2, D_, F_, 64, 64, SW128);
    const CUtensorMap mQ = map2d(q, D_, S_, 64, 64, SW128);
    const CUtensorMap mHst = map2d(h, F_, S_, 32, 16, SW64);
    CUtensorMap mXa[4], mXf[4], mXr[4], mXs[5];
    for (int i = 0; i < 4; i++) {
        mXa[i] = map2d(xs[i], D_, S_, 64, QKV_MC ? 64 : 128, SW128);
        mXf[i] = F1_BK == 64 ? map2d(xs[i], D_, S_, 64, 128, SW128) : map2d(xs[i], D_, S_, 32, 128, SW64);
        mXr[i] = map2d(xs[i], D_, S_, 64, 128, SW128);
    }
    for (int i = 0; i < 5; i++) mXs[i] = map2d(xs[i], D_, S_, 64, 64, SW128);
    const CUtensorMap mOa = map2d(o, D_, S_, 64, WO_MC ? 64 : 128, SW128);
    const CUtensorMap mHa = map2d(h, F_, S_, 64, F2_MC ? 64 : 128, SW128);

    for (int layer = 0; layer < 2; layer++) {
        const int xi = layer * 2;
        GemmParams p;
        p.stats_in = stats + (size_t)xi * 8 * S_; p.stats_out = nullptr; p.tk = 1 + 5 * layer;
        if (layer == 0) launch(qkv_kernel<true>, 128, 288, SM_QKV, QKV_MC ? 2 : 1, false, mXa[xi], mWq, mWk, mWv, mQ, p);
        else launch(qkv_kernel<false>, 128, 288, SM_QKV, QKV_MC ? 2 : 1, true, mXa[xi], mWq, mWk, mWv, mQ, p);
        launch(attn_kernel, layer == 0 ? 128 + SIDE_CTAS : 128, 512, ATT_SMEM, 1, true, wo, w1, w2, 2 + 5 * layer);
        p.stats_in = nullptr; p.stats_out = stats + (size_t)(xi + 1) * 8 * S_; p.tk = 3 + 5 * layer;
        launch(res_gemm_kernel<8, WO_STAGES>, 128, 288, SM_WO, WO_MC ? 2 : 1, true, mOa, mWo, mXr[xi], mXs[xi + 1], p);
        p.stats_in = stats + (size_t)(xi + 1) * 8 * S_; p.stats_out = nullptr; p.tk = 4 + 5 * layer;
        launch(ffn1_kernel, 128, F1_INLINE ? 256 : 288, SM_FFN1, F1_MC ? 2 : 1, true, mXf[xi + 1], mW1a, mW1b, mHst, p);
        p.stats_in = nullptr; p.stats_out = layer == 0 ? stats + (size_t)2 * 8 * S_ : nullptr; p.tk = 5 + 5 * layer;
        launch(res_gemm_kernel<28, FFN2_STAGES>, 128, 288, SM_FFN2, F2_MC ? 2 : 1, true, mHa, mW2, mXr[xi + 1], mXs[xi + 2], p);
    }
}
```

```cpp
#include <cuda_runtime.h>
#include <cuda_bf16.h>
#include <cuda.h>
#include <stdint.h>

#define F1_INLINE 0
#define QKV_MC 0
#define WO_MC 0
#define F2_MC 0
#define F1_MC 2
#define PREB 2
#define RES_WAIT0 0

namespace {

constexpr int S_ = 2048, D_ = 512, H_ = 32, F_ = 1792;

__device__ __align__(1024) __nv_bfloat16 g_q[S_ * D_];
__device__ __align__(1024) __nv_bfloat16 g_o[S_ * D_];
__device__ __align__(1024) __nv_bfloat16 g_x1[S_ * D_];
__device__ __align__(1024) __nv_bfloat16 g_x2[S_ * D_];
__device__ __align__(1024) __nv_bfloat16 g_x3[S_ * D_];
__device__ __align__(1024) __nv_bfloat16 g_h[S_ * F_];
__device__ __align__(1024) uint8_t g_kimg[S_ * 32];
__device__ __align__(1024) uint8_t g_vimg[(S_ / 16) * 768];
__device__ __align__(1024) float2 g_stats[4][8 * S_];
__device__ __align__(16) float g_cs_q[D_];
__device__ __align__(16) float g_cs_kv[32];
__device__ __align__(16) float g_cs_1[F_];
__device__ __align__(16) float g_kvmax[32];

#define TL(k, slot)

__device__ __forceinline__ uint32_t smem_u32(const void* p) { return (uint32_t)__cvta_generic_to_shared(p); }
__device__ __forceinline__ void mbar_init(uint32_t bar, uint32_t cnt) {
    asm volatile("mbarrier.init.shared::cta.b64 [%0], %1;" ::"r"(bar), "r"(cnt));
}
__device__ __forceinline__ void mbar_expect_tx(uint32_t bar, uint32_t bytes) {
    asm volatile("mbarrier.arrive.expect_tx.shared::cta.b64 _, [%0], %1;" ::"r"(bar), "r"(bytes) : "memory");
}
__device__ __forceinline__ void mbar_arrive(uint32_t bar) {
    asm volatile("mbarrier.arrive.shared::cta.b64 _, [%0];" ::"r"(bar) : "memory");
}
__device__ __forceinline__ void mbar_arrive_remote(uint32_t bar, uint32_t cta) {
    asm volatile("{\n.reg .b32 ra;\nmapa.shared::cluster.u32 ra, %0, %1;\nmbarrier.arrive.shared::cluster.b64 _, [ra];\n}" ::"r"(bar), "r"(cta) : "memory");
}
__device__ __forceinline__ void mbar_wait(uint32_t bar, uint32_t parity) {
    asm volatile("{\n.reg .pred p;\nWAIT_%=:\nmbarrier.try_wait.parity.shared::cta.b64 p, [%0], %1;\n@p bra DONE_%=;\nbra WAIT_%=;\nDONE_%=:\n}" ::"r"(bar), "r"(parity) : "memory");
}
__device__ __forceinline__ void bulk_load(uint32_t dst, const void* src, uint32_t bytes, uint32_t bar) {
    asm volatile("cp.async.bulk.shared::cluster.global.mbarrier::complete_tx::bytes [%0], [%1], %2, [%3];" ::"r"(dst), "l"(src), "r"(bytes), "r"(bar) : "memory");
}
__device__ __forceinline__ void tma2d(uint32_t dst, const CUtensorMap* m, int c0, int c1, uint32_t bar) {
    asm volatile("cp.async.bulk.tensor.2d.shared::cluster.global.mbarrier::complete_tx::bytes [%0], [%1, {%3, %4}], [%2];" ::"r"(dst), "l"(m), "r"(bar), "r"(c0), "r"(c1) : "memory");
}
__device__ __forceinline__ void tma2d_mc(uint32_t dst, const CUtensorMap* m, int c0, int c1, uint32_t bar, uint16_t mask) {
    asm volatile("cp.async.bulk.tensor.2d.shared::cluster.global.mbarrier::complete_tx::bytes.multicast::cluster [%0], [%1, {%3, %4}], [%2], %5;" ::"r"(dst), "l"(m), "r"(bar), "r"(c0), "r"(c1), "h"(mask) : "memory");
}
__device__ __forceinline__ void tma3d(uint32_t dst, const CUtensorMap* m, int c0, int c1, int c2, uint32_t bar) {
    asm volatile("cp.async.bulk.tensor.3d.shared::cluster.global.mbarrier::complete_tx::bytes [%0], [%1, {%3, %4, %5}], [%2];" ::"r"(dst), "l"(m), "r"(bar), "r"(c0), "r"(c1), "r"(c2) : "memory");
}
__device__ __forceinline__ void tma3d_mc(uint32_t dst, const CUtensorMap* m, int c0, int c1, int c2, uint32_t bar, uint16_t mask) {
    asm volatile("cp.async.bulk.tensor.3d.shared::cluster.global.mbarrier::complete_tx::bytes.multicast::cluster [%0], [%1, {%3, %4, %5}], [%2], %6;" ::"r"(dst), "l"(m), "r"(bar), "r"(c0), "r"(c1), "r"(c2), "h"(mask) : "memory");
}
__device__ __forceinline__ void tma2d_store(const CUtensorMap* m, uint32_t src, int c0, int c1) {
    asm volatile("cp.async.bulk.tensor.2d.global.shared::cta.bulk_group [%0, {%2, %3}], [%1];" ::"l"(m), "r"(src), "r"(c0), "r"(c1) : "memory");
}
__device__ __forceinline__ void tma3d_store(const CUtensorMap* m, uint32_t src, int c0, int c1, int c2) {
    asm volatile("cp.async.bulk.tensor.3d.global.shared::cta.bulk_group [%0, {%2, %3, %4}], [%1];" ::"l"(m), "r"(src), "r"(c0), "r"(c1), "r"(c2) : "memory");
}
__device__ __forceinline__ void bulk_commit() { asm volatile("cp.async.bulk.commit_group;" ::: "memory"); }
__device__ __forceinline__ void bulk_wait_read() { asm volatile("cp.async.bulk.wait_group.read 0;" ::: "memory"); }
__device__ __forceinline__ void prefetch_tmap(const CUtensorMap* m) { asm volatile("prefetch.tensormap [%0];" ::"l"(m) : "memory"); }
__device__ __forceinline__ void fence_async_smem() { asm volatile("fence.proxy.async.shared::cta;" ::: "memory"); }
__device__ __forceinline__ void fence_mbar_init() { asm volatile("fence.mbarrier_init.release.cluster;" ::: "memory"); }
__device__ __forceinline__ void cluster_sync() { asm volatile("barrier.cluster.arrive.release.aligned;\nbarrier.cluster.wait.acquire.aligned;" ::: "memory"); }
__device__ __forceinline__ uint32_t cluster_rank() { uint32_t r; asm volatile("mov.u32 %0, %%cluster_ctarank;" : "=r"(r)); return r; }
__device__ __forceinline__ void pdl_wait() { asm volatile("griddepcontrol.wait;" ::: "memory"); }
__device__ __forceinline__ void pdl_launch() { asm volatile("griddepcontrol.launch_dependents;" ::: "memory"); }
__device__ __forceinline__ bool elect_one() {
    uint32_t p;
    asm volatile("{\n.reg .pred p;\nelect.sync _|p, 0xffffffff;\nselp.b32 %0, 1, 0, p;\n}" : "=r"(p));
    return p != 0;
}
__device__ __forceinline__ void named_bar(int id, int n) { asm volatile("bar.sync %0, %1;" ::"r"(id), "r"(n) : "memory"); }

__device__ __forceinline__ void wg_fence() { asm volatile("wgmma.fence.sync.aligned;" ::: "memory"); }
__device__ __forceinline__ void wg_commit() { asm volatile("wgmma.commit_group.sync.aligned;" ::: "memory"); }
template <int N> __device__ __forceinline__ void wg_wait() { asm volatile("wgmma.wait_group.sync.aligned %0;" ::"n"(N) : "memory"); }
template <int N> __device__ __forceinline__ void fence_regs(float (&d)[N]) {
#pragma unroll
    for (int i = 0; i < N; i++) asm volatile("" : "+f"(d[i])::"memory");
}
__device__ __forceinline__ uint64_t mkdesc(uint32_t addr, uint32_t lbo, uint32_t sbo, uint32_t swz) {
    uint64_t d = 0;
    d |= (uint64_t)((addr & 0x3FFFF) >> 4);
    d |= (uint64_t)((lbo & 0x3FFFF) >> 4) << 16;
    d |= (uint64_t)((sbo & 0x3FFFF) >> 4) << 32;
    d |= (uint64_t)swz << 62;
    return d;
}
__device__ __forceinline__ void ldsm_x4(uint32_t& r0, uint32_t& r1, uint32_t& r2, uint32_t& r3, uint32_t addr) {
    asm volatile("ldmatrix.sync.aligned.m8n8.x4.shared.b16 {%0,%1,%2,%3}, [%4];" : "=r"(r0), "=r"(r1), "=r"(r2), "=r"(r3) : "r"(addr) : "memory");
}
__device__ __forceinline__ void stsm_x4(uint32_t addr, uint32_t r0, uint32_t r1, uint32_t r2, uint32_t r3) {
    asm volatile("stmatrix.sync.aligned.m8n8.x4.shared.b16 [%0], {%1,%2,%3,%4};" ::"r"(addr), "r"(r0), "r"(r1), "r"(r2), "r"(r3) : "memory");
}
__device__ __forceinline__ void ldsm_x4_t(uint32_t& r0, uint32_t& r1, uint32_t& r2, uint32_t& r3, uint32_t addr) {
    asm volatile("ldmatrix.sync.aligned.m8n8.x4.trans.shared.b16 {%0,%1,%2,%3}, [%4];" : "=r"(r0), "=r"(r1), "=r"(r2), "=r"(r3) : "r"(addr) : "memory");
}
__device__ __forceinline__ void hmma(float (&d)[4], uint32_t a0, uint32_t a1, uint32_t a2, uint32_t a3, uint32_t b0, uint32_t b1) {
    asm volatile("mma.sync.aligned.m16n8k16.row.col.f32.bf16.bf16.f32 {%0,%1,%2,%3}, {%4,%5,%6,%7}, {%8,%9}, {%0,%1,%2,%3};"
                 : "+f"(d[0]), "+f"(d[1]), "+f"(d[2]), "+f"(d[3]) : "r"(a0), "r"(a1), "r"(a2), "r"(a3), "r"(b0), "r"(b1));
}
__device__ __forceinline__ uint32_t pack_bf16(float lo, float hi) {
    uint32_t r;
    asm("cvt.rn.bf16x2.f32 %0, %1, %2;" : "=r"(r) : "f"(hi), "f"(lo));
    return r;
}
__device__ __forceinline__ float bf_lo(uint32_t v) { return __uint_as_float(v << 16); }
__device__ __forceinline__ float bf_hi(uint32_t v) { return __uint_as_float(v & 0xFFFF0000u); }

#define WG_REGS_4(o) "+f"(d[o]), "+f"(d[o + 1]), "+f"(d[o + 2]), "+f"(d[o + 3])
#define WG_REGS_8(o) WG_REGS_4(o), WG_REGS_4(o + 4)
#define WG_REGS_16(o) WG_REGS_8(o), WG_REGS_8(o + 8)
#define WG_REGS_32(o) WG_REGS_16(o), WG_REGS_16(o + 16)

__device__ __forceinline__ void wgmma_ss_n80_tb(float (&d)[40], uint64_t dA, uint64_t dB, int sc) {
    asm volatile("{\n.reg .pred p;\nsetp.ne.b32 p, %42, 0;\n"
                 "wgmma.mma_async.sync.aligned.m64n80k16.f32.bf16.bf16 "
                 "{%0,%1,%2,%3,%4,%5,%6,%7,%8,%9,%10,%11,%12,%13,%14,%15,%16,%17,%18,%19,%20,%21,%22,%23,%24,%25,%26,%27,%28,%29,%30,%31,"
                 "%32,%33,%34,%35,%36,%37,%38,%39}, %40, %41, p, 1, 1, 0, 1;\n}\n"
                 : WG_REGS_32(0), WG_REGS_8(32) : "l"(dA), "l"(dB), "r"(sc));
}
__device__ __forceinline__ void wgmma_ss_n64_tb(float (&d)[32], uint64_t dA, uint64_t dB, int sc) {
    asm volatile("{\n.reg .pred p;\nsetp.ne.b32 p, %34, 0;\n"
                 "wgmma.mma_async.sync.aligned.m64n64k16.f32.bf16.bf16 "
                 "{%0,%1,%2,%3,%4,%5,%6,%7,%8,%9,%10,%11,%12,%13,%14,%15,%16,%17,%18,%19,%20,%21,%22,%23,%24,%25,%26,%27,%28,%29,%30,%31}, "
                 "%32, %33, p, 1, 1, 0, 1;\n}\n"
                 : WG_REGS_32(0) : "l"(dA), "l"(dB), "r"(sc));
}
__device__ __forceinline__ void wgmma_ss_n224_tb(float (&d)[112], uint64_t dA, uint64_t dB, int sc) {
    asm volatile("{\n.reg .pred p;\nsetp.ne.b32 p, %114, 0;\n"
                 "wgmma.mma_async.sync.aligned.m64n224k16.f32.bf16.bf16 "
                 "{%0,%1,%2,%3,%4,%5,%6,%7,%8,%9,%10,%11,%12,%13,%14,%15,%16,%17,%18,%19,%20,%21,%22,%23,%24,%25,%26,%27,%28,%29,%30,%31,"
                 "%32,%33,%34,%35,%36,%37,%38,%39,%40,%41,%42,%43,%44,%45,%46,%47,%48,%49,%50,%51,%52,%53,%54,%55,%56,%57,%58,%59,%60,%61,%62,%63,"
                 "%64,%65,%66,%67,%68,%69,%70,%71,%72,%73,%74,%75,%76,%77,%78,%79,%80,%81,%82,%83,%84,%85,%86,%87,%88,%89,%90,%91,%92,%93,%94,%95,"
                 "%96,%97,%98,%99,%100,%101,%102,%103,%104,%105,%106,%107,%108,%109,%110,%111}, "
                 "%112, %113, p, 1, 1, 0, 1;\n}\n"
                 : WG_REGS_32(0), WG_REGS_32(32), WG_REGS_32(64), WG_REGS_16(96) : "l"(dA), "l"(dB), "r"(sc));
}
template <int BN> __device__ __forceinline__ void wgmma_ss_tb(float (&d)[BN / 2], uint64_t dA, uint64_t dB, int sc) {
    if constexpr (BN == 64) wgmma_ss_n64_tb(d, dA, dB, sc);
    else if constexpr (BN == 80) wgmma_ss_n80_tb(d, dA, dB, sc);
    else wgmma_ss_n224_tb(d, dA, dB, sc);
}
__device__ __forceinline__ void wgmma_rs_n64_z(float (&d)[32], uint32_t a0, uint32_t a1, uint32_t a2, uint32_t a3, uint64_t dB) {
    asm volatile("{\n.reg .pred p;\nsetp.ne.b32 p, 0, 0;\n"
                 "wgmma.mma_async.sync.aligned.m64n64k16.f32.bf16.bf16 "
                 "{%0,%1,%2,%3,%4,%5,%6,%7,%8,%9,%10,%11,%12,%13,%14,%15,%16,%17,%18,%19,%20,%21,%22,%23,%24,%25,%26,%27,%28,%29,%30,%31}, "
                 "{%32,%33,%34,%35}, %36, p, 1, 1, 0;\n}\n"
                 : "=f"(d[0]), "=f"(d[1]), "=f"(d[2]), "=f"(d[3]), "=f"(d[4]), "=f"(d[5]), "=f"(d[6]), "=f"(d[7]),
                   "=f"(d[8]), "=f"(d[9]), "=f"(d[10]), "=f"(d[11]), "=f"(d[12]), "=f"(d[13]), "=f"(d[14]), "=f"(d[15]),
                   "=f"(d[16]), "=f"(d[17]), "=f"(d[18]), "=f"(d[19]), "=f"(d[20]), "=f"(d[21]), "=f"(d[22]), "=f"(d[23]),
                   "=f"(d[24]), "=f"(d[25]), "=f"(d[26]), "=f"(d[27]), "=f"(d[28]), "=f"(d[29]), "=f"(d[30]), "=f"(d[31])
                 : "r"(a0), "r"(a1), "r"(a2), "r"(a3), "l"(dB));
}
__device__ __forceinline__ void wgmma_rs_n24_tb(float (&d)[12], uint32_t a0, uint32_t a1, uint32_t a2, uint32_t a3, uint64_t dB) {
    asm volatile("{\n.reg .pred p;\nsetp.eq.b32 p, 0, 0;\n"
                 "wgmma.mma_async.sync.aligned.m64n24k16.f32.bf16.bf16 "
                 "{%0,%1,%2,%3,%4,%5,%6,%7,%8,%9,%10,%11}, {%12,%13,%14,%15}, %16, p, 1, 1, 1;\n}\n"
                 : WG_REGS_8(0), WG_REGS_4(8) : "r"(a0), "r"(a1), "r"(a2), "r"(a3), "l"(dB));
}

constexpr int SIDE_CTAS = 4;
__device__ __forceinline__ void side_job(int cta, float* red  , const __nv_bfloat16* __restrict__ wo,
                                         const __nv_bfloat16* __restrict__ w1, const __nv_bfloat16* __restrict__ w2) {
    const int tid = threadIdx.x, warp = tid >> 5, lane = tid & 31;
    for (int line = cta * 512 + tid; line < 18432; line += SIDE_CTAS * 512) {
        const char* p = line < 4096 ? (const char*)wo + (size_t)line * 128 : (const char*)w2 + (size_t)(line - 4096) * 128;
        asm volatile("prefetch.global.L2 [%0];" ::"l"(p));
    }
    const int rg = lane >> 3, c8 = lane & 7;
    for (int slab = cta; slab < F_ / 64; slab += SIDE_CTAS) {
        const __nv_bfloat16* base = w1 + slab * 64 + c8 * 8;
        uint4 v[8];
#pragma unroll
        for (int i = 0; i < 8; i++) v[i] = __ldg((const uint4*)(base + (size_t)(warp * 32 + rg + 4 * i) * F_));
        float acc[8];
#pragma unroll
        for (int i = 0; i < 8; i++) acc[i] = 0.f;
#pragma unroll
        for (int i = 0; i < 8; i++) {
            acc[0] += bf_lo(v[i].x); acc[1] += bf_hi(v[i].x); acc[2] += bf_lo(v[i].y); acc[3] += bf_hi(v[i].y);
            acc[4] += bf_lo(v[i].z); acc[5] += bf_hi(v[i].z); acc[6] += bf_lo(v[i].w); acc[7] += bf_hi(v[i].w);
        }
#pragma unroll
        for (int i = 0; i < 8; i++) {
            acc[i] += __shfl_xor_sync(0xffffffffu, acc[i], 8);
            acc[i] += __shfl_xor_sync(0xffffffffu, acc[i], 16);
        }
        if (rg == 0) {
#pragma unroll
            for (int i = 0; i < 8; i++) red[warp * 64 + c8 * 8 + i] = acc[i];
        }
        __syncthreads();
        if (tid < 64) {
            float s = 0.f;
#pragma unroll
            for (int i = 0; i < 16; i++) s += red[i * 64 + tid];
            g_cs_1[slab * 64 + tid] = s;
        }
        __syncthreads();
    }
}

enum { EPI_QKV = 0, EPI_RES = 1, EPI_FFN1 = 2 };

struct GemmParams {
    const float2* stats_in;
    float2* stats_out;
    int tk;
};

template <int BK_, int NBLK> struct Geo {
    static constexpr int BK = BK_, A_BYTES = 128 * BK * 2, A_SWZ = BK == 64 ? 1 : 2, A_SBO = BK * 16;
    static constexpr int BLK = BK * 64;
    static constexpr int B_BYTES = NBLK * BLK, B_SWZ = 2, B_LBO = BLK, B_SBO = 512, B_KSTEP = 1024;
};
template <> struct Geo<64, 0> {
    static constexpr int BK = 64, A_BYTES = 128 * 128, A_SWZ = 1, A_SBO = 1024, BLK = 8192;
    static constexpr int B_BYTES = 64 * 128, B_SWZ = 1, B_LBO = 8192, B_SBO = 1024, B_KSTEP = 2048;
};
#define F1_BK 32
template <int EPI> struct EpiGeo;
template <> struct EpiGeo<EPI_QKV> { using G = Geo<64, 3>; };
template <> struct EpiGeo<EPI_RES> { using G = Geo<64, 0>; };
template <> struct EpiGeo<EPI_FFN1> { using G = Geo<F1_BK, 7>; };

template <int STAGES, int EPI> struct GemmSmem {
    using G = typename EpiGeo<EPI>::G;
    static constexpr int STAGE = G::A_BYTES + G::B_BYTES;
    static constexpr int AUX_OFF = STAGES * STAGE;
    static constexpr int TOTAL = AUX_OFF + 1152;
};

struct RowStatRaw { float2 a0, a1, b0, b1; };
__device__ __forceinline__ RowStatRaw load_row_stats(const float2* __restrict__ st, int row0, int c) {
    RowStatRaw r;
    r.a0 = st[(2 * c) * S_ + row0]; r.a1 = st[(2 * c + 1) * S_ + row0];
    r.b0 = st[(2 * c) * S_ + row0 + 8]; r.b1 = st[(2 * c + 1) * S_ + row0 + 8];
    return r;
}
__device__ __forceinline__ void finish_row_stats(const RowStatRaw& r, float& mean0, float& rstd0, float& mean1, float& rstd1) {
    float sa = r.a0.x + r.a1.x, sb = r.b0.x + r.b1.x;
    sa += __shfl_xor_sync(0xffffffffu, sa, 1); sa += __shfl_xor_sync(0xffffffffu, sa, 2);
    sb += __shfl_xor_sync(0xffffffffu, sb, 1); sb += __shfl_xor_sync(0xffffffffu, sb, 2);
    mean0 = sa * 0.125f; mean1 = sb * 0.125f;
    float ma = r.a0.y + r.a1.y + 64.f * ((r.a0.x - mean0) * (r.a0.x - mean0) + (r.a1.x - mean0) * (r.a1.x - mean0));
    float mb = r.b0.y + r.b1.y + 64.f * ((r.b0.x - mean1) * (r.b0.x - mean1) + (r.b1.x - mean1) * (r.b1.x - mean1));
    ma += __shfl_xor_sync(0xffffffffu, ma, 1); ma += __shfl_xor_sync(0xffffffffu, ma, 2);
    mb += __shfl_xor_sync(0xffffffffu, mb, 1); mb += __shfl_xor_sync(0xffffffffu, mb, 2);
    rstd0 = 1.0f / sqrtf(ma * (1.f / 512.f) + 1e-5f);
    rstd1 = 1.0f / sqrtf(mb * (1.f / 512.f) + 1e-5f);
}

template <int BN, int KB, int STAGES, int EPI, int MC, bool SELF = false>
__device__ __forceinline__ void gemm_body(const CUtensorMap* mapA, const CUtensorMap* mapB, const CUtensorMap* mapB2, const CUtensorMap* mapR,
                                          const CUtensorMap* mapC, const GemmParams& prm, int tile_m, int tile_n, uint8_t* smem_raw) {
    using SM = GemmSmem<STAGES, EPI>;
    using G = typename SM::G;
    constexpr bool XKV = BN == 80;
    constexpr int TN = EPI == EPI_QKV ? 64 : BN;
    pdl_launch();
    const uint32_t sbase = smem_u32(smem_raw);
    if (sbase & 1023) __trap();
    uint8_t* sgen = smem_raw;
    const uint32_t bar_full = sbase + SM::AUX_OFF, bar_empty = bar_full + 8 * STAGES;
    float* s_cs = (float*)(sgen + SM::AUX_OFF + 256);
    float* s_red = (float*)(sgen + SM::AUX_OFF + 768);
    const int tid = threadIdx.x, lane = tid & 31;
    const int warp = __shfl_sync(0xffffffffu, tid >> 5, 0);
    const uint32_t rank = MC ? cluster_rank() : 0;
    if (tid == 0) TL(prm.tk, 0);

    constexpr bool INLINE_PROD = EPI == EPI_FFN1 && F1_INLINE;
    constexpr int PWARP = INLINE_PROD ? 0 : 8;
    if (warp == PWARP && elect_one()) {
        prefetch_tmap(mapB); prefetch_tmap(mapA); prefetch_tmap(mapC);
        for (int s = 0; s < STAGES; s++) { mbar_init(bar_full + 8 * s, 1); mbar_init(bar_empty + 8 * s, MC ? 4 : 2); }
        fence_mbar_init();
    }
    __syncthreads();
    if (MC) cluster_sync();

    const int m0 = tile_m * 128, n0 = tile_n * TN;
    constexpr uint32_t STAGE_TX = G::A_BYTES + (EPI == EPI_QKV ? (XKV ? 3 : 2) * G::BLK : G::B_BYTES);
    auto loadB = [&](int kb, int s) {
        const uint32_t dst = sbase + s * SM::STAGE + G::A_BYTES, bar = bar_full + 8 * s;
        if constexpr (EPI == EPI_RES) {
            tma2d(dst, mapB, n0, kb * 64, bar);
        } else if constexpr (EPI == EPI_QKV) {
            tma3d(dst, mapB, 0, kb * G::BK, tile_n * 2, bar);
            if constexpr (XKV) tma2d(dst + 2 * G::BLK, mapB2, 0, kb * G::BK, bar);
        } else {
            if constexpr (MC == 2) {
                if (rank == 0) tma3d_mc(dst, mapB, 0, kb * G::BK, tile_n * 7, bar, 3);
                else tma3d_mc(dst + 4 * G::BLK, mapB2, 0, kb * G::BK, tile_n * 7 + 4, bar, 3);
            } else {
                tma3d(dst, mapB, 0, kb * G::BK, tile_n * 7, bar);
                tma3d(dst + 4 * G::BLK, mapB2, 0, kb * G::BK, tile_n * 7 + 4, bar);
            }
        }
    };
    auto loadA = [&](int kb, int s) {
        const uint32_t dst = sbase + s * SM::STAGE, bar = bar_full + 8 * s;
        if constexpr (MC == 1) tma2d_mc(dst + rank * (G::A_BYTES / 2), mapA, kb * G::BK, m0 + rank * 64, bar, 3);
        else tma2d(dst, mapA, kb * G::BK, m0, bar);
    };
    constexpr int PRE = STAGES < KB ? STAGES : KB;
#define F1_LAG 2
    constexpr int LAG = F1_LAG;
    constexpr int PRE_B = PRE < PREB ? PRE : PREB;
    auto prologue_loads = [&]() {
        if (elect_one()) {
#pragma unroll
            for (int kb = 0; kb < PRE; kb++) mbar_expect_tx(bar_full + 8 * kb, STAGE_TX);
#pragma unroll
            for (int kb = 0; kb < PRE_B; kb++) loadB(kb, kb);
        }
        if (!SELF) pdl_wait();
        if (elect_one()) {
#pragma unroll
            for (int kb = 0; kb < PRE; kb++) {
                loadA(kb, kb);
                if (kb + PRE_B < PRE) loadB(kb + PRE_B, kb + PRE_B);
            }
            if constexpr (EPI == EPI_RES && KB < STAGES) {
                mbar_expect_tx(bar_full + 8 * KB, 16384);
                tma2d(sbase + KB * SM::STAGE, mapR, n0, m0, bar_full + 8 * KB);
            }
        }
    };
    if (!INLINE_PROD && warp == 8) {
        prologue_loads();
        int s = PRE % STAGES, ph = (PRE / STAGES) & 1;
#pragma unroll 1
        for (int kb = PRE; kb < KB; kb++) {
            mbar_wait(bar_empty + 8 * s, ph ^ 1);
            if (elect_one()) {
                mbar_expect_tx(bar_full + 8 * s, STAGE_TX);
                loadB(kb, s);
                loadA(kb, s);
            }
            if (++s == STAGES) { s = 0; ph ^= 1; }
        }
        if constexpr (EPI == EPI_RES && KB >= STAGES) {
            mbar_wait(bar_empty + 8 * s, ph ^ 1);
            if (elect_one()) {
                mbar_expect_tx(bar_full + 8 * s, 16384);
                tma2d(sbase + s * SM::STAGE, mapR, n0, m0, bar_full + 8 * s);
            }
        }
    } else {
        if (INLINE_PROD && warp == 0) prologue_loads();
        const int wg = warp >> 2, g = lane >> 2, c = lane & 3;
        const int rloc = wg * 64 + (warp & 3) * 16 + g;
        const int row0 = m0 + rloc;
        float mean0 = 0.f, rstd0 = 1.f, mean1 = 0.f, rstd1 = 1.f;
        RowStatRaw raw;
        float csv = 0.f;
        float2 cskv[2] = {make_float2(0.f, 0.f), make_float2(0.f, 0.f)};
        auto ln_inputs = [&]() {
            pdl_wait();
            if constexpr (EPI != EPI_RES) {
                raw = load_row_stats(prm.stats_in, row0, c);
                const float* cs = EPI == EPI_FFN1 ? g_cs_1 + n0 : g_cs_q + n0;
                if (tid < TN) csv = cs[tid];
                if constexpr (XKV) {
                    cskv[0] = *(const float2*)(g_cs_kv + tile_n * 16 + 2 * c);
                    cskv[1] = *(const float2*)(g_cs_kv + tile_n * 16 + 8 + 2 * c);
                }
            }
        };
        if (!SELF) ln_inputs();
        float st_s[4] = {0.f, 0.f, 0.f, 0.f}, st_q0[4] = {0.f, 0.f, 0.f, 0.f}, st_q1[4] = {0.f, 0.f, 0.f, 0.f};
        float cs_a[4] = {0.f, 0.f, 0.f, 0.f}, cs_x[4] = {0.f, 0.f, 0.f, 0.f};
        float acc[BN / 2];
        const uint64_t dA0 = mkdesc(sbase + wg * (G::A_BYTES / 2), 16, G::A_SBO, G::A_SWZ);
        const uint64_t dB0 = mkdesc(sbase + G::A_BYTES, G::B_LBO, G::B_SBO, G::B_SWZ);
        int s = 0, ph = 0;
#pragma unroll 1
        for (int kb = 0; kb < KB; kb++) {
            mbar_wait(bar_full + 8 * s, ph);
            const uint64_t dA = dA0 + (uint64_t)(s * (SM::STAGE >> 4)), dB = dB0 + (uint64_t)(s * (SM::STAGE >> 4));
            wg_fence();
#pragma unroll
            for (int k = 0; k < G::BK / 16; k++) wgmma_ss_tb<BN>(acc, dA + (uint64_t)(k * 2), dB + (uint64_t)(k * (G::B_KSTEP >> 4)), (kb | k) != 0);
            wg_commit();
            if constexpr (SELF) {
                static_assert(!SELF || (STAGES >= KB && EPI == EPI_QKV), "SELF needs every k block resident");
                constexpr uint32_t ONES = 0x3F803F80u;
                const int mr = wg * 64 + (warp & 3) * 16 + (lane & 7) + ((lane >> 3) & 1) * 8;
                const uint32_t arow = sbase + s * SM::STAGE + mr * 128;
#pragma unroll
                for (int q = 0; q < 4; q++) {
                    uint32_t a0, a1, a2, a3;
                    ldsm_x4(a0, a1, a2, a3, arow + (((2 * q + (lane >> 4)) ^ (mr & 7)) << 4));
                    hmma(st_s, a0, a1, a2, a3, ONES, ONES);
                    hmma(st_q0, a0, a1, a2, a3, a0, a2);
                    hmma(st_q1, a0, a1, a2, a3, a1, a3);
                }
                const uint32_t bblk = sbase + s * SM::STAGE + G::A_BYTES;
#pragma unroll
                for (int q = 0; q < 2; q++) {
                    const int krow = q * 32 + lane;
                    uint32_t b0, b1, b2, b3;
                    ldsm_x4_t(b0, b1, b2, b3, bblk + (warp >> 2) * G::BLK + krow * 64 + (((warp & 3) ^ ((krow >> 1) & 3)) << 4));
                    hmma(cs_a, ONES, ONES, ONES, ONES, b0, b1);
                    hmma(cs_a, ONES, ONES, ONES, ONES, b2, b3);
                    if constexpr (XKV) {
                        if (warp < 2) {
                            ldsm_x4_t(b0, b1, b2, b3, bblk + 2 * G::BLK + krow * 64 + ((warp ^ ((krow >> 1) & 3)) << 4));
                            hmma(cs_x, ONES, ONES, ONES, ONES, b0, b1);
                            hmma(cs_x, ONES, ONES, ONES, ONES, b2, b3);
                        }
                    }
                }
            }
            if constexpr (EPI == EPI_RES && RES_WAIT0) {
                wg_wait<0>();
                if ((warp & 3) == 0 && elect_one()) {
                    if (MC) { mbar_arrive_remote(bar_empty + 8 * s, 0); mbar_arrive_remote(bar_empty + 8 * s, 1); }
                    else mbar_arrive(bar_empty + 8 * s);
                }
            } else if (kb > 0) {
                wg_wait<1>();
                const int sp = s == 0 ? STAGES - 1 : s - 1;
                if ((warp & 3) == 0 && elect_one()) {
                    if (MC) { mbar_arrive_remote(bar_empty + 8 * sp, 0); mbar_arrive_remote(bar_empty + 8 * sp, 1); }
                    else mbar_arrive(bar_empty + 8 * sp);
                }
                if (INLINE_PROD && warp == 0 && kb >= LAG && kb - LAG + STAGES < KB) {
                    const int sq = LAG == 1 ? sp : (sp == 0 ? STAGES - 1 : sp - 1);
                    mbar_wait(bar_empty + 8 * sq, ((kb - LAG) / STAGES) & 1);
                    if (elect_one()) {
                        mbar_expect_tx(bar_full + 8 * sq, STAGE_TX);
                        loadB(kb - LAG + STAGES, sq);
                        loadA(kb - LAG + STAGES, sq);
                    }
                }
            }
            if (++s == STAGES) { s = 0; ph ^= 1; }
        }
        if constexpr (SELF) {
            const int src = (lane & 28) | (g >> 1);
            const float qa = __shfl_sync(0xffffffffu, (g & 1) ? st_q0[1] : st_q0[0], src);
            const float qb = __shfl_sync(0xffffffffu, (g & 1) ? st_q1[3] : st_q1[2], src);
            mean0 = st_s[0] * (1.f / 512.f); mean1 = st_s[2] * (1.f / 512.f);
            rstd0 = 1.0f / sqrtf(fmaxf(qa * (1.f / 512.f) - mean0 * mean0, 0.f) + 1e-5f);
            rstd1 = 1.0f / sqrtf(fmaxf(qb * (1.f / 512.f) - mean1 * mean1, 0.f) + 1e-5f);
            if (lane < 4) {
                *(float2*)(s_cs + warp * 8 + 2 * c) = make_float2(cs_a[0], cs_a[1]);
                if (tile_m == 0) *(float2*)(g_cs_q + n0 + warp * 8 + 2 * c) = make_float2(cs_a[0], cs_a[1]);
                if constexpr (XKV) {
                    if (warp < 2) {
                        *(float2*)(s_cs + 64 + warp * 8 + 2 * c) = make_float2(cs_x[0], cs_x[1]);
                        if (tile_m == 0) *(float2*)(g_cs_kv + tile_n * 16 + warp * 8 + 2 * c) = make_float2(cs_x[0], cs_x[1]);
                    }
                }
            }
        } else if constexpr (EPI != EPI_RES) {
            finish_row_stats(raw, mean0, rstd0, mean1, rstd1);
            if (tid < TN) s_cs[tid] = csv;
        }
        wg_wait<0>();
        fence_regs(acc);
        if (tid == 0) TL(prm.tk, 2);
        if constexpr (EPI != EPI_RES) named_bar(1, 256);

        if constexpr (EPI != EPI_FFN1) {
            const uint32_t stile = sbase + (EPI == EPI_RES ? s * SM::STAGE : 0);
            const int mrow = wg * 64 + (warp & 3) * 16 + (lane & 7) + ((lane >> 3) & 1) * 8;
            const uint32_t rbase = stile + mrow * 128;
            if constexpr (EPI == EPI_RES) {
                mbar_wait(bar_full + 8 * s, ph);
                float s0 = 0.f, s1 = 0.f;
#pragma unroll
                for (int jj = 0; jj < 4; jj++) {
                    uint32_t r0, r1, r2, r3;
                    const uint32_t addr = rbase + (((2 * jj + (lane >> 4)) ^ (mrow & 7)) << 4);
                    ldsm_x4(r0, r1, r2, r3, addr);
                    const uint32_t u0 = pack_bf16(acc[8 * jj] + bf_lo(r0), acc[8 * jj + 1] + bf_hi(r0));
                    const uint32_t u1 = pack_bf16(acc[8 * jj + 2] + bf_lo(r1), acc[8 * jj + 3] + bf_hi(r1));
                    const uint32_t u2 = pack_bf16(acc[8 * jj + 4] + bf_lo(r2), acc[8 * jj + 5] + bf_hi(r2));
                    const uint32_t u3 = pack_bf16(acc[8 * jj + 6] + bf_lo(r3), acc[8 * jj + 7] + bf_hi(r3));
                    stsm_x4(addr, u0, u1, u2, u3);
                    acc[8 * jj] = bf_lo(u0); acc[8 * jj + 1] = bf_hi(u0); acc[8 * jj + 4] = bf_lo(u2); acc[8 * jj + 5] = bf_hi(u2);
                    acc[8 * jj + 2] = bf_lo(u1); acc[8 * jj + 3] = bf_hi(u1); acc[8 * jj + 6] = bf_lo(u3); acc[8 * jj + 7] = bf_hi(u3);
                    s0 += (acc[8 * jj] + acc[8 * jj + 1]) + (acc[8 * jj + 4] + acc[8 * jj + 5]);
                    s1 += (acc[8 * jj + 2] + acc[8 * jj + 3]) + (acc[8 * jj + 6] + acc[8 * jj + 7]);
                }
                fence_async_smem();
                named_bar(2 + wg, 128);
                if ((warp & 3) == 0 && elect_one()) { tma2d_store(mapC, stile + wg * 8192, n0, m0 + wg * 64); bulk_commit(); }
                if (prm.stats_out) {
                    s0 += __shfl_xor_sync(0xffffffffu, s0, 1); s0 += __shfl_xor_sync(0xffffffffu, s0, 2);
                    s1 += __shfl_xor_sync(0xffffffffu, s1, 1); s1 += __shfl_xor_sync(0xffffffffu, s1, 2);
                    const float mu0 = s0 * (1.f / 64.f), mu1 = s1 * (1.f / 64.f);
                    float q0 = 0.f, q1 = 0.f;
#pragma unroll
                    for (int j = 0; j < 8; j++) {
                        float d;
                        d = acc[4 * j] - mu0; q0 += d * d; d = acc[4 * j + 1] - mu0; q0 += d * d;
                        d = acc[4 * j + 2] - mu1; q1 += d * d; d = acc[4 * j + 3] - mu1; q1 += d * d;
                    }
                    q0 += __shfl_xor_sync(0xffffffffu, q0, 1); q0 += __shfl_xor_sync(0xffffffffu, q0, 2);
                    q1 += __shfl_xor_sync(0xffffffffu, q1, 1); q1 += __shfl_xor_sync(0xffffffffu, q1, 2);
                    if (c == 0) {
                        prm.stats_out[tile_n * S_ + row0] = make_float2(mu0, q0);
                        prm.stats_out[tile_n * S_ + row0 + 8] = make_float2(mu1, q1);
                    }
                }
            } else {
                const float sc = 0.25f * 1.4426950408889634f;
                const float a0 = rstd0 * sc, a1 = rstd1 * sc, rm0 = a0 * mean0, rm1 = a1 * mean1;
#pragma unroll
                for (int jj = 0; jj < 4; jj++) {
                    const float2 ca = *(const float2*)(s_cs + 16 * jj + 2 * c), cb = *(const float2*)(s_cs + 16 * jj + 8 + 2 * c);
                    const uint32_t u0 = pack_bf16(acc[8 * jj] * a0 - rm0 * ca.x, acc[8 * jj + 1] * a0 - rm0 * ca.y);
                    const uint32_t u1 = pack_bf16(acc[8 * jj + 2] * a1 - rm1 * ca.x, acc[8 * jj + 3] * a1 - rm1 * ca.y);
                    const uint32_t u2 = pack_bf16(acc[8 * jj + 4] * a0 - rm0 * cb.x, acc[8 * jj + 5] * a0 - rm0 * cb.y);
                    const uint32_t u3 = pack_bf16(acc[8 * jj + 6] * a1 - rm1 * cb.x, acc[8 * jj + 7] * a1 - rm1 * cb.y);
                    stsm_x4(rbase + (((2 * jj + (lane >> 4)) ^ (mrow & 7)) << 4), u0, u1, u2, u3);
                }
                fence_async_smem();
                named_bar(2 + wg, 128);
                if ((warp & 3) == 0 && elect_one()) { tma2d_store(mapC, stile + wg * 8192, n0, m0 + wg * 64); bulk_commit(); }
            }
            if constexpr (XKV) {
                {
                    const float* acx = &acc[32];
                    const float rm0 = rstd0 * mean0, rm1 = rstd1 * mean1;
                    float n0s = 0.f, n1s = 0.f, vmax = 0.f;
#pragma unroll
                    for (int j = 0; j < 2; j++) {
                        const float2 cs2 = SELF ? *(const float2*)(s_cs + 64 + 8 * j + 2 * c) : cskv[j];
                        const uint32_t u0 = pack_bf16(acx[4 * j] * rstd0 - rm0 * cs2.x, acx[4 * j + 1] * rstd0 - rm0 * cs2.y);
                        const uint32_t u1 = pack_bf16(acx[4 * j + 2] * rstd1 - rm1 * cs2.x, acx[4 * j + 3] * rstd1 - rm1 * cs2.y);
                        n0s += bf_lo(u0) * bf_lo(u0) + bf_hi(u0) * bf_hi(u0);
                        n1s += bf_lo(u1) * bf_lo(u1) + bf_hi(u1) * bf_hi(u1);
                        vmax = fmaxf(vmax, fmaxf(fmaxf(fabsf(bf_lo(u0)), fabsf(bf_hi(u0))), fmaxf(fabsf(bf_lo(u1)), fabsf(bf_hi(u1)))));
                        if (tile_n == 0) {
                            *(uint32_t*)(g_kimg + (row0 >> 3) * 256 + j * 128 + g * 16 + c * 4) = u0;
                            *(uint32_t*)(g_kimg + ((row0 + 8) >> 3) * 256 + j * 128 + g * 16 + c * 4) = u1;
                        } else {
                            uint8_t* vb = g_vimg + (row0 >> 4) * 768 + j * 256 + g * 16 + c * 4;
                            *(uint32_t*)(vb) = u0;
                            *(uint32_t*)(vb + 128) = u1;
                        }
                    }
                    if (tile_n == 1) {
                        uint8_t* vb = g_vimg + (row0 >> 4) * 768 + 512 + g * 16 + c * 4;
                        const uint32_t one = c == 0 ? 0x00003F80u : 0u;
                        *(uint32_t*)(vb) = one;
                        *(uint32_t*)(vb + 128) = one;
                    }
                    n0s += __shfl_xor_sync(0xffffffffu, n0s, 1); n0s += __shfl_xor_sync(0xffffffffu, n0s, 2);
                    n1s += __shfl_xor_sync(0xffffffffu, n1s, 1); n1s += __shfl_xor_sync(0xffffffffu, n1s, 2);
                    float km = tile_n == 0 ? fmaxf(n0s, n1s) : vmax;
                    if (!(n0s + n1s < INFINITY)) km = INFINITY;
#pragma unroll
                    for (int o = 1; o < 32; o <<= 1) km = fmaxf(km, __shfl_xor_sync(0xffffffffu, km, o));
                    if (lane == 0) s_red[warp] = km;
                    named_bar(1, 256);
                    if (tid == 0) {
                        float a = 0.f;
                        for (int i = 0; i < 8; i++) a = fmaxf(a, s_red[i]);
                        g_kvmax[tile_n * 16 + tile_m] = a;
                    }
                }
            }
            if ((warp & 3) == 0) bulk_wait_read();
        } else {
            const uint32_t stile = sbase + wg * (7 * 4096);
            const int mrow = (warp & 3) * 16 + (lane & 7) + ((lane >> 3) & 1) * 8;
            const float a0 = 0.5f * rstd0, a1 = 0.5f * rstd1, rm0 = a0 * mean0, rm1 = a1 * mean1;
#pragma unroll
            for (int jj = 0; jj < 14; jj++) {
                const float2 ca = *(const float2*)(s_cs + 16 * jj + 2 * c), cb = *(const float2*)(s_cs + 16 * jj + 8 + 2 * c);
                float y[8] = {acc[8 * jj] * a0 - rm0 * ca.x,     acc[8 * jj + 1] * a0 - rm0 * ca.y,
                              acc[8 * jj + 2] * a1 - rm1 * ca.x, acc[8 * jj + 3] * a1 - rm1 * ca.y,
                              acc[8 * jj + 4] * a0 - rm0 * cb.x, acc[8 * jj + 5] * a0 - rm0 * cb.y,
                              acc[8 * jj + 6] * a1 - rm1 * cb.x, acc[8 * jj + 7] * a1 - rm1 * cb.y};
#pragma unroll
                for (int i = 0; i < 8; i++) {
                    float t;
                    asm("tanh.approx.f32 %0, %1;" : "=f"(t) : "f"(y[i]));
                    y[i] = fmaf(y[i], t, y[i]);
                }
                const int chunk = (2 * jj + (lane >> 4)) & 3, blk = jj >> 1;
                stsm_x4(stile + blk * 4096 + mrow * 64 + ((chunk ^ ((mrow >> 1) & 3)) << 4),
                        pack_bf16(y[0], y[1]), pack_bf16(y[2], y[3]), pack_bf16(y[4], y[5]), pack_bf16(y[6], y[7]));
                if (jj & 1) {
                    fence_async_smem();
                    __syncwarp();
                    if (elect_one()) {
                        tma2d_store(mapC, stile + blk * 4096 + (warp & 3) * 1024, n0 + blk * 32, m0 + wg * 64 + (warp & 3) * 16);
                        bulk_commit();
                    }
                }
            }
            bulk_wait_read();
        }
    }
    if (tid == 0) TL(prm.tk, 3);
    if (MC) cluster_sync();
}

#define WO_ST 9
#define F2_ST 6
#define F1_ST (F1_BK == 64 ? 5 : 9)
#define QKV_ST 8
constexpr int QKV_STAGES = QKV_ST, WO_STAGES = WO_ST, FFN2_STAGES = F2_ST, FFN1_STAGES = F1_ST;
template <bool SELF>
__global__ void __launch_bounds__(288) qkv_kernel(const __grid_constant__ CUtensorMap mapA, const __grid_constant__ CUtensorMap mapWq,
                                                  const __grid_constant__ CUtensorMap mapWk, const __grid_constant__ CUtensorMap mapWv,
                                                  const __grid_constant__ CUtensorMap mapQ, const GemmParams prm) {
    extern __shared__ __align__(1024) uint8_t smem_raw[];
    const int tn = blockIdx.x & 7;
    if (tn < 2) gemm_body<80, 8, QKV_STAGES, EPI_QKV, QKV_MC, SELF>(&mapA, &mapWq, tn == 0 ? &mapWk : &mapWv, &mapA, &mapQ, prm, blockIdx.x >> 3, tn, smem_raw);
    else gemm_body<64, 8, QKV_STAGES, EPI_QKV, QKV_MC, SELF>(&mapA, &mapWq, &mapWq, &mapA, &mapQ, prm, blockIdx.x >> 3, tn, smem_raw);
}
template <int KB, int STAGES>
__global__ void __launch_bounds__(288) res_gemm_kernel(const __grid_constant__ CUtensorMap mapA, const __grid_constant__ CUtensorMap mapW,
                                                       const __grid_constant__ CUtensorMap mapR, const __grid_constant__ CUtensorMap mapC, const GemmParams prm) {
    extern __shared__ __align__(1024) uint8_t smem_raw[];
    gemm_body<64, KB, STAGES, EPI_RES, (KB == 8 ? WO_MC : F2_MC)>(&mapA, &mapW, &mapW, &mapR, &mapC, prm, blockIdx.x >> 3, blockIdx.x & 7, smem_raw);
}
__global__ void __launch_bounds__(F1_INLINE ? 256 : 288) ffn1_kernel(const __grid_constant__ CUtensorMap mapA, const __grid_constant__ CUtensorMap mapW4,
                                                   const __grid_constant__ CUtensorMap mapW3, const __grid_constant__ CUtensorMap mapH, const GemmParams prm) {
    extern __shared__ __align__(1024) uint8_t smem_raw[];
    const int pair = blockIdx.x >> 1, tile_n = pair & 7, tile_m = (pair >> 3) * 2 + (blockIdx.x & 1);
    gemm_body<224, 512 / F1_BK, FFN1_STAGES, EPI_FFN1, F1_MC>(&mapA, &mapW4, &mapW3, &mapA, &mapH, prm, tile_m, tile_n, smem_raw);
}

constexpr int NPOLY = 10;
__host__ __device__ constexpr bool is_mufu(int i) { return ((i + 1) * (16 - NPOLY)) / 16 != (i * (16 - NPOLY)) / 16; }

__device__ __forceinline__ float ex2(float x) { float r; asm("ex2.approx.ftz.f32 %0, %1;" : "=f"(r) : "f"(x)); return r; }
__device__ __forceinline__ uint32_t exp_pair_mufu(float a, float b) { return pack_bf16(ex2(a), ex2(b)); }
__device__ __forceinline__ uint32_t exp_pair_fma(float a, float b, uint32_t c3f) {
    constexpr float MAGIC = 98430.4140625f;
    const float ta = a + MAGIC, tb = b + (MAGIC - 143.5f);
    uint32_t y, m, r;
    asm("mad.lo.u32 %0, %1, 65536, %2;" : "=r"(y) : "r"(__float_as_uint(tb)), "r"(__float_as_uint(ta)));
    asm("lop3.b32 %0, %1, 0x007F007F, %2, 0xEA;" : "=r"(m) : "r"(y), "r"(c3f));
    const uint32_t e = y & 0xFF80FF80u;
    asm("fma.rn.bf16x2 %0, %1, %2, %3;" : "=r"(r) : "r"(y), "r"(m), "r"(e));
    return r;
}

constexpr int KCH = 256, NCH = S_ / KCH;
constexpr int K_BYTES = S_ * 32, V_BYTES = (S_ / 16) * 768;
constexpr int ATT_SMEM = K_BYTES + V_BYTES;

__global__ void __launch_bounds__(512, 1) attn_kernel(const __nv_bfloat16* __restrict__ wo, const __nv_bfloat16* __restrict__ w1,
                                                       const __nv_bfloat16* __restrict__ w2, int tk) {
    extern __shared__ __align__(1024) uint8_t smem[];
    __shared__ uint64_t bars[NCH];
    __shared__ int s_slow;
    const int tid = threadIdx.x, wg = tid >> 7, warp = (tid >> 5) & 3, lane = tid & 31;
    const uint32_t sK = smem_u32(smem), sV = sK + K_BYTES;
    if (blockIdx.x >= 128) {
        pdl_launch();
        side_job(blockIdx.x - 128, (float*)smem, wo, w1, w2);
        return;
    }
    if (tid == 0) TL(tk, 0);
    if (tid == 0) {
        for (int i = 0; i < NCH; i++) mbar_init(smem_u32(&bars[i]), 1);
        s_slow = 0;
        fence_mbar_init();
    }
    __syncthreads();
    pdl_launch();
    pdl_wait();
    if (tid == 0) TL(tk, 1);
    if (__shfl_sync(0xffffffffu, tid >> 5, 0) == 0 && elect_one()) {
#pragma unroll
        for (int i = 0; i < NCH; i++) {
            mbar_expect_tx(smem_u32(&bars[i]), KCH * 32 + (KCH / 16) * 768);
            bulk_load(sK + i * KCH * 32, g_kimg + i * KCH * 32, KCH * 32, smem_u32(&bars[i]));
            bulk_load(sV + i * (KCH / 16) * 768, g_vimg + i * (KCH / 16) * 768, (KCH / 16) * 768, smem_u32(&bars[i]));
        }
    }
    const int tb = blockIdx.x >> 3, hg = blockIdx.x & 7;
    const int head = hg * 4 + wg;
    const int g = lane >> 2, c = lane & 3;
    uint32_t qa[2][4];
    float qn = 0.f;
#pragma unroll
    for (int m = 0; m < 2; m++) {
        const int row = tb * 128 + m * 64 + warp * 16 + g;
        const uint32_t* p0 = (const uint32_t*)(g_q + (size_t)row * D_ + head * 16);
        const uint32_t* p1 = (const uint32_t*)(g_q + (size_t)(row + 8) * D_ + head * 16);
        qa[m][0] = p0[c]; qa[m][1] = p1[c]; qa[m][2] = p0[c + 4]; qa[m][3] = p1[c + 4];
        float n0 = bf_lo(qa[m][0]) * bf_lo(qa[m][0]) + bf_hi(qa[m][0]) * bf_hi(qa[m][0]) + bf_lo(qa[m][2]) * bf_lo(qa[m][2]) + bf_hi(qa[m][2]) * bf_hi(qa[m][2]);
        float n1 = bf_lo(qa[m][1]) * bf_lo(qa[m][1]) + bf_hi(qa[m][1]) * bf_hi(qa[m][1]) + bf_lo(qa[m][3]) * bf_lo(qa[m][3]) + bf_hi(qa[m][3]) * bf_hi(qa[m][3]);
        n0 += __shfl_xor_sync(0xffffffffu, n0, 1); n0 += __shfl_xor_sync(0xffffffffu, n0, 2);
        n1 += __shfl_xor_sync(0xffffffffu, n1, 1); n1 += __shfl_xor_sync(0xffffffffu, n1, 2);
        if (!(n0 == n0) || !(n1 == n1)) n0 = __int_as_float(0x7f800000);
        qn = fmaxf(qn, fmaxf(n0, n1));
    }
    {
        float km = 0.f, vm = 0.f;
#pragma unroll
        for (int i = 0; i < 16; i++) { km = fmaxf(km, g_kvmax[i]); vm = fmaxf(vm, g_kvmax[16 + i]); }
        const bool ok = (qn * km <= 10000.f) && (vm <= 16384.f);
        if (!ok) s_slow = 1;
    }
    float oacc[2][12];
#pragma unroll
    for (int m = 0; m < 2; m++)
#pragma unroll
        for (int i = 0; i < 12; i++) oacc[m][i] = 0.f;
    __syncthreads();
    const bool slow = s_slow != 0;

    const uint64_t dK0 = mkdesc(sK, 128, 256, 0);
    const uint64_t dV0 = mkdesc(sV, 128, 256, 0);
    uint32_t c3f;
    asm volatile("mov.b32 %0, 0x3F003F00;" : "=r"(c3f));
    if (!slow) {
#pragma unroll 1
        for (int t = 0; t < S_ / 64; t++) {
            if ((t & 3) == 0) mbar_wait(smem_u32(&bars[t >> 2]), 0);
            const uint64_t dK = dK0 + (uint64_t)(t * 64 * 32 / 16);
            const uint64_t dV = dV0 + (uint64_t)(t * 4 * 768 / 16);
#pragma unroll
            for (int m = 0; m < 2; m++) {
                float s[32];
                wg_fence();
                wgmma_rs_n64_z(s, qa[m][0], qa[m][1], qa[m][2], qa[m][3], dK);
                wg_commit();
                wg_wait<0>();
                fence_regs(s);
                uint32_t p[16];
#pragma unroll
                for (int i = 0; i < 16; i++) p[i] = is_mufu(i) ? exp_pair_mufu(s[2 * i], s[2 * i + 1]) : exp_pair_fma(s[2 * i], s[2 * i + 1], c3f);
                wg_fence();
#pragma unroll
                for (int kk = 0; kk < 4; kk++)
                    wgmma_rs_n24_tb(oacc[m], p[4 * kk], p[4 * kk + 1], p[4 * kk + 2], p[4 * kk + 3], dV + (uint64_t)(kk * 768 / 16));
                wg_commit();
            }
        }
        wg_wait<0>();
    } else {
        float mx[2][2] = {{-INFINITY, -INFINITY}, {-INFINITY, -INFINITY}};
#pragma unroll 1
        for (int t = 0; t < S_ / 64; t++) {
            if ((t & 3) == 0) mbar_wait(smem_u32(&bars[t >> 2]), 0);
            const uint64_t dK = dK0 + (uint64_t)(t * 64 * 32 / 16);
            const uint64_t dV = dV0 + (uint64_t)(t * 4 * 768 / 16);
#pragma unroll
            for (int m = 0; m < 2; m++) {
                float s[32];
                wg_fence();
                wgmma_rs_n64_z(s, qa[m][0], qa[m][1], qa[m][2], qa[m][3], dK);
                wg_commit();
                wg_wait<0>();
                fence_regs(s);
                fence_regs(oacc[m]);
                float r0 = mx[m][0], r1 = mx[m][1];
#pragma unroll
                for (int j = 0; j < 8; j++) {
                    r0 = fmaxf(r0, fmaxf(s[4 * j], s[4 * j + 1]));
                    r1 = fmaxf(r1, fmaxf(s[4 * j + 2], s[4 * j + 3]));
                }
                r0 = fmaxf(r0, __shfl_xor_sync(0xffffffffu, r0, 1)); r0 = fmaxf(r0, __shfl_xor_sync(0xffffffffu, r0, 2));
                r1 = fmaxf(r1, __shfl_xor_sync(0xffffffffu, r1, 1)); r1 = fmaxf(r1, __shfl_xor_sync(0xffffffffu, r1, 2));
                const float al0 = ex2(mx[m][0] - r0), al1 = ex2(mx[m][1] - r1);
                mx[m][0] = r0; mx[m][1] = r1;
#pragma unroll
                for (int j = 0; j < 3; j++) {
                    oacc[m][4 * j] *= al0; oacc[m][4 * j + 1] *= al0;
                    oacc[m][4 * j + 2] *= al1; oacc[m][4 * j + 3] *= al1;
                }
                uint32_t p[16];
#pragma unroll
                for (int j = 0; j < 8; j++) {
                    p[2 * j] = pack_bf16(ex2(s[4 * j] - r0), ex2(s[4 * j + 1] - r0));
                    p[2 * j + 1] = pack_bf16(ex2(s[4 * j + 2] - r1), ex2(s[4 * j + 3] - r1));
                }
                fence_regs(oacc[m]);
                wg_fence();
#pragma unroll
                for (int kk = 0; kk < 4; kk++)
                    wgmma_rs_n24_tb(oacc[m], p[4 * kk], p[4 * kk + 1], p[4 * kk + 2], p[4 * kk + 3], dV + (uint64_t)(kk * 768 / 16));
                wg_commit();
                wg_wait<0>();
            }
        }
    }
    fence_regs(oacc[0]); fence_regs(oacc[1]);
    if (tid == 0) TL(tk, 2);
#pragma unroll
    for (int m = 0; m < 2; m++) {
        const float l0 = __shfl_sync(0xffffffffu, oacc[m][8], lane & ~3);
        const float l1 = __shfl_sync(0xffffffffu, oacc[m][10], lane & ~3);
        const float r0 = 1.0f / l0, r1 = 1.0f / l1;
        const int row = tb * 128 + m * 64 + warp * 16 + g;
        uint32_t* p0 = (uint32_t*)(g_o + (size_t)row * D_ + head * 16);
        uint32_t* p1 = (uint32_t*)(g_o + (size_t)(row + 8) * D_ + head * 16);
        p0[c] = pack_bf16(oacc[m][0] * r0, oacc[m][1] * r0);
        p1[c] = pack_bf16(oacc[m][2] * r1, oacc[m][3] * r1);
        p0[c + 4] = pack_bf16(oacc[m][4] * r0, oacc[m][5] * r0);
        p1[c + 4] = pack_bf16(oacc[m][6] * r1, oacc[m][7] * r1);
    }
    if (tid == 0) TL(tk, 3);
}

typedef CUresult (*EncodeFn)(CUtensorMap*, CUtensorMapDataType, cuuint32_t, void*, const cuuint64_t*, const cuuint64_t*, const cuuint32_t*,
                             const cuuint32_t*, CUtensorMapInterleave, CUtensorMapSwizzle, CUtensorMapL2promotion, CUtensorMapFloatOOBfill);

EncodeFn get_encode() {
    static EncodeFn fn = nullptr;
    if (!fn) {
        void* p = nullptr;
        cudaDriverEntryPointQueryResult qr;
        cudaGetDriverEntryPoint("cuTensorMapEncodeTiled", &p, cudaEnableDefault, &qr);
        fn = (EncodeFn)p;
    }
    return fn;
}
CUtensorMap map2d(const void* ptr, uint64_t cols, uint64_t rows, uint32_t bc, uint32_t br, CUtensorMapSwizzle sw) {
    CUtensorMap m;
    cuuint64_t gd[2] = {cols, rows}, gs[1] = {cols * 2};
    cuuint32_t bx[2] = {bc, br}, es[2] = {1, 1};
    get_encode()(&m, CU_TENSOR_MAP_DATA_TYPE_BFLOAT16, 2, (void*)ptr, gd, gs, bx, es, CU_TENSOR_MAP_INTERLEAVE_NONE, sw,
                 CU_TENSOR_MAP_L2_PROMOTION_L2_128B, CU_TENSOR_MAP_FLOAT_OOB_FILL_NONE);
    return m;
}
CUtensorMap map3d32(const void* ptr, uint64_t cols, uint64_t rows, uint32_t br, uint32_t nb) {
    CUtensorMap m;
    cuuint64_t gd[3] = {32, rows, cols / 32}, gs[2] = {cols * 2, 64};
    cuuint32_t bx[3] = {32, br, nb}, es[3] = {1, 1, 1};
    get_encode()(&m, CU_TENSOR_MAP_DATA_TYPE_BFLOAT16, 3, (void*)ptr, gd, gs, bx, es, CU_TENSOR_MAP_INTERLEAVE_NONE, CU_TENSOR_MAP_SWIZZLE_64B,
                 CU_TENSOR_MAP_L2_PROMOTION_L2_128B, CU_TENSOR_MAP_FLOAT_OOB_FILL_NONE);
    return m;
}

template <typename... KArgs, typename... Args>
void launch(void (*kern)(KArgs...), int grid, int block, int smem, int cluster, bool pdl, Args... args) {
    cudaLaunchConfig_t cfg = {};
    cfg.gridDim = dim3(grid);
    cfg.blockDim = dim3(block);
    cfg.dynamicSmemBytes = smem;
    cfg.stream = cudaStreamPerThread;
    cudaLaunchAttribute at[2];
    int n = 0;
    if (cluster > 1) { at[n].id = cudaLaunchAttributeClusterDimension; at[n].val.clusterDim.x = cluster; at[n].val.clusterDim.y = 1; at[n].val.clusterDim.z = 1; n++; }
    if (pdl) { at[n].id = cudaLaunchAttributeProgrammaticStreamSerialization; at[n].val.programmaticStreamSerializationAllowed = 1; n++; }
    cfg.attrs = at;
    cfg.numAttrs = n;
    cudaLaunchKernelEx(&cfg, kern, KArgs(args)...);
}

template <typename T> void* sym(const T& s) { void* p = nullptr; cudaGetSymbolAddress(&p, s); return p; }

}

extern "C" void kernel_launch(void* const* d_in, const int* in_sizes, int n_in, void* d_out, int out_size) {
    const __nv_bfloat16* x = (const __nv_bfloat16*)d_in[0];
    const __nv_bfloat16* wq = (const __nv_bfloat16*)d_in[1];
    const __nv_bfloat16* wk = (const __nv_bfloat16*)d_in[2];
    const __nv_bfloat16* wv = (const __nv_bfloat16*)d_in[3];
    const __nv_bfloat16* wo = (const __nv_bfloat16*)d_in[4];
    const __nv_bfloat16* w1 = (const __nv_bfloat16*)d_in[6];
    const __nv_bfloat16* w2 = (const __nv_bfloat16*)d_in[7];

    constexpr int SM_QKV = GemmSmem<QKV_STAGES, EPI_QKV>::TOTAL;
    constexpr int HALF_PLUS = 116736;
    constexpr int SM_WO = GemmSmem<WO_STAGES, EPI_RES>::TOTAL > HALF_PLUS ? GemmSmem<WO_STAGES, EPI_RES>::TOTAL : HALF_PLUS;
    constexpr int SM_FFN2 = GemmSmem<FFN2_STAGES, EPI_RES>::TOTAL > HALF_PLUS ? GemmSmem<FFN2_STAGES, EPI_RES>::TOTAL : HALF_PLUS;
    constexpr int SM_FFN1 = GemmSmem<FFN1_STAGES, EPI_FFN1>::TOTAL;
    cudaFuncSetAttribute(qkv_kernel<false>, cudaFuncAttributeMaxDynamicSharedMemorySize, SM_QKV);
    cudaFuncSetAttribute(qkv_kernel<true>, cudaFuncAttributeMaxDynamicSharedMemorySize, SM_QKV);
    cudaFuncSetAttribute(res_gemm_kernel<8, WO_STAGES>, cudaFuncAttributeMaxDynamicSharedMemorySize, SM_WO);
    cudaFuncSetAttribute(ffn1_kernel, cudaFuncAttributeMaxDynamicSharedMemorySize, SM_FFN1);
    cudaFuncSetAttribute(res_gemm_kernel<28, FFN2_STAGES>, cudaFuncAttributeMaxDynamicSharedMemorySize, SM_FFN2);
    cudaFuncSetAttribute(attn_kernel, cudaFuncAttributeMaxDynamicSharedMemorySize, ATT_SMEM);
    cudaFuncSetAttribute(qkv_kernel<false>, cudaFuncAttributePreferredSharedMemoryCarveout, 100);
    cudaFuncSetAttribute(qkv_kernel<true>, cudaFuncAttributePreferredSharedMemoryCarveout, 100);
    cudaFuncSetAttribute(res_gemm_kernel<8, WO_STAGES>, cudaFuncAttributePreferredSharedMemoryCarveout, 100);
    cudaFuncSetAttribute(ffn1_kernel, cudaFuncAttributePreferredSharedMemoryCarveout, 100);
    cudaFuncSetAttribute(res_gemm_kernel<28, FFN2_STAGES>, cudaFuncAttributePreferredSharedMemoryCarveout, 100);
    cudaFuncSetAttribute(attn_kernel, cudaFuncAttributePreferredSharedMemoryCarveout, 100);

    void *q = sym(g_q), *o = sym(g_o), *x1 = sym(g_x1), *x2 = sym(g_x2), *x3 = sym(g_x3), *h = sym(g_h);
    float2* stats = (float2*)sym(g_stats);
    const void* xs[5] = {x, x1, x2, x3, d_out};

    const CUtensorMapSwizzle SW128 = CU_TENSOR_MAP_SWIZZLE_128B, SW64 = CU_TENSOR_MAP_SWIZZLE_64B;
    const CUtensorMap mWq = map3d32(wq, D_, D_, 64, 2);
    const CUtensorMap mWk = map2d(wk, 16, D_, 32, 64, SW64);
    const CUtensorMap mWv = map2d(wv, 16, D_, 32, 64, SW64);
    const CUtensorMap mWo = map2d(wo, D_, D_, 64, 64, SW128);
    const CUtensorMap mW1a = map3d32(w1, F_, D_, F1_BK, 4), mW1b = map3d32(w1, F_, D_, F1_BK, 3);
    const CUtensorMap mW2 = map2d(w2, D_, F_, 64, 64, SW128);
    const CUtensorMap mQ = map2d(q, D_, S_, 64, 64, SW128);
    const CUtensorMap mHst = map2d(h, F_, S_, 32, 16, SW64);
    CUtensorMap mXa[4], mXf[4], mXr[4], mXs[5];
    for (int i = 0; i < 4; i++) {
        mXa[i] = map2d(xs[i], D_, S_, 64, QKV_MC ? 64 : 128, SW128);
        mXf[i] = F1_BK == 64 ? map2d(xs[i], D_, S_, 64, 128, SW128) : map2d(xs[i], D_, S_, 32, 128, SW64);
        mXr[i] = map2d(xs[i], D_, S_, 64, 128, SW128);
    }
    for (int i = 0; i < 5; i++) mXs[i] = map2d(xs[i], D_, S_, 64, 64, SW128);
    const CUtensorMap mOa = map2d(o, D_, S_, 64, WO_MC ? 64 : 128, SW128);
    const CUtensorMap mHa = map2d(h, F_, S_, 64, F2_MC ? 64 : 128, SW128);

    for (int layer = 0; layer < 2; layer++) {
        const int xi = layer * 2;
        GemmParams p;
        p.stats_in = stats + (size_t)xi * 8 * S_; p.stats_out = nullptr; p.tk = 1 + 5 * layer;
        if (layer == 0) launch(qkv_kernel<true>, 128, 288, SM_QKV, QKV_MC ? 2 : 1, false, mXa[xi], mWq, mWk, mWv, mQ, p);
        else launch(qkv_kernel<false>, 128, 288, SM_QKV, QKV_MC ? 2 : 1, true, mXa[xi], mWq, mWk, mWv, mQ, p);
        launch(attn_kernel, layer == 0 ? 128 + SIDE_CTAS : 128, 512, ATT_SMEM, 1, true, wo, w1, w2, 2 + 5 * layer);
        p.stats_in = nullptr; p.stats_out = stats + (size_t)(xi + 1) * 8 * S_; p.tk = 3 + 5 * layer;
        launch(res_gemm_kernel<8, WO_STAGES>, 128, 288, SM_WO, WO_MC ? 2 : 1, true, mOa, mWo, mXr[xi], mXs[xi + 1], p);
        p.stats_in = stats + (size_t)(xi + 1) * 8 * S_; p.stats_out = nullptr; p.tk = 4 + 5 * layer;
        launch(ffn1_kernel, 128, F1_INLINE ? 256 : 288, SM_FFN1, F1_MC ? 2 : 1, true, mXf[xi + 1], mW1a, mW1b, mHst, p);
        p.stats_in = nullptr; p.stats_out = layer == 0 ? stats + (size_t)2 * 8 * S_ : nullptr; p.tk = 5 + 5 * layer;
        launch(res_gemm_kernel<28, FFN2_STAGES>, 128, 288, SM_FFN2, F2_MC ? 2 : 1, true, mHa, mW2, mXr[xi + 1], mXs[xi + 2], p);
    }
}
```

```cpp
#include <cuda_runtime.h>
#include <cuda_bf16.h>
#include <cuda.h>
#include <stdint.h>

#define F1_INLINE 0
#define QKV_MC 0
#define WO_MC 0
#define F2_MC 0
#define F1_MC 2
#define PREB 2
#define RES_WAIT0 0

namespace {

constexpr int S_ = 2048, D_ = 512, H_ = 32, F_ = 1792;

__device__ __align__(1024) __nv_bfloat16 g_q[S_ * D_];
__device__ __align__(1024) __nv_bfloat16 g_o[S_ * D_];
__device__ __align__(1024) __nv_bfloat16 g_x1[S_ * D_];
__device__ __align__(1024) __nv_bfloat16 g_x2[S_ * D_];
__device__ __align__(1024) __nv_bfloat16 g_x3[S_ * D_];
__device__ __align__(1024) __nv_bfloat16 g_h[S_ * F_];
__device__ __align__(1024) uint8_t g_kimg[S_ * 32];
__device__ __align__(1024) uint8_t g_vimg[(S_ / 16) * 768];
__device__ __align__(1024) float2 g_stats[4][8 * S_];
__device__ __align__(16) float g_cs_q[D_];
__device__ __align__(16) float g_cs_kv[32];
__device__ __align__(16) float g_cs_1[F_];
__device__ __align__(16) float g_kvmax[32];

#define TL(k, slot)

__device__ __forceinline__ uint32_t smem_u32(const void* p) { return (uint32_t)__cvta_generic_to_shared(p); }
__device__ __forceinline__ void mbar_init(uint32_t bar, uint32_t cnt) {
    asm volatile("mbarrier.init.shared::cta.b64 [%0], %1;" ::"r"(bar), "r"(cnt));
}
__device__ __forceinline__ void mbar_expect_tx(uint32_t bar, uint32_t bytes) {
    asm volatile("mbarrier.arrive.expect_tx.shared::cta.b64 _, [%0], %1;" ::"r"(bar), "r"(bytes) : "memory");
}
__device__ __forceinline__ void mbar_arrive(uint32_t bar) {
    asm volatile("mbarrier.arrive.shared::cta.b64 _, [%0];" ::"r"(bar) : "memory");
}
__device__ __forceinline__ void mbar_arrive_remote(uint32_t bar, uint32_t cta) {
    asm volatile("{\n.reg .b32 ra;\nmapa.shared::cluster.u32 ra, %0, %1;\nmbarrier.arrive.shared::cluster.b64 _, [ra];\n}" ::"r"(bar), "r"(cta) : "memory");
}
__device__ __forceinline__ void mbar_wait(uint32_t bar, uint32_t parity) {
    asm volatile("{\n.reg .pred p;\nWAIT_%=:\nmbarrier.try_wait.parity.shared::cta.b64 p, [%0], %1;\n@p bra DONE_%=;\nbra WAIT_%=;\nDONE_%=:\n}" ::"r"(bar), "r"(parity) : "memory");
}
__device__ __forceinline__ void bulk_load(uint32_t dst, const void* src, uint32_t bytes, uint32_t bar) {
    asm volatile("cp.async.bulk.shared::cluster.global.mbarrier::complete_tx::bytes [%0], [%1], %2, [%3];" ::"r"(dst), "l"(src), "r"(bytes), "r"(bar) : "memory");
}
__device__ __forceinline__ void tma2d(uint32_t dst, const CUtensorMap* m, int c0, int c1, uint32_t bar) {
    asm volatile("cp.async.bulk.tensor.2d.shared::cluster.global.mbarrier::complete_tx::bytes [%0], [%1, {%3, %4}], [%2];" ::"r"(dst), "l"(m), "r"(bar), "r"(c0), "r"(c1) : "memory");
}
__device__ __forceinline__ void tma2d_mc(uint32_t dst, const CUtensorMap* m, int c0, int c1, uint32_t bar, uint16_t mask) {
    asm volatile("cp.async.bulk.tensor.2d.shared::cluster.global.mbarrier::complete_tx::bytes.multicast::cluster [%0], [%1, {%3, %4}], [%2], %5;" ::"r"(dst), "l"(m), "r"(bar), "r"(c0), "r"(c1), "h"(mask) : "memory");
}
__device__ __forceinline__ void tma3d(uint32_t dst, const CUtensorMap* m, int c0, int c1, int c2, uint32_t bar) {
    asm volatile("cp.async.bulk.tensor.3d.shared::cluster.global.mbarrier::complete_tx::bytes [%0], [%1, {%3, %4, %5}], [%2];" ::"r"(dst), "l"(m), "r"(bar), "r"(c0), "r"(c1), "r"(c2) : "memory");
}
__device__ __forceinline__ void tma3d_mc(uint32_t dst, const CUtensorMap* m, int c0, int c1, int c2, uint32_t bar, uint16_t mask) {
    asm volatile("cp.async.bulk.tensor.3d.shared::cluster.global.mbarrier::complete_tx::bytes.multicast::cluster [%0], [%1, {%3, %4, %5}], [%2], %6;" ::"r"(dst), "l"(m), "r"(bar), "r"(c0), "r"(c1), "r"(c2), "h"(mask) : "memory");
}
__device__ __forceinline__ void tma2d_store(const CUtensorMap* m, uint32_t src, int c0, int c1) {
    asm volatile("cp.async.bulk.tensor.2d.global.shared::cta.bulk_group [%0, {%2, %3}], [%1];" ::"l"(m), "r"(src), "r"(c0), "r"(c1) : "memory");
}
__device__ __forceinline__ void tma3d_store(const CUtensorMap* m, uint32_t src, int c0, int c1, int c2) {
    asm volatile("cp.async.bulk.tensor.3d.global.shared::cta.bulk_group [%0, {%2, %3, %4}], [%1];" ::"l"(m), "r"(src), "r"(c0), "r"(c1), "r"(c2) : "memory");
}
__device__ __forceinline__ void bulk_commit() { asm volatile("cp.async.bulk.commit_group;" ::: "memory"); }
__device__ __forceinline__ void bulk_wait_read() { asm volatile("cp.async.bulk.wait_group.read 0;" ::: "memory"); }
__device__ __forceinline__ void prefetch_tmap(const CUtensorMap* m) { asm volatile("prefetch.tensormap [%0];" ::"l"(m) : "memory"); }
__device__ __forceinline__ void fence_async_smem() { asm volatile("fence.proxy.async.shared::cta;" ::: "memory"); }
__device__ __forceinline__ void fence_mbar_init() { asm volatile("fence.mbarrier_init.release.cluster;" ::: "memory"); }
__device__ __forceinline__ void cluster_sync() { asm volatile("barrier.cluster.arrive.release.aligned;\nbarrier.cluster.wait.acquire.aligned;" ::: "memory"); }
__device__ __forceinline__ uint32_t cluster_rank() { uint32_t r; asm volatile("mov.u32 %0, %%cluster_ctarank;" : "=r"(r)); return r; }
__device__ __forceinline__ void pdl_wait() { asm volatile("griddepcontrol.wait;" ::: "memory"); }
__device__ __forceinline__ void pdl_launch() { asm volatile("griddepcontrol.launch_dependents;" ::: "memory"); }
__device__ __forceinline__ bool elect_one() {
    uint32_t p;
    asm volatile("{\n.reg .pred p;\nelect.sync _|p, 0xffffffff;\nselp.b32 %0, 1, 0, p;\n}" : "=r"(p));
    return p != 0;
}
__device__ __forceinline__ void named_bar(int id, int n) { asm volatile("bar.sync %0, %1;" ::"r"(id), "r"(n) : "memory"); }

__device__ __forceinline__ void wg_fence() { asm volatile("wgmma.fence.sync.aligned;" ::: "memory"); }
__device__ __forceinline__ void wg_commit() { asm volatile("wgmma.commit_group.sync.aligned;" ::: "memory"); }
template <int N> __device__ __forceinline__ void wg_wait() { asm volatile("wgmma.wait_group.sync.aligned %0;" ::"n"(N) : "memory"); }
template <int N> __device__ __forceinline__ void fence_regs(float (&d)[N]) {
#pragma unroll
    for (int i = 0; i < N; i++) asm volatile("" : "+f"(d[i])::"memory");
}
__device__ __forceinline__ uint64_t mkdesc(uint32_t addr, uint32_t lbo, uint32_t sbo, uint32_t swz) {
    uint64_t d = 0;
    d |= (uint64_t)((addr & 0x3FFFF) >> 4);
    d |= (uint64_t)((lbo & 0x3FFFF) >> 4) << 16;
    d |= (uint64_t)((sbo & 0x3FFFF) >> 4) << 32;
    d |= (uint64_t)swz << 62;
    return d;
}
__device__ __forceinline__ void ldsm_x4(uint32_t& r0, uint32_t& r1, uint32_t& r2, uint32_t& r3, uint32_t addr) {
    asm volatile("ldmatrix.sync.aligned.m8n8.x4.shared.b16 {%0,%1,%2,%3}, [%4];" : "=r"(r0), "=r"(r1), "=r"(r2), "=r"(r3) : "r"(addr) : "memory");
}
__device__ __forceinline__ void stsm_x4(uint32_t addr, uint32_t r0, uint32_t r1, uint32_t r2, uint32_t r3) {
    asm volatile("stmatrix.sync.aligned.m8n8.x4.shared.b16 [%0], {%1,%2,%3,%4};" ::"r"(addr), "r"(r0), "r"(r1), "r"(r2), "r"(r3) : "memory");
}
__device__ __forceinline__ void ldsm_x4_t(uint32_t& r0, uint32_t& r1, uint32_t& r2, uint32_t& r3, uint32_t addr) {
    asm volatile("ldmatrix.sync.aligned.m8n8.x4.trans.shared.b16 {%0,%1,%2,%3}, [%4];" : "=r"(r0), "=r"(r1), "=r"(r2), "=r"(r3) : "r"(addr) : "memory");
}
__device__ __forceinline__ void hmma(float (&d)[4], uint32_t a0, uint32_t a1, uint32_t a2, uint32_t a3, uint32_t b0, uint32_t b1) {
    asm volatile("mma.sync.aligned.m16n8k16.row.col.f32.bf16.bf16.f32 {%0,%1,%2,%3}, {%4,%5,%6,%7}, {%8,%9}, {%0,%1,%2,%3};"
                 : "+f"(d[0]), "+f"(d[1]), "+f"(d[2]), "+f"(d[3]) : "r"(a0), "r"(a1), "r"(a2), "r"(a3), "r"(b0), "r"(b1));
}
__device__ __forceinline__ uint32_t pack_bf16(float lo, float hi) {
    uint32_t r;
    asm("cvt.rn.bf16x2.f32 %0, %1, %2;" : "=r"(r) : "f"(hi), "f"(lo));
    return r;
}
__device__ __forceinline__ float bf_lo(uint32_t v) { return __uint_as_float(v << 16); }
__device__ __forceinline__ float bf_hi(uint32_t v) { return __uint_as_float(v & 0xFFFF0000u); }

#define WG_REGS_4(o) "+f"(d[o]), "+f"(d[o + 1]), "+f"(d[o + 2]), "+f"(d[o + 3])
#define WG_REGS_8(o) WG_REGS_4(o), WG_REGS_4(o + 4)
#define WG_REGS_16(o) WG_REGS_8(o), WG_REGS_8(o + 8)
#define WG_REGS_32(o) WG_REGS_16(o), WG_REGS_16(o + 16)

__device__ __forceinline__ void wgmma_ss_n80_tb(float (&d)[40], uint64_t dA, uint64_t dB, int sc) {
    asm volatile("{\n.reg .pred p;\nsetp.ne.b32 p, %42, 0;\n"
                 "wgmma.mma_async.sync.aligned.m64n80k16.f32.bf16.bf16 "
                 "{%0,%1,%2,%3,%4,%5,%6,%7,%8,%9,%10,%11,%12,%13,%14,%15,%16,%17,%18,%19,%20,%21,%22,%23,%24,%25,%26,%27,%28,%29,%30,%31,"
                 "%32,%33,%34,%35,%36,%37,%38,%39}, %40, %41, p, 1, 1, 0, 1;\n}\n"
                 : WG_REGS_32(0), WG_REGS_8(32) : "l"(dA), "l"(dB), "r"(sc));
}
__device__ __forceinline__ void wgmma_ss_n64_tb(float (&d)[32], uint64_t dA, uint64_t dB, int sc) {
    asm volatile("{\n.reg .pred p;\nsetp.ne.b32 p, %34, 0;\n"
                 "wgmma.mma_async.sync.aligned.m64n64k16.f32.bf16.bf16 "
                 "{%0,%1,%2,%3,%4,%5,%6,%7,%8,%9,%10,%11,%12,%13,%14,%15,%16,%17,%18,%19,%20,%21,%22,%23,%24,%25,%26,%27,%28,%29,%30,%31}, "
                 "%32, %33, p, 1, 1, 0, 1;\n}\n"
                 : WG_REGS_32(0) : "l"(dA), "l"(dB), "r"(sc));
}
__device__ __forceinline__ void wgmma_ss_n224_tb(float (&d)[112], uint64_t dA, uint64_t dB, int sc) {
    asm volatile("{\n.reg .pred p;\nsetp.ne.b32 p, %114, 0;\n"
                 "wgmma.mma_async.sync.aligned.m64n224k16.f32.bf16.bf16 "
                 "{%0,%1,%2,%3,%4,%5,%6,%7,%8,%9,%10,%11,%12,%13,%14,%15,%16,%17,%18,%19,%20,%21,%22,%23,%24,%25,%26,%27,%28,%29,%30,%31,"
                 "%32,%33,%34,%35,%36,%37,%38,%39,%40,%41,%42,%43,%44,%45,%46,%47,%48,%49,%50,%51,%52,%53,%54,%55,%56,%57,%58,%59,%60,%61,%62,%63,"
                 "%64,%65,%66,%67,%68,%69,%70,%71,%72,%73,%74,%75,%76,%77,%78,%79,%80,%81,%82,%83,%84,%85,%86,%87,%88,%89,%90,%91,%92,%93,%94,%95,"
                 "%96,%97,%98,%99,%100,%101,%102,%103,%104,%105,%106,%107,%108,%109,%110,%111}, "
                 "%112, %113, p, 1, 1, 0, 1;\n}\n"
                 : WG_REGS_32(0), WG_REGS_32(32), WG_REGS_32(64), WG_REGS_16(96) : "l"(dA), "l"(dB), "r"(sc));
}
template <int BN> __device__ __forceinline__ void wgmma_ss_tb(float (&d)[BN / 2], uint64_t dA, uint64_t dB, int sc) {
    if constexpr (BN == 64) wgmma_ss_n64_tb(d, dA, dB, sc);
    else if constexpr (BN == 80) wgmma_ss_n80_tb(d, dA, dB, sc);
    else wgmma_ss_n224_tb(d, dA, dB, sc);
}
__device__ __forceinline__ void wgmma_rs_n64_z(float (&d)[32], uint32_t a0, uint32_t a1, uint32_t a2, uint32_t a3, uint64_t dB) {
    asm volatile("{\n.reg .pred p;\nsetp.ne.b32 p, 0, 0;\n"
                 "wgmma.mma_async.sync.aligned.m64n64k16.f32.bf16.bf16 "
                 "{%0,%1,%2,%3,%4,%5,%6,%7,%8,%9,%10,%11,%12,%13,%14,%15,%16,%17,%18,%19,%20,%21,%22,%23,%24,%25,%26,%27,%28,%29,%30,%31}, "
                 "{%32,%33,%34,%35}, %36, p, 1, 1, 0;\n}\n"
                 : "=f"(d[0]), "=f"(d[1]), "=f"(d[2]), "=f"(d[3]), "=f"(d[4]), "=f"(d[5]), "=f"(d[6]), "=f"(d[7]),
                   "=f"(d[8]), "=f"(d[9]), "=f"(d[10]), "=f"(d[11]), "=f"(d[12]), "=f"(d[13]), "=f"(d[14]), "=f"(d[15]),
                   "=f"(d[16]), "=f"(d[17]), "=f"(d[18]), "=f"(d[19]), "=f"(d[20]), "=f"(d[21]), "=f"(d[22]), "=f"(d[23]),
                   "=f"(d[24]), "=f"(d[25]), "=f"(d[26]), "=f"(d[27]), "=f"(d[28]), "=f"(d[29]), "=f"(d[30]), "=f"(d[31])
                 : "r"(a0), "r"(a1), "r"(a2), "r"(a3), "l"(dB));
}
__device__ __forceinline__ void wgmma_rs_n24_tb(float (&d)[12], uint32_t a0, uint32_t a1, uint32_t a2, uint32_t a3, uint64_t dB) {
    asm volatile("{\n.reg .pred p;\nsetp.eq.b32 p, 0, 0;\n"
                 "wgmma.mma_async.sync.aligned.m64n24k16.f32.bf16.bf16 "
                 "{%0,%1,%2,%3,%4,%5,%6,%7,%8,%9,%10,%11}, {%12,%13,%14,%15}, %16, p, 1, 1, 1;\n}\n"
                 : WG_REGS_8(0), WG_REGS_4(8) : "r"(a0), "r"(a1), "r"(a2), "r"(a3), "l"(dB));
}

constexpr int SIDE_CTAS = 4;
__device__ __forceinline__ void side_job(int cta, float* red  , const __nv_bfloat16* __restrict__ wo,
                                         const __nv_bfloat16* __restrict__ w1, const __nv_bfloat16* __restrict__ w2) {
    const int tid = threadIdx.x, warp = tid >> 5, lane = tid & 31;
    for (int line = cta * 512 + tid; line < 18432; line += SIDE_CTAS * 512) {
        const char* p = line < 4096 ? (const char*)wo + (size_t)line * 128 : (const char*)w2 + (size_t)(line - 4096) * 128;
        asm volatile("prefetch.global.L2 [%0];" ::"l"(p));
    }
    const int rg = lane >> 3, c8 = lane & 7;
    for (int slab = cta; slab < F_ / 64; slab += SIDE_CTAS) {
        const __nv_bfloat16* base = w1 + slab * 64 + c8 * 8;
        uint4 v[8];
#pragma unroll
        for (int i = 0; i < 8; i++) v[i] = __ldg((const uint4*)(base + (size_t)(warp * 32 + rg + 4 * i) * F_));
        float acc[8];
#pragma unroll
        for (int i = 0; i < 8; i++) acc[i] = 0.f;
#pragma unroll
        for (int i = 0; i < 8; i++) {
            acc[0] += bf_lo(v[i].x); acc[1] += bf_hi(v[i].x); acc[2] += bf_lo(v[i].y); acc[3] += bf_hi(v[i].y);
            acc[4] += bf_lo(v[i].z); acc[5] += bf_hi(v[i].z); acc[6] += bf_lo(v[i].w); acc[7] += bf_hi(v[i].w);
        }
#pragma unroll
        for (int i = 0; i < 8; i++) {
            acc[i] += __shfl_xor_sync(0xffffffffu, acc[i], 8);
            acc[i] += __shfl_xor_sync(0xffffffffu, acc[i], 16);
        }
        if (rg == 0) {
#pragma unroll
            for (int i = 0; i < 8; i++) red[warp * 64 + c8 * 8 + i] = acc[i];
        }
        __syncthreads();
        if (tid < 64) {
            float s = 0.f;
#pragma unroll
            for (int i = 0; i < 16; i++) s += red[i * 64 + tid];
            g_cs_1[slab * 64 + tid] = s;
        }
        __syncthreads();
    }
}

enum { EPI_QKV = 0, EPI_RES = 1, EPI_FFN1 = 2 };

struct GemmParams {
    const float2* stats_in;
    float2* stats_out;
    int tk;
};

template <int BK_, int NBLK> struct Geo {
    static constexpr int BK = BK_, A_BYTES = 128 * BK * 2, A_SWZ = BK == 64 ? 1 : 2, A_SBO = BK * 16;
    static constexpr int BLK = BK * 64;
    static constexpr int B_BYTES = NBLK * BLK, B_SWZ = 2, B_LBO = BLK, B_SBO = 512, B_KSTEP = 1024;
};
template <> struct Geo<64, 0> {
    static constexpr int BK = 64, A_BYTES = 128 * 128, A_SWZ = 1, A_SBO = 1024, BLK = 8192;
    static constexpr int B_BYTES = 64 * 128, B_SWZ = 1, B_LBO = 8192, B_SBO = 1024, B_KSTEP = 2048;
};
#define F1_BK 32
template <int EPI> struct EpiGeo;
template <> struct EpiGeo<EPI_QKV> { using G = Geo<64, 3>; };
template <> struct EpiGeo<EPI_RES> { using G = Geo<64, 0>; };
template <> struct EpiGeo<EPI_FFN1> { using G = Geo<F1_BK, 7>; };

template <int STAGES, int EPI> struct GemmSmem {
    using G = typename EpiGeo<EPI>::G;
    static constexpr int STAGE = G::A_BYTES + G::B_BYTES;
    static constexpr int AUX_OFF = STAGES * STAGE;
    static constexpr int TOTAL = AUX_OFF + 1152;
    static constexpr int TOTAL_SELF = AUX_OFF + 704 + 1024 + 1280;
};

struct RowStatRaw { float2 a0, a1, b0, b1; };
__device__ __forceinline__ RowStatRaw load_row_stats(const float2* __restrict__ st, int row0, int c) {
    RowStatRaw r;
    r.a0 = st[(2 * c) * S_ + row0]; r.a1 = st[(2 * c + 1) * S_ + row0];
    r.b0 = st[(2 * c) * S_ + row0 + 8]; r.b1 = st[(2 * c + 1) * S_ + row0 + 8];
    return r;
}
__device__ __forceinline__ void finish_row_stats(const RowStatRaw& r, float& mean0, float& rstd0, float& mean1, float& rstd1) {
    float sa = r.a0.x + r.a1.x, sb = r.b0.x + r.b1.x;
    sa += __shfl_xor_sync(0xffffffffu, sa, 1); sa += __shfl_xor_sync(0xffffffffu, sa, 2);
    sb += __shfl_xor_sync(0xffffffffu, sb, 1); sb += __shfl_xor_sync(0xffffffffu, sb, 2);
    mean0 = sa * 0.125f; mean1 = sb * 0.125f;
    float ma = r.a0.y + r.a1.y + 64.f * ((r.a0.x - mean0) * (r.a0.x - mean0) + (r.a1.x - mean0) * (r.a1.x - mean0));
    float mb = r.b0.y + r.b1.y + 64.f * ((r.b0.x - mean1) * (r.b0.x - mean1) + (r.b1.x - mean1) * (r.b1.x - mean1));
    ma += __shfl_xor_sync(0xffffffffu, ma, 1); ma += __shfl_xor_sync(0xffffffffu, ma, 2);
    mb += __shfl_xor_sync(0xffffffffu, mb, 1); mb += __shfl_xor_sync(0xffffffffu, mb, 2);
    rstd0 = 1.0f / sqrtf(ma * (1.f / 512.f) + 1e-5f);
    rstd1 = 1.0f / sqrtf(mb * (1.f / 512.f) + 1e-5f);
}

template <int BN, int KB, int STAGES, int EPI, int MC, bool SELF = false>
__device__ __forceinline__ void gemm_body(const CUtensorMap* mapA, const CUtensorMap* mapB, const CUtensorMap* mapB2, const CUtensorMap* mapR,
                                          const CUtensorMap* mapC, const GemmParams& prm, int tile_m, int tile_n, uint8_t* smem_raw) {
    using SM = GemmSmem<STAGES, EPI>;
    using G = typename SM::G;
    constexpr bool XKV = BN == 80;
    constexpr int TN = EPI == EPI_QKV ? 64 : BN;
    pdl_launch();
    const uint32_t sbase = smem_u32(smem_raw);
    if (sbase & 1023) __trap();
    uint8_t* sgen = smem_raw;
    const uint32_t bar_full = sbase + SM::AUX_OFF, bar_empty = bar_full + 8 * STAGES;
    float* s_cs = (float*)(sgen + SM::AUX_OFF + 256);
    float* s_row = (float*)(sgen + SM::AUX_OFF + 704);
    float* s_red = (float*)(sgen + SM::AUX_OFF + 640);
    const int tid = threadIdx.x, lane = tid & 31;
    const int warp = __shfl_sync(0xffffffffu, tid >> 5, 0);
    const uint32_t rank = MC ? cluster_rank() : 0;
    if (tid == 0) TL(prm.tk, 0);

    constexpr bool INLINE_PROD = EPI == EPI_FFN1 && F1_INLINE;
    constexpr int PWARP = INLINE_PROD ? 0 : 8;
    if (warp == PWARP && elect_one()) {
        prefetch_tmap(mapB); prefetch_tmap(mapA); prefetch_tmap(mapC);
        for (int s = 0; s < STAGES; s++) { mbar_init(bar_full + 8 * s, 1); mbar_init(bar_empty + 8 * s, MC ? 4 : 2); }
        fence_mbar_init();
    }
    __syncthreads();
    if (MC) cluster_sync();

    const int m0 = tile_m * 128, n0 = tile_n * TN;
    constexpr uint32_t STAGE_TX = G::A_BYTES + (EPI == EPI_QKV ? (XKV ? 3 : 2) * G::BLK : G::B_BYTES);
    auto loadB = [&](int kb, int s) {
        const uint32_t dst = sbase + s * SM::STAGE + G::A_BYTES, bar = bar_full + 8 * s;
        if constexpr (EPI == EPI_RES) {
            tma2d(dst, mapB, n0, kb * 64, bar);
        } else if constexpr (EPI == EPI_QKV) {
            tma3d(dst, mapB, 0, kb * G::BK, tile_n * 2, bar);
            if constexpr (XKV) tma2d(dst + 2 * G::BLK, mapB2, 0, kb * G::BK, bar);
        } else {
            if constexpr (MC == 2) {
                if (rank == 0) tma3d_mc(dst, mapB, 0, kb * G::BK, tile_n * 7, bar, 3);
                else tma3d_mc(dst + 4 * G::BLK, mapB2, 0, kb * G::BK, tile_n * 7 + 4, bar, 3);
            } else {
                tma3d(dst, mapB, 0, kb * G::BK, tile_n * 7, bar);
                tma3d(dst + 4 * G::BLK, mapB2, 0, kb * G::BK, tile_n * 7 + 4, bar);
            }
        }
    };
    auto loadA = [&](int kb, int s) {
        const uint32_t dst = sbase + s * SM::STAGE, bar = bar_full + 8 * s;
        if constexpr (MC == 1) tma2d_mc(dst + rank * (G::A_BYTES / 2), mapA, kb * G::BK, m0 + rank * 64, bar, 3);
        else tma2d(dst, mapA, kb * G::BK, m0, bar);
    };
    constexpr int PRE = STAGES < KB ? STAGES : KB;
#define F1_LAG 2
    constexpr int LAG = F1_LAG;
    constexpr int PRE_B = PRE < PREB ? PRE : PREB;
    auto prologue_loads = [&]() {
        if (elect_one()) {
#pragma unroll
            for (int kb = 0; kb < PRE; kb++) mbar_expect_tx(bar_full + 8 * kb, STAGE_TX);
#pragma unroll
            for (int kb = 0; kb < PRE_B; kb++) loadB(kb, kb);
        }
        if (!SELF) pdl_wait();
        if (elect_one()) {
#pragma unroll
            for (int kb = 0; kb < PRE; kb++) {
                loadA(kb, kb);
                if (kb + PRE_B < PRE) loadB(kb + PRE_B, kb + PRE_B);
            }
            if constexpr (EPI == EPI_RES && KB < STAGES) {
                mbar_expect_tx(bar_full + 8 * KB, 16384);
                tma2d(sbase + KB * SM::STAGE, mapR, n0, m0, bar_full + 8 * KB);
            }
        }
    };
    if (SELF && warp > 8) {
        static_assert(!SELF || (STAGES >= KB && EPI == EPI_QKV), "SELF needs every k block resident");
        const int t = tid - 288;
        float ss[4] = {0.f, 0.f, 0.f, 0.f}, sq[4] = {0.f, 0.f, 0.f, 0.f}, ca[8], cx[8];
#pragma unroll
        for (int i = 0; i < 8; i++) { ca[i] = 0.f; cx[i] = 0.f; }
#pragma unroll 1
        for (int kb = 0; kb < KB; kb++) {
            mbar_wait(bar_full + 8 * kb, 0);
            const uint32_t arow = sbase + kb * SM::STAGE + t * 128;
            uint32_t w[8][4];
#pragma unroll
            for (int j = 0; j < 8; j++)
                asm volatile("ld.shared.v4.u32 {%0,%1,%2,%3}, [%4];" : "=r"(w[j][0]), "=r"(w[j][1]), "=r"(w[j][2]), "=r"(w[j][3])
                             : "r"(arow + (((j + t) & 7) << 4)));
#pragma unroll
            for (int j = 0; j < 8; j++)
#pragma unroll
                for (int i = 0; i < 4; i++) {
                    const float lo = bf_lo(w[j][i]), hi = bf_hi(w[j][i]);
                    ss[i] += lo + hi;
                    sq[i] = fmaf(lo, lo, fmaf(hi, hi, sq[i]));
                }
            const uint32_t bblk = sbase + kb * SM::STAGE + G::A_BYTES;
            const int ch = t & 7;
#pragma unroll
            for (int r = 0; r < 4; r++) {
                const int krow = (t >> 3) * 4 + r;
                asm volatile("ld.shared.v4.u32 {%0,%1,%2,%3}, [%4];" : "=r"(w[r][0]), "=r"(w[r][1]), "=r"(w[r][2]), "=r"(w[r][3])
                             : "r"(bblk + (ch >> 2) * G::BLK + krow * 64 + (((ch & 3) ^ ((krow >> 1) & 3)) << 4)));
            }
            if constexpr (XKV) {
                const int krow = t >> 1;
                asm volatile("ld.shared.v4.u32 {%0,%1,%2,%3}, [%4];" : "=r"(w[4][0]), "=r"(w[4][1]), "=r"(w[4][2]), "=r"(w[4][3])
                             : "r"(bblk + 2 * G::BLK + krow * 64 + (((t & 1) ^ ((krow >> 1) & 3)) << 4)));
            }
#pragma unroll
            for (int r = 0; r < 4; r++)
#pragma unroll
                for (int i = 0; i < 4; i++) { ca[2 * i] += bf_lo(w[r][i]); ca[2 * i + 1] += bf_hi(w[r][i]); }
            if constexpr (XKV) {
#pragma unroll
                for (int i = 0; i < 4; i++) { cx[2 * i] += bf_lo(w[4][i]); cx[2 * i + 1] += bf_hi(w[4][i]); }
            }
        }
        const float md = ((ss[0] + ss[1]) + (ss[2] + ss[3])) * (1.f / 512.f);
        const float var = fmaxf(((sq[0] + sq[1]) + (sq[2] + sq[3])) * (1.f / 512.f) - md * md, 0.f);
        *(float2*)(s_row + 2 * t) = make_float2(md, 1.0f / sqrtf(var + 1e-5f));
#pragma unroll
        for (int i = 0; i < 8; i++) {
            ca[i] += __shfl_xor_sync(0xffffffffu, ca[i], 8);
            ca[i] += __shfl_xor_sync(0xffffffffu, ca[i], 16);
            if constexpr (XKV) {
                cx[i] += __shfl_xor_sync(0xffffffffu, cx[i], 2); cx[i] += __shfl_xor_sync(0xffffffffu, cx[i], 4);
                cx[i] += __shfl_xor_sync(0xffffffffu, cx[i], 8); cx[i] += __shfl_xor_sync(0xffffffffu, cx[i], 16);
            }
        }
        float* s_part = s_row + 256;
        const int sw = warp - 9;
        if (lane < 8) {
#pragma unroll
            for (int i = 0; i < 8; i++) s_part[sw * 80 + lane * 8 + i] = ca[i];
        }
        if (XKV && lane < 2) {
#pragma unroll
            for (int i = 0; i < 8; i++) s_part[sw * 80 + 64 + lane * 8 + i] = cx[i];
        }
        named_bar(5, 128);
        if (t < (XKV ? 80 : 64)) {
            const float v = (s_part[t] + s_part[80 + t]) + (s_part[160 + t] + s_part[240 + t]);
            s_cs[t] = v;
            if (tile_m == 0) {
                if (t < 64) g_cs_q[n0 + t] = v;
                else g_cs_kv[tile_n * 16 + t - 64] = v;
            }
        }
        named_bar(4, 384);
    } else if (!INLINE_PROD && warp == 8) {
        prologue_loads();
        int s = PRE % STAGES, ph = (PRE / STAGES) & 1;
#pragma unroll 1
        for (int kb = PRE; kb < KB; kb++) {
            mbar_wait(bar_empty + 8 * s, ph ^ 1);
            if (elect_one()) {
                mbar_expect_tx(bar_full + 8 * s, STAGE_TX);
                loadB(kb, s);
                loadA(kb, s);
            }
            if (++s == STAGES) { s = 0; ph ^= 1; }
        }
        if constexpr (EPI == EPI_RES && KB >= STAGES) {
            mbar_wait(bar_empty + 8 * s, ph ^ 1);
            if (elect_one()) {
                mbar_expect_tx(bar_full + 8 * s, 16384);
                tma2d(sbase + s * SM::STAGE, mapR, n0, m0, bar_full + 8 * s);
            }
        }
    } else {
        if (INLINE_PROD && warp == 0) prologue_loads();
        const int wg = warp >> 2, g = lane >> 2, c = lane & 3;
        const int rloc = wg * 64 + (warp & 3) * 16 + g;
        const int row0 = m0 + rloc;
        float mean0 = 0.f, rstd0 = 1.f, mean1 = 0.f, rstd1 = 1.f;
        RowStatRaw raw;
        float csv = 0.f;
        float2 cskv[2] = {make_float2(0.f, 0.f), make_float2(0.f, 0.f)};
        auto ln_inputs = [&]() {
            pdl_wait();
            if constexpr (EPI != EPI_RES) {
                raw = load_row_stats(prm.stats_in, row0, c);
                const float* cs = EPI == EPI_FFN1 ? g_cs_1 + n0 : g_cs_q + n0;
                if (tid < TN) csv = cs[tid];
                if constexpr (XKV) {
                    cskv[0] = *(const float2*)(g_cs_kv + tile_n * 16 + 2 * c);
                    cskv[1] = *(const float2*)(g_cs_kv + tile_n * 16 + 8 + 2 * c);
                }
            }
        };
        if (!SELF) ln_inputs();
        float acc[BN / 2];
        const uint64_t dA0 = mkdesc(sbase + wg * (G::A_BYTES / 2), 16, G::A_SBO, G::A_SWZ);
        const uint64_t dB0 = mkdesc(sbase + G::A_BYTES, G::B_LBO, G::B_SBO, G::B_SWZ);
        int s = 0, ph = 0;
#pragma unroll 1
        for (int kb = 0; kb < KB; kb++) {
            mbar_wait(bar_full + 8 * s, ph);
            const uint64_t dA = dA0 + (uint64_t)(s * (SM::STAGE >> 4)), dB = dB0 + (uint64_t)(s * (SM::STAGE >> 4));
            wg_fence();
#pragma unroll
            for (int k = 0; k < G::BK / 16; k++) wgmma_ss_tb<BN>(acc, dA + (uint64_t)(k * 2), dB + (uint64_t)(k * (G::B_KSTEP >> 4)), (kb | k) != 0);
            wg_commit();
            if constexpr (EPI == EPI_RES && RES_WAIT0) {
                wg_wait<0>();
                if ((warp & 3) == 0 && elect_one()) {
                    if (MC) { mbar_arrive_remote(bar_empty + 8 * s, 0); mbar_arrive_remote(bar_empty + 8 * s, 1); }
                    else mbar_arrive(bar_empty + 8 * s);
                }
            } else if (kb > 0) {
                wg_wait<1>();
                const int sp = s == 0 ? STAGES - 1 : s - 1;
                if ((warp & 3) == 0 && elect_one()) {
                    if (MC) { mbar_arrive_remote(bar_empty + 8 * sp, 0); mbar_arrive_remote(bar_empty + 8 * sp, 1); }
                    else mbar_arrive(bar_empty + 8 * sp);
                }
                if (INLINE_PROD && warp == 0 && kb >= LAG && kb - LAG + STAGES < KB) {
                    const int sq = LAG == 1 ? sp : (sp == 0 ? STAGES - 1 : sp - 1);
                    mbar_wait(bar_empty + 8 * sq, ((kb - LAG) / STAGES) & 1);
                    if (elect_one()) {
                        mbar_expect_tx(bar_full + 8 * sq, STAGE_TX);
                        loadB(kb - LAG + STAGES, sq);
                        loadA(kb - LAG + STAGES, sq);
                    }
                }
            }
            if (++s == STAGES) { s = 0; ph ^= 1; }
        }
        if constexpr (SELF) {
            named_bar(4, 384);
            const float2 r0 = *(const float2*)(s_row + 2 * rloc), r1 = *(const float2*)(s_row + 2 * rloc + 16);
            mean0 = r0.x; rstd0 = r0.y; mean1 = r1.x; rstd1 = r1.y;
        } else if constexpr (EPI != EPI_RES) {
            finish_row_stats(raw, mean0, rstd0, mean1, rstd1);
            if (tid < TN) s_cs[tid] = csv;
        }
        wg_wait<0>();
        fence_regs(acc);
        if (tid == 0) TL(prm.tk, 2);
        if constexpr (EPI != EPI_RES) named_bar(1, 256);

        if constexpr (EPI != EPI_FFN1) {
            const uint32_t stile = sbase + (EPI == EPI_RES ? s * SM::STAGE : 0);
            const int mrow = wg * 64 + (warp & 3) * 16 + (lane & 7) + ((lane >> 3) & 1) * 8;
            const uint32_t rbase = stile + mrow * 128;
            if constexpr (EPI == EPI_RES) {
                mbar_wait(bar_full + 8 * s, ph);
                float s0 = 0.f, s1 = 0.f;
#pragma unroll
                for (int jj = 0; jj < 4; jj++) {
                    uint32_t r0, r1, r2, r3;
                    const uint32_t addr = rbase + (((2 * jj + (lane >> 4)) ^ (mrow & 7)) << 4);
                    ldsm_x4(r0, r1, r2, r3, addr);
                    const uint32_t u0 = pack_bf16(acc[8 * jj] + bf_lo(r0), acc[8 * jj + 1] + bf_hi(r0));
                    const uint32_t u1 = pack_bf16(acc[8 * jj + 2] + bf_lo(r1), acc[8 * jj + 3] + bf_hi(r1));
                    const uint32_t u2 = pack_bf16(acc[8 * jj + 4] + bf_lo(r2), acc[8 * jj + 5] + bf_hi(r2));
                    const uint32_t u3 = pack_bf16(acc[8 * jj + 6] + bf_lo(r3), acc[8 * jj + 7] + bf_hi(r3));
                    stsm_x4(addr, u0, u1, u2, u3);
                    acc[8 * jj] = bf_lo(u0); acc[8 * jj + 1] = bf_hi(u0); acc[8 * jj + 4] = bf_lo(u2); acc[8 * jj + 5] = bf_hi(u2);
                    acc[8 * jj + 2] = bf_lo(u1); acc[8 * jj + 3] = bf_hi(u1); acc[8 * jj + 6] = bf_lo(u3); acc[8 * jj + 7] = bf_hi(u3);
                    s0 += (acc[8 * jj] + acc[8 * jj + 1]) + (acc[8 * jj + 4] + acc[8 * jj + 5]);
                    s1 += (acc[8 * jj + 2] + acc[8 * jj + 3]) + (acc[8 * jj + 6] + acc[8 * jj + 7]);
                }
                fence_async_smem();
                named_bar(2 + wg, 128);
                if ((warp & 3) == 0 && elect_one()) { tma2d_store(mapC, stile + wg * 8192, n0, m0 + wg * 64); bulk_commit(); }
                if (prm.stats_out) {
                    s0 += __shfl_xor_sync(0xffffffffu, s0, 1); s0 += __shfl_xor_sync(0xffffffffu, s0, 2);
                    s1 += __shfl_xor_sync(0xffffffffu, s1, 1); s1 += __shfl_xor_sync(0xffffffffu, s1, 2);
                    const float mu0 = s0 * (1.f / 64.f), mu1 = s1 * (1.f / 64.f);
                    float q0 = 0.f, q1 = 0.f;
#pragma unroll
                    for (int j = 0; j < 8; j++) {
                        float d;
                        d = acc[4 * j] - mu0; q0 += d * d; d = acc[4 * j + 1] - mu0; q0 += d * d;
                        d = acc[4 * j + 2] - mu1; q1 += d * d; d = acc[4 * j + 3] - mu1; q1 += d * d;
                    }
                    q0 += __shfl_xor_sync(0xffffffffu, q0, 1); q0 += __shfl_xor_sync(0xffffffffu, q0, 2);
                    q1 += __shfl_xor_sync(0xffffffffu, q1, 1); q1 += __shfl_xor_sync(0xffffffffu, q1, 2);
                    if (c == 0) {
                        prm.stats_out[tile_n * S_ + row0] = make_float2(mu0, q0);
                        prm.stats_out[tile_n * S_ + row0 + 8] = make_float2(mu1, q1);
                    }
                }
            } else {
                const float sc = 0.25f * 1.4426950408889634f;
                const float a0 = rstd0 * sc, a1 = rstd1 * sc, rm0 = a0 * mean0, rm1 = a1 * mean1;
#pragma unroll
                for (int jj = 0; jj < 4; jj++) {
                    const float2 ca = *(const float2*)(s_cs + 16 * jj + 2 * c), cb = *(const float2*)(s_cs + 16 * jj + 8 + 2 * c);
                    const uint32_t u0 = pack_bf16(acc[8 * jj] * a0 - rm0 * ca.x, acc[8 * jj + 1] * a0 - rm0 * ca.y);
                    const uint32_t u1 = pack_bf16(acc[8 * jj + 2] * a1 - rm1 * ca.x, acc[8 * jj + 3] * a1 - rm1 * ca.y);
                    const uint32_t u2 = pack_bf16(acc[8 * jj + 4] * a0 - rm0 * cb.x, acc[8 * jj + 5] * a0 - rm0 * cb.y);
                    const uint32_t u3 = pack_bf16(acc[8 * jj + 6] * a1 - rm1 * cb.x, acc[8 * jj + 7] * a1 - rm1 * cb.y);
                    stsm_x4(rbase + (((2 * jj + (lane >> 4)) ^ (mrow & 7)) << 4), u0, u1, u2, u3);
                }
                fence_async_smem();
                named_bar(2 + wg, 128);
                if ((warp & 3) == 0 && elect_one()) { tma2d_store(mapC, stile + wg * 8192, n0, m0 + wg * 64); bulk_commit(); }
            }
            if constexpr (XKV) {
                {
                    const float* acx = &acc[32];
                    const float rm0 = rstd0 * mean0, rm1 = rstd1 * mean1;
                    float n0s = 0.f, n1s = 0.f, vmax = 0.f;
#pragma unroll
                    for (int j = 0; j < 2; j++) {
                        const float2 cs2 = SELF ? *(const float2*)(s_cs + 64 + 8 * j + 2 * c) : cskv[j];
                        const uint32_t u0 = pack_bf16(acx[4 * j] * rstd0 - rm0 * cs2.x, acx[4 * j + 1] * rstd0 - rm0 * cs2.y);
                        const uint32_t u1 = pack_bf16(acx[4 * j + 2] * rstd1 - rm1 * cs2.x, acx[4 * j + 3] * rstd1 - rm1 * cs2.y);
                        n0s += bf_lo(u0) * bf_lo(u0) + bf_hi(u0) * bf_hi(u0);
                        n1s += bf_lo(u1) * bf_lo(u1) + bf_hi(u1) * bf_hi(u1);
                        vmax = fmaxf(vmax, fmaxf(fmaxf(fabsf(bf_lo(u0)), fabsf(bf_hi(u0))), fmaxf(fabsf(bf_lo(u1)), fabsf(bf_hi(u1)))));
                        if (tile_n == 0) {
                            *(uint32_t*)(g_kimg + (row0 >> 3) * 256 + j * 128 + g * 16 + c * 4) = u0;
                            *(uint32_t*)(g_kimg + ((row0 + 8) >> 3) * 256 + j * 128 + g * 16 + c * 4) = u1;
                        } else {
                            uint8_t* vb = g_vimg + (row0 >> 4) * 768 + j * 256 + g * 16 + c * 4;
                            *(uint32_t*)(vb) = u0;
                            *(uint32_t*)(vb + 128) = u1;
                        }
                    }
                    if (tile_n == 1) {
                        uint8_t* vb = g_vimg + (row0 >> 4) * 768 + 512 + g * 16 + c * 4;
                        const uint32_t one = c == 0 ? 0x00003F80u : 0u;
                        *(uint32_t*)(vb) = one;
                        *(uint32_t*)(vb + 128) = one;
                    }
                    n0s += __shfl_xor_sync(0xffffffffu, n0s, 1); n0s += __shfl_xor_sync(0xffffffffu, n0s, 2);
                    n1s += __shfl_xor_sync(0xffffffffu, n1s, 1); n1s += __shfl_xor_sync(0xffffffffu, n1s, 2);
                    float km = tile_n == 0 ? fmaxf(n0s, n1s) : vmax;
                    if (!(n0s + n1s < INFINITY)) km = INFINITY;
#pragma unroll
                    for (int o = 1; o < 32; o <<= 1) km = fmaxf(km, __shfl_xor_sync(0xffffffffu, km, o));
                    if (lane == 0) s_red[warp] = km;
                    named_bar(1, 256);
                    if (tid == 0) {
                        float a = 0.f;
                        for (int i = 0; i < 8; i++) a = fmaxf(a, s_red[i]);
                        g_kvmax[tile_n * 16 + tile_m] = a;
                    }
                }
            }
            if ((warp & 3) == 0) bulk_wait_read();
        } else {
            const uint32_t stile = sbase + wg * (7 * 4096);
            const int mrow = (warp & 3) * 16 + (lane & 7) + ((lane >> 3) & 1) * 8;
            const float a0 = 0.5f * rstd0, a1 = 0.5f * rstd1, rm0 = a0 * mean0, rm1 = a1 * mean1;
#pragma unroll
            for (int jj = 0; jj < 14; jj++) {
                const float2 ca = *(const float2*)(s_cs + 16 * jj + 2 * c), cb = *(const float2*)(s_cs + 16 * jj + 8 + 2 * c);
                float y[8] = {acc[8 * jj] * a0 - rm0 * ca.x,     acc[8 * jj + 1] * a0 - rm0 * ca.y,
                              acc[8 * jj + 2] * a1 - rm1 * ca.x, acc[8 * jj + 3] * a1 - rm1 * ca.y,
                              acc[8 * jj + 4] * a0 - rm0 * cb.x, acc[8 * jj + 5] * a0 - rm0 * cb.y,
                              acc[8 * jj + 6] * a1 - rm1 * cb.x, acc[8 * jj + 7] * a1 - rm1 * cb.y};
#pragma unroll
                for (int i = 0; i < 8; i++) {
                    float t;
                    asm("tanh.approx.f32 %0, %1;" : "=f"(t) : "f"(y[i]));
                    y[i] = fmaf(y[i], t, y[i]);
                }
                const int chunk = (2 * jj + (lane >> 4)) & 3, blk = jj >> 1;
                stsm_x4(stile + blk * 4096 + mrow * 64 + ((chunk ^ ((mrow >> 1) & 3)) << 4),
                        pack_bf16(y[0], y[1]), pack_bf16(y[2], y[3]), pack_bf16(y[4], y[5]), pack_bf16(y[6], y[7]));
                if (jj & 1) {
                    fence_async_smem();
                    __syncwarp();
                    if (elect_one()) {
                        tma2d_store(mapC, stile + blk * 4096 + (warp & 3) * 1024, n0 + blk * 32, m0 + wg * 64 + (warp & 3) * 16);
                        bulk_commit();
                    }
                }
            }
            bulk_wait_read();
        }
    }
    if (tid == 0) TL(prm.tk, 3);
    if (MC) cluster_sync();
}

#define WO_ST 9
#define F2_ST 6
#define F1_ST (F1_BK == 64 ? 5 : 9)
#define QKV_ST 8
constexpr int QKV_STAGES = QKV_ST, WO_STAGES = WO_ST, FFN2_STAGES = F2_ST, FFN1_STAGES = F1_ST;
template <bool SELF>
__global__ void __launch_bounds__(SELF ? 416 : 288) qkv_kernel(const __grid_constant__ CUtensorMap mapA, const __grid_constant__ CUtensorMap mapWq,
                                                  const __grid_constant__ CUtensorMap mapWk, const __grid_constant__ CUtensorMap mapWv,
                                                  const __grid_constant__ CUtensorMap mapQ, const GemmParams prm) {
    extern __shared__ __align__(1024) uint8_t smem_raw[];
    const int tn = blockIdx.x & 7;
    if (tn < 2) gemm_body<80, 8, QKV_STAGES, EPI_QKV, QKV_MC, SELF>(&mapA, &mapWq, tn == 0 ? &mapWk : &mapWv, &mapA, &mapQ, prm, blockIdx.x >> 3, tn, smem_raw);
    else gemm_body<64, 8, QKV_STAGES, EPI_QKV, QKV_MC, SELF>(&mapA, &mapWq, &mapWq, &mapA, &mapQ, prm, blockIdx.x >> 3, tn, smem_raw);
}
template <int KB, int STAGES>
__global__ void __launch_bounds__(288) res_gemm_kernel(const __grid_constant__ CUtensorMap mapA, const __grid_constant__ CUtensorMap mapW,
                                                       const __grid_constant__ CUtensorMap mapR, const __grid_constant__ CUtensorMap mapC, const GemmParams prm) {
    extern __shared__ __align__(1024) uint8_t smem_raw[];
    gemm_body<64, KB, STAGES, EPI_RES, (KB == 8 ? WO_MC : F2_MC)>(&mapA, &mapW, &mapW, &mapR, &mapC, prm, blockIdx.x >> 3, blockIdx.x & 7, smem_raw);
}
__global__ void __launch_bounds__(F1_INLINE ? 256 : 288) ffn1_kernel(const __grid_constant__ CUtensorMap mapA, const __grid_constant__ CUtensorMap mapW4,
                                                   const __grid_constant__ CUtensorMap mapW3, const __grid_constant__ CUtensorMap mapH, const GemmParams prm) {
    extern __shared__ __align__(1024) uint8_t smem_raw[];
    const int pair = blockIdx.x >> 1, tile_n = pair & 7, tile_m = (pair >> 3) * 2 + (blockIdx.x & 1);
    gemm_body<224, 512 / F1_BK, FFN1_STAGES, EPI_FFN1, F1_MC>(&mapA, &mapW4, &mapW3, &mapA, &mapH, prm, tile_m, tile_n, smem_raw);
}

constexpr int NPOLY = 10;
__host__ __device__ constexpr bool is_mufu(int i) { return ((i + 1) * (16 - NPOLY)) / 16 != (i * (16 - NPOLY)) / 16; }

__device__ __forceinline__ float ex2(float x) { float r; asm("ex2.approx.ftz.f32 %0, %1;" : "=f"(r) : "f"(x)); return r; }
__device__ __forceinline__ uint32_t exp_pair_mufu(float a, float b) { return pack_bf16(ex2(a), ex2(b)); }
__device__ __forceinline__ uint32_t exp_pair_fma(float a, float b, uint32_t c3f) {
    constexpr float MAGIC = 98430.4140625f;
    const float ta = a + MAGIC, tb = b + (MAGIC - 143.5f);
    uint32_t y, m, r;
    asm("mad.lo.u32 %0, %1, 65536, %2;" : "=r"(y) : "r"(__float_as_uint(tb)), "r"(__float_as_uint(ta)));
    asm("lop3.b32 %0, %1, 0x007F007F, %2, 0xEA;" : "=r"(m) : "r"(y), "r"(c3f));
    const uint32_t e = y & 0xFF80FF80u;
    asm("fma.rn.bf16x2 %0, %1, %2, %3;" : "=r"(r) : "r"(y), "r"(m), "r"(e));
    return r;
}

constexpr int KCH = 256, NCH = S_ / KCH;
constexpr int K_BYTES = S_ * 32, V_BYTES = (S_ / 16) * 768;
constexpr int ATT_SMEM = K_BYTES + V_BYTES;

__global__ void __launch_bounds__(512, 1) attn_kernel(const __nv_bfloat16* __restrict__ wo, const __nv_bfloat16* __restrict__ w1,
                                                       const __nv_bfloat16* __restrict__ w2, int tk) {
    extern __shared__ __align__(1024) uint8_t smem[];
    __shared__ uint64_t bars[NCH];
    __shared__ int s_slow;
    const int tid = threadIdx.x, wg = tid >> 7, warp = (tid >> 5) & 3, lane = tid & 31;
    const uint32_t sK = smem_u32(smem), sV = sK + K_BYTES;
    if (blockIdx.x >= 128) {
        pdl_launch();
        side_job(blockIdx.x - 128, (float*)smem, wo, w1, w2);
        return;
    }
    if (tid == 0) TL(tk, 0);
    if (tid == 0) {
        for (int i = 0; i < NCH; i++) mbar_init(smem_u32(&bars[i]), 1);
        s_slow = 0;
        fence_mbar_init();
    }
    __syncthreads();
    pdl_launch();
    pdl_wait();
    if (tid == 0) TL(tk, 1);
    if (__shfl_sync(0xffffffffu, tid >> 5, 0) == 0 && elect_one()) {
#pragma unroll
        for (int i = 0; i < NCH; i++) {
            mbar_expect_tx(smem_u32(&bars[i]), KCH * 32 + (KCH / 16) * 768);
            bulk_load(sK + i * KCH * 32, g_kimg + i * KCH * 32, KCH * 32, smem_u32(&bars[i]));
            bulk_load(sV + i * (KCH / 16) * 768, g_vimg + i * (KCH / 16) * 768, (KCH / 16) * 768, smem_u32(&bars[i]));
        }
    }
    const int tb = blockIdx.x >> 3, hg = blockIdx.x & 7;
    const int head = hg * 4 + wg;
    const int g = lane >> 2, c = lane & 3;
    uint32_t qa[2][4];
    float qn = 0.f;
#pragma unroll
    for (int m = 0; m < 2; m++) {
        const int row = tb * 128 + m * 64 + warp * 16 + g;
        const uint32_t* p0 = (const uint32_t*)(g_q + (size_t)row * D_ + head * 16);
        const uint32_t* p1 = (const uint32_t*)(g_q + (size_t)(row + 8) * D_ + head * 16);
        qa[m][0] = p0[c]; qa[m][1] = p1[c]; qa[m][2] = p0[c + 4]; qa[m][3] = p1[c + 4];
        float n0 = bf_lo(qa[m][0]) * bf_lo(qa[m][0]) + bf_hi(qa[m][0]) * bf_hi(qa[m][0]) + bf_lo(qa[m][2]) * bf_lo(qa[m][2]) + bf_hi(qa[m][2]) * bf_hi(qa[m][2]);
        float n1 = bf_lo(qa[m][1]) * bf_lo(qa[m][1]) + bf_hi(qa[m][1]) * bf_hi(qa[m][1]) + bf_lo(qa[m][3]) * bf_lo(qa[m][3]) + bf_hi(qa[m][3]) * bf_hi(qa[m][3]);
        n0 += __shfl_xor_sync(0xffffffffu, n0, 1); n0 += __shfl_xor_sync(0xffffffffu, n0, 2);
        n1 += __shfl_xor_sync(0xffffffffu, n1, 1); n1 += __shfl_xor_sync(0xffffffffu, n1, 2);
        if (!(n0 == n0) || !(n1 == n1)) n0 = __int_as_float(0x7f800000);
        qn = fmaxf(qn, fmaxf(n0, n1));
    }
    {
        float km = 0.f, vm = 0.f;
#pragma unroll
        for (int i = 0; i < 16; i++) { km = fmaxf(km, g_kvmax[i]); vm = fmaxf(vm, g_kvmax[16 + i]); }
        const bool ok = (qn * km <= 10000.f) && (vm <= 16384.f);
        if (!ok) s_slow = 1;
    }
    float oacc[2][12];
#pragma unroll
    for (int m = 0; m < 2; m++)
#pragma unroll
        for (int i = 0; i < 12; i++) oacc[m][i] = 0.f;
    __syncthreads();
    const bool slow = s_slow != 0;

    const uint64_t dK0 = mkdesc(sK, 128, 256, 0);
    const uint64_t dV0 = mkdesc(sV, 128, 256, 0);
    uint32_t c3f;
    asm volatile("mov.b32 %0, 0x3F003F00;" : "=r"(c3f));
    if (!slow) {
#pragma unroll 1
        for (int t = 0; t < S_ / 64; t++) {
            if ((t & 3) == 0) mbar_wait(smem_u32(&bars[t >> 2]), 0);
            const uint64_t dK = dK0 + (uint64_t)(t * 64 * 32 / 16);
            const uint64_t dV = dV0 + (uint64_t)(t * 4 * 768 / 16);
#pragma unroll
            for (int m = 0; m < 2; m++) {
                float s[32];
                wg_fence();
                wgmma_rs_n64_z(s, qa[m][0], qa[m][1], qa[m][2], qa[m][3], dK);
                wg_commit();
                wg_wait<0>();
                fence_regs(s);
                uint32_t p[16];
#pragma unroll
                for (int i = 0; i < 16; i++) p[i] = is_mufu(i) ? exp_pair_mufu(s[2 * i], s[2 * i + 1]) : exp_pair_fma(s[2 * i], s[2 * i + 1], c3f);
                wg_fence();
#pragma unroll
                for (int kk = 0; kk < 4; kk++)
                    wgmma_rs_n24_tb(oacc[m], p[4 * kk], p[4 * kk + 1], p[4 * kk + 2], p[4 * kk + 3], dV + (uint64_t)(kk * 768 / 16));
                wg_commit();
            }
        }
        wg_wait<0>();
    } else {
        float mx[2][2] = {{-INFINITY, -INFINITY}, {-INFINITY, -INFINITY}};
#pragma unroll 1
        for (int t = 0; t < S_ / 64; t++) {
            if ((t & 3) == 0) mbar_wait(smem_u32(&bars[t >> 2]), 0);
            const uint64_t dK = dK0 + (uint64_t)(t * 64 * 32 / 16);
            const uint64_t dV = dV0 + (uint64_t)(t * 4 * 768 / 16);
#pragma unroll
            for (int m = 0; m < 2; m++) {
                float s[32];
                wg_fence();
                wgmma_rs_n64_z(s, qa[m][0], qa[m][1], qa[m][2], qa[m][3], dK);
                wg_commit();
                wg_wait<0>();
                fence_regs(s);
                fence_regs(oacc[m]);
                float r0 = mx[m][0], r1 = mx[m][1];
#pragma unroll
                for (int j = 0; j < 8; j++) {
                    r0 = fmaxf(r0, fmaxf(s[4 * j], s[4 * j + 1]));
                    r1 = fmaxf(r1, fmaxf(s[4 * j + 2], s[4 * j + 3]));
                }
                r0 = fmaxf(r0, __shfl_xor_sync(0xffffffffu, r0, 1)); r0 = fmaxf(r0, __shfl_xor_sync(0xffffffffu, r0, 2));
                r1 = fmaxf(r1, __shfl_xor_sync(0xffffffffu, r1, 1)); r1 = fmaxf(r1, __shfl_xor_sync(0xffffffffu, r1, 2));
                const float al0 = ex2(mx[m][0] - r0), al1 = ex2(mx[m][1] - r1);
                mx[m][0] = r0; mx[m][1] = r1;
#pragma unroll
                for (int j = 0; j < 3; j++) {
                    oacc[m][4 * j] *= al0; oacc[m][4 * j + 1] *= al0;
                    oacc[m][4 * j + 2] *= al1; oacc[m][4 * j + 3] *= al1;
                }
                uint32_t p[16];
#pragma unroll
                for (int j = 0; j < 8; j++) {
                    p[2 * j] = pack_bf16(ex2(s[4 * j] - r0), ex2(s[4 * j + 1] - r0));
                    p[2 * j + 1] = pack_bf16(ex2(s[4 * j + 2] - r1), ex2(s[4 * j + 3] - r1));
                }
                fence_regs(oacc[m]);
                wg_fence();
#pragma unroll
                for (int kk = 0; kk < 4; kk++)
                    wgmma_rs_n24_tb(oacc[m], p[4 * kk], p[4 * kk + 1], p[4 * kk + 2], p[4 * kk + 3], dV + (uint64_t)(kk * 768 / 16));
                wg_commit();
                wg_wait<0>();
            }
        }
    }
    fence_regs(oacc[0]); fence_regs(oacc[1]);
    if (tid == 0) TL(tk, 2);
#pragma unroll
    for (int m = 0; m < 2; m++) {
        const float l0 = __shfl_sync(0xffffffffu, oacc[m][8], lane & ~3);
        const float l1 = __shfl_sync(0xffffffffu, oacc[m][10], lane & ~3);
        const float r0 = 1.0f / l0, r1 = 1.0f / l1;
        const int row = tb * 128 + m * 64 + warp * 16 + g;
        uint32_t* p0 = (uint32_t*)(g_o + (size_t)row * D_ + head * 16);
        uint32_t* p1 = (uint32_t*)(g_o + (size_t)(row + 8) * D_ + head * 16);
        p0[c] = pack_bf16(oacc[m][0] * r0, oacc[m][1] * r0);
        p1[c] = pack_bf16(oacc[m][2] * r1, oacc[m][3] * r1);
        p0[c + 4] = pack_bf16(oacc[m][4] * r0, oacc[m][5] * r0);
        p1[c + 4] = pack_bf16(oacc[m][6] * r1, oacc[m][7] * r1);
    }
    if (tid == 0) TL(tk, 3);
}

typedef CUresult (*EncodeFn)(CUtensorMap*, CUtensorMapDataType, cuuint32_t, void*, const cuuint64_t*, const cuuint64_t*, const cuuint32_t*,
                             const cuuint32_t*, CUtensorMapInterleave, CUtensorMapSwizzle, CUtensorMapL2promotion, CUtensorMapFloatOOBfill);

EncodeFn get_encode() {
    static EncodeFn fn = nullptr;
    if (!fn) {
        void* p = nullptr;
        cudaDriverEntryPointQueryResult qr;
        cudaGetDriverEntryPoint("cuTensorMapEncodeTiled", &p, cudaEnableDefault, &qr);
        fn = (EncodeFn)p;
    }
    return fn;
}
CUtensorMap map2d(const void* ptr, uint64_t cols, uint64_t rows, uint32_t bc, uint32_t br, CUtensorMapSwizzle sw) {
    CUtensorMap m;
    cuuint64_t gd[2] = {cols, rows}, gs[1] = {cols * 2};
    cuuint32_t bx[2] = {bc, br}, es[2] = {1, 1};
    get_encode()(&m, CU_TENSOR_MAP_DATA_TYPE_BFLOAT16, 2, (void*)ptr, gd, gs, bx, es, CU_TENSOR_MAP_INTERLEAVE_NONE, sw,
                 CU_TENSOR_MAP_L2_PROMOTION_L2_128B, CU_TENSOR_MAP_FLOAT_OOB_FILL_NONE);
    return m;
}
CUtensorMap map3d32(const void* ptr, uint64_t cols, uint64_t rows, uint32_t br, uint32_t nb) {
    CUtensorMap m;
    cuuint64_t gd[3] = {32, rows, cols / 32}, gs[2] = {cols * 2, 64};
    cuuint32_t bx[3] = {32, br, nb}, es[3] = {1, 1, 1};
    get_encode()(&m, CU_TENSOR_MAP_DATA_TYPE_BFLOAT16, 3, (void*)ptr, gd, gs, bx, es, CU_TENSOR_MAP_INTERLEAVE_NONE, CU_TENSOR_MAP_SWIZZLE_64B,
                 CU_TENSOR_MAP_L2_PROMOTION_L2_128B, CU_TENSOR_MAP_FLOAT_OOB_FILL_NONE);
    return m;
}

template <typename... KArgs, typename... Args>
void launch(void (*kern)(KArgs...), int grid, int block, int smem, int cluster, bool pdl, Args... args) {
    cudaLaunchConfig_t cfg = {};
    cfg.gridDim = dim3(grid);
    cfg.blockDim = dim3(block);
    cfg.dynamicSmemBytes = smem;
    cfg.stream = cudaStreamPerThread;
    cudaLaunchAttribute at[2];
    int n = 0;
    if (cluster > 1) { at[n].id = cudaLaunchAttributeClusterDimension; at[n].val.clusterDim.x = cluster; at[n].val.clusterDim.y = 1; at[n].val.clusterDim.z = 1; n++; }
    if (pdl) { at[n].id = cudaLaunchAttributeProgrammaticStreamSerialization; at[n].val.programmaticStreamSerializationAllowed = 1; n++; }
    cfg.attrs = at;
    cfg.numAttrs = n;
    cudaLaunchKernelEx(&cfg, kern, KArgs(args)...);
}

template <typename T> void* sym(const T& s) { void* p = nullptr; cudaGetSymbolAddress(&p, s); return p; }

}

extern "C" void kernel_launch(void* const* d_in, const int* in_sizes, int n_in, void* d_out, int out_size) {
    const __nv_bfloat16* x = (const __nv_bfloat16*)d_in[0];
    const __nv_bfloat16* wq = (const __nv_bfloat16*)d_in[1];
    const __nv_bfloat16* wk = (const __nv_bfloat16*)d_in[2];
    const __nv_bfloat16* wv = (const __nv_bfloat16*)d_in[3];
    const __nv_bfloat16* wo = (const __nv_bfloat16*)d_in[4];
    const __nv_bfloat16* w1 = (const __nv_bfloat16*)d_in[6];
    const __nv_bfloat16* w2 = (const __nv_bfloat16*)d_in[7];

    constexpr int SM_QKV = GemmSmem<QKV_STAGES, EPI_QKV>::TOTAL, SM_QKV0 = GemmSmem<QKV_STAGES, EPI_QKV>::TOTAL_SELF;
    static_assert(SM_QKV0 <= 232448, "shared memory");
    constexpr int HALF_PLUS = 116736;
    constexpr int SM_WO = GemmSmem<WO_STAGES, EPI_RES>::TOTAL > HALF_PLUS ? GemmSmem<WO_STAGES, EPI_RES>::TOTAL : HALF_PLUS;
    constexpr int SM_FFN2 = GemmSmem<FFN2_STAGES, EPI_RES>::TOTAL > HALF_PLUS ? GemmSmem<FFN2_STAGES, EPI_RES>::TOTAL : HALF_PLUS;
    constexpr int SM_FFN1 = GemmSmem<FFN1_STAGES, EPI_FFN1>::TOTAL;
    cudaFuncSetAttribute(qkv_kernel<false>, cudaFuncAttributeMaxDynamicSharedMemorySize, SM_QKV);
    cudaFuncSetAttribute(qkv_kernel<true>, cudaFuncAttributeMaxDynamicSharedMemorySize, SM_QKV0);
    cudaFuncSetAttribute(res_gemm_kernel<8, WO_STAGES>, cudaFuncAttributeMaxDynamicSharedMemorySize, SM_WO);
    cudaFuncSetAttribute(ffn1_kernel, cudaFuncAttributeMaxDynamicSharedMemorySize, SM_FFN1);
    cudaFuncSetAttribute(res_gemm_kernel<28, FFN2_STAGES>, cudaFuncAttributeMaxDynamicSharedMemorySize, SM_FFN2);
    cudaFuncSetAttribute(attn_kernel, cudaFuncAttributeMaxDynamicSharedMemorySize, ATT_SMEM);
    cudaFuncSetAttribute(qkv_kernel<false>, cudaFuncAttributePreferredSharedMemoryCarveout, 100);
    cudaFuncSetAttribute(qkv_kernel<true>, cudaFuncAttributePreferredSharedMemoryCarveout, 100);
    cudaFuncSetAttribute(res_gemm_kernel<8, WO_STAGES>, cudaFuncAttributePreferredSharedMemoryCarveout, 100);
    cudaFuncSetAttribute(ffn1_kernel, cudaFuncAttributePreferredSharedMemoryCarveout, 100);
    cudaFuncSetAttribute(res_gemm_kernel<28, FFN2_STAGES>, cudaFuncAttributePreferredSharedMemoryCarveout, 100);
    cudaFuncSetAttribute(attn_kernel, cudaFuncAttributePreferredSharedMemoryCarveout, 100);

    void *q = sym(g_q), *o = sym(g_o), *x1 = sym(g_x1), *x2 = sym(g_x2), *x3 = sym(g_x3), *h = sym(g_h);
    float2* stats = (float2*)sym(g_stats);
    const void* xs[5] = {x, x1, x2, x3, d_out};

    const CUtensorMapSwizzle SW128 = CU_TENSOR_MAP_SWIZZLE_128B, SW64 = CU_TENSOR_MAP_SWIZZLE_64B;
    const CUtensorMap mWq = map3d32(wq, D_, D_, 64, 2);
    const CUtensorMap mWk = map2d(wk, 16, D_, 32, 64, SW64);
    const CUtensorMap mWv = map2d(wv, 16, D_, 32, 64, SW64);
    const CUtensorMap mWo = map2d(wo, D_, D_, 64, 64, SW128);
    const CUtensorMap mW1a = map3d32(w1, F_, D_, F1_BK, 4), mW1b = map3d32(w1, F_, D_, F1_BK, 3);
    const CUtensorMap mW2 = map2d(w2, D_, F_, 64, 64, SW128);
    const CUtensorMap mQ = map2d(q, D_, S_, 64, 64, SW128);
    const CUtensorMap mHst = map2d(h, F_, S_, 32, 16, SW64);
    CUtensorMap mXa[4], mXf[4], mXr[4], mXs[5];
    for (int i = 0; i < 4; i++) {
        mXa[i] = map2d(xs[i], D_, S_, 64, QKV_MC ? 64 : 128, SW128);
        mXf[i] = F1_BK == 64 ? map2d(xs[i], D_, S_, 64, 128, SW128) : map2d(xs[i], D_, S_, 32, 128, SW64);
        mXr[i] = map2d(xs[i], D_, S_, 64, 128, SW128);
    }
    for (int i = 0; i < 5; i++) mXs[i] = map2d(xs[i], D_, S_, 64, 64, SW128);
    const CUtensorMap mOa = map2d(o, D_, S_, 64, WO_MC ? 64 : 128, SW128);
    const CUtensorMap mHa = map2d(h, F_, S_, 64, F2_MC ? 64 : 128, SW128);

    for (int layer = 0; layer < 2; layer++) {
        const int xi = layer * 2;
        GemmParams p;
        p.stats_in = stats + (size_t)xi * 8 * S_; p.stats_out = nullptr; p.tk = 1 + 5 * layer;
        if (layer == 0) launch(qkv_kernel<true>, 128, 416, SM_QKV0, QKV_MC ? 2 : 1, false, mXa[xi], mWq, mWk, mWv, mQ, p);
        else launch(qkv_kernel<false>, 128, 288, SM_QKV, QKV_MC ? 2 : 1, true, mXa[xi], mWq, mWk, mWv, mQ, p);
        launch(attn_kernel, layer == 0 ? 128 + SIDE_CTAS : 128, 512, ATT_SMEM, 1, true, wo, w1, w2, 2 + 5 * layer);
        p.stats_in = nullptr; p.stats_out = stats + (size_t)(xi + 1) * 8 * S_; p.tk = 3 + 5 * layer;
        launch(res_gemm_kernel<8, WO_STAGES>, 128, 288, SM_WO, WO_MC ? 2 : 1, true, mOa, mWo, mXr[xi], mXs[xi + 1], p);
        p.stats_in = stats + (size_t)(xi + 1) * 8 * S_; p.stats_out = nullptr; p.tk = 4 + 5 * layer;
        launch(ffn1_kernel, 128, F1_INLINE ? 256 : 288, SM_FFN1, F1_MC ? 2 : 1, true, mXf[xi + 1], mW1a, mW1b, mHst, p);
        p.stats_in = nullptr; p.stats_out = layer == 0 ? stats + (size_t)2 * 8 * S_ : nullptr; p.tk = 5 + 5 * layer;
        launch(res_gemm_kernel<28, FFN2_STAGES>, 128, 288, SM_FFN2, F2_MC ? 2 : 1, true, mHa, mW2, mXr[xi + 1], mXs[xi + 2], p);
    }
}
```

```cpp
#include <cuda_runtime.h>
#include <cuda_bf16.h>
#include <cuda.h>
#include <stdint.h>

#define F1_INLINE 0
#define QKV_MC 0
#define WO_MC 0
#define F2_MC 0
#define F1_MC 2
#define PREB 2
#define RES_WAIT0 0

namespace {

constexpr int S_ = 2048, D_ = 512, H_ = 32, F_ = 1792;

__device__ __align__(1024) __nv_bfloat16 g_q[S_ * D_];
__device__ __align__(1024) __nv_bfloat16 g_o[S_ * D_];
__device__ __align__(1024) __nv_bfloat16 g_x1[S_ * D_];
__device__ __align__(1024) __nv_bfloat16 g_x2[S_ * D_];
__device__ __align__(1024) __nv_bfloat16 g_x3[S_ * D_];
__device__ __align__(1024) __nv_bfloat16 g_h[S_ * F_];
__device__ __align__(1024) uint8_t g_kimg[S_ * 32];
__device__ __align__(1024) uint8_t g_vimg[(S_ / 16) * 768];
__device__ __align__(1024) float2 g_stats[4][8 * S_];
__device__ __align__(16) float g_cs_q[D_];
__device__ __align__(16) float g_cs_kv[32];
__device__ __align__(16) float g_cs_1[F_];
__device__ __align__(16) float g_kvmax[32];

#define TL(k, slot)

__device__ __forceinline__ uint32_t smem_u32(const void* p) { return (uint32_t)__cvta_generic_to_shared(p); }
__device__ __forceinline__ void mbar_init(uint32_t bar, uint32_t cnt) {
    asm volatile("mbarrier.init.shared::cta.b64 [%0], %1;" ::"r"(bar), "r"(cnt));
}
__device__ __forceinline__ void mbar_expect_tx(uint32_t bar, uint32_t bytes) {
    asm volatile("mbarrier.arrive.expect_tx.shared::cta.b64 _, [%0], %1;" ::"r"(bar), "r"(bytes) : "memory");
}
__device__ __forceinline__ void mbar_arrive(uint32_t bar) {
    asm volatile("mbarrier.arrive.shared::cta.b64 _, [%0];" ::"r"(bar) : "memory");
}
__device__ __forceinline__ void mbar_arrive_remote(uint32_t bar, uint32_t cta) {
    asm volatile("{\n.reg .b32 ra;\nmapa.shared::cluster.u32 ra, %0, %1;\nmbarrier.arrive.shared::cluster.b64 _, [ra];\n}" ::"r"(bar), "r"(cta) : "memory");
}
__device__ __forceinline__ void mbar_wait(uint32_t bar, uint32_t parity) {
    asm volatile("{\n.reg .pred p;\nWAIT_%=:\nmbarrier.try_wait.parity.shared::cta.b64 p, [%0], %1;\n@p bra DONE_%=;\nbra WAIT_%=;\nDONE_%=:\n}" ::"r"(bar), "r"(parity) : "memory");
}
__device__ __forceinline__ void bulk_load(uint32_t dst, const void* src, uint32_t bytes, uint32_t bar) {
    asm volatile("cp.async.bulk.shared::cluster.global.mbarrier::complete_tx::bytes [%0], [%1], %2, [%3];" ::"r"(dst), "l"(src), "r"(bytes), "r"(bar) : "memory");
}
__device__ __forceinline__ void tma2d(uint32_t dst, const CUtensorMap* m, int c0, int c1, uint32_t bar) {
    asm volatile("cp.async.bulk.tensor.2d.shared::cluster.global.mbarrier::complete_tx::bytes [%0], [%1, {%3, %4}], [%2];" ::"r"(dst), "l"(m), "r"(bar), "r"(c0), "r"(c1) : "memory");
}
__device__ __forceinline__ void tma2d_mc(uint32_t dst, const CUtensorMap* m, int c0, int c1, uint32_t bar, uint16_t mask) {
    asm volatile("cp.async.bulk.tensor.2d.shared::cluster.global.mbarrier::complete_tx::bytes.multicast::cluster [%0], [%1, {%3, %4}], [%2], %5;" ::"r"(dst), "l"(m), "r"(bar), "r"(c0), "r"(c1), "h"(mask) : "memory");
}
__device__ __forceinline__ void tma3d(uint32_t dst, const CUtensorMap* m, int c0, int c1, int c2, uint32_t bar) {
    asm volatile("cp.async.bulk.tensor.3d.shared::cluster.global.mbarrier::complete_tx::bytes [%0], [%1, {%3, %4, %5}], [%2];" ::"r"(dst), "l"(m), "r"(bar), "r"(c0), "r"(c1), "r"(c2) : "memory");
}
__device__ __forceinline__ void tma3d_mc(uint32_t dst, const CUtensorMap* m, int c0, int c1, int c2, uint32_t bar, uint16_t mask) {
    asm volatile("cp.async.bulk.tensor.3d.shared::cluster.global.mbarrier::complete_tx::bytes.multicast::cluster [%0], [%1, {%3, %4, %5}], [%2], %6;" ::"r"(dst), "l"(m), "r"(bar), "r"(c0), "r"(c1), "r"(c2), "h"(mask) : "memory");
}
__device__ __forceinline__ void tma2d_store(const CUtensorMap* m, uint32_t src, int c0, int c1) {
    asm volatile("cp.async.bulk.tensor.2d.global.shared::cta.bulk_group [%0, {%2, %3}], [%1];" ::"l"(m), "r"(src), "r"(c0), "r"(c1) : "memory");
}
__device__ __forceinline__ void tma3d_store(const CUtensorMap* m, uint32_t src, int c0, int c1, int c2) {
    asm volatile("cp.async.bulk.tensor.3d.global.shared::cta.bulk_group [%0, {%2, %3, %4}], [%1];" ::"l"(m), "r"(src), "r"(c0), "r"(c1), "r"(c2) : "memory");
}
__device__ __forceinline__ void bulk_commit() { asm volatile("cp.async.bulk.commit_group;" ::: "memory"); }
__device__ __forceinline__ void bulk_wait_read() { asm volatile("cp.async.bulk.wait_group.read 0;" ::: "memory"); }
__device__ __forceinline__ void prefetch_tmap(const CUtensorMap* m) { asm volatile("prefetch.tensormap [%0];" ::"l"(m) : "memory"); }
__device__ __forceinline__ void fence_async_smem() { asm volatile("fence.proxy.async.shared::cta;" ::: "memory"); }
__device__ __forceinline__ void fence_mbar_init() { asm volatile("fence.mbarrier_init.release.cluster;" ::: "memory"); }
__device__ __forceinline__ void cluster_sync() { asm volatile("barrier.cluster.arrive.release.aligned;\nbarrier.cluster.wait.acquire.aligned;" ::: "memory"); }
__device__ __forceinline__ uint32_t cluster_rank() { uint32_t r; asm volatile("mov.u32 %0, %%cluster_ctarank;" : "=r"(r)); return r; }
__device__ __forceinline__ void pdl_wait() { asm volatile("griddepcontrol.wait;" ::: "memory"); }
__device__ __forceinline__ void pdl_launch() { asm volatile("griddepcontrol.launch_dependents;" ::: "memory"); }
__device__ __forceinline__ bool elect_one() {
    uint32_t p;
    asm volatile("{\n.reg .pred p;\nelect.sync _|p, 0xffffffff;\nselp.b32 %0, 1, 0, p;\n}" : "=r"(p));
    return p != 0;
}
__device__ __forceinline__ void named_bar(int id, int n) { asm volatile("bar.sync %0, %1;" ::"r"(id), "r"(n) : "memory"); }

__device__ __forceinline__ void wg_fence() { asm volatile("wgmma.fence.sync.aligned;" ::: "memory"); }
__device__ __forceinline__ void wg_commit() { asm volatile("wgmma.commit_group.sync.aligned;" ::: "memory"); }
template <int N> __device__ __forceinline__ void wg_wait() { asm volatile("wgmma.wait_group.sync.aligned %0;" ::"n"(N) : "memory"); }
template <int N> __device__ __forceinline__ void fence_regs(float (&d)[N]) {
#pragma unroll
    for (int i = 0; i < N; i++) asm volatile("" : "+f"(d[i])::"memory");
}
__device__ __forceinline__ uint64_t mkdesc(uint32_t addr, uint32_t lbo, uint32_t sbo, uint32_t swz) {
    uint64_t d = 0;
    d |= (uint64_t)((addr & 0x3FFFF) >> 4);
    d |= (uint64_t)((lbo & 0x3FFFF) >> 4) << 16;
    d |= (uint64_t)((sbo & 0x3FFFF) >> 4) << 32;
    d |= (uint64_t)swz << 62;
    return d;
}
__device__ __forceinline__ void ldsm_x4(uint32_t& r0, uint32_t& r1, uint32_t& r2, uint32_t& r3, uint32_t addr) {
    asm volatile("ldmatrix.sync.aligned.m8n8.x4.shared.b16 {%0,%1,%2,%3}, [%4];" : "=r"(r0), "=r"(r1), "=r"(r2), "=r"(r3) : "r"(addr) : "memory");
}
__device__ __forceinline__ void stsm_x4(uint32_t addr, uint32_t r0, uint32_t r1, uint32_t r2, uint32_t r3) {
    asm volatile("stmatrix.sync.aligned.m8n8.x4.shared.b16 [%0], {%1,%2,%3,%4};" ::"r"(addr), "r"(r0), "r"(r1), "r"(r2), "r"(r3) : "memory");
}
__device__ __forceinline__ void ldsm_x4_t(uint32_t& r0, uint32_t& r1, uint32_t& r2, uint32_t& r3, uint32_t addr) {
    asm volatile("ldmatrix.sync.aligned.m8n8.x4.trans.shared.b16 {%0,%1,%2,%3}, [%4];" : "=r"(r0), "=r"(r1), "=r"(r2), "=r"(r3) : "r"(addr) : "memory");
}
__device__ __forceinline__ void hmma(float (&d)[4], uint32_t a0, uint32_t a1, uint32_t a2, uint32_t a3, uint32_t b0, uint32_t b1) {
    asm volatile("mma.sync.aligned.m16n8k16.row.col.f32.bf16.bf16.f32 {%0,%1,%2,%3}, {%4,%5,%6,%7}, {%8,%9}, {%0,%1,%2,%3};"
                 : "+f"(d[0]), "+f"(d[1]), "+f"(d[2]), "+f"(d[3]) : "r"(a0), "r"(a1), "r"(a2), "r"(a3), "r"(b0), "r"(b1));
}
__device__ __forceinline__ uint32_t pack_bf16(float lo, float hi) {
    uint32_t r;
    asm("cvt.rn.bf16x2.f32 %0, %1, %2;" : "=r"(r) : "f"(hi), "f"(lo));
    return r;
}
__device__ __forceinline__ float bf_lo(uint32_t v) { return __uint_as_float(v << 16); }
__device__ __forceinline__ float bf_hi(uint32_t v) { return __uint_as_float(v & 0xFFFF0000u); }

#define WG_REGS_4(o) "+f"(d[o]), "+f"(d[o + 1]), "+f"(d[o + 2]), "+f"(d[o + 3])
#define WG_REGS_8(o) WG_REGS_4(o), WG_REGS_4(o + 4)
#define WG_REGS_16(o) WG_REGS_8(o), WG_REGS_8(o + 8)
#define WG_REGS_32(o) WG_REGS_16(o), WG_REGS_16(o + 16)

__device__ __forceinline__ void wgmma_ss_n80_tb(float (&d)[40], uint64_t dA, uint64_t dB, int sc) {
    asm volatile("{\n.reg .pred p;\nsetp.ne.b32 p, %42, 0;\n"
                 "wgmma.mma_async.sync.aligned.m64n80k16.f32.bf16.bf16 "
                 "{%0,%1,%2,%3,%4,%5,%6,%7,%8,%9,%10,%11,%12,%13,%14,%15,%16,%17,%18,%19,%20,%21,%22,%23,%24,%25,%26,%27,%28,%29,%30,%31,"
                 "%32,%33,%34,%35,%36,%37,%38,%39}, %40, %41, p, 1, 1, 0, 1;\n}\n"
                 : WG_REGS_32(0), WG_REGS_8(32) : "l"(dA), "l"(dB), "r"(sc));
}
__device__ __forceinline__ void wgmma_ss_n64_tb(float (&d)[32], uint64_t dA, uint64_t dB, int sc) {
    asm volatile("{\n.reg .pred p;\nsetp.ne.b32 p, %34, 0;\n"
                 "wgmma.mma_async.sync.aligned.m64n64k16.f32.bf16.bf16 "
                 "{%0,%1,%2,%3,%4,%5,%6,%7,%8,%9,%10,%11,%12,%13,%14,%15,%16,%17,%18,%19,%20,%21,%22,%23,%24,%25,%26,%27,%28,%29,%30,%31}, "
                 "%32, %33, p, 1, 1, 0, 1;\n}\n"
                 : WG_REGS_32(0) : "l"(dA), "l"(dB), "r"(sc));
}
__device__ __forceinline__ void wgmma_ss_n224_tb(float (&d)[112], uint64_t dA, uint64_t dB, int sc) {
    asm volatile("{\n.reg .pred p;\nsetp.ne.b32 p, %114, 0;\n"
                 "wgmma.mma_async.sync.aligned.m64n224k16.f32.bf16.bf16 "
                 "{%0,%1,%2,%3,%4,%5,%6,%7,%8,%9,%10,%11,%12,%13,%14,%15,%16,%17,%18,%19,%20,%21,%22,%23,%24,%25,%26,%27,%28,%29,%30,%31,"
                 "%32,%33,%34,%35,%36,%37,%38,%39,%40,%41,%42,%43,%44,%45,%46,%47,%48,%49,%50,%51,%52,%53,%54,%55,%56,%57,%58,%59,%60,%61,%62,%63,"
                 "%64,%65,%66,%67,%68,%69,%70,%71,%72,%73,%74,%75,%76,%77,%78,%79,%80,%81,%82,%83,%84,%85,%86,%87,%88,%89,%90,%91,%92,%93,%94,%95,"
                 "%96,%97,%98,%99,%100,%101,%102,%103,%104,%105,%106,%107,%108,%109,%110,%111}, "
                 "%112, %113, p, 1, 1, 0, 1;\n}\n"
                 : WG_REGS_32(0), WG_REGS_32(32), WG_REGS_32(64), WG_REGS_16(96) : "l"(dA), "l"(dB), "r"(sc));
}
template <int BN> __device__ __forceinline__ void wgmma_ss_tb(float (&d)[BN / 2], uint64_t dA, uint64_t dB, int sc) {
    if constexpr (BN == 64) wgmma_ss_n64_tb(d, dA, dB, sc);
    else if constexpr (BN == 80) wgmma_ss_n80_tb(d, dA, dB, sc);
    else wgmma_ss_n224_tb(d, dA, dB, sc);
}
__device__ __forceinline__ void wgmma_rs_n64_z(float (&d)[32], uint32_t a0, uint32_t a1, uint32_t a2, uint32_t a3, uint64_t dB) {
    asm volatile("{\n.reg .pred p;\nsetp.ne.b32 p, 0, 0;\n"
                 "wgmma.mma_async.sync.aligned.m64n64k16.f32.bf16.bf16 "
                 "{%0,%1,%2,%3,%4,%5,%6,%7,%8,%9,%10,%11,%12,%13,%14,%15,%16,%17,%18,%19,%20,%21,%22,%23,%24,%25,%26,%27,%28,%29,%30,%31}, "
                 "{%32,%33,%34,%35}, %36, p, 1, 1, 0;\n}\n"
                 : "=f"(d[0]), "=f"(d[1]), "=f"(d[2]), "=f"(d[3]), "=f"(d[4]), "=f"(d[5]), "=f"(d[6]), "=f"(d[7]),
                   "=f"(d[8]), "=f"(d[9]), "=f"(d[10]), "=f"(d[11]), "=f"(d[12]), "=f"(d[13]), "=f"(d[14]), "=f"(d[15]),
                   "=f"(d[16]), "=f"(d[17]), "=f"(d[18]), "=f"(d[19]), "=f"(d[20]), "=f"(d[21]), "=f"(d[22]), "=f"(d[23]),
                   "=f"(d[24]), "=f"(d[25]), "=f"(d[26]), "=f"(d[27]), "=f"(d[28]), "=f"(d[29]), "=f"(d[30]), "=f"(d[31])
                 : "r"(a0), "r"(a1), "r"(a2), "r"(a3), "l"(dB));
}
__device__ __forceinline__ void wgmma_rs_n24_tb(float (&d)[12], uint32_t a0, uint32_t a1, uint32_t a2, uint32_t a3, uint64_t dB) {
    asm volatile("{\n.reg .pred p;\nsetp.eq.b32 p, 0, 0;\n"
                 "wgmma.mma_async.sync.aligned.m64n24k16.f32.bf16.bf16 "
                 "{%0,%1,%2,%3,%4,%5,%6,%7,%8,%9,%10,%11}, {%12,%13,%14,%15}, %16, p, 1, 1, 1;\n}\n"
                 : WG_REGS_8(0), WG_REGS_4(8) : "r"(a0), "r"(a1), "r"(a2), "r"(a3), "l"(dB));
}

constexpr int SIDE_CTAS = 4;
__device__ __forceinline__ void side_job(int cta, float* red  , const __nv_bfloat16* __restrict__ wo,
                                         const __nv_bfloat16* __restrict__ w1, const __nv_bfloat16* __restrict__ w2) {
    const int tid = threadIdx.x, warp = tid >> 5, lane = tid & 31;
    for (int line = cta * 512 + tid; line < 18432; line += SIDE_CTAS * 512) {
        const char* p = line < 4096 ? (const char*)wo + (size_t)line * 128 : (const char*)w2 + (size_t)(line - 4096) * 128;
        asm volatile("prefetch.global.L2 [%0];" ::"l"(p));
    }
    const int rg = lane >> 3, c8 = lane & 7;
    for (int slab = cta; slab < F_ / 64; slab += SIDE_CTAS) {
        const __nv_bfloat16* base = w1 + slab * 64 + c8 * 8;
        uint4 v[8];
#pragma unroll
        for (int i = 0; i < 8; i++) v[i] = __ldg((const uint4*)(base + (size_t)(warp * 32 + rg + 4 * i) * F_));
        float acc[8];
#pragma unroll
        for (int i = 0; i < 8; i++) acc[i] = 0.f;
#pragma unroll
        for (int i = 0; i < 8; i++) {
            acc[0] += bf_lo(v[i].x); acc[1] += bf_hi(v[i].x); acc[2] += bf_lo(v[i].y); acc[3] += bf_hi(v[i].y);
            acc[4] += bf_lo(v[i].z); acc[5] += bf_hi(v[i].z); acc[6] += bf_lo(v[i].w); acc[7] += bf_hi(v[i].w);
        }
#pragma unroll
        for (int i = 0; i < 8; i++) {
            acc[i] += __shfl_xor_sync(0xffffffffu, acc[i], 8);
            acc[i] += __shfl_xor_sync(0xffffffffu, acc[i], 16);
        }
        if (rg == 0) {
#pragma unroll
            for (int i = 0; i < 8; i++) red[warp * 64 + c8 * 8 + i] = acc[i];
        }
        __syncthreads();
        if (tid < 64) {
            float s = 0.f;
#pragma unroll
            for (int i = 0; i < 16; i++) s += red[i * 64 + tid];
            g_cs_1[slab * 64 + tid] = s;
        }
        __syncthreads();
    }
}

enum { EPI_QKV = 0, EPI_RES = 1, EPI_FFN1 = 2 };

struct GemmParams {
    const float2* stats_in;
    float2* stats_out;
    int tk;
};

template <int BK_, int NBLK> struct Geo {
    static constexpr int BK = BK_, A_BYTES = 128 * BK * 2, A_SWZ = BK == 64 ? 1 : 2, A_SBO = BK * 16;
    static constexpr int BLK = BK * 64;
    static constexpr int B_BYTES = NBLK * BLK, B_SWZ = 2, B_LBO = BLK, B_SBO = 512, B_KSTEP = 1024;
};
template <> struct Geo<64, 0> {
    static constexpr int BK = 64, A_BYTES = 128 * 128, A_SWZ = 1, A_SBO = 1024, BLK = 8192;
    static constexpr int B_BYTES = 64 * 128, B_SWZ = 1, B_LBO = 8192, B_SBO = 1024, B_KSTEP = 2048;
};
#define F1_BK 32
template <int EPI> struct EpiGeo;
template <> struct EpiGeo<EPI_QKV> { using G = Geo<64, 3>; };
template <> struct EpiGeo<EPI_RES> { using G = Geo<64, 0>; };
template <> struct EpiGeo<EPI_FFN1> { using G = Geo<F1_BK, 7>; };

template <int STAGES, int EPI> struct GemmSmem {
    using G = typename EpiGeo<EPI>::G;
    static constexpr int STAGE = G::A_BYTES + G::B_BYTES;
    static constexpr int AUX_OFF = STAGES * STAGE;
    static constexpr int TOTAL = AUX_OFF + 1152;
    static constexpr int TOTAL_SELF = AUX_OFF + 704 + 1024 + 1280;
};

struct RowStatRaw { float2 a0, a1, b0, b1; };
__device__ __forceinline__ RowStatRaw load_row_stats(const float2* __restrict__ st, int row0, int c) {
    RowStatRaw r;
    r.a0 = st[(2 * c) * S_ + row0]; r.a1 = st[(2 * c + 1) * S_ + row0];
    r.b0 = st[(2 * c) * S_ + row0 + 8]; r.b1 = st[(2 * c + 1) * S_ + row0 + 8];
    return r;
}
__device__ __forceinline__ void finish_row_stats(const RowStatRaw& r, float& mean0, float& rstd0, float& mean1, float& rstd1) {
    float sa = r.a0.x + r.a1.x, sb = r.b0.x + r.b1.x;
    sa += __shfl_xor_sync(0xffffffffu, sa, 1); sa += __shfl_xor_sync(0xffffffffu, sa, 2);
    sb += __shfl_xor_sync(0xffffffffu, sb, 1); sb += __shfl_xor_sync(0xffffffffu, sb, 2);
    mean0 = sa * 0.125f; mean1 = sb * 0.125f;
    float ma = r.a0.y + r.a1.y + 64.f * ((r.a0.x - mean0) * (r.a0.x - mean0) + (r.a1.x - mean0) * (r.a1.x - mean0));
    float mb = r.b0.y + r.b1.y + 64.f * ((r.b0.x - mean1) * (r.b0.x - mean1) + (r.b1.x - mean1) * (r.b1.x - mean1));
    ma += __shfl_xor_sync(0xffffffffu, ma, 1); ma += __shfl_xor_sync(0xffffffffu, ma, 2);
    mb += __shfl_xor_sync(0xffffffffu, mb, 1); mb += __shfl_xor_sync(0xffffffffu, mb, 2);
    rstd0 = 1.0f / sqrtf(ma * (1.f / 512.f) + 1e-5f);
    rstd1 = 1.0f / sqrtf(mb * (1.f / 512.f) + 1e-5f);
}

template <int BN, int KB, int STAGES, int EPI, int MC, bool SELF = false>
__device__ __forceinline__ void gemm_body(const CUtensorMap* mapA, const CUtensorMap* mapB, const CUtensorMap* mapB2, const CUtensorMap* mapR,
                                          const CUtensorMap* mapC, const GemmParams& prm, int tile_m, int tile_n, uint8_t* smem_raw) {
    using SM = GemmSmem<STAGES, EPI>;
    using G = typename SM::G;
    constexpr bool XKV = BN == 80;
    constexpr int TN = EPI == EPI_QKV ? 64 : BN;
    pdl_launch();
    const uint32_t sbase = smem_u32(smem_raw);
    if (sbase & 1023) __trap();
    uint8_t* sgen = smem_raw;
    const uint32_t bar_full = sbase + SM::AUX_OFF, bar_empty = bar_full + 8 * STAGES;
    float* s_cs = (float*)(sgen + SM::AUX_OFF + 256);
    float* s_row = (float*)(sgen + SM::AUX_OFF + 704);
    float* s_red = (float*)(sgen + SM::AUX_OFF + 640);
    const int tid = threadIdx.x, lane = tid & 31;
    const int warp = __shfl_sync(0xffffffffu, tid >> 5, 0);
    const uint32_t rank = MC ? cluster_rank() : 0;
    if (tid == 0) TL(prm.tk, 0);

    constexpr bool INLINE_PROD = EPI == EPI_FFN1 && F1_INLINE;
    constexpr int PWARP = INLINE_PROD ? 0 : 8;
    if (warp == PWARP && elect_one()) {
        prefetch_tmap(mapB); prefetch_tmap(mapA); prefetch_tmap(mapC);
        for (int s = 0; s < STAGES; s++) { mbar_init(bar_full + 8 * s, 1); mbar_init(bar_empty + 8 * s, MC ? 4 : 2); }
        fence_mbar_init();
    }
    __syncthreads();
    if (MC) cluster_sync();

    const int m0 = tile_m * 128, n0 = tile_n * TN;
    constexpr uint32_t STAGE_TX = G::A_BYTES + (EPI == EPI_QKV ? (XKV ? 3 : 2) * G::BLK : G::B_BYTES);
    auto loadB = [&](int kb, int s) {
        const uint32_t dst = sbase + s * SM::STAGE + G::A_BYTES, bar = bar_full + 8 * s;
        if constexpr (EPI == EPI_RES) {
            tma2d(dst, mapB, n0, kb * 64, bar);
        } else if constexpr (EPI == EPI_QKV) {
            tma3d(dst, mapB, 0, kb * G::BK, tile_n * 2, bar);
            if constexpr (XKV) tma2d(dst + 2 * G::BLK, mapB2, 0, kb * G::BK, bar);
        } else {
            if constexpr (MC == 2) {
                if (rank == 0) tma3d_mc(dst, mapB, 0, kb * G::BK, tile_n * 7, bar, 3);
                else tma3d_mc(dst + 4 * G::BLK, mapB2, 0, kb * G::BK, tile_n * 7 + 4, bar, 3);
            } else {
                tma3d(dst, mapB, 0, kb * G::BK, tile_n * 7, bar);
                tma3d(dst + 4 * G::BLK, mapB2, 0, kb * G::BK, tile_n * 7 + 4, bar);
            }
        }
    };
    auto loadA = [&](int kb, int s) {
        const uint32_t dst = sbase + s * SM::STAGE, bar = bar_full + 8 * s;
        if constexpr (MC == 1) tma2d_mc(dst + rank * (G::A_BYTES / 2), mapA, kb * G::BK, m0 + rank * 64, bar, 3);
        else tma2d(dst, mapA, kb * G::BK, m0, bar);
    };
    constexpr int PRE = STAGES < KB ? STAGES : KB;
#define F1_LAG 2
    constexpr int LAG = F1_LAG;
    constexpr int PRE_B = PRE < PREB ? PRE : PREB;
    auto prologue_loads = [&]() {
        if (elect_one()) {
#pragma unroll
            for (int kb = 0; kb < PRE; kb++) mbar_expect_tx(bar_full + 8 * kb, STAGE_TX);
#pragma unroll
            for (int kb = 0; kb < PRE_B; kb++) loadB(kb, kb);
        }
        if (!SELF) pdl_wait();
        if (elect_one()) {
#pragma unroll
            for (int kb = 0; kb < PRE; kb++) {
                loadA(kb, kb);
                if (kb + PRE_B < PRE) loadB(kb + PRE_B, kb + PRE_B);
            }
            if constexpr (EPI == EPI_RES && KB < STAGES) {
                mbar_expect_tx(bar_full + 8 * KB, 16384);
                tma2d(sbase + KB * SM::STAGE, mapR, n0, m0, bar_full + 8 * KB);
            }
        }
    };
    if (SELF && warp > 8) {
        static_assert(!SELF || (STAGES >= KB && EPI == EPI_QKV), "SELF needs every k block resident");
        const int t = tid - 288;
        float ss[4] = {0.f, 0.f, 0.f, 0.f}, sq[4] = {0.f, 0.f, 0.f, 0.f}, ca[8], cx[8];
#pragma unroll
        for (int i = 0; i < 8; i++) { ca[i] = 0.f; cx[i] = 0.f; }
#pragma unroll 1
        for (int kb = 0; kb < KB; kb++) {
            mbar_wait(bar_full + 8 * kb, 0);
            const uint32_t arow = sbase + kb * SM::STAGE + (t >> 1) * 128;
            const uint32_t bblk = sbase + kb * SM::STAGE + G::A_BYTES;
            uint32_t w[7][4];
#pragma unroll
            for (int j = 0; j < 4; j++)
                asm volatile("ld.shared.v4.u32 {%0,%1,%2,%3}, [%4];" : "=r"(w[j][0]), "=r"(w[j][1]), "=r"(w[j][2]), "=r"(w[j][3])
                             : "r"(arow + (((2 * j + (t & 1) + 2 * ((t >> 1) & 3)) & 7) << 4)));
#pragma unroll
            for (int r = 0; r < 2; r++) {
                const int krow = (t >> 3) * 2 + r, ch = t & 7;
                asm volatile("ld.shared.v4.u32 {%0,%1,%2,%3}, [%4];" : "=r"(w[4 + r][0]), "=r"(w[4 + r][1]), "=r"(w[4 + r][2]), "=r"(w[4 + r][3])
                             : "r"(bblk + (ch >> 2) * G::BLK + krow * 64 + (((ch & 3) ^ ((krow >> 1) & 3)) << 4)));
            }
            if constexpr (XKV) {
                const int krow = (t >> 1) & 63;
                asm volatile("ld.shared.v4.u32 {%0,%1,%2,%3}, [%4];" : "=r"(w[6][0]), "=r"(w[6][1]), "=r"(w[6][2]), "=r"(w[6][3])
                             : "r"(bblk + 2 * G::BLK + krow * 64 + (((t & 1) ^ ((krow >> 1) & 3)) << 4)));
            }
#pragma unroll
            for (int j = 0; j < 4; j++)
#pragma unroll
                for (int i = 0; i < 4; i++) {
                    const float lo = bf_lo(w[j][i]), hi = bf_hi(w[j][i]);
                    ss[i] += lo + hi;
                    sq[i] = fmaf(lo, lo, fmaf(hi, hi, sq[i]));
                }
#pragma unroll
            for (int r = 0; r < 2; r++)
#pragma unroll
                for (int i = 0; i < 4; i++) { ca[2 * i] += bf_lo(w[4 + r][i]); ca[2 * i + 1] += bf_hi(w[4 + r][i]); }
            if constexpr (XKV) {
                if (t < 128) {
#pragma unroll
                    for (int i = 0; i < 4; i++) { cx[2 * i] += bf_lo(w[6][i]); cx[2 * i + 1] += bf_hi(w[6][i]); }
                }
            }
        }
        float tsum = (ss[0] + ss[1]) + (ss[2] + ss[3]), tsq = (sq[0] + sq[1]) + (sq[2] + sq[3]);
        tsum += __shfl_xor_sync(0xffffffffu, tsum, 1);
        tsq += __shfl_xor_sync(0xffffffffu, tsq, 1);
        if ((t & 1) == 0) {
            const float md = tsum * (1.f / 512.f);
            const float var = fmaxf(tsq * (1.f / 512.f) - md * md, 0.f);
            *(float2*)(s_row + t) = make_float2(md, 1.0f / sqrtf(var + 1e-5f));
        }
#pragma unroll
        for (int i = 0; i < 8; i++) {
            ca[i] += __shfl_xor_sync(0xffffffffu, ca[i], 8);
            ca[i] += __shfl_xor_sync(0xffffffffu, ca[i], 16);
            if constexpr (XKV) {
                cx[i] += __shfl_xor_sync(0xffffffffu, cx[i], 2); cx[i] += __shfl_xor_sync(0xffffffffu, cx[i], 4);
                cx[i] += __shfl_xor_sync(0xffffffffu, cx[i], 8); cx[i] += __shfl_xor_sync(0xffffffffu, cx[i], 16);
            }
        }
        float* s_part = s_row + 256;
        const int sw = warp - 9;
        if (sw >= 4) {
            if (lane < 8) {
#pragma unroll
                for (int i = 0; i < 8; i++) s_part[(sw - 4) * 80 + lane * 8 + i] = ca[i];
            }
        }
        named_bar(5, 256);
        if (sw < 4) {
            if (lane < 8) {
#pragma unroll
                for (int i = 0; i < 8; i++) s_part[sw * 80 + lane * 8 + i] += ca[i];
            }
            if (XKV && lane < 2) {
#pragma unroll
                for (int i = 0; i < 8; i++) s_part[sw * 80 + 64 + lane * 8 + i] = cx[i];
            }
        }
        named_bar(5, 256);
        if (t < (XKV ? 80 : 64)) {
            const float v = (s_part[t] + s_part[80 + t]) + (s_part[160 + t] + s_part[240 + t]);
            s_cs[t] = v;
            if (tile_m == 0) {
                if (t < 64) g_cs_q[n0 + t] = v;
                else g_cs_kv[tile_n * 16 + t - 64] = v;
            }
        }
        named_bar(4, 512);
    } else if (!INLINE_PROD && warp == 8) {
        prologue_loads();
        int s = PRE % STAGES, ph = (PRE / STAGES) & 1;
#pragma unroll 1
        for (int kb = PRE; kb < KB; kb++) {
            mbar_wait(bar_empty + 8 * s, ph ^ 1);
            if (elect_one()) {
                mbar_expect_tx(bar_full + 8 * s, STAGE_TX);
                loadB(kb, s);
                loadA(kb, s);
            }
            if (++s == STAGES) { s = 0; ph ^= 1; }
        }
        if constexpr (EPI == EPI_RES && KB >= STAGES) {
            mbar_wait(bar_empty + 8 * s, ph ^ 1);
            if (elect_one()) {
                mbar_expect_tx(bar_full + 8 * s, 16384);
                tma2d(sbase + s * SM::STAGE, mapR, n0, m0, bar_full + 8 * s);
            }
        }
    } else {
        if (INLINE_PROD && warp == 0) prologue_loads();
        const int wg = warp >> 2, g = lane >> 2, c = lane & 3;
        const int rloc = wg * 64 + (warp & 3) * 16 + g;
        const int row0 = m0 + rloc;
        float mean0 = 0.f, rstd0 = 1.f, mean1 = 0.f, rstd1 = 1.f;
        RowStatRaw raw;
        float csv = 0.f;
        float2 cskv[2] = {make_float2(0.f, 0.f), make_float2(0.f, 0.f)};
        auto ln_inputs = [&]() {
            pdl_wait();
            if constexpr (EPI != EPI_RES) {
                raw = load_row_stats(prm.stats_in, row0, c);
                const float* cs = EPI == EPI_FFN1 ? g_cs_1 + n0 : g_cs_q + n0;
                if (tid < TN) csv = cs[tid];
                if constexpr (XKV) {
                    cskv[0] = *(const float2*)(g_cs_kv + tile_n * 16 + 2 * c);
                    cskv[1] = *(const float2*)(g_cs_kv + tile_n * 16 + 8 + 2 * c);
                }
            }
        };
        if (!SELF) ln_inputs();
        float acc[BN / 2];
        const uint64_t dA0 = mkdesc(sbase + wg * (G::A_BYTES / 2), 16, G::A_SBO, G::A_SWZ);
        const uint64_t dB0 = mkdesc(sbase + G::A_BYTES, G::B_LBO, G::B_SBO, G::B_SWZ);
        int s = 0, ph = 0;
#pragma unroll 1
        for (int kb = 0; kb < KB; kb++) {
            mbar_wait(bar_full + 8 * s, ph);
            const uint64_t dA = dA0 + (uint64_t)(s * (SM::STAGE >> 4)), dB = dB0 + (uint64_t)(s * (SM::STAGE >> 4));
            wg_fence();
#pragma unroll
            for (int k = 0; k < G::BK / 16; k++) wgmma_ss_tb<BN>(acc, dA + (uint64_t)(k * 2), dB + (uint64_t)(k * (G::B_KSTEP >> 4)), (kb | k) != 0);
            wg_commit();
            if constexpr (EPI == EPI_RES && RES_WAIT0) {
                wg_wait<0>();
                if ((warp & 3) == 0 && elect_one()) {
                    if (MC) { mbar_arrive_remote(bar_empty + 8 * s, 0); mbar_arrive_remote(bar_empty + 8 * s, 1); }
                    else mbar_arrive(bar_empty + 8 * s);
                }
            } else if (kb > 0) {
                wg_wait<1>();
                const int sp = s == 0 ? STAGES - 1 : s - 1;
                if ((warp & 3) == 0 && elect_one()) {
                    if (MC) { mbar_arrive_remote(bar_empty + 8 * sp, 0); mbar_arrive_remote(bar_empty + 8 * sp, 1); }
                    else mbar_arrive(bar_empty + 8 * sp);
                }
                if (INLINE_PROD && warp == 0 && kb >= LAG && kb - LAG + STAGES < KB) {
                    const int sq = LAG == 1 ? sp : (sp == 0 ? STAGES - 1 : sp - 1);
                    mbar_wait(bar_empty + 8 * sq, ((kb - LAG) / STAGES) & 1);
                    if (elect_one()) {
                        mbar_expect_tx(bar_full + 8 * sq, STAGE_TX);
                        loadB(kb - LAG + STAGES, sq);
                        loadA(kb - LAG + STAGES, sq);
                    }
                }
            }
            if (++s == STAGES) { s = 0; ph ^= 1; }
        }
        if constexpr (SELF) {
            named_bar(4, 512);
            const float2 r0 = *(const float2*)(s_row + 2 * rloc), r1 = *(const float2*)(s_row + 2 * rloc + 16);
            mean0 = r0.x; rstd0 = r0.y; mean1 = r1.x; rstd1 = r1.y;
        } else if constexpr (EPI != EPI_RES) {
            finish_row_stats(raw, mean0, rstd0, mean1, rstd1);
            if (tid < TN) s_cs[tid] = csv;
        }
        wg_wait<0>();
        fence_regs(acc);
        if (tid == 0) TL(prm.tk, 2);
        if constexpr (EPI != EPI_RES) named_bar(1, 256);

        if constexpr (EPI != EPI_FFN1) {
            const uint32_t stile = sbase + (EPI == EPI_RES ? s * SM::STAGE : 0);
            const int mrow = wg * 64 + (warp & 3) * 16 + (lane & 7) + ((lane >> 3) & 1) * 8;
            const uint32_t rbase = stile + mrow * 128;
            if constexpr (EPI == EPI_RES) {
                mbar_wait(bar_full + 8 * s, ph);
                float s0 = 0.f, s1 = 0.f;
#pragma unroll
                for (int jj = 0; jj < 4; jj++) {
                    uint32_t r0, r1, r2, r3;
                    const uint32_t addr = rbase + (((2 * jj + (lane >> 4)) ^ (mrow & 7)) << 4);
                    ldsm_x4(r0, r1, r2, r3, addr);
                    const uint32_t u0 = pack_bf16(acc[8 * jj] + bf_lo(r0), acc[8 * jj + 1] + bf_hi(r0));
                    const uint32_t u1 = pack_bf16(acc[8 * jj + 2] + bf_lo(r1), acc[8 * jj + 3] + bf_hi(r1));
                    const uint32_t u2 = pack_bf16(acc[8 * jj + 4] + bf_lo(r2), acc[8 * jj + 5] + bf_hi(r2));
                    const uint32_t u3 = pack_bf16(acc[8 * jj + 6] + bf_lo(r3), acc[8 * jj + 7] + bf_hi(r3));
                    stsm_x4(addr, u0, u1, u2, u3);
                    acc[8 * jj] = bf_lo(u0); acc[8 * jj + 1] = bf_hi(u0); acc[8 * jj + 4] = bf_lo(u2); acc[8 * jj + 5] = bf_hi(u2);
                    acc[8 * jj + 2] = bf_lo(u1); acc[8 * jj + 3] = bf_hi(u1); acc[8 * jj + 6] = bf_lo(u3); acc[8 * jj + 7] = bf_hi(u3);
                    s0 += (acc[8 * jj] + acc[8 * jj + 1]) + (acc[8 * jj + 4] + acc[8 * jj + 5]);
                    s1 += (acc[8 * jj + 2] + acc[8 * jj + 3]) + (acc[8 * jj + 6] + acc[8 * jj + 7]);
                }
                fence_async_smem();
                named_bar(2 + wg, 128);
                if ((warp & 3) == 0 && elect_one()) { tma2d_store(mapC, stile + wg * 8192, n0, m0 + wg * 64); bulk_commit(); }
                if (prm.stats_out) {
                    s0 += __shfl_xor_sync(0xffffffffu, s0, 1); s0 += __shfl_xor_sync(0xffffffffu, s0, 2);
                    s1 += __shfl_xor_sync(0xffffffffu, s1, 1); s1 += __shfl_xor_sync(0xffffffffu, s1, 2);
                    const float mu0 = s0 * (1.f / 64.f), mu1 = s1 * (1.f / 64.f);
                    float q0 = 0.f, q1 = 0.f;
#pragma unroll
                    for (int j = 0; j < 8; j++) {
                        float d;
                        d = acc[4 * j] - mu0; q0 += d * d; d = acc[4 * j + 1] - mu0; q0 += d * d;
                        d = acc[4 * j + 2] - mu1; q1 += d * d; d = acc[4 * j + 3] - mu1; q1 += d * d;
                    }
                    q0 += __shfl_xor_sync(0xffffffffu, q0, 1); q0 += __shfl_xor_sync(0xffffffffu, q0, 2);
                    q1 += __shfl_xor_sync(0xffffffffu, q1, 1); q1 += __shfl_xor_sync(0xffffffffu, q1, 2);
                    if (c == 0) {
                        prm.stats_out[tile_n * S_ + row0] = make_float2(mu0, q0);
                        prm.stats_out[tile_n * S_ + row0 + 8] = make_float2(mu1, q1);
                    }
                }
            } else {
                const float sc = 0.25f * 1.4426950408889634f;
                const float a0 = rstd0 * sc, a1 = rstd1 * sc, rm0 = a0 * mean0, rm1 = a1 * mean1;
#pragma unroll
                for (int jj = 0; jj < 4; jj++) {
                    const float2 ca = *(const float2*)(s_cs + 16 * jj + 2 * c), cb = *(const float2*)(s_cs + 16 * jj + 8 + 2 * c);
                    const uint32_t u0 = pack_bf16(acc[8 * jj] * a0 - rm0 * ca.x, acc[8 * jj + 1] * a0 - rm0 * ca.y);
                    const uint32_t u1 = pack_bf16(acc[8 * jj + 2] * a1 - rm1 * ca.x, acc[8 * jj + 3] * a1 - rm1 * ca.y);
                    const uint32_t u2 = pack_bf16(acc[8 * jj + 4] * a0 - rm0 * cb.x, acc[8 * jj + 5] * a0 - rm0 * cb.y);
                    const uint32_t u3 = pack_bf16(acc[8 * jj + 6] * a1 - rm1 * cb.x, acc[8 * jj + 7] * a1 - rm1 * cb.y);
                    stsm_x4(rbase + (((2 * jj + (lane >> 4)) ^ (mrow & 7)) << 4), u0, u1, u2, u3);
                }
                fence_async_smem();
                named_bar(2 + wg, 128);
                if ((warp & 3) == 0 && elect_one()) { tma2d_store(mapC, stile + wg * 8192, n0, m0 + wg * 64); bulk_commit(); }
            }
            if constexpr (XKV) {
                {
                    const float* acx = &acc[32];
                    const float rm0 = rstd0 * mean0, rm1 = rstd1 * mean1;
                    float n0s = 0.f, n1s = 0.f, vmax = 0.f;
#pragma unroll
                    for (int j = 0; j < 2; j++) {
                        const float2 cs2 = SELF ? *(const float2*)(s_cs + 64 + 8 * j + 2 * c) : cskv[j];
                        const uint32_t u0 = pack_bf16(acx[4 * j] * rstd0 - rm0 * cs2.x, acx[4 * j + 1] * rstd0 - rm0 * cs2.y);
                        const uint32_t u1 = pack_bf16(acx[4 * j + 2] * rstd1 - rm1 * cs2.x, acx[4 * j + 3] * rstd1 - rm1 * cs2.y);
                        n0s += bf_lo(u0) * bf_lo(u0) + bf_hi(u0) * bf_hi(u0);
                        n1s += bf_lo(u1) * bf_lo(u1) + bf_hi(u1) * bf_hi(u1);
                        vmax = fmaxf(vmax, fmaxf(fmaxf(fabsf(bf_lo(u0)), fabsf(bf_hi(u0))), fmaxf(fabsf(bf_lo(u1)), fabsf(bf_hi(u1)))));
                        if (tile_n == 0) {
                            *(uint32_t*)(g_kimg + (row0 >> 3) * 256 + j * 128 + g * 16 + c * 4) = u0;
                            *(uint32_t*)(g_kimg + ((row0 + 8) >> 3) * 256 + j * 128 + g * 16 + c * 4) = u1;
                        } else {
                            uint8_t* vb = g_vimg + (row0 >> 4) * 768 + j * 256 + g * 16 + c * 4;
                            *(uint32_t*)(vb) = u0;
                            *(uint32_t*)(vb + 128) = u1;
                        }
                    }
                    if (tile_n == 1) {
                        uint8_t* vb = g_vimg + (row0 >> 4) * 768 + 512 + g * 16 + c * 4;
                        const uint32_t one = c == 0 ? 0x00003F80u : 0u;
                        *(uint32_t*)(vb) = one;
                        *(uint32_t*)(vb + 128) = one;
                    }
                    n0s += __shfl_xor_sync(0xffffffffu, n0s, 1); n0s += __shfl_xor_sync(0xffffffffu, n0s, 2);
                    n1s += __shfl_xor_sync(0xffffffffu, n1s, 1); n1s += __shfl_xor_sync(0xffffffffu, n1s, 2);
                    float km = tile_n == 0 ? fmaxf(n0s, n1s) : vmax;
                    if (!(n0s + n1s < INFINITY)) km = INFINITY;
#pragma unroll
                    for (int o = 1; o < 32; o <<= 1) km = fmaxf(km, __shfl_xor_sync(0xffffffffu, km, o));
                    if (lane == 0) s_red[warp] = km;
                    named_bar(1, 256);
                    if (tid == 0) {
                        float a = 0.f;
                        for (int i = 0; i < 8; i++) a = fmaxf(a, s_red[i]);
                        g_kvmax[tile_n * 16 + tile_m] = a;
                    }
                }
            }
            if ((warp & 3) == 0) bulk_wait_read();
        } else {
            const uint32_t stile = sbase + wg * (7 * 4096);
            const int mrow = (warp & 3) * 16 + (lane & 7) + ((lane >> 3) & 1) * 8;
            const float a0 = 0.5f * rstd0, a1 = 0.5f * rstd1, rm0 = a0 * mean0, rm1 = a1 * mean1;
#pragma unroll
            for (int jj = 0; jj < 14; jj++) {
                const float2 ca = *(const float2*)(s_cs + 16 * jj + 2 * c), cb = *(const float2*)(s_cs + 16 * jj + 8 + 2 * c);
                float y[8] = {acc[8 * jj] * a0 - rm0 * ca.x,     acc[8 * jj + 1] * a0 - rm0 * ca.y,
                              acc[8 * jj + 2] * a1 - rm1 * ca.x, acc[8 * jj + 3] * a1 - rm1 * ca.y,
                              acc[8 * jj + 4] * a0 - rm0 * cb.x, acc[8 * jj + 5] * a0 - rm0 * cb.y,
                              acc[8 * jj + 6] * a1 - rm1 * cb.x, acc[8 * jj + 7] * a1 - rm1 * cb.y};
#pragma unroll
                for (int i = 0; i < 8; i++) {
                    float t;
                    asm("tanh.approx.f32 %0, %1;" : "=f"(t) : "f"(y[i]));
                    y[i] = fmaf(y[i], t, y[i]);
                }
                const int chunk = (2 * jj + (lane >> 4)) & 3, blk = jj >> 1;
                stsm_x4(stile + blk * 4096 + mrow * 64 + ((chunk ^ ((mrow >> 1) & 3)) << 4),
                        pack_bf16(y[0], y[1]), pack_bf16(y[2], y[3]), pack_bf16(y[4], y[5]), pack_bf16(y[6], y[7]));
                if (jj & 1) {
                    fence_async_smem();
                    __syncwarp();
                    if (elect_one()) {
                        tma2d_store(mapC, stile + blk * 4096 + (warp & 3) * 1024, n0 + blk * 32, m0 + wg * 64 + (warp & 3) * 16);
                        bulk_commit();
                    }
                }
            }
            bulk_wait_read();
        }
    }
    if (tid == 0) TL(prm.tk, 3);
    if (MC) cluster_sync();
}

#define WO_ST 9
#define F2_ST 6
#define F1_ST (F1_BK == 64 ? 5 : 9)
#define QKV_ST 8
constexpr int QKV_STAGES = QKV_ST, WO_STAGES = WO_ST, FFN2_STAGES = F2_ST, FFN1_STAGES = F1_ST;
template <bool SELF>
__global__ void __launch_bounds__(SELF ? 544 : 288) qkv_kernel(const __grid_constant__ CUtensorMap mapA, const __grid_constant__ CUtensorMap mapWq,
                                                  const __grid_constant__ CUtensorMap mapWk, const __grid_constant__ CUtensorMap mapWv,
                                                  const __grid_constant__ CUtensorMap mapQ, const GemmParams prm) {
    extern __shared__ __align__(1024) uint8_t smem_raw[];
    const int tn = blockIdx.x & 7;
    if (tn < 2) gemm_body<80, 8, QKV_STAGES, EPI_QKV, QKV_MC, SELF>(&mapA, &mapWq, tn == 0 ? &mapWk : &mapWv, &mapA, &mapQ, prm, blockIdx.x >> 3, tn, smem_raw);
    else gemm_body<64, 8, QKV_STAGES, EPI_QKV, QKV_MC, SELF>(&mapA, &mapWq, &mapWq, &mapA, &mapQ, prm, blockIdx.x >> 3, tn, smem_raw);
}
template <int KB, int STAGES>
__global__ void __launch_bounds__(288) res_gemm_kernel(const __grid_constant__ CUtensorMap mapA, const __grid_constant__ CUtensorMap mapW,
                                                       const __grid_constant__ CUtensorMap mapR, const __grid_constant__ CUtensorMap mapC, const GemmParams prm) {
    extern __shared__ __align__(1024) uint8_t smem_raw[];
    gemm_body<64, KB, STAGES, EPI_RES, (KB == 8 ? WO_MC : F2_MC)>(&mapA, &mapW, &mapW, &mapR, &mapC, prm, blockIdx.x >> 3, blockIdx.x & 7, smem_raw);
}
__global__ void __launch_bounds__(F1_INLINE ? 256 : 288) ffn1_kernel(const __grid_constant__ CUtensorMap mapA, const __grid_constant__ CUtensorMap mapW4,
                                                   const __grid_constant__ CUtensorMap mapW3, const __grid_constant__ CUtensorMap mapH, const GemmParams prm) {
    extern __shared__ __align__(1024) uint8_t smem_raw[];
    const int pair = blockIdx.x >> 1, tile_n = pair & 7, tile_m = (pair >> 3) * 2 + (blockIdx.x & 1);
    gemm_body<224, 512 / F1_BK, FFN1_STAGES, EPI_FFN1, F1_MC>(&mapA, &mapW4, &mapW3, &mapA, &mapH, prm, tile_m, tile_n, smem_raw);
}

constexpr int NPOLY = 10;
__host__ __device__ constexpr bool is_mufu(int i) { return ((i + 1) * (16 - NPOLY)) / 16 != (i * (16 - NPOLY)) / 16; }

__device__ __forceinline__ float ex2(float x) { float r; asm("ex2.approx.ftz.f32 %0, %1;" : "=f"(r) : "f"(x)); return r; }
__device__ __forceinline__ uint32_t exp_pair_mufu(float a, float b) { return pack_bf16(ex2(a), ex2(b)); }
__device__ __forceinline__ uint32_t exp_pair_fma(float a, float b, uint32_t c3f) {
    constexpr float MAGIC = 98430.4140625f;
    const float ta = a + MAGIC, tb = b + (MAGIC - 143.5f);
    uint32_t y, m, r;
    asm("mad.lo.u32 %0, %1, 65536, %2;" : "=r"(y) : "r"(__float_as_uint(tb)), "r"(__float_as_uint(ta)));
    asm("lop3.b32 %0, %1, 0x007F007F, %2, 0xEA;" : "=r"(m) : "r"(y), "r"(c3f));
    const uint32_t e = y & 0xFF80FF80u;
    asm("fma.rn.bf16x2 %0, %1, %2, %3;" : "=r"(r) : "r"(y), "r"(m), "r"(e));
    return r;
}

constexpr int KCH = 256, NCH = S_ / KCH;
constexpr int K_BYTES = S_ * 32, V_BYTES = (S_ / 16) * 768;
constexpr int ATT_SMEM = K_BYTES + V_BYTES;

__global__ void __launch_bounds__(512, 1) attn_kernel(const __nv_bfloat16* __restrict__ wo, const __nv_bfloat16* __restrict__ w1,
                                                       const __nv_bfloat16* __restrict__ w2, int tk) {
    extern __shared__ __align__(1024) uint8_t smem[];
    __shared__ uint64_t bars[NCH];
    __shared__ int s_slow;
    const int tid = threadIdx.x, wg = tid >> 7, warp = (tid >> 5) & 3, lane = tid & 31;
    const uint32_t sK = smem_u32(smem), sV = sK + K_BYTES;
    if (blockIdx.x >= 128) {
        pdl_launch();
        side_job(blockIdx.x - 128, (float*)smem, wo, w1, w2);
        return;
    }
    if (tid == 0) TL(tk, 0);
    if (tid == 0) {
        for (int i = 0; i < NCH; i++) mbar_init(smem_u32(&bars[i]), 1);
        s_slow = 0;
        fence_mbar_init();
    }
    __syncthreads();
    pdl_launch();
    pdl_wait();
    if (tid == 0) TL(tk, 1);
    if (__shfl_sync(0xffffffffu, tid >> 5, 0) == 0 && elect_one()) {
#pragma unroll
        for (int i = 0; i < NCH; i++) {
            mbar_expect_tx(smem_u32(&bars[i]), KCH * 32 + (KCH / 16) * 768);
            bulk_load(sK + i * KCH * 32, g_kimg + i * KCH * 32, KCH * 32, smem_u32(&bars[i]));
            bulk_load(sV + i * (KCH / 16) * 768, g_vimg + i * (KCH / 16) * 768, (KCH / 16) * 768, smem_u32(&bars[i]));
        }
    }
    const int tb = blockIdx.x >> 3, hg = blockIdx.x & 7;
    const int head = hg * 4 + wg;
    const int g = lane >> 2, c = lane & 3;
    uint32_t qa[2][4];
    float qn = 0.f;
#pragma unroll
    for (int m = 0; m < 2; m++) {
        const int row = tb * 128 + m * 64 + warp * 16 + g;
        const uint32_t* p0 = (const uint32_t*)(g_q + (size_t)row * D_ + head * 16);
        const uint32_t* p1 = (const uint32_t*)(g_q + (size_t)(row + 8) * D_ + head * 16);
        qa[m][0] = p0[c]; qa[m][1] = p1[c]; qa[m][2] = p0[c + 4]; qa[m][3] = p1[c + 4];
        float n0 = bf_lo(qa[m][0]) * bf_lo(qa[m][0]) + bf_hi(qa[m][0]) * bf_hi(qa[m][0]) + bf_lo(qa[m][2]) * bf_lo(qa[m][2]) + bf_hi(qa[m][2]) * bf_hi(qa[m][2]);
        float n1 = bf_lo(qa[m][1]) * bf_lo(qa[m][1]) + bf_hi(qa[m][1]) * bf_hi(qa[m][1]) + bf_lo(qa[m][3]) * bf_lo(qa[m][3]) + bf_hi(qa[m][3]) * bf_hi(qa[m][3]);
        n0 += __shfl_xor_sync(0xffffffffu, n0, 1); n0 += __shfl_xor_sync(0xffffffffu, n0, 2);
        n1 += __shfl_xor_sync(0xffffffffu, n1, 1); n1 += __shfl_xor_sync(0xffffffffu, n1, 2);
        if (!(n0 == n0) || !(n1 == n1)) n0 = __int_as_float(0x7f800000);
        qn = fmaxf(qn, fmaxf(n0, n1));
    }
    {
        float km = 0.f, vm = 0.f;
#pragma unroll
        for (int i = 0; i < 16; i++) { km = fmaxf(km, g_kvmax[i]); vm = fmaxf(vm, g_kvmax[16 + i]); }
        const bool ok = (qn * km <= 10000.f) && (vm <= 16384.f);
        if (!ok) s_slow = 1;
    }
    float oacc[2][12];
#pragma unroll
    for (int m = 0; m < 2; m++)
#pragma unroll
        for (int i = 0; i < 12; i++) oacc[m][i] = 0.f;
    __syncthreads();
    const bool slow = s_slow != 0;

    const uint64_t dK0 = mkdesc(sK, 128, 256, 0);
    const uint64_t dV0 = mkdesc(sV, 128, 256, 0);
    uint32_t c3f;
    asm volatile("mov.b32 %0, 0x3F003F00;" : "=r"(c3f));
    if (!slow) {
#pragma unroll 1
        for (int t = 0; t < S_ / 64; t++) {
            if ((t & 3) == 0) mbar_wait(smem_u32(&bars[t >> 2]), 0);
            const uint64_t dK = dK0 + (uint64_t)(t * 64 * 32 / 16);
            const uint64_t dV = dV0 + (uint64_t)(t * 4 * 768 / 16);
#pragma unroll
            for (int m = 0; m < 2; m++) {
                float s[32];
                wg_fence();
                wgmma_rs_n64_z(s, qa[m][0], qa[m][1], qa[m][2], qa[m][3], dK);
                wg_commit();
                wg_wait<0>();
                fence_regs(s);
                uint32_t p[16];
#pragma unroll
                for (int i = 0; i < 16; i++) p[i] = is_mufu(i) ? exp_pair_mufu(s[2 * i], s[2 * i + 1]) : exp_pair_fma(s[2 * i], s[2 * i + 1], c3f);
                wg_fence();
#pragma unroll
                for (int kk = 0; kk < 4; kk++)
                    wgmma_rs_n24_tb(oacc[m], p[4 * kk], p[4 * kk + 1], p[4 * kk + 2], p[4 * kk + 3], dV + (uint64_t)(kk * 768 / 16));
                wg_commit();
            }
        }
        wg_wait<0>();
    } else {
        float mx[2][2] = {{-INFINITY, -INFINITY}, {-INFINITY, -INFINITY}};
#pragma unroll 1
        for (int t = 0; t < S_ / 64; t++) {
            if ((t & 3) == 0) mbar_wait(smem_u32(&bars[t >> 2]), 0);
            const uint64_t dK = dK0 + (uint64_t)(t * 64 * 32 / 16);
            const uint64_t dV = dV0 + (uint64_t)(t * 4 * 768 / 16);
#pragma unroll
            for (int m = 0; m < 2; m++) {
                float s[32];
                wg_fence();
                wgmma_rs_n64_z(s, qa[m][0], qa[m][1], qa[m][2], qa[m][3], dK);
                wg_commit();
                wg_wait<0>();
                fence_regs(s);
                fence_regs(oacc[m]);
                float r0 = mx[m][0], r1 = mx[m][1];
#pragma unroll
                for (int j = 0; j < 8; j++) {
                    r0 = fmaxf(r0, fmaxf(s[4 * j], s[4 * j + 1]));
                    r1 = fmaxf(r1, fmaxf(s[4 * j + 2], s[4 * j + 3]));
                }
                r0 = fmaxf(r0, __shfl_xor_sync(0xffffffffu, r0, 1)); r0 = fmaxf(r0, __shfl_xor_sync(0xffffffffu, r0, 2));
                r1 = fmaxf(r1, __shfl_xor_sync(0xffffffffu, r1, 1)); r1 = fmaxf(r1, __shfl_xor_sync(0xffffffffu, r1, 2));
                const float al0 = ex2(mx[m][0] - r0), al1 = ex2(mx[m][1] - r1);
                mx[m][0] = r0; mx[m][1] = r1;
#pragma unroll
                for (int j = 0; j < 3; j++) {
                    oacc[m][4 * j] *= al0; oacc[m][4 * j + 1] *= al0;
                    oacc[m][4 * j + 2] *= al1; oacc[m][4 * j + 3] *= al1;
                }
                uint32_t p[16];
#pragma unroll
                for (int j = 0; j < 8; j++) {
                    p[2 * j] = pack_bf16(ex2(s[4 * j] - r0), ex2(s[4 * j + 1] - r0));
                    p[2 * j + 1] = pack_bf16(ex2(s[4 * j + 2] - r1), ex2(s[4 * j + 3] - r1));
                }
                fence_regs(oacc[m]);
                wg_fence();
#pragma unroll
                for (int kk = 0; kk < 4; kk++)
                    wgmma_rs_n24_tb(oacc[m], p[4 * kk], p[4 * kk + 1], p[4 * kk + 2], p[4 * kk + 3], dV + (uint64_t)(kk * 768 / 16));
                wg_commit();
                wg_wait<0>();
            }
        }
    }
    fence_regs(oacc[0]); fence_regs(oacc[1]);
    if (tid == 0) TL(tk, 2);
#pragma unroll
    for (int m = 0; m < 2; m++) {
        const float l0 = __shfl_sync(0xffffffffu, oacc[m][8], lane & ~3);
        const float l1 = __shfl_sync(0xffffffffu, oacc[m][10], lane & ~3);
        const float r0 = 1.0f / l0, r1 = 1.0f / l1;
        const int row = tb * 128 + m * 64 + warp * 16 + g;
        uint32_t* p0 = (uint32_t*)(g_o + (size_t)row * D_ + head * 16);
        uint32_t* p1 = (uint32_t*)(g_o + (size_t)(row + 8) * D_ + head * 16);
        p0[c] = pack_bf16(oacc[m][0] * r0, oacc[m][1] * r0);
        p1[c] = pack_bf16(oacc[m][2] * r1, oacc[m][3] * r1);
        p0[c + 4] = pack_bf16(oacc[m][4] * r0, oacc[m][5] * r0);
        p1[c + 4] = pack_bf16(oacc[m][6] * r1, oacc[m][7] * r1);
    }
    if (tid == 0) TL(tk, 3);
}

typedef CUresult (*EncodeFn)(CUtensorMap*, CUtensorMapDataType, cuuint32_t, void*, const cuuint64_t*, const cuuint64_t*, const cuuint32_t*,
                             const cuuint32_t*, CUtensorMapInterleave, CUtensorMapSwizzle, CUtensorMapL2promotion, CUtensorMapFloatOOBfill);

EncodeFn get_encode() {
    static EncodeFn fn = nullptr;
    if (!fn) {
        void* p = nullptr;
        cudaDriverEntryPointQueryResult qr;
        cudaGetDriverEntryPoint("cuTensorMapEncodeTiled", &p, cudaEnableDefault, &qr);
        fn = (EncodeFn)p;
    }
    return fn;
}
CUtensorMap map2d(const void* ptr, uint64_t cols, uint64_t rows, uint32_t bc, uint32_t br, CUtensorMapSwizzle sw) {
    CUtensorMap m;
    cuuint64_t gd[2] = {cols, rows}, gs[1] = {cols * 2};
    cuuint32_t bx[2] = {bc, br}, es[2] = {1, 1};
    get_encode()(&m, CU_TENSOR_MAP_DATA_TYPE_BFLOAT16, 2, (void*)ptr, gd, gs, bx, es, CU_TENSOR_MAP_INTERLEAVE_NONE, sw,
                 CU_TENSOR_MAP_L2_PROMOTION_L2_128B, CU_TENSOR_MAP_FLOAT_OOB_FILL_NONE);
    return m;
}
CUtensorMap map3d32(const void* ptr, uint64_t cols, uint64_t rows, uint32_t br, uint32_t nb) {
    CUtensorMap m;
    cuuint64_t gd[3] = {32, rows, cols / 32}, gs[2] = {cols * 2, 64};
    cuuint32_t bx[3] = {32, br, nb}, es[3] = {1, 1, 1};
    get_encode()(&m, CU_TENSOR_MAP_DATA_TYPE_BFLOAT16, 3, (void*)ptr, gd, gs, bx, es, CU_TENSOR_MAP_INTERLEAVE_NONE, CU_TENSOR_MAP_SWIZZLE_64B,
                 CU_TENSOR_MAP_L2_PROMOTION_L2_128B, CU_TENSOR_MAP_FLOAT_OOB_FILL_NONE);
    return m;
}

template <typename... KArgs, typename... Args>
void launch(void (*kern)(KArgs...), int grid, int block, int smem, int cluster, bool pdl, Args... args) {
    cudaLaunchConfig_t cfg = {};
    cfg.gridDim = dim3(grid);
    cfg.blockDim = dim3(block);
    cfg.dynamicSmemBytes = smem;
    cfg.stream = cudaStreamPerThread;
    cudaLaunchAttribute at[2];
    int n = 0;
    if (cluster > 1) { at[n].id = cudaLaunchAttributeClusterDimension; at[n].val.clusterDim.x = cluster; at[n].val.clusterDim.y = 1; at[n].val.clusterDim.z = 1; n++; }
    if (pdl) { at[n].id = cudaLaunchAttributeProgrammaticStreamSerialization; at[n].val.programmaticStreamSerializationAllowed = 1; n++; }
    cfg.attrs = at;
    cfg.numAttrs = n;
    cudaLaunchKernelEx(&cfg, kern, KArgs(args)...);
}

template <typename T> void* sym(const T& s) { void* p = nullptr; cudaGetSymbolAddress(&p, s); return p; }

}

extern "C" void kernel_launch(void* const* d_in, const int* in_sizes, int n_in, void* d_out, int out_size) {
    const __nv_bfloat16* x = (const __nv_bfloat16*)d_in[0];
    const __nv_bfloat16* wq = (const __nv_bfloat16*)d_in[1];
    const __nv_bfloat16* wk = (const __nv_bfloat16*)d_in[2];
    const __nv_bfloat16* wv = (const __nv_bfloat16*)d_in[3];
    const __nv_bfloat16* wo = (const __nv_bfloat16*)d_in[4];
    const __nv_bfloat16* w1 = (const __nv_bfloat16*)d_in[6];
    const __nv_bfloat16* w2 = (const __nv_bfloat16*)d_in[7];

    constexpr int SM_QKV = GemmSmem<QKV_STAGES, EPI_QKV>::TOTAL, SM_QKV0 = GemmSmem<QKV_STAGES, EPI_QKV>::TOTAL_SELF;
    static_assert(SM_QKV0 <= 232448, "shared memory");
    constexpr int HALF_PLUS = 116736;
    constexpr int SM_WO = GemmSmem<WO_STAGES, EPI_RES>::TOTAL > HALF_PLUS ? GemmSmem<WO_STAGES, EPI_RES>::TOTAL : HALF_PLUS;
    constexpr int SM_FFN2 = GemmSmem<FFN2_STAGES, EPI_RES>::TOTAL > HALF_PLUS ? GemmSmem<FFN2_STAGES, EPI_RES>::TOTAL : HALF_PLUS;
    constexpr int SM_FFN1 = GemmSmem<FFN1_STAGES, EPI_FFN1>::TOTAL;
    cudaFuncSetAttribute(qkv_kernel<false>, cudaFuncAttributeMaxDynamicSharedMemorySize, SM_QKV);
    cudaFuncSetAttribute(qkv_kernel<true>, cudaFuncAttributeMaxDynamicSharedMemorySize, SM_QKV0);
    cudaFuncSetAttribute(res_gemm_kernel<8, WO_STAGES>, cudaFuncAttributeMaxDynamicSharedMemorySize, SM_WO);
    cudaFuncSetAttribute(ffn1_kernel, cudaFuncAttributeMaxDynamicSharedMemorySize, SM_FFN1);
    cudaFuncSetAttribute(res_gemm_kernel<28, FFN2_STAGES>, cudaFuncAttributeMaxDynamicSharedMemorySize, SM_FFN2);
    cudaFuncSetAttribute(attn_kernel, cudaFuncAttributeMaxDynamicSharedMemorySize, ATT_SMEM);
    cudaFuncSetAttribute(qkv_kernel<false>, cudaFuncAttributePreferredSharedMemoryCarveout, 100);
    cudaFuncSetAttribute(qkv_kernel<true>, cudaFuncAttributePreferredSharedMemoryCarveout, 100);
    cudaFuncSetAttribute(res_gemm_kernel<8, WO_STAGES>, cudaFuncAttributePreferredSharedMemoryCarveout, 100);
    cudaFuncSetAttribute(ffn1_kernel, cudaFuncAttributePreferredSharedMemoryCarveout, 100);
    cudaFuncSetAttribute(res_gemm_kernel<28, FFN2_STAGES>, cudaFuncAttributePreferredSharedMemoryCarveout, 100);
    cudaFuncSetAttribute(attn_kernel, cudaFuncAttributePreferredSharedMemoryCarveout, 100);

    void *q = sym(g_q), *o = sym(g_o), *x1 = sym(g_x1), *x2 = sym(g_x2), *x3 = sym(g_x3), *h = sym(g_h);
    float2* stats = (float2*)sym(g_stats);
    const void* xs[5] = {x, x1, x2, x3, d_out};

    const CUtensorMapSwizzle SW128 = CU_TENSOR_MAP_SWIZZLE_128B, SW64 = CU_TENSOR_MAP_SWIZZLE_64B;
    const CUtensorMap mWq = map3d32(wq, D_, D_, 64, 2);
    const CUtensorMap mWk = map2d(wk, 16, D_, 32, 64, SW64);
    const CUtensorMap mWv = map2d(wv, 16, D_, 32, 64, SW64);
    const CUtensorMap mWo = map2d(wo, D_, D_, 64, 64, SW128);
    const CUtensorMap mW1a = map3d32(w1, F_, D_, F1_BK, 4), mW1b = map3d32(w1, F_, D_, F1_BK, 3);
    const CUtensorMap mW2 = map2d(w2, D_, F_, 64, 64, SW128);
    const CUtensorMap mQ = map2d(q, D_, S_, 64, 64, SW128);
    const CUtensorMap mHst = map2d(h, F_, S_, 32, 16, SW64);
    CUtensorMap mXa[4], mXf[4], mXr[4], mXs[5];
    for (int i = 0; i < 4; i++) {
        mXa[i] = map2d(xs[i], D_, S_, 64, QKV_MC ? 64 : 128, SW128);
        mXf[i] = F1_BK == 64 ? map2d(xs[i], D_, S_, 64, 128, SW128) : map2d(xs[i], D_, S_, 32, 128, SW64);
        mXr[i] = map2d(xs[i], D_, S_, 64, 128, SW128);
    }
    for (int i = 0; i < 5; i++) mXs[i] = map2d(xs[i], D_, S_, 64, 64, SW128);
    const CUtensorMap mOa = map2d(o, D_, S_, 64, WO_MC ? 64 : 128, SW128);
    const CUtensorMap mHa = map2d(h, F_, S_, 64, F2_MC ? 64 : 128, SW128);

    for (int layer = 0; layer < 2; layer++) {
        const int xi = layer * 2;
        GemmParams p;
        p.stats_in = stats + (size_t)xi * 8 * S_; p.stats_out = nullptr; p.tk = 1 + 5 * layer;
        if (layer == 0) launch(qkv_kernel<true>, 128, 544, SM_QKV0, QKV_MC ? 2 : 1, false, mXa[xi], mWq, mWk, mWv, mQ, p);
        else launch(qkv_kernel<false>, 128, 288, SM_QKV, QKV_MC ? 2 : 1, true, mXa[xi], mWq, mWk, mWv, mQ, p);
        launch(attn_kernel, layer == 0 ? 128 + SIDE_CTAS : 128, 512, ATT_SMEM, 1, true, wo, w1, w2, 2 + 5 * layer);
        p.stats_in = nullptr; p.stats_out = stats + (size_t)(xi + 1) * 8 * S_; p.tk = 3 + 5 * layer;
        launch(res_gemm_kernel<8, WO_STAGES>, 128, 288, SM_WO, WO_MC ? 2 : 1, true, mOa, mWo, mXr[xi], mXs[xi + 1], p);
        p.stats_in = stats + (size_t)(xi + 1) * 8 * S_; p.stats_out = nullptr; p.tk = 4 + 5 * layer;
        launch(ffn1_kernel, 128, F1_INLINE ? 256 : 288, SM_FFN1, F1_MC ? 2 : 1, true, mXf[xi + 1], mW1a, mW1b, mHst, p);
        p.stats_in = nullptr; p.stats_out = layer == 0 ? stats + (size_t)2 * 8 * S_ : nullptr; p.tk = 5 + 5 * layer;
        launch(res_gemm_kernel<28, FFN2_STAGES>, 128, 288, SM_FFN2, F2_MC ? 2 : 1, true, mHa, mW2, mXr[xi + 1], mXs[xi + 2], p);
    }
}
```

```cpp
#include <cuda_runtime.h>
#include <cuda_bf16.h>
#include <cuda.h>
#include <stdint.h>

#define F1_INLINE 0
#define QKV_MC 0
#define WO_MC 0
#define F2_MC 0
#define F1_MC 2
#define PREB 2
#define RES_WAIT0 0

namespace {

constexpr int S_ = 2048, D_ = 512, H_ = 32, F_ = 1792;

__device__ __align__(1024) __nv_bfloat16 g_q[S_ * D_];
__device__ __align__(1024) __nv_bfloat16 g_o[S_ * D_];
__device__ __align__(1024) __nv_bfloat16 g_x1[S_ * D_];
__device__ __align__(1024) __nv_bfloat16 g_x2[S_ * D_];
__device__ __align__(1024) __nv_bfloat16 g_x3[S_ * D_];
__device__ __align__(1024) __nv_bfloat16 g_h[S_ * F_];
__device__ __align__(1024) uint8_t g_kimg[S_ * 32];
__device__ __align__(1024) uint8_t g_vimg[(S_ / 16) * 768];
__device__ __align__(1024) float2 g_stats[4][8 * S_];
__device__ __align__(16) float g_cs_q[D_];
__device__ __align__(16) float g_cs_kv[32];
__device__ __align__(16) float g_cs_1[F_];
__device__ __align__(16) float g_kvmax[32];

#define TL(k, slot)

__device__ __forceinline__ uint32_t smem_u32(const void* p) { return (uint32_t)__cvta_generic_to_shared(p); }
__device__ __forceinline__ void mbar_init(uint32_t bar, uint32_t cnt) {
    asm volatile("mbarrier.init.shared::cta.b64 [%0], %1;" ::"r"(bar), "r"(cnt));
}
__device__ __forceinline__ void mbar_expect_tx(uint32_t bar, uint32_t bytes) {
    asm volatile("mbarrier.arrive.expect_tx.shared::cta.b64 _, [%0], %1;" ::"r"(bar), "r"(bytes) : "memory");
}
__device__ __forceinline__ void mbar_arrive(uint32_t bar) {
    asm volatile("mbarrier.arrive.shared::cta.b64 _, [%0];" ::"r"(bar) : "memory");
}
__device__ __forceinline__ void mbar_arrive_remote(uint32_t bar, uint32_t cta) {
    asm volatile("{\n.reg .b32 ra;\nmapa.shared::cluster.u32 ra, %0, %1;\nmbarrier.arrive.shared::cluster.b64 _, [ra];\n}" ::"r"(bar), "r"(cta) : "memory");
}
__device__ __forceinline__ void mbar_wait(uint32_t bar, uint32_t parity) {
    asm volatile("{\n.reg .pred p;\nWAIT_%=:\nmbarrier.try_wait.parity.shared::cta.b64 p, [%0], %1;\n@p bra DONE_%=;\nbra WAIT_%=;\nDONE_%=:\n}" ::"r"(bar), "r"(parity) : "memory");
}
__device__ __forceinline__ void bulk_load(uint32_t dst, const void* src, uint32_t bytes, uint32_t bar) {
    asm volatile("cp.async.bulk.shared::cluster.global.mbarrier::complete_tx::bytes [%0], [%1], %2, [%3];" ::"r"(dst), "l"(src), "r"(bytes), "r"(bar) : "memory");
}
__device__ __forceinline__ void tma2d(uint32_t dst, const CUtensorMap* m, int c0, int c1, uint32_t bar) {
    asm volatile("cp.async.bulk.tensor.2d.shared::cluster.global.mbarrier::complete_tx::bytes [%0], [%1, {%3, %4}], [%2];" ::"r"(dst), "l"(m), "r"(bar), "r"(c0), "r"(c1) : "memory");
}
__device__ __forceinline__ void tma2d_mc(uint32_t dst, const CUtensorMap* m, int c0, int c1, uint32_t bar, uint16_t mask) {
    asm volatile("cp.async.bulk.tensor.2d.shared::cluster.global.mbarrier::complete_tx::bytes.multicast::cluster [%0], [%1, {%3, %4}], [%2], %5;" ::"r"(dst), "l"(m), "r"(bar), "r"(c0), "r"(c1), "h"(mask) : "memory");
}
__device__ __forceinline__ void tma3d(uint32_t dst, const CUtensorMap* m, int c0, int c1, int c2, uint32_t bar) {
    asm volatile("cp.async.bulk.tensor.3d.shared::cluster.global.mbarrier::complete_tx::bytes [%0], [%1, {%3, %4, %5}], [%2];" ::"r"(dst), "l"(m), "r"(bar), "r"(c0), "r"(c1), "r"(c2) : "memory");
}
__device__ __forceinline__ void tma3d_mc(uint32_t dst, const CUtensorMap* m, int c0, int c1, int c2, uint32_t bar, uint16_t mask) {
    asm volatile("cp.async.bulk.tensor.3d.shared::cluster.global.mbarrier::complete_tx::bytes.multicast::cluster [%0], [%1, {%3, %4, %5}], [%2], %6;" ::"r"(dst), "l"(m), "r"(bar), "r"(c0), "r"(c1), "r"(c2), "h"(mask) : "memory");
}
__device__ __forceinline__ void tma2d_store(const CUtensorMap* m, uint32_t src, int c0, int c1) {
    asm volatile("cp.async.bulk.tensor.2d.global.shared::cta.bulk_group [%0, {%2, %3}], [%1];" ::"l"(m), "r"(src), "r"(c0), "r"(c1) : "memory");
}
__device__ __forceinline__ void tma3d_store(const CUtensorMap* m, uint32_t src, int c0, int c1, int c2) {
    asm volatile("cp.async.bulk.tensor.3d.global.shared::cta.bulk_group [%0, {%2, %3, %4}], [%1];" ::"l"(m), "r"(src), "r"(c0), "r"(c1), "r"(c2) : "memory");
}
__device__ __forceinline__ void bulk_commit() { asm volatile("cp.async.bulk.commit_group;" ::: "memory"); }
__device__ __forceinline__ void bulk_wait_read() { asm volatile("cp.async.bulk.wait_group.read 0;" ::: "memory"); }
__device__ __forceinline__ void prefetch_tmap(const CUtensorMap* m) { asm volatile("prefetch.tensormap [%0];" ::"l"(m) : "memory"); }
__device__ __forceinline__ void fence_async_smem() { asm volatile("fence.proxy.async.shared::cta;" ::: "memory"); }
__device__ __forceinline__ void fence_mbar_init() { asm volatile("fence.mbarrier_init.release.cluster;" ::: "memory"); }
__device__ __forceinline__ void cluster_sync() { asm volatile("barrier.cluster.arrive.release.aligned;\nbarrier.cluster.wait.acquire.aligned;" ::: "memory"); }
__device__ __forceinline__ uint32_t cluster_rank() { uint32_t r; asm volatile("mov.u32 %0, %%cluster_ctarank;" : "=r"(r)); return r; }
__device__ __forceinline__ void pdl_wait() { asm volatile("griddepcontrol.wait;" ::: "memory"); }
__device__ __forceinline__ void pdl_launch() { asm volatile("griddepcontrol.launch_dependents;" ::: "memory"); }
__device__ __forceinline__ bool elect_one() {
    uint32_t p;
    asm volatile("{\n.reg .pred p;\nelect.sync _|p, 0xffffffff;\nselp.b32 %0, 1, 0, p;\n}" : "=r"(p));
    return p != 0;
}
__device__ __forceinline__ void named_bar(int id, int n) { asm volatile("bar.sync %0, %1;" ::"r"(id), "r"(n) : "memory"); }

__device__ __forceinline__ void wg_fence() { asm volatile("wgmma.fence.sync.aligned;" ::: "memory"); }
__device__ __forceinline__ void wg_commit() { asm volatile("wgmma.commit_group.sync.aligned;" ::: "memory"); }
template <int N> __device__ __forceinline__ void wg_wait() { asm volatile("wgmma.wait_group.sync.aligned %0;" ::"n"(N) : "memory"); }
template <int N> __device__ __forceinline__ void fence_regs(float (&d)[N]) {
#pragma unroll
    for (int i = 0; i < N; i++) asm volatile("" : "+f"(d[i])::"memory");
}
__device__ __forceinline__ uint64_t mkdesc(uint32_t addr, uint32_t lbo, uint32_t sbo, uint32_t swz) {
    uint64_t d = 0;
    d |= (uint64_t)((addr & 0x3FFFF) >> 4);
    d |= (uint64_t)((lbo & 0x3FFFF) >> 4) << 16;
    d |= (uint64_t)((sbo & 0x3FFFF) >> 4) << 32;
    d |= (uint64_t)swz << 62;
    return d;
}
__device__ __forceinline__ void ldsm_x4(uint32_t& r0, uint32_t& r1, uint32_t& r2, uint32_t& r3, uint32_t addr) {
    asm volatile("ldmatrix.sync.aligned.m8n8.x4.shared.b16 {%0,%1,%2,%3}, [%4];" : "=r"(r0), "=r"(r1), "=r"(r2), "=r"(r3) : "r"(addr) : "memory");
}
__device__ __forceinline__ void stsm_x4(uint32_t addr, uint32_t r0, uint32_t r1, uint32_t r2, uint32_t r3) {
    asm volatile("stmatrix.sync.aligned.m8n8.x4.shared.b16 [%0], {%1,%2,%3,%4};" ::"r"(addr), "r"(r0), "r"(r1), "r"(r2), "r"(r3) : "memory");
}
__device__ __forceinline__ void ldsm_x4_t(uint32_t& r0, uint32_t& r1, uint32_t& r2, uint32_t& r3, uint32_t addr) {
    asm volatile("ldmatrix.sync.aligned.m8n8.x4.trans.shared.b16 {%0,%1,%2,%3}, [%4];" : "=r"(r0), "=r"(r1), "=r"(r2), "=r"(r3) : "r"(addr) : "memory");
}
__device__ __forceinline__ void hmma(float (&d)[4], uint32_t a0, uint32_t a1, uint32_t a2, uint32_t a3, uint32_t b0, uint32_t b1) {
    asm volatile("mma.sync.aligned.m16n8k16.row.col.f32.bf16.bf16.f32 {%0,%1,%2,%3}, {%4,%5,%6,%7}, {%8,%9}, {%0,%1,%2,%3};"
                 : "+f"(d[0]), "+f"(d[1]), "+f"(d[2]), "+f"(d[3]) : "r"(a0), "r"(a1), "r"(a2), "r"(a3), "r"(b0), "r"(b1));
}
__device__ __forceinline__ uint32_t pack_bf16(float lo, float hi) {
    uint32_t r;
    asm("cvt.rn.bf16x2.f32 %0, %1, %2;" : "=r"(r) : "f"(hi), "f"(lo));
    return r;
}
__device__ __forceinline__ float bf_lo(uint32_t v) { return __uint_as_float(v << 16); }
__device__ __forceinline__ float bf_hi(uint32_t v) { return __uint_as_float(v & 0xFFFF0000u); }

#define WG_REGS_4(o) "+f"(d[o]), "+f"(d[o + 1]), "+f"(d[o + 2]), "+f"(d[o + 3])
#define WG_REGS_8(o) WG_REGS_4(o), WG_REGS_4(o + 4)
#define WG_REGS_16(o) WG_REGS_8(o), WG_REGS_8(o + 8)
#define WG_REGS_32(o) WG_REGS_16(o), WG_REGS_16(o + 16)

__device__ __forceinline__ void wgmma_ss_n80_tb(float (&d)[40], uint64_t dA, uint64_t dB, int sc) {
    asm volatile("{\n.reg .pred p;\nsetp.ne.b32 p, %42, 0;\n"
                 "wgmma.mma_async.sync.aligned.m64n80k16.f32.bf16.bf16 "
                 "{%0,%1,%2,%3,%4,%5,%6,%7,%8,%9,%10,%11,%12,%13,%14,%15,%16,%17,%18,%19,%20,%21,%22,%23,%24,%25,%26,%27,%28,%29,%30,%31,"
                 "%32,%33,%34,%35,%36,%37,%38,%39}, %40, %41, p, 1, 1, 0, 1;\n}\n"
                 : WG_REGS_32(0), WG_REGS_8(32) : "l"(dA), "l"(dB), "r"(sc));
}
__device__ __forceinline__ void wgmma_ss_n64_tb(float (&d)[32], uint64_t dA, uint64_t dB, int sc) {
    asm volatile("{\n.reg .pred p;\nsetp.ne.b32 p, %34, 0;\n"
                 "wgmma.mma_async.sync.aligned.m64n64k16.f32.bf16.bf16 "
                 "{%0,%1,%2,%3,%4,%5,%6,%7,%8,%9,%10,%11,%12,%13,%14,%15,%16,%17,%18,%19,%20,%21,%22,%23,%24,%25,%26,%27,%28,%29,%30,%31}, "
                 "%32, %33, p, 1, 1, 0, 1;\n}\n"
                 : WG_REGS_32(0) : "l"(dA), "l"(dB), "r"(sc));
}
__device__ __forceinline__ void wgmma_ss_n224_tb(float (&d)[112], uint64_t dA, uint64_t dB, int sc) {
    asm volatile("{\n.reg .pred p;\nsetp.ne.b32 p, %114, 0;\n"
                 "wgmma.mma_async.sync.aligned.m64n224k16.f32.bf16.bf16 "
                 "{%0,%1,%2,%3,%4,%5,%6,%7,%8,%9,%10,%11,%12,%13,%14,%15,%16,%17,%18,%19,%20,%21,%22,%23,%24,%25,%26,%27,%28,%29,%30,%31,"
                 "%32,%33,%34,%35,%36,%37,%38,%39,%40,%41,%42,%43,%44,%45,%46,%47,%48,%49,%50,%51,%52,%53,%54,%55,%56,%57,%58,%59,%60,%61,%62,%63,"
                 "%64,%65,%66,%67,%68,%69,%70,%71,%72,%73,%74,%75,%76,%77,%78,%79,%80,%81,%82,%83,%84,%85,%86,%87,%88,%89,%90,%91,%92,%93,%94,%95,"
                 "%96,%97,%98,%99,%100,%101,%102,%103,%104,%105,%106,%107,%108,%109,%110,%111}, "
                 "%112, %113, p, 1, 1, 0, 1;\n}\n"
                 : WG_REGS_32(0), WG_REGS_32(32), WG_REGS_32(64), WG_REGS_16(96) : "l"(dA), "l"(dB), "r"(sc));
}
template <int BN> __device__ __forceinline__ void wgmma_ss_tb(float (&d)[BN / 2], uint64_t dA, uint64_t dB, int sc) {
    if constexpr (BN == 64) wgmma_ss_n64_tb(d, dA, dB, sc);
    else if constexpr (BN == 80) wgmma_ss_n80_tb(d, dA, dB, sc);
    else wgmma_ss_n224_tb(d, dA, dB, sc);
}
__device__ __forceinline__ void wgmma_rs_n64_z(float (&d)[32], uint32_t a0, uint32_t a1, uint32_t a2, uint32_t a3, uint64_t dB) {
    asm volatile("{\n.reg .pred p;\nsetp.ne.b32 p, 0, 0;\n"
                 "wgmma.mma_async.sync.aligned.m64n64k16.f32.bf16.bf16 "
                 "{%0,%1,%2,%3,%4,%5,%6,%7,%8,%9,%10,%11,%12,%13,%14,%15,%16,%17,%18,%19,%20,%21,%22,%23,%24,%25,%26,%27,%28,%29,%30,%31}, "
                 "{%32,%33,%34,%35}, %36, p, 1, 1, 0;\n}\n"
                 : "=f"(d[0]), "=f"(d[1]), "=f"(d[2]), "=f"(d[3]), "=f"(d[4]), "=f"(d[5]), "=f"(d[6]), "=f"(d[7]),
                   "=f"(d[8]), "=f"(d[9]), "=f"(d[10]), "=f"(d[11]), "=f"(d[12]), "=f"(d[13]), "=f"(d[14]), "=f"(d[15]),
                   "=f"(d[16]), "=f"(d[17]), "=f"(d[18]), "=f"(d[19]), "=f"(d[20]), "=f"(d[21]), "=f"(d[22]), "=f"(d[23]),
                   "=f"(d[24]), "=f"(d[25]), "=f"(d[26]), "=f"(d[27]), "=f"(d[28]), "=f"(d[29]), "=f"(d[30]), "=f"(d[31])
                 : "r"(a0), "r"(a1), "r"(a2), "r"(a3), "l"(dB));
}
__device__ __forceinline__ void wgmma_rs_n24_tb(float (&d)[12], uint32_t a0, uint32_t a1, uint32_t a2, uint32_t a3, uint64_t dB) {
    asm volatile("{\n.reg .pred p;\nsetp.eq.b32 p, 0, 0;\n"
                 "wgmma.mma_async.sync.aligned.m64n24k16.f32.bf16.bf16 "
                 "{%0,%1,%2,%3,%4,%5,%6,%7,%8,%9,%10,%11}, {%12,%13,%14,%15}, %16, p, 1, 1, 1;\n}\n"
                 : WG_REGS_8(0), WG_REGS_4(8) : "r"(a0), "r"(a1), "r"(a2), "r"(a3), "l"(dB));
}

constexpr int SIDE_CTAS = 4;
__device__ __forceinline__ void side_job(int cta, float* red  , const __nv_bfloat16* __restrict__ wo,
                                         const __nv_bfloat16* __restrict__ w1, const __nv_bfloat16* __restrict__ w2) {
    const int tid = threadIdx.x, warp = tid >> 5, lane = tid & 31;
    for (int line = cta * 512 + tid; line < 18432; line += SIDE_CTAS * 512) {
        const char* p = line < 4096 ? (const char*)wo + (size_t)line * 128 : (const char*)w2 + (size_t)(line - 4096) * 128;
        asm volatile("prefetch.global.L2 [%0];" ::"l"(p));
    }
    const int rg = lane >> 3, c8 = lane & 7;
    for (int slab = cta; slab < F_ / 64; slab += SIDE_CTAS) {
        const __nv_bfloat16* base = w1 + slab * 64 + c8 * 8;
        uint4 v[8];
#pragma unroll
        for (int i = 0; i < 8; i++) v[i] = __ldg((const uint4*)(base + (size_t)(warp * 32 + rg + 4 * i) * F_));
        float acc[8];
#pragma unroll
        for (int i = 0; i < 8; i++) acc[i] = 0.f;
#pragma unroll
        for (int i = 0; i < 8; i++) {
            acc[0] += bf_lo(v[i].x); acc[1] += bf_hi(v[i].x); acc[2] += bf_lo(v[i].y); acc[3] += bf_hi(v[i].y);
            acc[4] += bf_lo(v[i].z); acc[5] += bf_hi(v[i].z); acc[6] += bf_lo(v[i].w); acc[7] += bf_hi(v[i].w);
        }
#pragma unroll
        for (int i = 0; i < 8; i++) {
            acc[i] += __shfl_xor_sync(0xffffffffu, acc[i], 8);
            acc[i] += __shfl_xor_sync(0xffffffffu, acc[i], 16);
        }
        if (rg == 0) {
#pragma unroll
            for (int i = 0; i < 8; i++) red[warp * 64 + c8 * 8 + i] = acc[i];
        }
        __syncthreads();
        if (tid < 64) {
            float s = 0.f;
#pragma unroll
            for (int i = 0; i < 16; i++) s += red[i * 64 + tid];
            g_cs_1[slab * 64 + tid] = s;
        }
        __syncthreads();
    }
}

enum { EPI_QKV = 0, EPI_RES = 1, EPI_FFN1 = 2 };

struct GemmParams {
    const float2* stats_in;
    float2* stats_out;
    const __nv_bfloat16* wkv;
    const __nv_bfloat16* wv;
    int tk;
};

template <int BK_, int NBLK> struct Geo {
    static constexpr int BK = BK_, A_BYTES = 128 * BK * 2, A_SWZ = BK == 64 ? 1 : 2, A_SBO = BK * 16;
    static constexpr int BLK = BK * 64;
    static constexpr int B_BYTES = NBLK * BLK, B_SWZ = 2, B_LBO = BLK, B_SBO = 512, B_KSTEP = 1024;
};
template <> struct Geo<64, 0> {
    static constexpr int BK = 64, A_BYTES = 128 * 128, A_SWZ = 1, A_SBO = 1024, BLK = 8192;
    static constexpr int B_BYTES = 64 * 128, B_SWZ = 1, B_LBO = 8192, B_SBO = 1024, B_KSTEP = 2048;
};
#define F1_BK 32
template <int EPI> struct EpiGeo;
template <> struct EpiGeo<EPI_QKV> { using G = Geo<64, 3>; };
template <> struct EpiGeo<EPI_RES> { using G = Geo<64, 0>; };
template <> struct EpiGeo<EPI_FFN1> { using G = Geo<F1_BK, 7>; };

template <int STAGES, int EPI> struct GemmSmem {
    using G = typename EpiGeo<EPI>::G;
    static constexpr int STAGE = G::A_BYTES + G::B_BYTES;
    static constexpr int AUX_OFF = STAGES * STAGE;
    static constexpr int TOTAL = AUX_OFF + 1152;
    static constexpr int TOTAL_SELF = AUX_OFF + 704 + 1024 + 1280;
};

struct RowStatRaw { float2 a0, a1, b0, b1; };
__device__ __forceinline__ RowStatRaw load_row_stats(const float2* __restrict__ st, int row0, int c) {
    RowStatRaw r;
    r.a0 = st[(2 * c) * S_ + row0]; r.a1 = st[(2 * c + 1) * S_ + row0];
    r.b0 = st[(2 * c) * S_ + row0 + 8]; r.b1 = st[(2 * c + 1) * S_ + row0 + 8];
    return r;
}
__device__ __forceinline__ void finish_row_stats(const RowStatRaw& r, float& mean0, float& rstd0, float& mean1, float& rstd1) {
    float sa = r.a0.x + r.a1.x, sb = r.b0.x + r.b1.x;
    sa += __shfl_xor_sync(0xffffffffu, sa, 1); sa += __shfl_xor_sync(0xffffffffu, sa, 2);
    sb += __shfl_xor_sync(0xffffffffu, sb, 1); sb += __shfl_xor_sync(0xffffffffu, sb, 2);
    mean0 = sa * 0.125f; mean1 = sb * 0.125f;
    float ma = r.a0.y + r.a1.y + 64.f * ((r.a0.x - mean0) * (r.a0.x - mean0) + (r.a1.x - mean0) * (r.a1.x - mean0));
    float mb = r.b0.y + r.b1.y + 64.f * ((r.b0.x - mean1) * (r.b0.x - mean1) + (r.b1.x - mean1) * (r.b1.x - mean1));
    ma += __shfl_xor_sync(0xffffffffu, ma, 1); ma += __shfl_xor_sync(0xffffffffu, ma, 2);
    mb += __shfl_xor_sync(0xffffffffu, mb, 1); mb += __shfl_xor_sync(0xffffffffu, mb, 2);
    rstd0 = 1.0f / sqrtf(ma * (1.f / 512.f) + 1e-5f);
    rstd1 = 1.0f / sqrtf(mb * (1.f / 512.f) + 1e-5f);
}

template <int BN, int KB, int STAGES, int EPI, int MC, bool SELF = false>
__device__ __forceinline__ void gemm_body(const CUtensorMap* mapA, const CUtensorMap* mapB, const CUtensorMap* mapB2, const CUtensorMap* mapR,
                                          const CUtensorMap* mapC, const GemmParams& prm, int tile_m, int tile_n, uint8_t* smem_raw) {
    using SM = GemmSmem<STAGES, EPI>;
    using G = typename SM::G;
    constexpr bool XKV = BN == 80;
    constexpr int TN = EPI == EPI_QKV ? 64 : BN;
    pdl_launch();
    const uint32_t sbase = smem_u32(smem_raw);
    if (sbase & 1023) __trap();
    uint8_t* sgen = smem_raw;
    const uint32_t bar_full = sbase + SM::AUX_OFF, bar_empty = bar_full + 8 * STAGES;
    float* s_cs = (float*)(sgen + SM::AUX_OFF + 256);
    float* s_row = (float*)(sgen + SM::AUX_OFF + 704);
    float* s_red = (float*)(sgen + SM::AUX_OFF + 640);
    const int tid = threadIdx.x, lane = tid & 31;
    const int warp = __shfl_sync(0xffffffffu, tid >> 5, 0);
    const uint32_t rank = MC ? cluster_rank() : 0;
    if (tid == 0) TL(prm.tk, 0);

    constexpr bool INLINE_PROD = EPI == EPI_FFN1 && F1_INLINE;
    constexpr int PWARP = INLINE_PROD ? 0 : 8;
    if (warp == PWARP && elect_one()) {
        prefetch_tmap(mapB); prefetch_tmap(mapA); prefetch_tmap(mapC);
        for (int s = 0; s < STAGES; s++) { mbar_init(bar_full + 8 * s, 1); mbar_init(bar_empty + 8 * s, MC ? 4 : 2); }
        fence_mbar_init();
    }
    __syncthreads();
    if (MC) cluster_sync();

    const int m0 = tile_m * 128, n0 = tile_n * TN;
    constexpr uint32_t STAGE_TX = G::A_BYTES + (EPI == EPI_QKV ? 2 * G::BLK : G::B_BYTES);
    auto loadB = [&](int kb, int s) {
        const uint32_t dst = sbase + s * SM::STAGE + G::A_BYTES, bar = bar_full + 8 * s;
        if constexpr (EPI == EPI_RES) {
            tma2d(dst, mapB, n0, kb * 64, bar);
        } else if constexpr (EPI == EPI_QKV) {
            tma3d(dst, mapB, 0, kb * G::BK, tile_n * 2, bar);
        } else {
            if constexpr (MC == 2) {
                if (rank == 0) tma3d_mc(dst, mapB, 0, kb * G::BK, tile_n * 7, bar, 3);
                else tma3d_mc(dst + 4 * G::BLK, mapB2, 0, kb * G::BK, tile_n * 7 + 4, bar, 3);
            } else {
                tma3d(dst, mapB, 0, kb * G::BK, tile_n * 7, bar);
                tma3d(dst + 4 * G::BLK, mapB2, 0, kb * G::BK, tile_n * 7 + 4, bar);
            }
        }
    };
    auto loadA = [&](int kb, int s) {
        const uint32_t dst = sbase + s * SM::STAGE, bar = bar_full + 8 * s;
        if constexpr (MC == 1) tma2d_mc(dst + rank * (G::A_BYTES / 2), mapA, kb * G::BK, m0 + rank * 64, bar, 3);
        else tma2d(dst, mapA, kb * G::BK, m0, bar);
    };
    constexpr int PRE = STAGES < KB ? STAGES : KB;
#define F1_LAG 2
    constexpr int LAG = F1_LAG;
    constexpr int PRE_B = PRE < PREB ? PRE : PREB;
    auto prologue_loads = [&]() {
        if (elect_one()) {
#pragma unroll
            for (int kb = 0; kb < PRE; kb++) mbar_expect_tx(bar_full + 8 * kb, STAGE_TX);
#pragma unroll
            for (int kb = 0; kb < PRE_B; kb++) loadB(kb, kb);
        }
        if (!SELF) pdl_wait();
        if (elect_one()) {
#pragma unroll
            for (int kb = 0; kb < PRE; kb++) {
                loadA(kb, kb);
                if (kb + PRE_B < PRE) loadB(kb + PRE_B, kb + PRE_B);
            }
            if constexpr (EPI == EPI_RES && KB < STAGES) {
                mbar_expect_tx(bar_full + 8 * KB, 16384);
                tma2d(sbase + KB * SM::STAGE, mapR, n0, m0, bar_full + 8 * KB);
            }
        }
    };
    if (SELF && warp > 8) {
        static_assert(!SELF || (STAGES >= KB && EPI == EPI_QKV), "SELF needs every k block resident");
        const int t = tid - 288;
        float ss[4] = {0.f, 0.f, 0.f, 0.f}, sq[4] = {0.f, 0.f, 0.f, 0.f}, ca[8], cx[8];
#pragma unroll
        for (int i = 0; i < 8; i++) { ca[i] = 0.f; cx[i] = 0.f; }
        if constexpr (XKV) named_bar(6, 512);
#pragma unroll 1
        for (int kb = 0; kb < KB; kb++) {
            mbar_wait(bar_full + 8 * kb, 0);
            const uint32_t arow = sbase + kb * SM::STAGE + (t >> 1) * 128;
            const uint32_t bblk = sbase + kb * SM::STAGE + G::A_BYTES;
            uint32_t w[7][4];
#pragma unroll
            for (int j = 0; j < 4; j++)
                asm volatile("ld.shared.v4.u32 {%0,%1,%2,%3}, [%4];" : "=r"(w[j][0]), "=r"(w[j][1]), "=r"(w[j][2]), "=r"(w[j][3])
                             : "r"(arow + (((2 * j + (t & 1) + 2 * ((t >> 1) & 3)) & 7) << 4)));
#pragma unroll
            for (int r = 0; r < 2; r++) {
                const int krow = (t >> 3) * 2 + r, ch = t & 7;
                asm volatile("ld.shared.v4.u32 {%0,%1,%2,%3}, [%4];" : "=r"(w[4 + r][0]), "=r"(w[4 + r][1]), "=r"(w[4 + r][2]), "=r"(w[4 + r][3])
                             : "r"(bblk + (ch >> 2) * G::BLK + krow * 64 + (((ch & 3) ^ ((krow >> 1) & 3)) << 4)));
            }
            if constexpr (XKV) {
                const int krow = (t >> 1) & 63;
                asm volatile("ld.shared.v4.u32 {%0,%1,%2,%3}, [%4];" : "=r"(w[6][0]), "=r"(w[6][1]), "=r"(w[6][2]), "=r"(w[6][3])
                             : "r"(bblk + 2 * G::BLK + krow * 64 + (((t & 1) ^ ((krow >> 1) & 3)) << 4)));
            }
#pragma unroll
            for (int j = 0; j < 4; j++)
#pragma unroll
                for (int i = 0; i < 4; i++) {
                    const float lo = bf_lo(w[j][i]), hi = bf_hi(w[j][i]);
                    ss[i] += lo + hi;
                    sq[i] = fmaf(lo, lo, fmaf(hi, hi, sq[i]));
                }
#pragma unroll
            for (int r = 0; r < 2; r++)
#pragma unroll
                for (int i = 0; i < 4; i++) { ca[2 * i] += bf_lo(w[4 + r][i]); ca[2 * i + 1] += bf_hi(w[4 + r][i]); }
            if constexpr (XKV) {
                if (t < 128) {
#pragma unroll
                    for (int i = 0; i < 4; i++) { cx[2 * i] += bf_lo(w[6][i]); cx[2 * i + 1] += bf_hi(w[6][i]); }
                }
            }
        }
        float tsum = (ss[0] + ss[1]) + (ss[2] + ss[3]), tsq = (sq[0] + sq[1]) + (sq[2] + sq[3]);
        tsum += __shfl_xor_sync(0xffffffffu, tsum, 1);
        tsq += __shfl_xor_sync(0xffffffffu, tsq, 1);
        if ((t & 1) == 0) {
            const float md = tsum * (1.f / 512.f);
            const float var = fmaxf(tsq * (1.f / 512.f) - md * md, 0.f);
            *(float2*)(s_row + t) = make_float2(md, 1.0f / sqrtf(var + 1e-5f));
        }
#pragma unroll
        for (int i = 0; i < 8; i++) {
            ca[i] += __shfl_xor_sync(0xffffffffu, ca[i], 8);
            ca[i] += __shfl_xor_sync(0xffffffffu, ca[i], 16);
            if constexpr (XKV) {
                cx[i] += __shfl_xor_sync(0xffffffffu, cx[i], 2); cx[i] += __shfl_xor_sync(0xffffffffu, cx[i], 4);
                cx[i] += __shfl_xor_sync(0xffffffffu, cx[i], 8); cx[i] += __shfl_xor_sync(0xffffffffu, cx[i], 16);
            }
        }
        float* s_part = s_row + 256;
        const int sw = warp - 9;
        if (sw >= 4) {
            if (lane < 8) {
#pragma unroll
                for (int i = 0; i < 8; i++) s_part[(sw - 4) * 80 + lane * 8 + i] = ca[i];
            }
        }
        named_bar(5, 256);
        if (sw < 4) {
            if (lane < 8) {
#pragma unroll
                for (int i = 0; i < 8; i++) s_part[sw * 80 + lane * 8 + i] += ca[i];
            }
            if (XKV && lane < 2) {
#pragma unroll
                for (int i = 0; i < 8; i++) s_part[sw * 80 + 64 + lane * 8 + i] = cx[i];
            }
        }
        named_bar(5, 256);
        if (t < (XKV ? 80 : 64)) {
            const float v = (s_part[t] + s_part[80 + t]) + (s_part[160 + t] + s_part[240 + t]);
            s_cs[t] = v;
            if (tile_m == 0) {
                if (t < 64) g_cs_q[n0 + t] = v;
                else g_cs_kv[tile_n * 16 + t - 64] = v;
            }
        }
        named_bar(4, 512);
    } else if (!INLINE_PROD && warp == 8) {
        prologue_loads();
        int s = PRE % STAGES, ph = (PRE / STAGES) & 1;
#pragma unroll 1
        for (int kb = PRE; kb < KB; kb++) {
            mbar_wait(bar_empty + 8 * s, ph ^ 1);
            if (elect_one()) {
                mbar_expect_tx(bar_full + 8 * s, STAGE_TX);
                loadB(kb, s);
                loadA(kb, s);
            }
            if (++s == STAGES) { s = 0; ph ^= 1; }
        }
        if constexpr (EPI == EPI_RES && KB >= STAGES) {
            mbar_wait(bar_empty + 8 * s, ph ^ 1);
            if (elect_one()) {
                mbar_expect_tx(bar_full + 8 * s, 16384);
                tma2d(sbase + s * SM::STAGE, mapR, n0, m0, bar_full + 8 * s);
            }
        }
    } else {
        if (INLINE_PROD && warp == 0) prologue_loads();
        const int wg = warp >> 2, g = lane >> 2, c = lane & 3;
        const int rloc = wg * 64 + (warp & 3) * 16 + g;
        const int row0 = m0 + rloc;
        float mean0 = 0.f, rstd0 = 1.f, mean1 = 0.f, rstd1 = 1.f;
        if constexpr (XKV) {
            static_assert(!XKV || STAGES >= KB, "the K / V weight block must stay resident");
            const __nv_bfloat16* wsrc = tile_n == 0 ? prm.wkv : prm.wv;
            uint4 v[4];
#pragma unroll
            for (int i = 0; i < 4; i++) v[i] = __ldg((const uint4*)wsrc + tid + 256 * i);
#pragma unroll
            for (int i = 0; i < 4; i++) {
                const int idx = tid + 256 * i, k = idx >> 1, kr = k & 63;
                const uint32_t dst = sbase + (k >> 6) * SM::STAGE + G::A_BYTES + 2 * G::BLK + kr * 64 + (((idx & 1) ^ ((kr >> 1) & 3)) << 4);
                asm volatile("st.shared.v4.u32 [%0], {%1,%2,%3,%4};" ::"r"(dst), "r"(v[i].x), "r"(v[i].y), "r"(v[i].z), "r"(v[i].w) : "memory");
            }
            fence_async_smem();
            if constexpr (SELF) named_bar(6, 512); else named_bar(6, 256);
        }
        RowStatRaw raw;
        float csv = 0.f;
        float2 cskv[2] = {make_float2(0.f, 0.f), make_float2(0.f, 0.f)};
        auto ln_inputs = [&]() {
            pdl_wait();
            if constexpr (EPI != EPI_RES) {
                raw = load_row_stats(prm.stats_in, row0, c);
                const float* cs = EPI == EPI_FFN1 ? g_cs_1 + n0 : g_cs_q + n0;
                if (tid < TN) csv = cs[tid];
                if constexpr (XKV) {
                    cskv[0] = *(const float2*)(g_cs_kv + tile_n * 16 + 2 * c);
                    cskv[1] = *(const float2*)(g_cs_kv + tile_n * 16 + 8 + 2 * c);
                }
            }
        };
        if (!SELF) ln_inputs();
        float acc[BN / 2];
        const uint64_t dA0 = mkdesc(sbase + wg * (G::A_BYTES / 2), 16, G::A_SBO, G::A_SWZ);
        const uint64_t dB0 = mkdesc(sbase + G::A_BYTES, G::B_LBO, G::B_SBO, G::B_SWZ);
        int s = 0, ph = 0;
#pragma unroll 1
        for (int kb = 0; kb < KB; kb++) {
            mbar_wait(bar_full + 8 * s, ph);
            const uint64_t dA = dA0 + (uint64_t)(s * (SM::STAGE >> 4)), dB = dB0 + (uint64_t)(s * (SM::STAGE >> 4));
            wg_fence();
#pragma unroll
            for (int k = 0; k < G::BK / 16; k++) wgmma_ss_tb<BN>(acc, dA + (uint64_t)(k * 2), dB + (uint64_t)(k * (G::B_KSTEP >> 4)), (kb | k) != 0);
            wg_commit();
            if constexpr (EPI == EPI_RES && RES_WAIT0) {
                wg_wait<0>();
                if ((warp & 3) == 0 && elect_one()) {
                    if (MC) { mbar_arrive_remote(bar_empty + 8 * s, 0); mbar_arrive_remote(bar_empty + 8 * s, 1); }
                    else mbar_arrive(bar_empty + 8 * s);
                }
            } else if (kb > 0) {
                wg_wait<1>();
                const int sp = s == 0 ? STAGES - 1 : s - 1;
                if ((warp & 3) == 0 && elect_one()) {
                    if (MC) { mbar_arrive_remote(bar_empty + 8 * sp, 0); mbar_arrive_remote(bar_empty + 8 * sp, 1); }
                    else mbar_arrive(bar_empty + 8 * sp);
                }
                if (INLINE_PROD && warp == 0 && kb >= LAG && kb - LAG + STAGES < KB) {
                    const int sq = LAG == 1 ? sp : (sp == 0 ? STAGES - 1 : sp - 1);
                    mbar_wait(bar_empty + 8 * sq, ((kb - LAG) / STAGES) & 1);
                    if (elect_one()) {
                        mbar_expect_tx(bar_full + 8 * sq, STAGE_TX);
                        loadB(kb - LAG + STAGES, sq);
                        loadA(kb - LAG + STAGES, sq);
                    }
                }
            }
            if (++s == STAGES) { s = 0; ph ^= 1; }
        }
        if constexpr (SELF) {
            named_bar(4, 512);
            const float2 r0 = *(const float2*)(s_row + 2 * rloc), r1 = *(const float2*)(s_row + 2 * rloc + 16);
            mean0 = r0.x; rstd0 = r0.y; mean1 = r1.x; rstd1 = r1.y;
        } else if constexpr (EPI != EPI_RES) {
            finish_row_stats(raw, mean0, rstd0, mean1, rstd1);
            if (tid < TN) s_cs[tid] = csv;
        }
        wg_wait<0>();
        fence_regs(acc);
        if (tid == 0) TL(prm.tk, 2);
        if constexpr (EPI != EPI_RES) named_bar(1, 256);

        if constexpr (EPI != EPI_FFN1) {
            const uint32_t stile = sbase + (EPI == EPI_RES ? s * SM::STAGE : 0);
            const int mrow = wg * 64 + (warp & 3) * 16 + (lane & 7) + ((lane >> 3) & 1) * 8;
            const uint32_t rbase = stile + mrow * 128;
            if constexpr (EPI == EPI_RES) {
                mbar_wait(bar_full + 8 * s, ph);
                float s0 = 0.f, s1 = 0.f;
#pragma unroll
                for (int jj = 0; jj < 4; jj++) {
                    uint32_t r0, r1, r2, r3;
                    const uint32_t addr = rbase + (((2 * jj + (lane >> 4)) ^ (mrow & 7)) << 4);
                    ldsm_x4(r0, r1, r2, r3, addr);
                    const uint32_t u0 = pack_bf16(acc[8 * jj] + bf_lo(r0), acc[8 * jj + 1] + bf_hi(r0));
                    const uint32_t u1 = pack_bf16(acc[8 * jj + 2] + bf_lo(r1), acc[8 * jj + 3] + bf_hi(r1));
                    const uint32_t u2 = pack_bf16(acc[8 * jj + 4] + bf_lo(r2), acc[8 * jj + 5] + bf_hi(r2));
                    const uint32_t u3 = pack_bf16(acc[8 * jj + 6] + bf_lo(r3), acc[8 * jj + 7] + bf_hi(r3));
                    stsm_x4(addr, u0, u1, u2, u3);
                    acc[8 * jj] = bf_lo(u0); acc[8 * jj + 1] = bf_hi(u0); acc[8 * jj + 4] = bf_lo(u2); acc[8 * jj + 5] = bf_hi(u2);
                    acc[8 * jj + 2] = bf_lo(u1); acc[8 * jj + 3] = bf_hi(u1); acc[8 * jj + 6] = bf_lo(u3); acc[8 * jj + 7] = bf_hi(u3);
                    s0 += (acc[8 * jj] + acc[8 * jj + 1]) + (acc[8 * jj + 4] + acc[8 * jj + 5]);
                    s1 += (acc[8 * jj + 2] + acc[8 * jj + 3]) + (acc[8 * jj + 6] + acc[8 * jj + 7]);
                }
                fence_async_smem();
                named_bar(2 + wg, 128);
                if ((warp & 3) == 0 && elect_one()) { tma2d_store(mapC, stile + wg * 8192, n0, m0 + wg * 64); bulk_commit(); }
                if (prm.stats_out) {
                    s0 += __shfl_xor_sync(0xffffffffu, s0, 1); s0 += __shfl_xor_sync(0xffffffffu, s0, 2);
                    s1 += __shfl_xor_sync(0xffffffffu, s1, 1); s1 += __shfl_xor_sync(0xffffffffu, s1, 2);
                    const float mu0 = s0 * (1.f / 64.f), mu1 = s1 * (1.f / 64.f);
                    float q0 = 0.f, q1 = 0.f;
#pragma unroll
                    for (int j = 0; j < 8; j++) {
                        float d;
                        d = acc[4 * j] - mu0; q0 += d * d; d = acc[4 * j + 1] - mu0; q0 += d * d;
                        d = acc[4 * j + 2] - mu1; q1 += d * d; d = acc[4 * j + 3] - mu1; q1 += d * d;
                    }
                    q0 += __shfl_xor_sync(0xffffffffu, q0, 1); q0 += __shfl_xor_sync(0xffffffffu, q0, 2);
                    q1 += __shfl_xor_sync(0xffffffffu, q1, 1); q1 += __shfl_xor_sync(0xffffffffu, q1, 2);
                    if (c == 0) {
                        prm.stats_out[tile_n * S_ + row0] = make_float2(mu0, q0);
                        prm.stats_out[tile_n * S_ + row0 + 8] = make_float2(mu1, q1);
                    }
                }
            } else {
                const float sc = 0.25f * 1.4426950408889634f;
                const float a0 = rstd0 * sc, a1 = rstd1 * sc, rm0 = a0 * mean0, rm1 = a1 * mean1;
#pragma unroll
                for (int jj = 0; jj < 4; jj++) {
                    const float2 ca = *(const float2*)(s_cs + 16 * jj + 2 * c), cb = *(const float2*)(s_cs + 16 * jj + 8 + 2 * c);
                    const uint32_t u0 = pack_bf16(acc[8 * jj] * a0 - rm0 * ca.x, acc[8 * jj + 1] * a0 - rm0 * ca.y);
                    const uint32_t u1 = pack_bf16(acc[8 * jj + 2] * a1 - rm1 * ca.x, acc[8 * jj + 3] * a1 - rm1 * ca.y);
                    const uint32_t u2 = pack_bf16(acc[8 * jj + 4] * a0 - rm0 * cb.x, acc[8 * jj + 5] * a0 - rm0 * cb.y);
                    const uint32_t u3 = pack_bf16(acc[8 * jj + 6] * a1 - rm1 * cb.x, acc[8 * jj + 7] * a1 - rm1 * cb.y);
                    stsm_x4(rbase + (((2 * jj + (lane >> 4)) ^ (mrow & 7)) << 4), u0, u1, u2, u3);
                }
                fence_async_smem();
                named_bar(2 + wg, 128);
                if ((warp & 3) == 0 && elect_one()) { tma2d_store(mapC, stile + wg * 8192, n0, m0 + wg * 64); bulk_commit(); }
            }
            if constexpr (XKV) {
                {
                    const float* acx = &acc[32];
                    const float rm0 = rstd0 * mean0, rm1 = rstd1 * mean1;
                    float n0s = 0.f, n1s = 0.f, vmax = 0.f;
#pragma unroll
                    for (int j = 0; j < 2; j++) {
                        const float2 cs2 = SELF ? *(const float2*)(s_cs + 64 + 8 * j + 2 * c) : cskv[j];
                        const uint32_t u0 = pack_bf16(acx[4 * j] * rstd0 - rm0 * cs2.x, acx[4 * j + 1] * rstd0 - rm0 * cs2.y);
                        const uint32_t u1 = pack_bf16(acx[4 * j + 2] * rstd1 - rm1 * cs2.x, acx[4 * j + 3] * rstd1 - rm1 * cs2.y);
                        n0s += bf_lo(u0) * bf_lo(u0) + bf_hi(u0) * bf_hi(u0);
                        n1s += bf_lo(u1) * bf_lo(u1) + bf_hi(u1) * bf_hi(u1);
                        vmax = fmaxf(vmax, fmaxf(fmaxf(fabsf(bf_lo(u0)), fabsf(bf_hi(u0))), fmaxf(fabsf(bf_lo(u1)), fabsf(bf_hi(u1)))));
                        if (tile_n == 0) {
                            *(uint32_t*)(g_kimg + (row0 >> 3) * 256 + j * 128 + g * 16 + c * 4) = u0;
                            *(uint32_t*)(g_kimg + ((row0 + 8) >> 3) * 256 + j * 128 + g * 16 + c * 4) = u1;
                        } else {
                            uint8_t* vb = g_vimg + (row0 >> 4) * 768 + j * 256 + g * 16 + c * 4;
                            *(uint32_t*)(vb) = u0;
                            *(uint32_t*)(vb + 128) = u1;
                        }
                    }
                    if (tile_n == 1) {
                        uint8_t* vb = g_vimg + (row0 >> 4) * 768 + 512 + g * 16 + c * 4;
                        const uint32_t one = c == 0 ? 0x00003F80u : 0u;
                        *(uint32_t*)(vb) = one;
                        *(uint32_t*)(vb + 128) = one;
                    }
                    n0s += __shfl_xor_sync(0xffffffffu, n0s, 1); n0s += __shfl_xor_sync(0xffffffffu, n0s, 2);
                    n1s += __shfl_xor_sync(0xffffffffu, n1s, 1); n1s += __shfl_xor_sync(0xffffffffu, n1s, 2);
                    float km = tile_n == 0 ? fmaxf(n0s, n1s) : vmax;
                    if (!(n0s + n1s < INFINITY)) km = INFINITY;
#pragma unroll
                    for (int o = 1; o < 32; o <<= 1) km = fmaxf(km, __shfl_xor_sync(0xffffffffu, km, o));
                    if (lane == 0) s_red[warp] = km;
                    named_bar(1, 256);
                    if (tid == 0) {
                        float a = 0.f;
                        for (int i = 0; i < 8; i++) a = fmaxf(a, s_red[i]);
                        g_kvmax[tile_n * 16 + tile_m] = a;
                    }
                }
            }
            if ((warp & 3) == 0) bulk_wait_read();
        } else {
            const uint32_t stile = sbase + wg * (7 * 4096);
            const int mrow = (warp & 3) * 16 + (lane & 7) + ((lane >> 3) & 1) * 8;
            const float a0 = 0.5f * rstd0, a1 = 0.5f * rstd1, rm0 = a0 * mean0, rm1 = a1 * mean1;
#pragma unroll
            for (int jj = 0; jj < 14; jj++) {
                const float2 ca = *(const float2*)(s_cs + 16 * jj + 2 * c), cb = *(const float2*)(s_cs + 16 * jj + 8 + 2 * c);
                float y[8] = {acc[8 * jj] * a0 - rm0 * ca.x,     acc[8 * jj + 1] * a0 - rm0 * ca.y,
                              acc[8 * jj + 2] * a1 - rm1 * ca.x, acc[8 * jj + 3] * a1 - rm1 * ca.y,
                              acc[8 * jj + 4] * a0 - rm0 * cb.x, acc[8 * jj + 5] * a0 - rm0 * cb.y,
                              acc[8 * jj + 6] * a1 - rm1 * cb.x, acc[8 * jj + 7] * a1 - rm1 * cb.y};
#pragma unroll
                for (int i = 0; i < 8; i++) {
                    float t;
                    asm("tanh.approx.f32 %0, %1;" : "=f"(t) : "f"(y[i]));
                    y[i] = fmaf(y[i], t, y[i]);
                }
                const int chunk = (2 * jj + (lane >> 4)) & 3, blk = jj >> 1;
                stsm_x4(stile + blk * 4096 + mrow * 64 + ((chunk ^ ((mrow >> 1) & 3)) << 4),
                        pack_bf16(y[0], y[1]), pack_bf16(y[2], y[3]), pack_bf16(y[4], y[5]), pack_bf16(y[6], y[7]));
                if (jj & 1) {
                    fence_async_smem();
                    __syncwarp();
                    if (elect_one()) {
                        tma2d_store(mapC, stile + blk * 4096 + (warp & 3) * 1024, n0 + blk * 32, m0 + wg * 64 + (warp & 3) * 16);
                        bulk_commit();
                    }
                }
            }
            bulk_wait_read();
        }
    }
    if (tid == 0) TL(prm.tk, 3);
    if (MC) cluster_sync();
}

#define WO_ST 9
#define F2_ST 6
#define F1_ST (F1_BK == 64 ? 5 : 9)
#define QKV_ST 8
constexpr int QKV_STAGES = QKV_ST, WO_STAGES = WO_ST, FFN2_STAGES = F2_ST, FFN1_STAGES = F1_ST;
template <bool SELF>
__global__ void __launch_bounds__(SELF ? 544 : 288) qkv_kernel(const __grid_constant__ CUtensorMap mapA, const __grid_constant__ CUtensorMap mapWq,
                                                  const __grid_constant__ CUtensorMap mapQ, const GemmParams prm) {
    extern __shared__ __align__(1024) uint8_t smem_raw[];
    const int tn = blockIdx.x & 7;
    if (tn < 2) gemm_body<80, 8, QKV_STAGES, EPI_QKV, QKV_MC, SELF>(&mapA, &mapWq, &mapWq, &mapA, &mapQ, prm, blockIdx.x >> 3, tn, smem_raw);
    else gemm_body<64, 8, QKV_STAGES, EPI_QKV, QKV_MC, SELF>(&mapA, &mapWq, &mapWq, &mapA, &mapQ, prm, blockIdx.x >> 3, tn, smem_raw);
}
template <int KB, int STAGES>
__global__ void __launch_bounds__(288) res_gemm_kernel(const __grid_constant__ CUtensorMap mapA, const __grid_constant__ CUtensorMap mapW,
                                                       const __grid_constant__ CUtensorMap mapR, const __grid_constant__ CUtensorMap mapC, const GemmParams prm) {
    extern __shared__ __align__(1024) uint8_t smem_raw[];
    gemm_body<64, KB, STAGES, EPI_RES, (KB == 8 ? WO_MC : F2_MC)>(&mapA, &mapW, &mapW, &mapR, &mapC, prm, blockIdx.x >> 3, blockIdx.x & 7, smem_raw);
}
__global__ void __launch_bounds__(F1_INLINE ? 256 : 288) ffn1_kernel(const __grid_constant__ CUtensorMap mapA, const __grid_constant__ CUtensorMap mapW4,
                                                   const __grid_constant__ CUtensorMap mapW3, const __grid_constant__ CUtensorMap mapH, const GemmParams prm) {
    extern __shared__ __align__(1024) uint8_t smem_raw[];
    const int pair = blockIdx.x >> 1, tile_n = pair & 7, tile_m = (pair >> 3) * 2 + (blockIdx.x & 1);
    gemm_body<224, 512 / F1_BK, FFN1_STAGES, EPI_FFN1, F1_MC>(&mapA, &mapW4, &mapW3, &mapA, &mapH, prm, tile_m, tile_n, smem_raw);
}

constexpr int NPOLY = 10;
__host__ __device__ constexpr bool is_mufu(int i) { return ((i + 1) * (16 - NPOLY)) / 16 != (i * (16 - NPOLY)) / 16; }

__device__ __forceinline__ float ex2(float x) { float r; asm("ex2.approx.ftz.f32 %0, %1;" : "=f"(r) : "f"(x)); return r; }
__device__ __forceinline__ uint32_t exp_pair_mufu(float a, float b) { return pack_bf16(ex2(a), ex2(b)); }
__device__ __forceinline__ uint32_t exp_pair_fma(float a, float b, uint32_t c3f) {
    constexpr float MAGIC = 98430.4140625f;
    const float ta = a + MAGIC, tb = b + (MAGIC - 143.5f);
    uint32_t y, m, r;
    asm("mad.lo.u32 %0, %1, 65536, %2;" : "=r"(y) : "r"(__float_as_uint(tb)), "r"(__float_as_uint(ta)));
    asm("lop3.b32 %0, %1, 0x007F007F, %2, 0xEA;" : "=r"(m) : "r"(y), "r"(c3f));
    const uint32_t e = y & 0xFF80FF80u;
    asm("fma.rn.bf16x2 %0, %1, %2, %3;" : "=r"(r) : "r"(y), "r"(m), "r"(e));
    return r;
}

constexpr int KCH = 256, NCH = S_ / KCH;
constexpr int K_BYTES = S_ * 32, V_BYTES = (S_ / 16) * 768;
constexpr int ATT_SMEM = K_BYTES + V_BYTES;

__global__ void __launch_bounds__(512, 1) attn_kernel(const __nv_bfloat16* __restrict__ wo, const __nv_bfloat16* __restrict__ w1,
                                                       const __nv_bfloat16* __restrict__ w2, int tk) {
    extern __shared__ __align__(1024) uint8_t smem[];
    __shared__ uint64_t bars[NCH];
    __shared__ int s_slow;
    const int tid = threadIdx.x, wg = tid >> 7, warp = (tid >> 5) & 3, lane = tid & 31;
    const uint32_t sK = smem_u32(smem), sV = sK + K_BYTES;
    if (blockIdx.x >= 128) {
        pdl_launch();
        side_job(blockIdx.x - 128, (float*)smem, wo, w1, w2);
        return;
    }
    if (tid == 0) TL(tk, 0);
    if (tid == 0) {
        for (int i = 0; i < NCH; i++) mbar_init(smem_u32(&bars[i]), 1);
        s_slow = 0;
        fence_mbar_init();
    }
    __syncthreads();
    pdl_launch();
    pdl_wait();
    if (tid == 0) TL(tk, 1);
    if (__shfl_sync(0xffffffffu, tid >> 5, 0) == 0 && elect_one()) {
#pragma unroll
        for (int i = 0; i < NCH; i++) {
            mbar_expect_tx(smem_u32(&bars[i]), KCH * 32 + (KCH / 16) * 768);
            bulk_load(sK + i * KCH * 32, g_kimg + i * KCH * 32, KCH * 32, smem_u32(&bars[i]));
            bulk_load(sV + i * (KCH / 16) * 768, g_vimg + i * (KCH / 16) * 768, (KCH / 16) * 768, smem_u32(&bars[i]));
        }
    }
    const int tb = blockIdx.x >> 3, hg = blockIdx.x & 7;
    const int head = hg * 4 + wg;
    const int g = lane >> 2, c = lane & 3;
    uint32_t qa[2][4];
    float qn = 0.f;
#pragma unroll
    for (int m = 0; m < 2; m++) {
        const int row = tb * 128 + m * 64 + warp * 16 + g;
        const uint32_t* p0 = (const uint32_t*)(g_q + (size_t)row * D_ + head * 16);
        const uint32_t* p1 = (const uint32_t*)(g_q + (size_t)(row + 8) * D_ + head * 16);
        qa[m][0] = p0[c]; qa[m][1] = p1[c]; qa[m][2] = p0[c + 4]; qa[m][3] = p1[c + 4];
        float n0 = bf_lo(qa[m][0]) * bf_lo(qa[m][0]) + bf_hi(qa[m][0]) * bf_hi(qa[m][0]) + bf_lo(qa[m][2]) * bf_lo(qa[m][2]) + bf_hi(qa[m][2]) * bf_hi(qa[m][2]);
        float n1 = bf_lo(qa[m][1]) * bf_lo(qa[m][1]) + bf_hi(qa[m][1]) * bf_hi(qa[m][1]) + bf_lo(qa[m][3]) * bf_lo(qa[m][3]) + bf_hi(qa[m][3]) * bf_hi(qa[m][3]);
        n0 += __shfl_xor_sync(0xffffffffu, n0, 1); n0 += __shfl_xor_sync(0xffffffffu, n0, 2);
        n1 += __shfl_xor_sync(0xffffffffu, n1, 1); n1 += __shfl_xor_sync(0xffffffffu, n1, 2);
        if (!(n0 == n0) || !(n1 == n1)) n0 = __int_as_float(0x7f800000);
        qn = fmaxf(qn, fmaxf(n0, n1));
    }
    {
        float km = 0.f, vm = 0.f;
#pragma unroll
        for (int i = 0; i < 16; i++) { km = fmaxf(km, g_kvmax[i]); vm = fmaxf(vm, g_kvmax[16 + i]); }
        const bool ok = (qn * km <= 10000.f) && (vm <= 16384.f);
        if (!ok) s_slow = 1;
    }
    float oacc[2][12];
#pragma unroll
    for (int m = 0; m < 2; m++)
#pragma unroll
        for (int i = 0; i < 12; i++) oacc[m][i] = 0.f;
    __syncthreads();
    const bool slow = s_slow != 0;

    const uint64_t dK0 = mkdesc(sK, 128, 256, 0);
    const uint64_t dV0 = mkdesc(sV, 128, 256, 0);
    uint32_t c3f;
    asm volatile("mov.b32 %0, 0x3F003F00;" : "=r"(c3f));
    if (!slow) {
#pragma unroll 1
        for (int t = 0; t < S_ / 64; t++) {
            if ((t & 3) == 0) mbar_wait(smem_u32(&bars[t >> 2]), 0);
            const uint64_t dK = dK0 + (uint64_t)(t * 64 * 32 / 16);
            const uint64_t dV = dV0 + (uint64_t)(t * 4 * 768 / 16);
#pragma unroll
            for (int m = 0; m < 2; m++) {
                float s[32];
                wg_fence();
                wgmma_rs_n64_z(s, qa[m][0], qa[m][1], qa[m][2], qa[m][3], dK);
                wg_commit();
                wg_wait<0>();
                fence_regs(s);
                uint32_t p[16];
#pragma unroll
                for (int i = 0; i < 16; i++) p[i] = is_mufu(i) ? exp_pair_mufu(s[2 * i], s[2 * i + 1]) : exp_pair_fma(s[2 * i], s[2 * i + 1], c3f);
                wg_fence();
#pragma unroll
                for (int kk = 0; kk < 4; kk++)
                    wgmma_rs_n24_tb(oacc[m], p[4 * kk], p[4 * kk + 1], p[4 * kk + 2], p[4 * kk + 3], dV + (uint64_t)(kk * 768 / 16));
                wg_commit();
            }
        }
        wg_wait<0>();
    } else {
        float mx[2][2] = {{-INFINITY, -INFINITY}, {-INFINITY, -INFINITY}};
#pragma unroll 1
        for (int t = 0; t < S_ / 64; t++) {
            if ((t & 3) == 0) mbar_wait(smem_u32(&bars[t >> 2]), 0);
            const uint64_t dK = dK0 + (uint64_t)(t * 64 * 32 / 16);
            const uint64_t dV = dV0 + (uint64_t)(t * 4 * 768 / 16);
#pragma unroll
            for (int m = 0; m < 2; m++) {
                float s[32];
                wg_fence();
                wgmma_rs_n64_z(s, qa[m][0], qa[m][1], qa[m][2], qa[m][3], dK);
                wg_commit();
                wg_wait<0>();
                fence_regs(s);
                fence_regs(oacc[m]);
                float r0 = mx[m][0], r1 = mx[m][1];
#pragma unroll
                for (int j = 0; j < 8; j++) {
                    r0 = fmaxf(r0, fmaxf(s[4 * j], s[4 * j + 1]));
                    r1 = fmaxf(r1, fmaxf(s[4 * j + 2], s[4 * j + 3]));
                }
                r0 = fmaxf(r0, __shfl_xor_sync(0xffffffffu, r0, 1)); r0 = fmaxf(r0, __shfl_xor_sync(0xffffffffu, r0, 2));
                r1 = fmaxf(r1, __shfl_xor_sync(0xffffffffu, r1, 1)); r1 = fmaxf(r1, __shfl_xor_sync(0xffffffffu, r1, 2));
                const float al0 = ex2(mx[m][0] - r0), al1 = ex2(mx[m][1] - r1);
                mx[m][0] = r0; mx[m][1] = r1;
#pragma unroll
                for (int j = 0; j < 3; j++) {
                    oacc[m][4 * j] *= al0; oacc[m][4 * j + 1] *= al0;
                    oacc[m][4 * j + 2] *= al1; oacc[m][4 * j + 3] *= al1;
                }
                uint32_t p[16];
#pragma unroll
                for (int j = 0; j < 8; j++) {
                    p[2 * j] = pack_bf16(ex2(s[4 * j] - r0), ex2(s[4 * j + 1] - r0));
                    p[2 * j + 1] = pack_bf16(ex2(s[4 * j + 2] - r1), ex2(s[4 * j + 3] - r1));
                }
                fence_regs(oacc[m]);
                wg_fence();
#pragma unroll
                for (int kk = 0; kk < 4; kk++)
                    wgmma_rs_n24_tb(oacc[m], p[4 * kk], p[4 * kk + 1], p[4 * kk + 2], p[4 * kk + 3], dV + (uint64_t)(kk * 768 / 16));
                wg_commit();
                wg_wait<0>();
            }
        }
    }
    fence_regs(oacc[0]); fence_regs(oacc[1]);
    if (tid == 0) TL(tk, 2);
#pragma unroll
    for (int m = 0; m < 2; m++) {
        const float l0 = __shfl_sync(0xffffffffu, oacc[m][8], lane & ~3);
        const float l1 = __shfl_sync(0xffffffffu, oacc[m][10], lane & ~3);
        const float r0 = 1.0f / l0, r1 = 1.0f / l1;
        const int row = tb * 128 + m * 64 + warp * 16 + g;
        uint32_t* p0 = (uint32_t*)(g_o + (size_t)row * D_ + head * 16);
        uint32_t* p1 = (uint32_t*)(g_o + (size_t)(row + 8) * D_ + head * 16);
        p0[c] = pack_bf16(oacc[m][0] * r0, oacc[m][1] * r0);
        p1[c] = pack_bf16(oacc[m][2] * r1, oacc[m][3] * r1);
        p0[c + 4] = pack_bf16(oacc[m][4] * r0, oacc[m][5] * r0);
        p1[c + 4] = pack_bf16(oacc[m][6] * r1, oacc[m][7] * r1);
    }
    if (tid == 0) TL(tk, 3);
}

typedef CUresult (*EncodeFn)(CUtensorMap*, CUtensorMapDataType, cuuint32_t, void*, const cuuint64_t*, const cuuint64_t*, const cuuint32_t*,
                             const cuuint32_t*, CUtensorMapInterleave, CUtensorMapSwizzle, CUtensorMapL2promotion, CUtensorMapFloatOOBfill);

EncodeFn get_encode() {
    static EncodeFn fn = nullptr;
    if (!fn) {
        void* p = nullptr;
        cudaDriverEntryPointQueryResult qr;
        cudaGetDriverEntryPoint("cuTensorMapEncodeTiled", &p, cudaEnableDefault, &qr);
        fn = (EncodeFn)p;
    }
    return fn;
}
CUtensorMap map2d(const void* ptr, uint64_t cols, uint64_t rows, uint32_t bc, uint32_t br, CUtensorMapSwizzle sw) {
    CUtensorMap m;
    cuuint64_t gd[2] = {cols, rows}, gs[1] = {cols * 2};
    cuuint32_t bx[2] = {bc, br}, es[2] = {1, 1};
    get_encode()(&m, CU_TENSOR_MAP_DATA_TYPE_BFLOAT16, 2, (void*)ptr, gd, gs, bx, es, CU_TENSOR_MAP_INTERLEAVE_NONE, sw,
                 CU_TENSOR_MAP_L2_PROMOTION_L2_128B, CU_TENSOR_MAP_FLOAT_OOB_FILL_NONE);
    return m;
}
CUtensorMap map3d32(const void* ptr, uint64_t cols, uint64_t rows, uint32_t br, uint32_t nb) {
    CUtensorMap m;
    cuuint64_t gd[3] = {32, rows, cols / 32}, gs[2] = {cols * 2, 64};
    cuuint32_t bx[3] = {32, br, nb}, es[3] = {1, 1, 1};
    get_encode()(&m, CU_TENSOR_MAP_DATA_TYPE_BFLOAT16, 3, (void*)ptr, gd, gs, bx, es, CU_TENSOR_MAP_INTERLEAVE_NONE, CU_TENSOR_MAP_SWIZZLE_64B,
                 CU_TENSOR_MAP_L2_PROMOTION_L2_128B, CU_TENSOR_MAP_FLOAT_OOB_FILL_NONE);
    return m;
}

template <typename... KArgs, typename... Args>
void launch(void (*kern)(KArgs...), int grid, int block, int smem, int cluster, bool pdl, Args... args) {
    cudaLaunchConfig_t cfg = {};
    cfg.gridDim = dim3(grid);
    cfg.blockDim = dim3(block);
    cfg.dynamicSmemBytes = smem;
    cfg.stream = cudaStreamPerThread;
    cudaLaunchAttribute at[2];
    int n = 0;
    if (cluster > 1) { at[n].id = cudaLaunchAttributeClusterDimension; at[n].val.clusterDim.x = cluster; at[n].val.clusterDim.y = 1; at[n].val.clusterDim.z = 1; n++; }
    if (pdl) { at[n].id = cudaLaunchAttributeProgrammaticStreamSerialization; at[n].val.programmaticStreamSerializationAllowed = 1; n++; }
    cfg.attrs = at;
    cfg.numAttrs = n;
    cudaLaunchKernelEx(&cfg, kern, KArgs(args)...);
}

template <typename T> void* sym(const T& s) { void* p = nullptr; cudaGetSymbolAddress(&p, s); return p; }

}

extern "C" void kernel_launch(void* const* d_in, const int* in_sizes, int n_in, void* d_out, int out_size) {
    const __nv_bfloat16* x = (const __nv_bfloat16*)d_in[0];
    const __nv_bfloat16* wq = (const __nv_bfloat16*)d_in[1];
    const __nv_bfloat16* wk = (const __nv_bfloat16*)d_in[2];
    const __nv_bfloat16* wv = (const __nv_bfloat16*)d_in[3];
    const __nv_bfloat16* wo = (const __nv_bfloat16*)d_in[4];
    const __nv_bfloat16* w1 = (const __nv_bfloat16*)d_in[6];
    const __nv_bfloat16* w2 = (const __nv_bfloat16*)d_in[7];

    constexpr int SM_QKV = GemmSmem<QKV_STAGES, EPI_QKV>::TOTAL, SM_QKV0 = GemmSmem<QKV_STAGES, EPI_QKV>::TOTAL_SELF;
    static_assert(SM_QKV0 <= 232448, "shared memory");
    constexpr int HALF_PLUS = 116736;
    constexpr int SM_WO = GemmSmem<WO_STAGES, EPI_RES>::TOTAL > HALF_PLUS ? GemmSmem<WO_STAGES, EPI_RES>::TOTAL : HALF_PLUS;
    constexpr int SM_FFN2 = GemmSmem<FFN2_STAGES, EPI_RES>::TOTAL > HALF_PLUS ? GemmSmem<FFN2_STAGES, EPI_RES>::TOTAL : HALF_PLUS;
    constexpr int SM_FFN1 = GemmSmem<FFN1_STAGES, EPI_FFN1>::TOTAL;
    cudaFuncSetAttribute(qkv_kernel<false>, cudaFuncAttributeMaxDynamicSharedMemorySize, SM_QKV);
    cudaFuncSetAttribute(qkv_kernel<true>, cudaFuncAttributeMaxDynamicSharedMemorySize, SM_QKV0);
    cudaFuncSetAttribute(res_gemm_kernel<8, WO_STAGES>, cudaFuncAttributeMaxDynamicSharedMemorySize, SM_WO);
    cudaFuncSetAttribute(ffn1_kernel, cudaFuncAttributeMaxDynamicSharedMemorySize, SM_FFN1);
    cudaFuncSetAttribute(res_gemm_kernel<28, FFN2_STAGES>, cudaFuncAttributeMaxDynamicSharedMemorySize, SM_FFN2);
    cudaFuncSetAttribute(attn_kernel, cudaFuncAttributeMaxDynamicSharedMemorySize, ATT_SMEM);
    cudaFuncSetAttribute(qkv_kernel<false>, cudaFuncAttributePreferredSharedMemoryCarveout, 100);
    cudaFuncSetAttribute(qkv_kernel<true>, cudaFuncAttributePreferredSharedMemoryCarveout, 100);
    cudaFuncSetAttribute(res_gemm_kernel<8, WO_STAGES>, cudaFuncAttributePreferredSharedMemoryCarveout, 100);
    cudaFuncSetAttribute(ffn1_kernel, cudaFuncAttributePreferredSharedMemoryCarveout, 100);
    cudaFuncSetAttribute(res_gemm_kernel<28, FFN2_STAGES>, cudaFuncAttributePreferredSharedMemoryCarveout, 100);
    cudaFuncSetAttribute(attn_kernel, cudaFuncAttributePreferredSharedMemoryCarveout, 100);

    void *q = sym(g_q), *o = sym(g_o), *x1 = sym(g_x1), *x2 = sym(g_x2), *x3 = sym(g_x3), *h = sym(g_h);
    float2* stats = (float2*)sym(g_stats);
    const void* xs[5] = {x, x1, x2, x3, d_out};

    const CUtensorMapSwizzle SW128 = CU_TENSOR_MAP_SWIZZLE_128B, SW64 = CU_TENSOR_MAP_SWIZZLE_64B;
    const CUtensorMap mWq = map3d32(wq, D_, D_, 64, 2);
    const CUtensorMap mWo = map2d(wo, D_, D_, 64, 64, SW128);
    const CUtensorMap mW1a = map3d32(w1, F_, D_, F1_BK, 4), mW1b = map3d32(w1, F_, D_, F1_BK, 3);
    const CUtensorMap mW2 = map2d(w2, D_, F_, 64, 64, SW128);
    const CUtensorMap mQ = map2d(q, D_, S_, 64, 64, SW128);
    const CUtensorMap mHst = map2d(h, F_, S_, 32, 16, SW64);
    CUtensorMap mXa[4], mXf[4], mXr[4], mXs[5];
    for (int i = 0; i < 4; i++) {
        mXa[i] = map2d(xs[i], D_, S_, 64, QKV_MC ? 64 : 128, SW128);
        mXf[i] = F1_BK == 64 ? map2d(xs[i], D_, S_, 64, 128, SW128) : map2d(xs[i], D_, S_, 32, 128, SW64);
        mXr[i] = map2d(xs[i], D_, S_, 64, 128, SW128);
    }
    for (int i = 0; i < 5; i++) mXs[i] = map2d(xs[i], D_, S_, 64, 64, SW128);
    const CUtensorMap mOa = map2d(o, D_, S_, 64, WO_MC ? 64 : 128, SW128);
    const CUtensorMap mHa = map2d(h, F_, S_, 64, F2_MC ? 64 : 128, SW128);

    for (int layer = 0; layer < 2; layer++) {
        const int xi = layer * 2;
        GemmParams p;
        p.wkv = wk; p.wv = wv;
        p.stats_in = stats + (size_t)xi * 8 * S_; p.stats_out = nullptr; p.tk = 1 + 5 * layer;
        if (layer == 0) launch(qkv_kernel<true>, 128, 544, SM_QKV0, QKV_MC ? 2 : 1, false, mXa[xi], mWq, mQ, p);
        else launch(qkv_kernel<false>, 128, 288, SM_QKV, QKV_MC ? 2 : 1, true, mXa[xi], mWq, mQ, p);
        launch(attn_kernel, layer == 0 ? 128 + SIDE_CTAS : 128, 512, ATT_SMEM, 1, true, wo, w1, w2, 2 + 5 * layer);
        p.stats_in = nullptr; p.stats_out = stats + (size_t)(xi + 1) * 8 * S_; p.tk = 3 + 5 * layer;
        launch(res_gemm_kernel<8, WO_STAGES>, 128, 288, SM_WO, WO_MC ? 2 : 1, true, mOa, mWo, mXr[xi], mXs[xi + 1], p);
        p.stats_in = stats + (size_t)(xi + 1) * 8 * S_; p.stats_out = nullptr; p.tk = 4 + 5 * layer;
        launch(ffn1_kernel, 128, F1_INLINE ? 256 : 288, SM_FFN1, F1_MC ? 2 : 1, true, mXf[xi + 1], mW1a, mW1b, mHst, p);
        p.stats_in = nullptr; p.stats_out = layer == 0 ? stats + (size_t)2 * 8 * S_ : nullptr; p.tk = 5 + 5 * layer;
        launch(res_gemm_kernel<28, FFN2_STAGES>, 128, 288, SM_FFN2, F2_MC ? 2 : 1, true, mHa, mW2, mXr[xi + 1], mXs[xi + 2], p);
    }
}
```

```cpp
#include <cuda_runtime.h>
#include <cuda_bf16.h>
#include <cuda.h>
#include <stdint.h>

#define F1_INLINE 0
#define QKV_MC 0
#define WO_MC 0
#define F2_MC 0
#define F1_MC 2
#define PREB 2
#define RES_WAIT0 0

namespace {

constexpr int S_ = 2048, D_ = 512, H_ = 32, F_ = 1792;

__device__ __align__(1024) __nv_bfloat16 g_q[S_ * D_];
__device__ __align__(1024) __nv_bfloat16 g_o[S_ * D_];
__device__ __align__(1024) __nv_bfloat16 g_x1[S_ * D_];
__device__ __align__(1024) __nv_bfloat16 g_x2[S_ * D_];
__device__ __align__(1024) __nv_bfloat16 g_x3[S_ * D_];
__device__ __align__(1024) __nv_bfloat16 g_h[S_ * F_];
__device__ __align__(1024) uint8_t g_kimg[S_ * 32];
__device__ __align__(1024) uint8_t g_vimg[(S_ / 16) * 768];
__device__ __align__(1024) float2 g_stats[4][8 * S_];
__device__ __align__(16) float g_cs_q[D_];
__device__ __align__(16) float g_cs_kv[32];
__device__ __align__(16) float g_cs_1[F_];
__device__ __align__(16) float g_kvmax[32];

#define TL(k, slot)

__device__ __forceinline__ uint32_t smem_u32(const void* p) { return (uint32_t)__cvta_generic_to_shared(p); }
__device__ __forceinline__ void mbar_init(uint32_t bar, uint32_t cnt) {
    asm volatile("mbarrier.init.shared::cta.b64 [%0], %1;" ::"r"(bar), "r"(cnt));
}
__device__ __forceinline__ void mbar_expect_tx(uint32_t bar, uint32_t bytes) {
    asm volatile("mbarrier.arrive.expect_tx.shared::cta.b64 _, [%0], %1;" ::"r"(bar), "r"(bytes) : "memory");
}
__device__ __forceinline__ void mbar_arrive(uint32_t bar) {
    asm volatile("mbarrier.arrive.shared::cta.b64 _, [%0];" ::"r"(bar) : "memory");
}
__device__ __forceinline__ void mbar_arrive_remote(uint32_t bar, uint32_t cta) {
    asm volatile("{\n.reg .b32 ra;\nmapa.shared::cluster.u32 ra, %0, %1;\nmbarrier.arrive.shared::cluster.b64 _, [ra];\n}" ::"r"(bar), "r"(cta) : "memory");
}
__device__ __forceinline__ void mbar_wait(uint32_t bar, uint32_t parity) {
    asm volatile("{\n.reg .pred p;\nWAIT_%=:\nmbarrier.try_wait.parity.shared::cta.b64 p, [%0], %1;\n@p bra DONE_%=;\nbra WAIT_%=;\nDONE_%=:\n}" ::"r"(bar), "r"(parity) : "memory");
}
__device__ __forceinline__ void bulk_load(uint32_t dst, const void* src, uint32_t bytes, uint32_t bar) {
    asm volatile("cp.async.bulk.shared::cluster.global.mbarrier::complete_tx::bytes [%0], [%1], %2, [%3];" ::"r"(dst), "l"(src), "r"(bytes), "r"(bar) : "memory");
}
__device__ __forceinline__ void tma2d(uint32_t dst, const CUtensorMap* m, int c0, int c1, uint32_t bar) {
    asm volatile("cp.async.bulk.tensor.2d.shared::cluster.global.mbarrier::complete_tx::bytes [%0], [%1, {%3, %4}], [%2];" ::"r"(dst), "l"(m), "r"(bar), "r"(c0), "r"(c1) : "memory");
}
__device__ __forceinline__ void tma2d_mc(uint32_t dst, const CUtensorMap* m, int c0, int c1, uint32_t bar, uint16_t mask) {
    asm volatile("cp.async.bulk.tensor.2d.shared::cluster.global.mbarrier::complete_tx::bytes.multicast::cluster [%0], [%1, {%3, %4}], [%2], %5;" ::"r"(dst), "l"(m), "r"(bar), "r"(c0), "r"(c1), "h"(mask) : "memory");
}
__device__ __forceinline__ void tma3d(uint32_t dst, const CUtensorMap* m, int c0, int c1, int c2, uint32_t bar) {
    asm volatile("cp.async.bulk.tensor.3d.shared::cluster.global.mbarrier::complete_tx::bytes [%0], [%1, {%3, %4, %5}], [%2];" ::"r"(dst), "l"(m), "r"(bar), "r"(c0), "r"(c1), "r"(c2) : "memory");
}
__device__ __forceinline__ void tma3d_mc(uint32_t dst, const CUtensorMap* m, int c0, int c1, int c2, uint32_t bar, uint16_t mask) {
    asm volatile("cp.async.bulk.tensor.3d.shared::cluster.global.mbarrier::complete_tx::bytes.multicast::cluster [%0], [%1, {%3, %4, %5}], [%2], %6;" ::"r"(dst), "l"(m), "r"(bar), "r"(c0), "r"(c1), "r"(c2), "h"(mask) : "memory");
}
__device__ __forceinline__ void tma2d_store(const CUtensorMap* m, uint32_t src, int c0, int c1) {
    asm volatile("cp.async.bulk.tensor.2d.global.shared::cta.bulk_group [%0, {%2, %3}], [%1];" ::"l"(m), "r"(src), "r"(c0), "r"(c1) : "memory");
}
__device__ __forceinline__ void tma3d_store(const CUtensorMap* m, uint32_t src, int c0, int c1, int c2) {
    asm volatile("cp.async.bulk.tensor.3d.global.shared::cta.bulk_group [%0, {%2, %3, %4}], [%1];" ::"l"(m), "r"(src), "r"(c0), "r"(c1), "r"(c2) : "memory");
}
__device__ __forceinline__ void bulk_commit() { asm volatile("cp.async.bulk.commit_group;" ::: "memory"); }
__device__ __forceinline__ void bulk_wait_read() { asm volatile("cp.async.bulk.wait_group.read 0;" ::: "memory"); }
__device__ __forceinline__ void prefetch_tmap(const CUtensorMap* m) { asm volatile("prefetch.tensormap [%0];" ::"l"(m) : "memory"); }
__device__ __forceinline__ void fence_async_smem() { asm volatile("fence.proxy.async.shared::cta;" ::: "memory"); }
__device__ __forceinline__ void fence_mbar_init() { asm volatile("fence.mbarrier_init.release.cluster;" ::: "memory"); }
__device__ __forceinline__ void cluster_sync() { asm volatile("barrier.cluster.arrive.release.aligned;\nbarrier.cluster.wait.acquire.aligned;" ::: "memory"); }
__device__ __forceinline__ uint32_t cluster_rank() { uint32_t r; asm volatile("mov.u32 %0, %%cluster_ctarank;" : "=r"(r)); return r; }
__device__ __forceinline__ void pdl_wait() { asm volatile("griddepcontrol.wait;" ::: "memory"); }
__device__ __forceinline__ void pdl_launch() { asm volatile("griddepcontrol.launch_dependents;" ::: "memory"); }
__device__ __forceinline__ bool elect_one() {
    uint32_t p;
    asm volatile("{\n.reg .pred p;\nelect.sync _|p, 0xffffffff;\nselp.b32 %0, 1, 0, p;\n}" : "=r"(p));
    return p != 0;
}
__device__ __forceinline__ void named_bar(int id, int n) { asm volatile("bar.sync %0, %1;" ::"r"(id), "r"(n) : "memory"); }

__device__ __forceinline__ void wg_fence() { asm volatile("wgmma.fence.sync.aligned;" ::: "memory"); }
__device__ __forceinline__ void wg_commit() { asm volatile("wgmma.commit_group.sync.aligned;" ::: "memory"); }
template <int N> __device__ __forceinline__ void wg_wait() { asm volatile("wgmma.wait_group.sync.aligned %0;" ::"n"(N) : "memory"); }
template <int N> __device__ __forceinline__ void fence_regs(float (&d)[N]) {
#pragma unroll
    for (int i = 0; i < N; i++) asm volatile("" : "+f"(d[i])::"memory");
}
__device__ __forceinline__ uint64_t mkdesc(uint32_t addr, uint32_t lbo, uint32_t sbo, uint32_t swz) {
    uint64_t d = 0;
    d |= (uint64_t)((addr & 0x3FFFF) >> 4);
    d |= (uint64_t)((lbo & 0x3FFFF) >> 4) << 16;
    d |= (uint64_t)((sbo & 0x3FFFF) >> 4) << 32;
    d |= (uint64_t)swz << 62;
    return d;
}
__device__ __forceinline__ void ldsm_x4(uint32_t& r0, uint32_t& r1, uint32_t& r2, uint32_t& r3, uint32_t addr) {
    asm volatile("ldmatrix.sync.aligned.m8n8.x4.shared.b16 {%0,%1,%2,%3}, [%4];" : "=r"(r0), "=r"(r1), "=r"(r2), "=r"(r3) : "r"(addr) : "memory");
}
__device__ __forceinline__ void stsm_x4(uint32_t addr, uint32_t r0, uint32_t r1, uint32_t r2, uint32_t r3) {
    asm volatile("stmatrix.sync.aligned.m8n8.x4.shared.b16 [%0], {%1,%2,%3,%4};" ::"r"(addr), "r"(r0), "r"(r1), "r"(r2), "r"(r3) : "memory");
}
__device__ __forceinline__ void ldsm_x4_t(uint32_t& r0, uint32_t& r1, uint32_t& r2, uint32_t& r3, uint32_t addr) {
    asm volatile("ldmatrix.sync.aligned.m8n8.x4.trans.shared.b16 {%0,%1,%2,%3}, [%4];" : "=r"(r0), "=r"(r1), "=r"(r2), "=r"(r3) : "r"(addr) : "memory");
}
__device__ __forceinline__ void hmma(float (&d)[4], uint32_t a0, uint32_t a1, uint32_t a2, uint32_t a3, uint32_t b0, uint32_t b1) {
    asm volatile("mma.sync.aligned.m16n8k16.row.col.f32.bf16.bf16.f32 {%0,%1,%2,%3}, {%4,%5,%6,%7}, {%8,%9}, {%0,%1,%2,%3};"
                 : "+f"(d[0]), "+f"(d[1]), "+f"(d[2]), "+f"(d[3]) : "r"(a0), "r"(a1), "r"(a2), "r"(a3), "r"(b0), "r"(b1));
}
__device__ __forceinline__ uint32_t pack_bf16(float lo, float hi) {
    uint32_t r;
    asm("cvt.rn.bf16x2.f32 %0, %1, %2;" : "=r"(r) : "f"(hi), "f"(lo));
    return r;
}
__device__ __forceinline__ float bf_lo(uint32_t v) { return __uint_as_float(v << 16); }
__device__ __forceinline__ float bf_hi(uint32_t v) { return __uint_as_float(v & 0xFFFF0000u); }

#define WG_REGS_4(o) "+f"(d[o]), "+f"(d[o + 1]), "+f"(d[o + 2]), "+f"(d[o + 3])
#define WG_REGS_8(o) WG_REGS_4(o), WG_REGS_4(o + 4)
#define WG_REGS_16(o) WG_REGS_8(o), WG_REGS_8(o + 8)
#define WG_REGS_32(o) WG_REGS_16(o), WG_REGS_16(o + 16)

__device__ __forceinline__ void wgmma_ss_n80_tb(float (&d)[40], uint64_t dA, uint64_t dB, int sc) {
    asm volatile("{\n.reg .pred p;\nsetp.ne.b32 p, %42, 0;\n"
                 "wgmma.mma_async.sync.aligned.m64n80k16.f32.bf16.bf16 "
                 "{%0,%1,%2,%3,%4,%5,%6,%7,%8,%9,%10,%11,%12,%13,%14,%15,%16,%17,%18,%19,%20,%21,%22,%23,%24,%25,%26,%27,%28,%29,%30,%31,"
                 "%32,%33,%34,%35,%36,%37,%38,%39}, %40, %41, p, 1, 1, 0, 1;\n}\n"
                 : WG_REGS_32(0), WG_REGS_8(32) : "l"(dA), "l"(dB), "r"(sc));
}
__device__ __forceinline__ void wgmma_ss_n64_tb(float (&d)[32], uint64_t dA, uint64_t dB, int sc) {
    asm volatile("{\n.reg .pred p;\nsetp.ne.b32 p, %34, 0;\n"
                 "wgmma.mma_async.sync.aligned.m64n64k16.f32.bf16.bf16 "
                 "{%0,%1,%2,%3,%4,%5,%6,%7,%8,%9,%10,%11,%12,%13,%14,%15,%16,%17,%18,%19,%20,%21,%22,%23,%24,%25,%26,%27,%28,%29,%30,%31}, "
                 "%32, %33, p, 1, 1, 0, 1;\n}\n"
                 : WG_REGS_32(0) : "l"(dA), "l"(dB), "r"(sc));
}
__device__ __forceinline__ void wgmma_ss_n224_tb(float (&d)[112], uint64_t dA, uint64_t dB, int sc) {
    asm volatile("{\n.reg .pred p;\nsetp.ne.b32 p, %114, 0;\n"
                 "wgmma.mma_async.sync.aligned.m64n224k16.f32.bf16.bf16 "
                 "{%0,%1,%2,%3,%4,%5,%6,%7,%8,%9,%10,%11,%12,%13,%14,%15,%16,%17,%18,%19,%20,%21,%22,%23,%24,%25,%26,%27,%28,%29,%30,%31,"
                 "%32,%33,%34,%35,%36,%37,%38,%39,%40,%41,%42,%43,%44,%45,%46,%47,%48,%49,%50,%51,%52,%53,%54,%55,%56,%57,%58,%59,%60,%61,%62,%63,"
                 "%64,%65,%66,%67,%68,%69,%70,%71,%72,%73,%74,%75,%76,%77,%78,%79,%80,%81,%82,%83,%84,%85,%86,%87,%88,%89,%90,%91,%92,%93,%94,%95,"
                 "%96,%97,%98,%99,%100,%101,%102,%103,%104,%105,%106,%107,%108,%109,%110,%111}, "
                 "%112, %113, p, 1, 1, 0, 1;\n}\n"
                 : WG_REGS_32(0), WG_REGS_32(32), WG_REGS_32(64), WG_REGS_16(96) : "l"(dA), "l"(dB), "r"(sc));
}
template <int BN> __device__ __forceinline__ void wgmma_ss_tb(float (&d)[BN / 2], uint64_t dA, uint64_t dB, int sc) {
    if constexpr (BN == 64) wgmma_ss_n64_tb(d, dA, dB, sc);
    else if constexpr (BN == 80) wgmma_ss_n80_tb(d, dA, dB, sc);
    else wgmma_ss_n224_tb(d, dA, dB, sc);
}
__device__ __forceinline__ void wgmma_rs_n64_tb(float (&d)[32], uint32_t a, uint64_t dB, int sc) {
    asm volatile("{\n.reg .pred p;\nsetp.ne.b32 p, %34, 0;\n"
                 "wgmma.mma_async.sync.aligned.m64n64k16.f32.bf16.bf16 "
                 "{%0,%1,%2,%3,%4,%5,%6,%7,%8,%9,%10,%11,%12,%13,%14,%15,%16,%17,%18,%19,%20,%21,%22,%23,%24,%25,%26,%27,%28,%29,%30,%31}, "
                 "{%32,%32,%32,%32}, %33, p, 1, 1, 1;\n}\n"
                 : WG_REGS_32(0) : "r"(a), "l"(dB), "r"(sc));
}
__device__ __forceinline__ void wgmma_rs_n80_tb(float (&d)[40], uint32_t a, uint64_t dB, int sc) {
    asm volatile("{\n.reg .pred p;\nsetp.ne.b32 p, %42, 0;\n"
                 "wgmma.mma_async.sync.aligned.m64n80k16.f32.bf16.bf16 "
                 "{%0,%1,%2,%3,%4,%5,%6,%7,%8,%9,%10,%11,%12,%13,%14,%15,%16,%17,%18,%19,%20,%21,%22,%23,%24,%25,%26,%27,%28,%29,%30,%31,"
                 "%32,%33,%34,%35,%36,%37,%38,%39}, {%40,%40,%40,%40}, %41, p, 1, 1, 1;\n}\n"
                 : WG_REGS_32(0), WG_REGS_8(32) : "r"(a), "l"(dB), "r"(sc));
}
template <int BN> __device__ __forceinline__ void wgmma_rs_ones(float (&d)[BN / 2], uint64_t dB, int sc) {
    if constexpr (BN == 80) wgmma_rs_n80_tb(d, 0x3F803F80u, dB, sc);
    else if constexpr (BN == 64) wgmma_rs_n64_tb(d, 0x3F803F80u, dB, sc);
}
__device__ __forceinline__ void wgmma_rs_n64_z(float (&d)[32], uint32_t a0, uint32_t a1, uint32_t a2, uint32_t a3, uint64_t dB) {
    asm volatile("{\n.reg .pred p;\nsetp.ne.b32 p, 0, 0;\n"
                 "wgmma.mma_async.sync.aligned.m64n64k16.f32.bf16.bf16 "
                 "{%0,%1,%2,%3,%4,%5,%6,%7,%8,%9,%10,%11,%12,%13,%14,%15,%16,%17,%18,%19,%20,%21,%22,%23,%24,%25,%26,%27,%28,%29,%30,%31}, "
                 "{%32,%33,%34,%35}, %36, p, 1, 1, 0;\n}\n"
                 : "=f"(d[0]), "=f"(d[1]), "=f"(d[2]), "=f"(d[3]), "=f"(d[4]), "=f"(d[5]), "=f"(d[6]), "=f"(d[7]),
                   "=f"(d[8]), "=f"(d[9]), "=f"(d[10]), "=f"(d[11]), "=f"(d[12]), "=f"(d[13]), "=f"(d[14]), "=f"(d[15]),
                   "=f"(d[16]), "=f"(d[17]), "=f"(d[18]), "=f"(d[19]), "=f"(d[20]), "=f"(d[21]), "=f"(d[22]), "=f"(d[23]),
                   "=f"(d[24]), "=f"(d[25]), "=f"(d[26]), "=f"(d[27]), "=f"(d[28]), "=f"(d[29]), "=f"(d[30]), "=f"(d[31])
                 : "r"(a0), "r"(a1), "r"(a2), "r"(a3), "l"(dB));
}
__device__ __forceinline__ void wgmma_rs_n24_tb(float (&d)[12], uint32_t a0, uint32_t a1, uint32_t a2, uint32_t a3, uint64_t dB) {
    asm volatile("{\n.reg .pred p;\nsetp.eq.b32 p, 0, 0;\n"
                 "wgmma.mma_async.sync.aligned.m64n24k16.f32.bf16.bf16 "
                 "{%0,%1,%2,%3,%4,%5,%6,%7,%8,%9,%10,%11}, {%12,%13,%14,%15}, %16, p, 1, 1, 1;\n}\n"
                 : WG_REGS_8(0), WG_REGS_4(8) : "r"(a0), "r"(a1), "r"(a2), "r"(a3), "l"(dB));
}

constexpr int SIDE_CTAS = 4;
__device__ __forceinline__ void side_job(int cta, float* red  , const __nv_bfloat16* __restrict__ wo,
                                         const __nv_bfloat16* __restrict__ w1, const __nv_bfloat16* __restrict__ w2) {
    const int tid = threadIdx.x, warp = tid >> 5, lane = tid & 31;
    for (int line = cta * 512 + tid; line < 18432; line += SIDE_CTAS * 512) {
        const char* p = line < 4096 ? (const char*)wo + (size_t)line * 128 : (const char*)w2 + (size_t)(line - 4096) * 128;
        asm volatile("prefetch.global.L2 [%0];" ::"l"(p));
    }
    const int rg = lane >> 3, c8 = lane & 7;
    for (int slab = cta; slab < F_ / 64; slab += SIDE_CTAS) {
        const __nv_bfloat16* base = w1 + slab * 64 + c8 * 8;
        uint4 v[8];
#pragma unroll
        for (int i = 0; i < 8; i++) v[i] = __ldg((const uint4*)(base + (size_t)(warp * 32 + rg + 4 * i) * F_));
        float acc[8];
#pragma unroll
        for (int i = 0; i < 8; i++) acc[i] = 0.f;
#pragma unroll
        for (int i = 0; i < 8; i++) {
            acc[0] += bf_lo(v[i].x); acc[1] += bf_hi(v[i].x); acc[2] += bf_lo(v[i].y); acc[3] += bf_hi(v[i].y);
            acc[4] += bf_lo(v[i].z); acc[5] += bf_hi(v[i].z); acc[6] += bf_lo(v[i].w); acc[7] += bf_hi(v[i].w);
        }
#pragma unroll
        for (int i = 0; i < 8; i++) {
            acc[i] += __shfl_xor_sync(0xffffffffu, acc[i], 8);
            acc[i] += __shfl_xor_sync(0xffffffffu, acc[i], 16);
        }
        if (rg == 0) {
#pragma unroll
            for (int i = 0; i < 8; i++) red[warp * 64 + c8 * 8 + i] = acc[i];
        }
        __syncthreads();
        if (tid < 64) {
            float s = 0.f;
#pragma unroll
            for (int i = 0; i < 16; i++) s += red[i * 64 + tid];
            g_cs_1[slab * 64 + tid] = s;
        }
        __syncthreads();
    }
}

enum { EPI_QKV = 0, EPI_RES = 1, EPI_FFN1 = 2 };

struct GemmParams {
    const float2* stats_in;
    float2* stats_out;
    const __nv_bfloat16* wkv;
    const __nv_bfloat16* wv;
    int tk;
};

template <int BK_, int NBLK> struct Geo {
    static constexpr int BK = BK_, A_BYTES = 128 * BK * 2, A_SWZ = BK == 64 ? 1 : 2, A_SBO = BK * 16;
    static constexpr int BLK = BK * 64;
    static constexpr int B_BYTES = NBLK * BLK, B_SWZ = 2, B_LBO = BLK, B_SBO = 512, B_KSTEP = 1024;
};
template <> struct Geo<64, 0> {
    static constexpr int BK = 64, A_BYTES = 128 * 128, A_SWZ = 1, A_SBO = 1024, BLK = 8192;
    static constexpr int B_BYTES = 64 * 128, B_SWZ = 1, B_LBO = 8192, B_SBO = 1024, B_KSTEP = 2048;
};
#define F1_BK 32
template <int EPI> struct EpiGeo;
template <> struct EpiGeo<EPI_QKV> { using G = Geo<64, 3>; };
template <> struct EpiGeo<EPI_RES> { using G = Geo<64, 0>; };
template <> struct EpiGeo<EPI_FFN1> { using G = Geo<F1_BK, 7>; };

template <int STAGES, int EPI> struct GemmSmem {
    using G = typename EpiGeo<EPI>::G;
    static constexpr int STAGE = G::A_BYTES + G::B_BYTES;
    static constexpr int AUX_OFF = STAGES * STAGE;
    static constexpr int TOTAL = AUX_OFF + 1152;
    static constexpr int TOTAL_SELF = AUX_OFF + 704 + 1024 + 1280;
};

struct RowStatRaw { float2 a0, a1, b0, b1; };
__device__ __forceinline__ RowStatRaw load_row_stats(const float2* __restrict__ st, int row0, int c) {
    RowStatRaw r;
    r.a0 = st[(2 * c) * S_ + row0]; r.a1 = st[(2 * c + 1) * S_ + row0];
    r.b0 = st[(2 * c) * S_ + row0 + 8]; r.b1 = st[(2 * c + 1) * S_ + row0 + 8];
    return r;
}
__device__ __forceinline__ void finish_row_stats(const RowStatRaw& r, float& mean0, float& rstd0, float& mean1, float& rstd1) {
    float sa = r.a0.x + r.a1.x, sb = r.b0.x + r.b1.x;
    sa += __shfl_xor_sync(0xffffffffu, sa, 1); sa += __shfl_xor_sync(0xffffffffu, sa, 2);
    sb += __shfl_xor_sync(0xffffffffu, sb, 1); sb += __shfl_xor_sync(0xffffffffu, sb, 2);
    mean0 = sa * 0.125f; mean1 = sb * 0.125f;
    float ma = r.a0.y + r.a1.y + 64.f * ((r.a0.x - mean0) * (r.a0.x - mean0) + (r.a1.x - mean0) * (r.a1.x - mean0));
    float mb = r.b0.y + r.b1.y + 64.f * ((r.b0.x - mean1) * (r.b0.x - mean1) + (r.b1.x - mean1) * (r.b1.x - mean1));
    ma += __shfl_xor_sync(0xffffffffu, ma, 1); ma += __shfl_xor_sync(0xffffffffu, ma, 2);
    mb += __shfl_xor_sync(0xffffffffu, mb, 1); mb += __shfl_xor_sync(0xffffffffu, mb, 2);
    rstd0 = 1.0f / sqrtf(ma * (1.f / 512.f) + 1e-5f);
    rstd1 = 1.0f / sqrtf(mb * (1.f / 512.f) + 1e-5f);
}

template <int BN, int KB, int STAGES, int EPI, int MC, bool SELF = false>
__device__ __forceinline__ void gemm_body(const CUtensorMap* mapA, const CUtensorMap* mapB, const CUtensorMap* mapB2, const CUtensorMap* mapR,
                                          const CUtensorMap* mapC, const GemmParams& prm, int tile_m, int tile_n, uint8_t* smem_raw) {
    using SM = GemmSmem<STAGES, EPI>;
    using G = typename SM::G;
    constexpr bool XKV = BN == 80;
    constexpr int TN = EPI == EPI_QKV ? 64 : BN;
    pdl_launch();
    const uint32_t sbase = smem_u32(smem_raw);
    if (sbase & 1023) __trap();
    uint8_t* sgen = smem_raw;
    const uint32_t bar_full = sbase + SM::AUX_OFF, bar_empty = bar_full + 8 * STAGES;
    float* s_cs = (float*)(sgen + SM::AUX_OFF + 256);
    float* s_row = (float*)(sgen + SM::AUX_OFF + 704);
    float* s_red = (float*)(sgen + SM::AUX_OFF + 640);
    const int tid = threadIdx.x, lane = tid & 31;
    const int warp = __shfl_sync(0xffffffffu, tid >> 5, 0);
    const uint32_t rank = MC ? cluster_rank() : 0;
    if (tid == 0) TL(prm.tk, 0);

    constexpr bool INLINE_PROD = EPI == EPI_FFN1 && F1_INLINE;
    constexpr int PWARP = INLINE_PROD ? 0 : 8;
    if (warp == PWARP && elect_one()) {
        prefetch_tmap(mapB); prefetch_tmap(mapA); prefetch_tmap(mapC);
        for (int s = 0; s < STAGES; s++) { mbar_init(bar_full + 8 * s, 1); mbar_init(bar_empty + 8 * s, MC ? 4 : 2); }
        fence_mbar_init();
    }
    __syncthreads();
    if (MC) cluster_sync();

    const int m0 = tile_m * 128, n0 = tile_n * TN;
    constexpr uint32_t STAGE_TX = G::A_BYTES + (EPI == EPI_QKV ? 2 * G::BLK : G::B_BYTES);
    auto loadB = [&](int kb, int s) {
        const uint32_t dst = sbase + s * SM::STAGE + G::A_BYTES, bar = bar_full + 8 * s;
        if constexpr (EPI == EPI_RES) {
            tma2d(dst, mapB, n0, kb * 64, bar);
        } else if constexpr (EPI == EPI_QKV) {
            tma3d(dst, mapB, 0, kb * G::BK, tile_n * 2, bar);
        } else {
            if constexpr (MC == 2) {
                if (rank == 0) tma3d_mc(dst, mapB, 0, kb * G::BK, tile_n * 7, bar, 3);
                else tma3d_mc(dst + 4 * G::BLK, mapB2, 0, kb * G::BK, tile_n * 7 + 4, bar, 3);
            } else {
                tma3d(dst, mapB, 0, kb * G::BK, tile_n * 7, bar);
                tma3d(dst + 4 * G::BLK, mapB2, 0, kb * G::BK, tile_n * 7 + 4, bar);
            }
        }
    };
    auto loadA = [&](int kb, int s) {
        const uint32_t dst = sbase + s * SM::STAGE, bar = bar_full + 8 * s;
        if constexpr (MC == 1) tma2d_mc(dst + rank * (G::A_BYTES / 2), mapA, kb * G::BK, m0 + rank * 64, bar, 3);
        else tma2d(dst, mapA, kb * G::BK, m0, bar);
    };
    constexpr int PRE = STAGES < KB ? STAGES : KB;
#define F1_LAG 2
    constexpr int LAG = F1_LAG;
    constexpr int PRE_B = PRE < PREB ? PRE : PREB;
    auto prologue_loads = [&]() {
        if (elect_one()) {
#pragma unroll
            for (int kb = 0; kb < PRE; kb++) mbar_expect_tx(bar_full + 8 * kb, STAGE_TX);
#pragma unroll
            for (int kb = 0; kb < PRE_B; kb++) loadB(kb, kb);
        }
        if (!SELF) pdl_wait();
        if (elect_one()) {
#pragma unroll
            for (int kb = 0; kb < PRE; kb++) {
                loadA(kb, kb);
                if (kb + PRE_B < PRE) loadB(kb + PRE_B, kb + PRE_B);
            }
            if constexpr (EPI == EPI_RES && KB < STAGES) {
                mbar_expect_tx(bar_full + 8 * KB, 16384);
                tma2d(sbase + KB * SM::STAGE, mapR, n0, m0, bar_full + 8 * KB);
            }
        }
    };
    if (SELF && warp > 8) {
        static_assert(!SELF || (STAGES >= KB && EPI == EPI_QKV), "SELF needs every k block resident");
        const int t = tid - 288;
        float ss[4] = {0.f, 0.f, 0.f, 0.f}, sq[4] = {0.f, 0.f, 0.f, 0.f};
        const bool csw = (warp >> 2) == 3;
        float csum[BN / 2];
        const uint64_t dB0 = mkdesc(sbase + G::A_BYTES, G::B_LBO, G::B_SBO, G::B_SWZ);
        if constexpr (XKV) named_bar(6, 512);
#pragma unroll 1
        for (int kb = 0; kb < KB; kb++) {
            mbar_wait(bar_full + 8 * kb, 0);
            if (csw) {
                const uint64_t dB = dB0 + (uint64_t)(kb * (SM::STAGE >> 4));
                wg_fence();
#pragma unroll
                for (int k = 0; k < G::BK / 16; k++) {
                    if constexpr (SELF) wgmma_rs_ones<BN>(csum, dB + (uint64_t)(k * (G::B_KSTEP >> 4)), (kb | k) != 0);
                }
                wg_commit();
            }
            const uint32_t arow = sbase + kb * SM::STAGE + (t >> 1) * 128;
            uint32_t w[4][4];
#pragma unroll
            for (int j = 0; j < 4; j++)
                asm volatile("ld.shared.v4.u32 {%0,%1,%2,%3}, [%4];" : "=r"(w[j][0]), "=r"(w[j][1]), "=r"(w[j][2]), "=r"(w[j][3])
                             : "r"(arow + (((2 * j + (t & 1) + 2 * ((t >> 1) & 3)) & 7) << 4)));
#pragma unroll
            for (int j = 0; j < 4; j++)
#pragma unroll
                for (int i = 0; i < 4; i++) {
                    const float lo = bf_lo(w[j][i]), hi = bf_hi(w[j][i]);
                    ss[i] += lo + hi;
                    sq[i] = fmaf(lo, lo, fmaf(hi, hi, sq[i]));
                }
        }
        float tsum = (ss[0] + ss[1]) + (ss[2] + ss[3]), tsq = (sq[0] + sq[1]) + (sq[2] + sq[3]);
        tsum += __shfl_xor_sync(0xffffffffu, tsum, 1);
        tsq += __shfl_xor_sync(0xffffffffu, tsq, 1);
        if ((t & 1) == 0) {
            const float md = tsum * (1.f / 512.f);
            const float var = fmaxf(tsq * (1.f / 512.f) - md * md, 0.f);
            *(float2*)(s_row + t) = make_float2(md, 1.0f / sqrtf(var + 1e-5f));
        }
        if (csw) {
            wg_wait<0>();
            fence_regs(csum);
            if (warp == 12 && lane < 4) {
#pragma unroll
                for (int j = 0; j < BN / 8; j++) {
                    const float2 v = make_float2(csum[4 * j], csum[4 * j + 1]);
                    *(float2*)(s_cs + 8 * j + 2 * lane) = v;
                    if (tile_m == 0) {
                        if (j < 8) *(float2*)(g_cs_q + n0 + 8 * j + 2 * lane) = v;
                        else *(float2*)(g_cs_kv + tile_n * 16 + 8 * (j - 8) + 2 * lane) = v;
                    }
                }
            }
        }
        named_bar(4, 512);
    } else if (!INLINE_PROD && warp == 8) {
        prologue_loads();
        int s = PRE % STAGES, ph = (PRE / STAGES) & 1;
#pragma unroll 1
        for (int kb = PRE; kb < KB; kb++) {
            mbar_wait(bar_empty + 8 * s, ph ^ 1);
            if (elect_one()) {
                mbar_expect_tx(bar_full + 8 * s, STAGE_TX);
                loadB(kb, s);
                loadA(kb, s);
            }
            if (++s == STAGES) { s = 0; ph ^= 1; }
        }
        if constexpr (EPI == EPI_RES && KB >= STAGES) {
            mbar_wait(bar_empty + 8 * s, ph ^ 1);
            if (elect_one()) {
                mbar_expect_tx(bar_full + 8 * s, 16384);
                tma2d(sbase + s * SM::STAGE, mapR, n0, m0, bar_full + 8 * s);
            }
        }
    } else {
        if (INLINE_PROD && warp == 0) prologue_loads();
        const int wg = warp >> 2, g = lane >> 2, c = lane & 3;
        const int rloc = wg * 64 + (warp & 3) * 16 + g;
        const int row0 = m0 + rloc;
        float mean0 = 0.f, rstd0 = 1.f, mean1 = 0.f, rstd1 = 1.f;
        if constexpr (XKV) {
            static_assert(!XKV || STAGES >= KB, "the K / V weight block must stay resident");
            const __nv_bfloat16* wsrc = tile_n == 0 ? prm.wkv : prm.wv;
            uint4 v[4];
#pragma unroll
            for (int i = 0; i < 4; i++) v[i] = __ldg((const uint4*)wsrc + tid + 256 * i);
#pragma unroll
            for (int i = 0; i < 4; i++) {
                const int idx = tid + 256 * i, k = idx >> 1, kr = k & 63;
                const uint32_t dst = sbase + (k >> 6) * SM::STAGE + G::A_BYTES + 2 * G::BLK + kr * 64 + (((idx & 1) ^ ((kr >> 1) & 3)) << 4);
                asm volatile("st.shared.v4.u32 [%0], {%1,%2,%3,%4};" ::"r"(dst), "r"(v[i].x), "r"(v[i].y), "r"(v[i].z), "r"(v[i].w) : "memory");
            }
            fence_async_smem();
            if constexpr (SELF) named_bar(6, 512); else named_bar(6, 256);
        }
        RowStatRaw raw;
        float csv = 0.f;
        float2 cskv[2] = {make_float2(0.f, 0.f), make_float2(0.f, 0.f)};
        auto ln_inputs = [&]() {
            pdl_wait();
            if constexpr (EPI != EPI_RES) {
                raw = load_row_stats(prm.stats_in, row0, c);
                const float* cs = EPI == EPI_FFN1 ? g_cs_1 + n0 : g_cs_q + n0;
                if (tid < TN) csv = cs[tid];
                if constexpr (XKV) {
                    cskv[0] = *(const float2*)(g_cs_kv + tile_n * 16 + 2 * c);
                    cskv[1] = *(const float2*)(g_cs_kv + tile_n * 16 + 8 + 2 * c);
                }
            }
        };
        if (!SELF) ln_inputs();
        float acc[BN / 2];
        const uint64_t dA0 = mkdesc(sbase + wg * (G::A_BYTES / 2), 16, G::A_SBO, G::A_SWZ);
        const uint64_t dB0 = mkdesc(sbase + G::A_BYTES, G::B_LBO, G::B_SBO, G::B_SWZ);
        int s = 0, ph = 0;
#pragma unroll 1
        for (int kb = 0; kb < KB; kb++) {
            mbar_wait(bar_full + 8 * s, ph);
            const uint64_t dA = dA0 + (uint64_t)(s * (SM::STAGE >> 4)), dB = dB0 + (uint64_t)(s * (SM::STAGE >> 4));
            wg_fence();
#pragma unroll
            for (int k = 0; k < G::BK / 16; k++) wgmma_ss_tb<BN>(acc, dA + (uint64_t)(k * 2), dB + (uint64_t)(k * (G::B_KSTEP >> 4)), (kb | k) != 0);
            wg_commit();
            if constexpr (EPI == EPI_RES && RES_WAIT0) {
                wg_wait<0>();
                if ((warp & 3) == 0 && elect_one()) {
                    if (MC) { mbar_arrive_remote(bar_empty + 8 * s, 0); mbar_arrive_remote(bar_empty + 8 * s, 1); }
                    else mbar_arrive(bar_empty + 8 * s);
                }
            } else if (kb > 0) {
                wg_wait<1>();
                const int sp = s == 0 ? STAGES - 1 : s - 1;
                if ((warp & 3) == 0 && elect_one()) {
                    if (MC) { mbar_arrive_remote(bar_empty + 8 * sp, 0); mbar_arrive_remote(bar_empty + 8 * sp, 1); }
                    else mbar_arrive(bar_empty + 8 * sp);
                }
                if (INLINE_PROD && warp == 0 && kb >= LAG && kb - LAG + STAGES < KB) {
                    const int sq = LAG == 1 ? sp : (sp == 0 ? STAGES - 1 : sp - 1);
                    mbar_wait(bar_empty + 8 * sq, ((kb - LAG) / STAGES) & 1);
                    if (elect_one()) {
                        mbar_expect_tx(bar_full + 8 * sq, STAGE_TX);
                        loadB(kb - LAG + STAGES, sq);
                        loadA(kb - LAG + STAGES, sq);
                    }
                }
            }
            if (++s == STAGES) { s = 0; ph ^= 1; }
        }
        if constexpr (SELF) {
            named_bar(4, 512);
            const float2 r0 = *(const float2*)(s_row + 2 * rloc), r1 = *(const float2*)(s_row + 2 * rloc + 16);
            mean0 = r0.x; rstd0 = r0.y; mean1 = r1.x; rstd1 = r1.y;
        } else if constexpr (EPI != EPI_RES) {
            finish_row_stats(raw, mean0, rstd0, mean1, rstd1);
            if (tid < TN) s_cs[tid] = csv;
        }
        wg_wait<0>();
        fence_regs(acc);
        if (tid == 0) TL(prm.tk, 2);
        if constexpr (EPI != EPI_RES) named_bar(1, 256);

        if constexpr (EPI != EPI_FFN1) {
            const uint32_t stile = sbase + (EPI == EPI_RES ? s * SM::STAGE : 0);
            const int mrow = wg * 64 + (warp & 3) * 16 + (lane & 7) + ((lane >> 3) & 1) * 8;
            const uint32_t rbase = stile + mrow * 128;
            if constexpr (EPI == EPI_RES) {
                mbar_wait(bar_full + 8 * s, ph);
                float s0 = 0.f, s1 = 0.f;
#pragma unroll
                for (int jj = 0; jj < 4; jj++) {
                    uint32_t r0, r1, r2, r3;
                    const uint32_t addr = rbase + (((2 * jj + (lane >> 4)) ^ (mrow & 7)) << 4);
                    ldsm_x4(r0, r1, r2, r3, addr);
                    const uint32_t u0 = pack_bf16(acc[8 * jj] + bf_lo(r0), acc[8 * jj + 1] + bf_hi(r0));
                    const uint32_t u1 = pack_bf16(acc[8 * jj + 2] + bf_lo(r1), acc[8 * jj + 3] + bf_hi(r1));
                    const uint32_t u2 = pack_bf16(acc[8 * jj + 4] + bf_lo(r2), acc[8 * jj + 5] + bf_hi(r2));
                    const uint32_t u3 = pack_bf16(acc[8 * jj + 6] + bf_lo(r3), acc[8 * jj + 7] + bf_hi(r3));
                    stsm_x4(addr, u0, u1, u2, u3);
                    acc[8 * jj] = bf_lo(u0); acc[8 * jj + 1] = bf_hi(u0); acc[8 * jj + 4] = bf_lo(u2); acc[8 * jj + 5] = bf_hi(u2);
                    acc[8 * jj + 2] = bf_lo(u1); acc[8 * jj + 3] = bf_hi(u1); acc[8 * jj + 6] = bf_lo(u3); acc[8 * jj + 7] = bf_hi(u3);
                    s0 += (acc[8 * jj] + acc[8 * jj + 1]) + (acc[8 * jj + 4] + acc[8 * jj + 5]);
                    s1 += (acc[8 * jj + 2] + acc[8 * jj + 3]) + (acc[8 * jj + 6] + acc[8 * jj + 7]);
                }
                fence_async_smem();
                named_bar(2 + wg, 128);
                if ((warp & 3) == 0 && elect_one()) { tma2d_store(mapC, stile + wg * 8192, n0, m0 + wg * 64); bulk_commit(); }
                if (prm.stats_out) {
                    s0 += __shfl_xor_sync(0xffffffffu, s0, 1); s0 += __shfl_xor_sync(0xffffffffu, s0, 2);
                    s1 += __shfl_xor_sync(0xffffffffu, s1, 1); s1 += __shfl_xor_sync(0xffffffffu, s1, 2);
                    const float mu0 = s0 * (1.f / 64.f), mu1 = s1 * (1.f / 64.f);
                    float q0 = 0.f, q1 = 0.f;
#pragma unroll
                    for (int j = 0; j < 8; j++) {
                        float d;
                        d = acc[4 * j] - mu0; q0 += d * d; d = acc[4 * j + 1] - mu0; q0 += d * d;
                        d = acc[4 * j + 2] - mu1; q1 += d * d; d = acc[4 * j + 3] - mu1; q1 += d * d;
                    }
                    q0 += __shfl_xor_sync(0xffffffffu, q0, 1); q0 += __shfl_xor_sync(0xffffffffu, q0, 2);
                    q1 += __shfl_xor_sync(0xffffffffu, q1, 1); q1 += __shfl_xor_sync(0xffffffffu, q1, 2);
                    if (c == 0) {
                        prm.stats_out[tile_n * S_ + row0] = make_float2(mu0, q0);
                        prm.stats_out[tile_n * S_ + row0 + 8] = make_float2(mu1, q1);
                    }
                }
            } else {
                const float sc = 0.25f * 1.4426950408889634f;
                const float a0 = rstd0 * sc, a1 = rstd1 * sc, rm0 = a0 * mean0, rm1 = a1 * mean1;
#pragma unroll
                for (int jj = 0; jj < 4; jj++) {
                    const float2 ca = *(const float2*)(s_cs + 16 * jj + 2 * c), cb = *(const float2*)(s_cs + 16 * jj + 8 + 2 * c);
                    const uint32_t u0 = pack_bf16(acc[8 * jj] * a0 - rm0 * ca.x, acc[8 * jj + 1] * a0 - rm0 * ca.y);
                    const uint32_t u1 = pack_bf16(acc[8 * jj + 2] * a1 - rm1 * ca.x, acc[8 * jj + 3] * a1 - rm1 * ca.y);
                    const uint32_t u2 = pack_bf16(acc[8 * jj + 4] * a0 - rm0 * cb.x, acc[8 * jj + 5] * a0 - rm0 * cb.y);
                    const uint32_t u3 = pack_bf16(acc[8 * jj + 6] * a1 - rm1 * cb.x, acc[8 * jj + 7] * a1 - rm1 * cb.y);
                    stsm_x4(rbase + (((2 * jj + (lane >> 4)) ^ (mrow & 7)) << 4), u0, u1, u2, u3);
                }
                fence_async_smem();
                named_bar(2 + wg, 128);
                if ((warp & 3) == 0 && elect_one()) { tma2d_store(mapC, stile + wg * 8192, n0, m0 + wg * 64); bulk_commit(); }
            }
            if constexpr (XKV) {
                {
                    const float* acx = &acc[32];
                    const float rm0 = rstd0 * mean0, rm1 = rstd1 * mean1;
                    float n0s = 0.f, n1s = 0.f, vmax = 0.f;
#pragma unroll
                    for (int j = 0; j < 2; j++) {
                        const float2 cs2 = SELF ? *(const float2*)(s_cs + 64 + 8 * j + 2 * c) : cskv[j];
                        const uint32_t u0 = pack_bf16(acx[4 * j] * rstd0 - rm0 * cs2.x, acx[4 * j + 1] * rstd0 - rm0 * cs2.y);
                        const uint32_t u1 = pack_bf16(acx[4 * j + 2] * rstd1 - rm1 * cs2.x, acx[4 * j + 3] * rstd1 - rm1 * cs2.y);
                        n0s += bf_lo(u0) * bf_lo(u0) + bf_hi(u0) * bf_hi(u0);
                        n1s += bf_lo(u1) * bf_lo(u1) + bf_hi(u1) * bf_hi(u1);
                        vmax = fmaxf(vmax, fmaxf(fmaxf(fabsf(bf_lo(u0)), fabsf(bf_hi(u0))), fmaxf(fabsf(bf_lo(u1)), fabsf(bf_hi(u1)))));
                        if (tile_n == 0) {
                            *(uint32_t*)(g_kimg + (row0 >> 3) * 256 + j * 128 + g * 16 + c * 4) = u0;
                            *(uint32_t*)(g_kimg + ((row0 + 8) >> 3) * 256 + j * 128 + g * 16 + c * 4) = u1;
                        } else {
                            uint8_t* vb = g_vimg + (row0 >> 4) * 768 + j * 256 + g * 16 + c * 4;
                            *(uint32_t*)(vb) = u0;
                            *(uint32_t*)(vb + 128) = u1;
                        }
                    }
                    if (tile_n == 1) {
                        uint8_t* vb = g_vimg + (row0 >> 4) * 768 + 512 + g * 16 + c * 4;
                        const uint32_t one = c == 0 ? 0x00003F80u : 0u;
                        *(uint32_t*)(vb) = one;
                        *(uint32_t*)(vb + 128) = one;
                    }
                    n0s += __shfl_xor_sync(0xffffffffu, n0s, 1); n0s += __shfl_xor_sync(0xffffffffu, n0s, 2);
                    n1s += __shfl_xor_sync(0xffffffffu, n1s, 1); n1s += __shfl_xor_sync(0xffffffffu, n1s, 2);
                    float km = tile_n == 0 ? fmaxf(n0s, n1s) : vmax;
                    if (!(n0s + n1s < INFINITY)) km = INFINITY;
#pragma unroll
                    for (int o = 1; o < 32; o <<= 1) km = fmaxf(km, __shfl_xor_sync(0xffffffffu, km, o));
                    if (lane == 0) s_red[warp] = km;
                    named_bar(1, 256);
                    if (tid == 0) {
                        float a = 0.f;
                        for (int i = 0; i < 8; i++) a = fmaxf(a, s_red[i]);
                        g_kvmax[tile_n * 16 + tile_m] = a;
                    }
                }
            }
            if ((warp & 3) == 0) bulk_wait_read();
        } else {
            const uint32_t stile = sbase + wg * (7 * 4096);
            const int mrow = (warp & 3) * 16 + (lane & 7) + ((lane >> 3) & 1) * 8;
            const float a0 = 0.5f * rstd0, a1 = 0.5f * rstd1, rm0 = a0 * mean0, rm1 = a1 * mean1;
#pragma unroll
            for (int jj = 0; jj < 14; jj++) {
                const float2 ca = *(const float2*)(s_cs + 16 * jj + 2 * c), cb = *(const float2*)(s_cs + 16 * jj + 8 + 2 * c);
                float y[8] = {acc[8 * jj] * a0 - rm0 * ca.x,     acc[8 * jj + 1] * a0 - rm0 * ca.y,
                              acc[8 * jj + 2] * a1 - rm1 * ca.x, acc[8 * jj + 3] * a1 - rm1 * ca.y,
                              acc[8 * jj + 4] * a0 - rm0 * cb.x, acc[8 * jj + 5] * a0 - rm0 * cb.y,
                              acc[8 * jj + 6] * a1 - rm1 * cb.x, acc[8 * jj + 7] * a1 - rm1 * cb.y};
#pragma unroll
                for (int i = 0; i < 8; i++) {
                    float t;
                    asm("tanh.approx.f32 %0, %1;" : "=f"(t) : "f"(y[i]));
                    y[i] = fmaf(y[i], t, y[i]);
                }
                const int chunk = (2 * jj + (lane >> 4)) & 3, blk = jj >> 1;
                stsm_x4(stile + blk * 4096 + mrow * 64 + ((chunk ^ ((mrow >> 1) & 3)) << 4),
                        pack_bf16(y[0], y[1]), pack_bf16(y[2], y[3]), pack_bf16(y[4], y[5]), pack_bf16(y[6], y[7]));
                if (jj & 1) {
                    fence_async_smem();
                    __syncwarp();
                    if (elect_one()) {
                        tma2d_store(mapC, stile + blk * 4096 + (warp & 3) * 1024, n0 + blk * 32, m0 + wg * 64 + (warp & 3) * 16);
                        bulk_commit();
                    }
                }
            }
            bulk_wait_read();
        }
    }
    if (tid == 0) TL(prm.tk, 3);
    if (MC) cluster_sync();
}

#define WO_ST 9
#define F2_ST 6
#define F1_ST (F1_BK == 64 ? 5 : 9)
#define QKV_ST 8
constexpr int QKV_STAGES = QKV_ST, WO_STAGES = WO_ST, FFN2_STAGES = F2_ST, FFN1_STAGES = F1_ST;
template <bool SELF>
__global__ void __launch_bounds__(SELF ? 544 : 288) qkv_kernel(const __grid_constant__ CUtensorMap mapA, const __grid_constant__ CUtensorMap mapWq,
                                                  const __grid_constant__ CUtensorMap mapQ, const GemmParams prm) {
    extern __shared__ __align__(1024) uint8_t smem_raw[];
    const int tn = blockIdx.x & 7;
    if (tn < 2) gemm_body<80, 8, QKV_STAGES, EPI_QKV, QKV_MC, SELF>(&mapA, &mapWq, &mapWq, &mapA, &mapQ, prm, blockIdx.x >> 3, tn, smem_raw);
    else gemm_body<64, 8, QKV_STAGES, EPI_QKV, QKV_MC, SELF>(&mapA, &mapWq, &mapWq, &mapA, &mapQ, prm, blockIdx.x >> 3, tn, smem_raw);
}
template <int KB, int STAGES>
__global__ void __launch_bounds__(288) res_gemm_kernel(const __grid_constant__ CUtensorMap mapA, const __grid_constant__ CUtensorMap mapW,
                                                       const __grid_constant__ CUtensorMap mapR, const __grid_constant__ CUtensorMap mapC, const GemmParams prm) {
    extern __shared__ __align__(1024) uint8_t smem_raw[];
    gemm_body<64, KB, STAGES, EPI_RES, (KB == 8 ? WO_MC : F2_MC)>(&mapA, &mapW, &mapW, &mapR, &mapC, prm, blockIdx.x >> 3, blockIdx.x & 7, smem_raw);
}
__global__ void __launch_bounds__(F1_INLINE ? 256 : 288) ffn1_kernel(const __grid_constant__ CUtensorMap mapA, const __grid_constant__ CUtensorMap mapW4,
                                                   const __grid_constant__ CUtensorMap mapW3, const __grid_constant__ CUtensorMap mapH, const GemmParams prm) {
    extern __shared__ __align__(1024) uint8_t smem_raw[];
    const int pair = blockIdx.x >> 1, tile_n = pair & 7, tile_m = (pair >> 3) * 2 + (blockIdx.x & 1);
    gemm_body<224, 512 / F1_BK, FFN1_STAGES, EPI_FFN1, F1_MC>(&mapA, &mapW4, &mapW3, &mapA, &mapH, prm, tile_m, tile_n, smem_raw);
}

constexpr int NPOLY = 10;
__host__ __device__ constexpr bool is_mufu(int i) { return ((i + 1) * (16 - NPOLY)) / 16 != (i * (16 - NPOLY)) / 16; }

__device__ __forceinline__ float ex2(float x) { float r; asm("ex2.approx.ftz.f32 %0, %1;" : "=f"(r) : "f"(x)); return r; }
__device__ __forceinline__ uint32_t exp_pair_mufu(float a, float b) { return pack_bf16(ex2(a), ex2(b)); }
__device__ __forceinline__ uint32_t exp_pair_fma(float a, float b, uint32_t c3f) {
    constexpr float MAGIC = 98430.4140625f;
    const float ta = a + MAGIC, tb = b + (MAGIC - 143.5f);
    uint32_t y, m, r;
    asm("mad.lo.u32 %0, %1, 65536, %2;" : "=r"(y) : "r"(__float_as_uint(tb)), "r"(__float_as_uint(ta)));
    asm("lop3.b32 %0, %1, 0x007F007F, %2, 0xEA;" : "=r"(m) : "r"(y), "r"(c3f));
    const uint32_t e = y & 0xFF80FF80u;
    asm("fma.rn.bf16x2 %0, %1, %2, %3;" : "=r"(r) : "r"(y), "r"(m), "r"(e));
    return r;
}

constexpr int KCH = 256, NCH = S_ / KCH;
constexpr int K_BYTES = S_ * 32, V_BYTES = (S_ / 16) * 768;
constexpr int ATT_SMEM = K_BYTES + V_BYTES;

__global__ void __launch_bounds__(512, 1) attn_kernel(const __nv_bfloat16* __restrict__ wo, const __nv_bfloat16* __restrict__ w1,
                                                       const __nv_bfloat16* __restrict__ w2, int tk) {
    extern __shared__ __align__(1024) uint8_t smem[];
    __shared__ uint64_t bars[NCH];
    __shared__ int s_slow;
    const int tid = threadIdx.x, wg = tid >> 7, warp = (tid >> 5) & 3, lane = tid & 31;
    const uint32_t sK = smem_u32(smem), sV = sK + K_BYTES;
    if (blockIdx.x >= 128) {
        pdl_launch();
        side_job(blockIdx.x - 128, (float*)smem, wo, w1, w2);
        return;
    }
    if (tid == 0) TL(tk, 0);
    if (tid == 0) {
        for (int i = 0; i < NCH; i++) mbar_init(smem_u32(&bars[i]), 1);
        s_slow = 0;
        fence_mbar_init();
    }
    __syncthreads();
    pdl_launch();
    pdl_wait();
    if (tid == 0) TL(tk, 1);
    if (__shfl_sync(0xffffffffu, tid >> 5, 0) == 0 && elect_one()) {
#pragma unroll
        for (int i = 0; i < NCH; i++) {
            mbar_expect_tx(smem_u32(&bars[i]), KCH * 32 + (KCH / 16) * 768);
            bulk_load(sK + i * KCH * 32, g_kimg + i * KCH * 32, KCH * 32, smem_u32(&bars[i]));
            bulk_load(sV + i * (KCH / 16) * 768, g_vimg + i * (KCH / 16) * 768, (KCH / 16) * 768, smem_u32(&bars[i]));
        }
    }
    const int tb = blockIdx.x >> 3, hg = blockIdx.x & 7;
    const int head = hg * 4 + wg;
    const int g = lane >> 2, c = lane & 3;
    uint32_t qa[2][4];
    float qn = 0.f;
#pragma unroll
    for (int m = 0; m < 2; m++) {
        const int row = tb * 128 + m * 64 + warp * 16 + g;
        const uint32_t* p0 = (const uint32_t*)(g_q + (size_t)row * D_ + head * 16);
        const uint32_t* p1 = (const uint32_t*)(g_q + (size_t)(row + 8) * D_ + head * 16);
        qa[m][0] = p0[c]; qa[m][1] = p1[c]; qa[m][2] = p0[c + 4]; qa[m][3] = p1[c + 4];
        float n0 = bf_lo(qa[m][0]) * bf_lo(qa[m][0]) + bf_hi(qa[m][0]) * bf_hi(qa[m][0]) + bf_lo(qa[m][2]) * bf_lo(qa[m][2]) + bf_hi(qa[m][2]) * bf_hi(qa[m][2]);
        float n1 = bf_lo(qa[m][1]) * bf_lo(qa[m][1]) + bf_hi(qa[m][1]) * bf_hi(qa[m][1]) + bf_lo(qa[m][3]) * bf_lo(qa[m][3]) + bf_hi(qa[m][3]) * bf_hi(qa[m][3]);
        n0 += __shfl_xor_sync(0xffffffffu, n0, 1); n0 += __shfl_xor_sync(0xffffffffu, n0, 2);
        n1 += __shfl_xor_sync(0xffffffffu, n1, 1); n1 += __shfl_xor_sync(0xffffffffu, n1, 2);
        if (!(n0 == n0) || !(n1 == n1)) n0 = __int_as_float(0x7f800000);
        qn = fmaxf(qn, fmaxf(n0, n1));
    }
    {
        float km = 0.f, vm = 0.f;
#pragma unroll
        for (int i = 0; i < 16; i++) { km = fmaxf(km, g_kvmax[i]); vm = fmaxf(vm, g_kvmax[16 + i]); }
        const bool ok = (qn * km <= 10000.f) && (vm <= 16384.f);
        if (!ok) s_slow = 1;
    }
    float oacc[2][12];
#pragma unroll
    for (int m = 0; m < 2; m++)
#pragma unroll
        for (int i = 0; i < 12; i++) oacc[m][i] = 0.f;
    __syncthreads();
    const bool slow = s_slow != 0;

    const uint64_t dK0 = mkdesc(sK, 128, 256, 0);
    const uint64_t dV0 = mkdesc(sV, 128, 256, 0);
    uint32_t c3f;
    asm volatile("mov.b32 %0, 0x3F003F00;" : "=r"(c3f));
    if (!slow) {
#pragma unroll 1
        for (int t = 0; t < S_ / 64; t++) {
            if ((t & 3) == 0) mbar_wait(smem_u32(&bars[t >> 2]), 0);
            const uint64_t dK = dK0 + (uint64_t)(t * 64 * 32 / 16);
            const uint64_t dV = dV0 + (uint64_t)(t * 4 * 768 / 16);
#pragma unroll
            for (int m = 0; m < 2; m++) {
                float s[32];
                wg_fence();
                wgmma_rs_n64_z(s, qa[m][0], qa[m][1], qa[m][2], qa[m][3], dK);
                wg_commit();
                wg_wait<0>();
                fence_regs(s);
                uint32_t p[16];
#pragma unroll
                for (int i = 0; i < 16; i++) p[i] = is_mufu(i) ? exp_pair_mufu(s[2 * i], s[2 * i + 1]) : exp_pair_fma(s[2 * i], s[2 * i + 1], c3f);
                wg_fence();
#pragma unroll
                for (int kk = 0; kk < 4; kk++)
                    wgmma_rs_n24_tb(oacc[m], p[4 * kk], p[4 * kk + 1], p[4 * kk + 2], p[4 * kk + 3], dV + (uint64_t)(kk * 768 / 16));
                wg_commit();
            }
        }
        wg_wait<0>();
    } else {
        float mx[2][2] = {{-INFINITY, -INFINITY}, {-INFINITY, -INFINITY}};
#pragma unroll 1
        for (int t = 0; t < S_ / 64; t++) {
            if ((t & 3) == 0) mbar_wait(smem_u32(&bars[t >> 2]), 0);
            const uint64_t dK = dK0 + (uint64_t)(t * 64 * 32 / 16);
            const uint64_t dV = dV0 + (uint64_t)(t * 4 * 768 / 16);
#pragma unroll
            for (int m = 0; m < 2; m++) {
                float s[32];
                wg_fence();
                wgmma_rs_n64_z(s, qa[m][0], qa[m][1], qa[m][2], qa[m][3], dK);
                wg_commit();
                wg_wait<0>();
                fence_regs(s);
                fence_regs(oacc[m]);
                float r0 = mx[m][0], r1 = mx[m][1];
#pragma unroll
                for (int j = 0; j < 8; j++) {
                    r0 = fmaxf(r0, fmaxf(s[4 * j], s[4 * j + 1]));
                    r1 = fmaxf(r1, fmaxf(s[4 * j + 2], s[4 * j + 3]));
                }
                r0 = fmaxf(r0, __shfl_xor_sync(0xffffffffu, r0, 1)); r0 = fmaxf(r0, __shfl_xor_sync(0xffffffffu, r0, 2));
                r1 = fmaxf(r1, __shfl_xor_sync(0xffffffffu, r1, 1)); r1 = fmaxf(r1, __shfl_xor_sync(0xffffffffu, r1, 2));
                const float al0 = ex2(mx[m][0] - r0), al1 = ex2(mx[m][1] - r1);
                mx[m][0] = r0; mx[m][1] = r1;
#pragma unroll
                for (int j = 0; j < 3; j++) {
                    oacc[m][4 * j] *= al0; oacc[m][4 * j + 1] *= al0;
                    oacc[m][4 * j + 2] *= al1; oacc[m][4 * j + 3] *= al1;
                }
                uint32_t p[16];
#pragma unroll
                for (int j = 0; j < 8; j++) {
                    p[2 * j] = pack_bf16(ex2(s[4 * j] - r0), ex2(s[4 * j + 1] - r0));
                    p[2 * j + 1] = pack_bf16(ex2(s[4 * j + 2] - r1), ex2(s[4 * j + 3] - r1));
                }
                fence_regs(oacc[m]);
                wg_fence();
#pragma unroll
                for (int kk = 0; kk < 4; kk++)
                    wgmma_rs_n24_tb(oacc[m], p[4 * kk], p[4 * kk + 1], p[4 * kk + 2], p[4 * kk + 3], dV + (uint64_t)(kk * 768 / 16));
                wg_commit();
                wg_wait<0>();
            }
        }
    }
    fence_regs(oacc[0]); fence_regs(oacc[1]);
    if (tid == 0) TL(tk, 2);
#pragma unroll
    for (int m = 0; m < 2; m++) {
        const float l0 = __shfl_sync(0xffffffffu, oacc[m][8], lane & ~3);
        const float l1 = __shfl_sync(0xffffffffu, oacc[m][10], lane & ~3);
        const float r0 = 1.0f / l0, r1 = 1.0f / l1;
        const int row = tb * 128 + m * 64 + warp * 16 + g;
        uint32_t* p0 = (uint32_t*)(g_o + (size_t)row * D_ + head * 16);
        uint32_t* p1 = (uint32_t*)(g_o + (size_t)(row + 8) * D_ + head * 16);
        p0[c] = pack_bf16(oacc[m][0] * r0, oacc[m][1] * r0);
        p1[c] = pack_bf16(oacc[m][2] * r1, oacc[m][3] * r1);
        p0[c + 4] = pack_bf16(oacc[m][4] * r0, oacc[m][5] * r0);
        p1[c + 4] = pack_bf16(oacc[m][6] * r1, oacc[m][7] * r1);
    }
    if (tid == 0) TL(tk, 3);
}

typedef CUresult (*EncodeFn)(CUtensorMap*, CUtensorMapDataType, cuuint32_t, void*, const cuuint64_t*, const cuuint64_t*, const cuuint32_t*,
                             const cuuint32_t*, CUtensorMapInterleave, CUtensorMapSwizzle, CUtensorMapL2promotion, CUtensorMapFloatOOBfill);

EncodeFn get_encode() {
    static EncodeFn fn = nullptr;
    if (!fn) {
        void* p = nullptr;
        cudaDriverEntryPointQueryResult qr;
        cudaGetDriverEntryPoint("cuTensorMapEncodeTiled", &p, cudaEnableDefault, &qr);
        fn = (EncodeFn)p;
    }
    return fn;
}
CUtensorMap map2d(const void* ptr, uint64_t cols, uint64_t rows, uint32_t bc, uint32_t br, CUtensorMapSwizzle sw) {
    CUtensorMap m;
    cuuint64_t gd[2] = {cols, rows}, gs[1] = {cols * 2};
    cuuint32_t bx[2] = {bc, br}, es[2] = {1, 1};
    get_encode()(&m, CU_TENSOR_MAP_DATA_TYPE_BFLOAT16, 2, (void*)ptr, gd, gs, bx, es, CU_TENSOR_MAP_INTERLEAVE_NONE, sw,
                 CU_TENSOR_MAP_L2_PROMOTION_L2_128B, CU_TENSOR_MAP_FLOAT_OOB_FILL_NONE);
    return m;
}
CUtensorMap map3d32(const void* ptr, uint64_t cols, uint64_t rows, uint32_t br, uint32_t nb) {
    CUtensorMap m;
    cuuint64_t gd[3] = {32, rows, cols / 32}, gs[2] = {cols * 2, 64};
    cuuint32_t bx[3] = {32, br, nb}, es[3] = {1, 1, 1};
    get_encode()(&m, CU_TENSOR_MAP_DATA_TYPE_BFLOAT16, 3, (void*)ptr, gd, gs, bx, es, CU_TENSOR_MAP_INTERLEAVE_NONE, CU_TENSOR_MAP_SWIZZLE_64B,
                 CU_TENSOR_MAP_L2_PROMOTION_L2_128B, CU_TENSOR_MAP_FLOAT_OOB_FILL_NONE);
    return m;
}

template <typename... KArgs, typename... Args>
void launch(void (*kern)(KArgs...), int grid, int block, int smem, int cluster, bool pdl, Args... args) {
    cudaLaunchConfig_t cfg = {};
    cfg.gridDim = dim3(grid);
    cfg.blockDim = dim3(block);
    cfg.dynamicSmemBytes = smem;
    cfg.stream = cudaStreamPerThread;
    cudaLaunchAttribute at[2];
    int n = 0;
    if (cluster > 1) { at[n].id = cudaLaunchAttributeClusterDimension; at[n].val.clusterDim.x = cluster; at[n].val.clusterDim.y = 1; at[n].val.clusterDim.z = 1; n++; }
    if (pdl) { at[n].id = cudaLaunchAttributeProgrammaticStreamSerialization; at[n].val.programmaticStreamSerializationAllowed = 1; n++; }
    cfg.attrs = at;
    cfg.numAttrs = n;
    cudaLaunchKernelEx(&cfg, kern, KArgs(args)...);
}

template <typename T> void* sym(const T& s) { void* p = nullptr; cudaGetSymbolAddress(&p, s); return p; }

}

extern "C" void kernel_launch(void* const* d_in, const int* in_sizes, int n_in, void* d_out, int out_size) {
    const __nv_bfloat16* x = (const __nv_bfloat16*)d_in[0];
    const __nv_bfloat16* wq = (const __nv_bfloat16*)d_in[1];
    const __nv_bfloat16* wk = (const __nv_bfloat16*)d_in[2];
    const __nv_bfloat16* wv = (const __nv_bfloat16*)d_in[3];
    const __nv_bfloat16* wo = (const __nv_bfloat16*)d_in[4];
    const __nv_bfloat16* w1 = (const __nv_bfloat16*)d_in[6];
    const __nv_bfloat16* w2 = (const __nv_bfloat16*)d_in[7];

    constexpr int SM_QKV = GemmSmem<QKV_STAGES, EPI_QKV>::TOTAL, SM_QKV0 = GemmSmem<QKV_STAGES, EPI_QKV>::TOTAL_SELF;
    static_assert(SM_QKV0 <= 232448, "shared memory");
    constexpr int HALF_PLUS = 116736;
    constexpr int SM_WO = GemmSmem<WO_STAGES, EPI_RES>::TOTAL > HALF_PLUS ? GemmSmem<WO_STAGES, EPI_RES>::TOTAL : HALF_PLUS;
    constexpr int SM_FFN2 = GemmSmem<FFN2_STAGES, EPI_RES>::TOTAL > HALF_PLUS ? GemmSmem<FFN2_STAGES, EPI_RES>::TOTAL : HALF_PLUS;
    constexpr int SM_FFN1 = GemmSmem<FFN1_STAGES, EPI_FFN1>::TOTAL;
    cudaFuncSetAttribute(qkv_kernel<false>, cudaFuncAttributeMaxDynamicSharedMemorySize, SM_QKV);
    cudaFuncSetAttribute(qkv_kernel<true>, cudaFuncAttributeMaxDynamicSharedMemorySize, SM_QKV0);
    cudaFuncSetAttribute(res_gemm_kernel<8, WO_STAGES>, cudaFuncAttributeMaxDynamicSharedMemorySize, SM_WO);
    cudaFuncSetAttribute(ffn1_kernel, cudaFuncAttributeMaxDynamicSharedMemorySize, SM_FFN1);
    cudaFuncSetAttribute(res_gemm_kernel<28, FFN2_STAGES>, cudaFuncAttributeMaxDynamicSharedMemorySize, SM_FFN2);
    cudaFuncSetAttribute(attn_kernel, cudaFuncAttributeMaxDynamicSharedMemorySize, ATT_SMEM);
    cudaFuncSetAttribute(qkv_kernel<false>, cudaFuncAttributePreferredSharedMemoryCarveout, 100);
    cudaFuncSetAttribute(qkv_kernel<true>, cudaFuncAttributePreferredSharedMemoryCarveout, 100);
    cudaFuncSetAttribute(res_gemm_kernel<8, WO_STAGES>, cudaFuncAttributePreferredSharedMemoryCarveout, 100);
    cudaFuncSetAttribute(ffn1_kernel, cudaFuncAttributePreferredSharedMemoryCarveout, 100);
    cudaFuncSetAttribute(res_gemm_kernel<28, FFN2_STAGES>, cudaFuncAttributePreferredSharedMemoryCarveout, 100);
    cudaFuncSetAttribute(attn_kernel, cudaFuncAttributePreferredSharedMemoryCarveout, 100);

    void *q = sym(g_q), *o = sym(g_o), *x1 = sym(g_x1), *x2 = sym(g_x2), *x3 = sym(g_x3), *h = sym(g_h);
    float2* stats = (float2*)sym(g_stats);
    const void* xs[5] = {x, x1, x2, x3, d_out};

    const CUtensorMapSwizzle SW128 = CU_TENSOR_MAP_SWIZZLE_128B, SW64 = CU_TENSOR_MAP_SWIZZLE_64B;
    const CUtensorMap mWq = map3d32(wq, D_, D_, 64, 2);
    const CUtensorMap mWo = map2d(wo, D_, D_, 64, 64, SW128);
    const CUtensorMap mW1a = map3d32(w1, F_, D_, F1_BK, 4), mW1b = map3d32(w1, F_, D_, F1_BK, 3);
    const CUtensorMap mW2 = map2d(w2, D_, F_, 64, 64, SW128);
    const CUtensorMap mQ = map2d(q, D_, S_, 64, 64, SW128);
    const CUtensorMap mHst = map2d(h, F_, S_, 32, 16, SW64);
    CUtensorMap mXa[4], mXf[4], mXr[4], mXs[5];
    for (int i = 0; i < 4; i++) {
        mXa[i] = map2d(xs[i], D_, S_, 64, QKV_MC ? 64 : 128, SW128);
        mXf[i] = F1_BK == 64 ? map2d(xs[i], D_, S_, 64, 128, SW128) : map2d(xs[i], D_, S_, 32, 128, SW64);
        mXr[i] = map2d(xs[i], D_, S_, 64, 128, SW128);
    }
    for (int i = 0; i < 5; i++) mXs[i] = map2d(xs[i], D_, S_, 64, 64, SW128);
    const CUtensorMap mOa = map2d(o, D_, S_, 64, WO_MC ? 64 : 128, SW128);
    const CUtensorMap mHa = map2d(h, F_, S_, 64, F2_MC ? 64 : 128, SW128);

    for (int layer = 0; layer < 2; layer++) {
        const int xi = layer * 2;
        GemmParams p;
        p.wkv = wk; p.wv = wv;
        p.stats_in = stats + (size_t)xi * 8 * S_; p.stats_out = nullptr; p.tk = 1 + 5 * layer;
        if (layer == 0) launch(qkv_kernel<true>, 128, 544, SM_QKV0, QKV_MC ? 2 : 1, false, mXa[xi], mWq, mQ, p);
        else launch(qkv_kernel<false>, 128, 288, SM_QKV, QKV_MC ? 2 : 1, true, mXa[xi], mWq, mQ, p);
        launch(attn_kernel, layer == 0 ? 128 + SIDE_CTAS : 128, 512, ATT_SMEM, 1, true, wo, w1, w2, 2 + 5 * layer);
        p.stats_in = nullptr; p.stats_out = stats + (size_t)(xi + 1) * 8 * S_; p.tk = 3 + 5 * layer;
        launch(res_gemm_kernel<8, WO_STAGES>, 128, 288, SM_WO, WO_MC ? 2 : 1, true, mOa, mWo, mXr[xi], mXs[xi + 1], p);
        p.stats_in = stats + (size_t)(xi + 1) * 8 * S_; p.stats_out = nullptr; p.tk = 4 + 5 * layer;
        launch(ffn1_kernel, 128, F1_INLINE ? 256 : 288, SM_FFN1, F1_MC ? 2 : 1, true, mXf[xi + 1], mW1a, mW1b, mHst, p);
        p.stats_in = nullptr; p.stats_out = layer == 0 ? stats + (size_t)2 * 8 * S_ : nullptr; p.tk = 5 + 5 * layer;
        launch(res_gemm_kernel<28, FFN2_STAGES>, 128, 288, SM_FFN2, F2_MC ? 2 : 1, true, mHa, mW2, mXr[xi + 1], mXs[xi + 2], p);
    }
}
```

```cpp
#include <cuda_runtime.h>
#include <cuda_bf16.h>
#include <cuda.h>
#include <stdint.h>

#define F1_INLINE 0
#define QKV_MC 0
#define WO_MC 0
#define F2_MC 0
#define F1_MC 2
#define PREB 2
#define RES_WAIT0 0

namespace {

constexpr int S_ = 2048, D_ = 512, H_ = 32, F_ = 1792;

__device__ __align__(1024) __nv_bfloat16 g_q[S_ * D_];
__device__ __align__(1024) __nv_bfloat16 g_o[S_ * D_];
__device__ __align__(1024) __nv_bfloat16 g_x1[S_ * D_];
__device__ __align__(1024) __nv_bfloat16 g_x2[S_ * D_];
__device__ __align__(1024) __nv_bfloat16 g_x3[S_ * D_];
__device__ __align__(1024) __nv_bfloat16 g_h[S_ * F_];
__device__ __align__(1024) uint8_t g_kimg[S_ * 32];
__device__ __align__(1024) uint8_t g_vimg[(S_ / 16) * 768];
__device__ __align__(1024) float2 g_stats[4][8 * S_];
__device__ __align__(16) float g_cs_q[D_];
__device__ __align__(16) float g_cs_kv[32];
__device__ __align__(16) float g_cs_1[F_];
__device__ __align__(16) float g_kvmax[32];

#define TL(k, slot)

__device__ __forceinline__ uint32_t smem_u32(const void* p) { return (uint32_t)__cvta_generic_to_shared(p); }
__device__ __forceinline__ void mbar_init(uint32_t bar, uint32_t cnt) {
    asm volatile("mbarrier.init.shared::cta.b64 [%0], %1;" ::"r"(bar), "r"(cnt));
}
__device__ __forceinline__ void mbar_expect_tx(uint32_t bar, uint32_t bytes) {
    asm volatile("mbarrier.arrive.expect_tx.shared::cta.b64 _, [%0], %1;" ::"r"(bar), "r"(bytes) : "memory");
}
__device__ __forceinline__ void mbar_arrive(uint32_t bar) {
    asm volatile("mbarrier.arrive.shared::cta.b64 _, [%0];" ::"r"(bar) : "memory");
}
__device__ __forceinline__ void mbar_arrive_remote(uint32_t bar, uint32_t cta) {
    asm volatile("{\n.reg .b32 ra;\nmapa.shared::cluster.u32 ra, %0, %1;\nmbarrier.arrive.shared::cluster.b64 _, [ra];\n}" ::"r"(bar), "r"(cta) : "memory");
}
__device__ __forceinline__ void mbar_wait(uint32_t bar, uint32_t parity) {
    asm volatile("{\n.reg .pred p;\nWAIT_%=:\nmbarrier.try_wait.parity.shared::cta.b64 p, [%0], %1;\n@p bra DONE_%=;\nbra WAIT_%=;\nDONE_%=:\n}" ::"r"(bar), "r"(parity) : "memory");
}
__device__ __forceinline__ void bulk_load(uint32_t dst, const void* src, uint32_t bytes, uint32_t bar) {
    asm volatile("cp.async.bulk.shared::cluster.global.mbarrier::complete_tx::bytes [%0], [%1], %2, [%3];" ::"r"(dst), "l"(src), "r"(bytes), "r"(bar) : "memory");
}
__device__ __forceinline__ void tma2d(uint32_t dst, const CUtensorMap* m, int c0, int c1, uint32_t bar) {
    asm volatile("cp.async.bulk.tensor.2d.shared::cluster.global.mbarrier::complete_tx::bytes [%0], [%1, {%3, %4}], [%2];" ::"r"(dst), "l"(m), "r"(bar), "r"(c0), "r"(c1) : "memory");
}
__device__ __forceinline__ void tma2d_mc(uint32_t dst, const CUtensorMap* m, int c0, int c1, uint32_t bar, uint16_t mask) {
    asm volatile("cp.async.bulk.tensor.2d.shared::cluster.global.mbarrier::complete_tx::bytes.multicast::cluster [%0], [%1, {%3, %4}], [%2], %5;" ::"r"(dst), "l"(m), "r"(bar), "r"(c0), "r"(c1), "h"(mask) : "memory");
}
__device__ __forceinline__ void tma3d(uint32_t dst, const CUtensorMap* m, int c0, int c1, int c2, uint32_t bar) {
    asm volatile("cp.async.bulk.tensor.3d.shared::cluster.global.mbarrier::complete_tx::bytes [%0], [%1, {%3, %4, %5}], [%2];" ::"r"(dst), "l"(m), "r"(bar), "r"(c0), "r"(c1), "r"(c2) : "memory");
}
__device__ __forceinline__ void tma3d_mc(uint32_t dst, const CUtensorMap* m, int c0, int c1, int c2, uint32_t bar, uint16_t mask) {
    asm volatile("cp.async.bulk.tensor.3d.shared::cluster.global.mbarrier::complete_tx::bytes.multicast::cluster [%0], [%1, {%3, %4, %5}], [%2], %6;" ::"r"(dst), "l"(m), "r"(bar), "r"(c0), "r"(c1), "r"(c2), "h"(mask) : "memory");
}
__device__ __forceinline__ void tma2d_store(const CUtensorMap* m, uint32_t src, int c0, int c1) {
    asm volatile("cp.async.bulk.tensor.2d.global.shared::cta.bulk_group [%0, {%2, %3}], [%1];" ::"l"(m), "r"(src), "r"(c0), "r"(c1) : "memory");
}
__device__ __forceinline__ void tma3d_store(const CUtensorMap* m, uint32_t src, int c0, int c1, int c2) {
    asm volatile("cp.async.bulk.tensor.3d.global.shared::cta.bulk_group [%0, {%2, %3, %4}], [%1];" ::"l"(m), "r"(src), "r"(c0), "r"(c1), "r"(c2) : "memory");
}
__device__ __forceinline__ void bulk_commit() { asm volatile("cp.async.bulk.commit_group;" ::: "memory"); }
__device__ __forceinline__ void bulk_wait_read() { asm volatile("cp.async.bulk.wait_group.read 0;" ::: "memory"); }
__device__ __forceinline__ void prefetch_tmap(const CUtensorMap* m) { asm volatile("prefetch.tensormap [%0];" ::"l"(m) : "memory"); }
__device__ __forceinline__ void fence_async_smem() { asm volatile("fence.proxy.async.shared::cta;" ::: "memory"); }
__device__ __forceinline__ void fence_mbar_init() { asm volatile("fence.mbarrier_init.release.cluster;" ::: "memory"); }
__device__ __forceinline__ void cluster_sync() { asm volatile("barrier.cluster.arrive.release.aligned;\nbarrier.cluster.wait.acquire.aligned;" ::: "memory"); }
__device__ __forceinline__ uint32_t cluster_rank() { uint32_t r; asm volatile("mov.u32 %0, %%cluster_ctarank;" : "=r"(r)); return r; }
__device__ __forceinline__ void pdl_wait() { asm volatile("griddepcontrol.wait;" ::: "memory"); }
__device__ __forceinline__ void pdl_launch() { asm volatile("griddepcontrol.launch_dependents;" ::: "memory"); }
__device__ __forceinline__ bool elect_one() {
    uint32_t p;
    asm volatile("{\n.reg .pred p;\nelect.sync _|p, 0xffffffff;\nselp.b32 %0, 1, 0, p;\n}" : "=r"(p));
    return p != 0;
}
__device__ __forceinline__ void named_bar(int id, int n) { asm volatile("bar.sync %0, %1;" ::"r"(id), "r"(n) : "memory"); }

__device__ __forceinline__ void wg_fence() { asm volatile("wgmma.fence.sync.aligned;" ::: "memory"); }
__device__ __forceinline__ void wg_commit() { asm volatile("wgmma.commit_group.sync.aligned;" ::: "memory"); }
template <int N> __device__ __forceinline__ void wg_wait() { asm volatile("wgmma.wait_group.sync.aligned %0;" ::"n"(N) : "memory"); }
template <int N> __device__ __forceinline__ void fence_regs(float (&d)[N]) {
#pragma unroll
    for (int i = 0; i < N; i++) asm volatile("" : "+f"(d[i])::"memory");
}
__device__ __forceinline__ uint64_t mkdesc(uint32_t addr, uint32_t lbo, uint32_t sbo, uint32_t swz) {
    uint64_t d = 0;
    d |= (uint64_t)((addr & 0x3FFFF) >> 4);
    d |= (uint64_t)((lbo & 0x3FFFF) >> 4) << 16;
    d |= (uint64_t)((sbo & 0x3FFFF) >> 4) << 32;
    d |= (uint64_t)swz << 62;
    return d;
}
__device__ __forceinline__ void ldsm_x4(uint32_t& r0, uint32_t& r1, uint32_t& r2, uint32_t& r3, uint32_t addr) {
    asm volatile("ldmatrix.sync.aligned.m8n8.x4.shared.b16 {%0,%1,%2,%3}, [%4];" : "=r"(r0), "=r"(r1), "=r"(r2), "=r"(r3) : "r"(addr) : "memory");
}
__device__ __forceinline__ void stsm_x4(uint32_t addr, uint32_t r0, uint32_t r1, uint32_t r2, uint32_t r3) {
    asm volatile("stmatrix.sync.aligned.m8n8.x4.shared.b16 [%0], {%1,%2,%3,%4};" ::"r"(addr), "r"(r0), "r"(r1), "r"(r2), "r"(r3) : "memory");
}
__device__ __forceinline__ void ldsm_x4_t(uint32_t& r0, uint32_t& r1, uint32_t& r2, uint32_t& r3, uint32_t addr) {
    asm volatile("ldmatrix.sync.aligned.m8n8.x4.trans.shared.b16 {%0,%1,%2,%3}, [%4];" : "=r"(r0), "=r"(r1), "=r"(r2), "=r"(r3) : "r"(addr) : "memory");
}
__device__ __forceinline__ void hmma(float (&d)[4], uint32_t a0, uint32_t a1, uint32_t a2, uint32_t a3, uint32_t b0, uint32_t b1) {
    asm volatile("mma.sync.aligned.m16n8k16.row.col.f32.bf16.bf16.f32 {%0,%1,%2,%3}, {%4,%5,%6,%7}, {%8,%9}, {%0,%1,%2,%3};"
                 : "+f"(d[0]), "+f"(d[1]), "+f"(d[2]), "+f"(d[3]) : "r"(a0), "r"(a1), "r"(a2), "r"(a3), "r"(b0), "r"(b1));
}
__device__ __forceinline__ uint32_t pack_bf16(float lo, float hi) {
    uint32_t r;
    asm("cvt.rn.bf16x2.f32 %0, %1, %2;" : "=r"(r) : "f"(hi), "f"(lo));
    return r;
}
__device__ __forceinline__ float bf_lo(uint32_t v) { return __uint_as_float(v << 16); }
__device__ __forceinline__ float bf_hi(uint32_t v) { return __uint_as_float(v & 0xFFFF0000u); }

#define WG_REGS_4(o) "+f"(d[o]), "+f"(d[o + 1]), "+f"(d[o + 2]), "+f"(d[o + 3])
#define WG_REGS_8(o) WG_REGS_4(o), WG_REGS_4(o + 4)
#define WG_REGS_16(o) WG_REGS_8(o), WG_REGS_8(o + 8)
#define WG_REGS_32(o) WG_REGS_16(o), WG_REGS_16(o + 16)

__device__ __forceinline__ void wgmma_ss_n80_tb(float (&d)[40], uint64_t dA, uint64_t dB, int sc) {
    asm volatile("{\n.reg .pred p;\nsetp.ne.b32 p, %42, 0;\n"
                 "wgmma.mma_async.sync.aligned.m64n80k16.f32.bf16.bf16 "
                 "{%0,%1,%2,%3,%4,%5,%6,%7,%8,%9,%10,%11,%12,%13,%14,%15,%16,%17,%18,%19,%20,%21,%22,%23,%24,%25,%26,%27,%28,%29,%30,%31,"
                 "%32,%33,%34,%35,%36,%37,%38,%39}, %40, %41, p, 1, 1, 0, 1;\n}\n"
                 : WG_REGS_32(0), WG_REGS_8(32) : "l"(dA), "l"(dB), "r"(sc));
}
__device__ __forceinline__ void wgmma_ss_n64_tb(float (&d)[32], uint64_t dA, uint64_t dB, int sc) {
    asm volatile("{\n.reg .pred p;\nsetp.ne.b32 p, %34, 0;\n"
                 "wgmma.mma_async.sync.aligned.m64n64k16.f32.bf16.bf16 "
                 "{%0,%1,%2,%3,%4,%5,%6,%7,%8,%9,%10,%11,%12,%13,%14,%15,%16,%17,%18,%19,%20,%21,%22,%23,%24,%25,%26,%27,%28,%29,%30,%31}, "
                 "%32, %33, p, 1, 1, 0, 1;\n}\n"
                 : WG_REGS_32(0) : "l"(dA), "l"(dB), "r"(sc));
}
__device__ __forceinline__ void wgmma_ss_n224_tb(float (&d)[112], uint64_t dA, uint64_t dB, int sc) {
    asm volatile("{\n.reg .pred p;\nsetp.ne.b32 p, %114, 0;\n"
                 "wgmma.mma_async.sync.aligned.m64n224k16.f32.bf16.bf16 "
                 "{%0,%1,%2,%3,%4,%5,%6,%7,%8,%9,%10,%11,%12,%13,%14,%15,%16,%17,%18,%19,%20,%21,%22,%23,%24,%25,%26,%27,%28,%29,%30,%31,"
                 "%32,%33,%34,%35,%36,%37,%38,%39,%40,%41,%42,%43,%44,%45,%46,%47,%48,%49,%50,%51,%52,%53,%54,%55,%56,%57,%58,%59,%60,%61,%62,%63,"
                 "%64,%65,%66,%67,%68,%69,%70,%71,%72,%73,%74,%75,%76,%77,%78,%79,%80,%81,%82,%83,%84,%85,%86,%87,%88,%89,%90,%91,%92,%93,%94,%95,"
                 "%96,%97,%98,%99,%100,%101,%102,%103,%104,%105,%106,%107,%108,%109,%110,%111}, "
                 "%112, %113, p, 1, 1, 0, 1;\n}\n"
                 : WG_REGS_32(0), WG_REGS_32(32), WG_REGS_32(64), WG_REGS_16(96) : "l"(dA), "l"(dB), "r"(sc));
}
template <int BN> __device__ __forceinline__ void wgmma_ss_tb(float (&d)[BN / 2], uint64_t dA, uint64_t dB, int sc) {
    if constexpr (BN == 64) wgmma_ss_n64_tb(d, dA, dB, sc);
    else if constexpr (BN == 80) wgmma_ss_n80_tb(d, dA, dB, sc);
    else wgmma_ss_n224_tb(d, dA, dB, sc);
}
__device__ __forceinline__ void wgmma_rs_n64_tb(float (&d)[32], uint32_t a, uint64_t dB, int sc) {
    asm volatile("{\n.reg .pred p;\nsetp.ne.b32 p, %34, 0;\n"
                 "wgmma.mma_async.sync.aligned.m64n64k16.f32.bf16.bf16 "
                 "{%0,%1,%2,%3,%4,%5,%6,%7,%8,%9,%10,%11,%12,%13,%14,%15,%16,%17,%18,%19,%20,%21,%22,%23,%24,%25,%26,%27,%28,%29,%30,%31}, "
                 "{%32,%32,%32,%32}, %33, p, 1, 1, 1;\n}\n"
                 : WG_REGS_32(0) : "r"(a), "l"(dB), "r"(sc));
}
__device__ __forceinline__ void wgmma_rs_n80_tb(float (&d)[40], uint32_t a, uint64_t dB, int sc) {
    asm volatile("{\n.reg .pred p;\nsetp.ne.b32 p, %42, 0;\n"
                 "wgmma.mma_async.sync.aligned.m64n80k16.f32.bf16.bf16 "
                 "{%0,%1,%2,%3,%4,%5,%6,%7,%8,%9,%10,%11,%12,%13,%14,%15,%16,%17,%18,%19,%20,%21,%22,%23,%24,%25,%26,%27,%28,%29,%30,%31,"
                 "%32,%33,%34,%35,%36,%37,%38,%39}, {%40,%40,%40,%40}, %41, p, 1, 1, 1;\n}\n"
                 : WG_REGS_32(0), WG_REGS_8(32) : "r"(a), "l"(dB), "r"(sc));
}
template <int BN> __device__ __forceinline__ void wgmma_rs_ones(float (&d)[BN / 2], uint64_t dB, int sc) {
    if constexpr (BN == 80) wgmma_rs_n80_tb(d, 0x3F803F80u, dB, sc);
    else if constexpr (BN == 64) wgmma_rs_n64_tb(d, 0x3F803F80u, dB, sc);
}
__device__ __forceinline__ void wgmma_rs_n64_z(float (&d)[32], uint32_t a0, uint32_t a1, uint32_t a2, uint32_t a3, uint64_t dB) {
    asm volatile("{\n.reg .pred p;\nsetp.ne.b32 p, 0, 0;\n"
                 "wgmma.mma_async.sync.aligned.m64n64k16.f32.bf16.bf16 "
                 "{%0,%1,%2,%3,%4,%5,%6,%7,%8,%9,%10,%11,%12,%13,%14,%15,%16,%17,%18,%19,%20,%21,%22,%23,%24,%25,%26,%27,%28,%29,%30,%31}, "
                 "{%32,%33,%34,%35}, %36, p, 1, 1, 0;\n}\n"
                 : "=f"(d[0]), "=f"(d[1]), "=f"(d[2]), "=f"(d[3]), "=f"(d[4]), "=f"(d[5]), "=f"(d[6]), "=f"(d[7]),
                   "=f"(d[8]), "=f"(d[9]), "=f"(d[10]), "=f"(d[11]), "=f"(d[12]), "=f"(d[13]), "=f"(d[14]), "=f"(d[15]),
                   "=f"(d[16]), "=f"(d[17]), "=f"(d[18]), "=f"(d[19]), "=f"(d[20]), "=f"(d[21]), "=f"(d[22]), "=f"(d[23]),
                   "=f"(d[24]), "=f"(d[25]), "=f"(d[26]), "=f"(d[27]), "=f"(d[28]), "=f"(d[29]), "=f"(d[30]), "=f"(d[31])
                 : "r"(a0), "r"(a1), "r"(a2), "r"(a3), "l"(dB));
}
__device__ __forceinline__ void wgmma_rs_n24_tb(float (&d)[12], uint32_t a0, uint32_t a1, uint32_t a2, uint32_t a3, uint64_t dB) {
    asm volatile("{\n.reg .pred p;\nsetp.eq.b32 p, 0, 0;\n"
                 "wgmma.mma_async.sync.aligned.m64n24k16.f32.bf16.bf16 "
                 "{%0,%1,%2,%3,%4,%5,%6,%7,%8,%9,%10,%11}, {%12,%13,%14,%15}, %16, p, 1, 1, 1;\n}\n"
                 : WG_REGS_8(0), WG_REGS_4(8) : "r"(a0), "r"(a1), "r"(a2), "r"(a3), "l"(dB));
}

constexpr int SIDE_CTAS = 4;
__device__ __forceinline__ void side_job(int cta, float* red  , const __nv_bfloat16* __restrict__ wo,
                                         const __nv_bfloat16* __restrict__ w1, const __nv_bfloat16* __restrict__ w2) {
    const int tid = threadIdx.x, warp = tid >> 5, lane = tid & 31;
    for (int line = cta * 512 + tid; line < 18432; line += SIDE_CTAS * 512) {
        const char* p = line < 4096 ? (const char*)wo + (size_t)line * 128 : (const char*)w2 + (size_t)(line - 4096) * 128;
        asm volatile("prefetch.global.L2 [%0];" ::"l"(p));
    }
    const int rg = lane >> 3, c8 = lane & 7;
    for (int slab = cta; slab < F_ / 64; slab += SIDE_CTAS) {
        const __nv_bfloat16* base = w1 + slab * 64 + c8 * 8;
        uint4 v[8];
#pragma unroll
        for (int i = 0; i < 8; i++) v[i] = __ldg((const uint4*)(base + (size_t)(warp * 32 + rg + 4 * i) * F_));
        float acc[8];
#pragma unroll
        for (int i = 0; i < 8; i++) acc[i] = 0.f;
#pragma unroll
        for (int i = 0; i < 8; i++) {
            acc[0] += bf_lo(v[i].x); acc[1] += bf_hi(v[i].x); acc[2] += bf_lo(v[i].y); acc[3] += bf_hi(v[i].y);
            acc[4] += bf_lo(v[i].z); acc[5] += bf_hi(v[i].z); acc[6] += bf_lo(v[i].w); acc[7] += bf_hi(v[i].w);
        }
#pragma unroll
        for (int i = 0; i < 8; i++) {
            acc[i] += __shfl_xor_sync(0xffffffffu, acc[i], 8);
            acc[i] += __shfl_xor_sync(0xffffffffu, acc[i], 16);
        }
        if (rg == 0) {
#pragma unroll
            for (int i = 0; i < 8; i++) red[warp * 64 + c8 * 8 + i] = acc[i];
        }
        __syncthreads();
        if (tid < 64) {
            float s = 0.f;
#pragma unroll
            for (int i = 0; i < 16; i++) s += red[i * 64 + tid];
            g_cs_1[slab * 64 + tid] = s;
        }
        __syncthreads();
    }
}

enum { EPI_QKV = 0, EPI_RES = 1, EPI_FFN1 = 2 };

struct GemmParams {
    const float2* stats_in;
    float2* stats_out;
    const __nv_bfloat16* wkv;
    const __nv_bfloat16* wv;
    int tk;
};

template <int BK_, int NBLK> struct Geo {
    static constexpr int BK = BK_, A_BYTES = 128 * BK * 2, A_SWZ = BK == 64 ? 1 : 2, A_SBO = BK * 16;
    static constexpr int BLK = BK * 64;
    static constexpr int B_BYTES = NBLK * BLK, B_SWZ = 2, B_LBO = BLK, B_SBO = 512, B_KSTEP = 1024;
};
template <> struct Geo<64, 0> {
    static constexpr int BK = 64, A_BYTES = 128 * 128, A_SWZ = 1, A_SBO = 1024, BLK = 8192;
    static constexpr int B_BYTES = 64 * 128, B_SWZ = 1, B_LBO = 8192, B_SBO = 1024, B_KSTEP = 2048;
};
#define F1_BK 32
template <int EPI> struct EpiGeo;
template <> struct EpiGeo<EPI_QKV> { using G = Geo<64, 3>; };
template <> struct EpiGeo<EPI_RES> { using G = Geo<64, 0>; };
template <> struct EpiGeo<EPI_FFN1> { using G = Geo<F1_BK, 7>; };

template <int STAGES, int EPI> struct GemmSmem {
    using G = typename EpiGeo<EPI>::G;
    static constexpr int STAGE = G::A_BYTES + G::B_BYTES;
    static constexpr int AUX_OFF = STAGES * STAGE;
    static constexpr int TOTAL = AUX_OFF + 1152;
    static constexpr int TOTAL_SELF = AUX_OFF + 704 + 1024 + 1280;
};

struct RowStatRaw { float2 a0, a1, b0, b1; };
__device__ __forceinline__ RowStatRaw load_row_stats(const float2* __restrict__ st, int row0, int c) {
    RowStatRaw r;
    r.a0 = st[(2 * c) * S_ + row0]; r.a1 = st[(2 * c + 1) * S_ + row0];
    r.b0 = st[(2 * c) * S_ + row0 + 8]; r.b1 = st[(2 * c + 1) * S_ + row0 + 8];
    return r;
}
__device__ __forceinline__ void finish_row_stats(const RowStatRaw& r, float& mean0, float& rstd0, float& mean1, float& rstd1) {
    float sa = r.a0.x + r.a1.x, sb = r.b0.x + r.b1.x;
    sa += __shfl_xor_sync(0xffffffffu, sa, 1); sa += __shfl_xor_sync(0xffffffffu, sa, 2);
    sb += __shfl_xor_sync(0xffffffffu, sb, 1); sb += __shfl_xor_sync(0xffffffffu, sb, 2);
    mean0 = sa * 0.125f; mean1 = sb * 0.125f;
    float ma = r.a0.y + r.a1.y + 64.f * ((r.a0.x - mean0) * (r.a0.x - mean0) + (r.a1.x - mean0) * (r.a1.x - mean0));
    float mb = r.b0.y + r.b1.y + 64.f * ((r.b0.x - mean1) * (r.b0.x - mean1) + (r.b1.x - mean1) * (r.b1.x - mean1));
    ma += __shfl_xor_sync(0xffffffffu, ma, 1); ma += __shfl_xor_sync(0xffffffffu, ma, 2);
    mb += __shfl_xor_sync(0xffffffffu, mb, 1); mb += __shfl_xor_sync(0xffffffffu, mb, 2);
    rstd0 = 1.0f / sqrtf(ma * (1.f / 512.f) + 1e-5f);
    rstd1 = 1.0f / sqrtf(mb * (1.f / 512.f) + 1e-5f);
}

template <int BN, int KB, int STAGES, int EPI, int MC, bool SELF = false>
__device__ __forceinline__ void gemm_body(const CUtensorMap* mapA, const CUtensorMap* mapB, const CUtensorMap* mapB2, const CUtensorMap* mapR,
                                          const CUtensorMap* mapC, const GemmParams& prm, int tile_m, int tile_n, uint8_t* smem_raw) {
    using SM = GemmSmem<STAGES, EPI>;
    using G = typename SM::G;
    constexpr bool XKV = BN == 80;
    constexpr int TN = EPI == EPI_QKV ? 64 : BN;
    pdl_launch();
    const uint32_t sbase = smem_u32(smem_raw);
    if (sbase & 1023) __trap();
    uint8_t* sgen = smem_raw;
    const uint32_t bar_full = sbase + SM::AUX_OFF, bar_empty = bar_full + 8 * STAGES;
    float* s_cs = (float*)(sgen + SM::AUX_OFF + 256);
    float* s_row = (float*)(sgen + SM::AUX_OFF + 704);
    float* s_red = (float*)(sgen + SM::AUX_OFF + 640);
    const int tid = threadIdx.x, lane = tid & 31;
    const int warp = __shfl_sync(0xffffffffu, tid >> 5, 0);
    const uint32_t rank = MC ? cluster_rank() : 0;
    if (tid == 0) TL(prm.tk, 0);

    constexpr bool INLINE_PROD = EPI == EPI_FFN1 && F1_INLINE;
    constexpr int PWARP = INLINE_PROD ? 0 : 8;
    if (warp == PWARP && elect_one()) {
        prefetch_tmap(mapB); prefetch_tmap(mapA); prefetch_tmap(mapC);
        for (int s = 0; s < STAGES; s++) { mbar_init(bar_full + 8 * s, 1); mbar_init(bar_empty + 8 * s, MC ? 4 : 2); }
        fence_mbar_init();
    }
    __syncthreads();
    if (MC) cluster_sync();

    const int m0 = tile_m * 128, n0 = tile_n * TN;
    constexpr uint32_t STAGE_TX = G::A_BYTES + (EPI == EPI_QKV ? 2 * G::BLK : G::B_BYTES);
    auto loadB = [&](int kb, int s) {
        const uint32_t dst = sbase + s * SM::STAGE + G::A_BYTES, bar = bar_full + 8 * s;
        if constexpr (EPI == EPI_RES) {
            tma2d(dst, mapB, n0, kb * 64, bar);
        } else if constexpr (EPI == EPI_QKV) {
            tma3d(dst, mapB, 0, kb * G::BK, tile_n * 2, bar);
        } else {
            if constexpr (MC == 2) {
                if (rank == 0) tma3d_mc(dst, mapB, 0, kb * G::BK, tile_n * 7, bar, 3);
                else tma3d_mc(dst + 4 * G::BLK, mapB2, 0, kb * G::BK, tile_n * 7 + 4, bar, 3);
            } else {
                tma3d(dst, mapB, 0, kb * G::BK, tile_n * 7, bar);
                tma3d(dst + 4 * G::BLK, mapB2, 0, kb * G::BK, tile_n * 7 + 4, bar);
            }
        }
    };
    auto loadA = [&](int kb, int s) {
        const uint32_t dst = sbase + s * SM::STAGE, bar = bar_full + 8 * s;
        if constexpr (MC == 1) tma2d_mc(dst + rank * (G::A_BYTES / 2), mapA, kb * G::BK, m0 + rank * 64, bar, 3);
        else tma2d(dst, mapA, kb * G::BK, m0, bar);
    };
    constexpr int PRE = STAGES < KB ? STAGES : KB;
#define F1_LAG 2
    constexpr int LAG = F1_LAG;
    constexpr int PRE_B = PRE < PREB ? PRE : PREB;
    auto prologue_loads = [&]() {
        if (elect_one()) {
#pragma unroll
            for (int kb = 0; kb < PRE; kb++) mbar_expect_tx(bar_full + 8 * kb, STAGE_TX);
#pragma unroll
            for (int kb = 0; kb < PRE_B; kb++) loadB(kb, kb);
        }
        if (!SELF) pdl_wait();
        if (elect_one()) {
#pragma unroll
            for (int kb = 0; kb < PRE; kb++) {
                loadA(kb, kb);
                if (kb + PRE_B < PRE) loadB(kb + PRE_B, kb + PRE_B);
            }
            if constexpr (EPI == EPI_RES && KB < STAGES) {
                mbar_expect_tx(bar_full + 8 * KB, 16384);
                tma2d(sbase + KB * SM::STAGE, mapR, n0, m0, bar_full + 8 * KB);
            }
        }
    };
    if (SELF && warp > 8) {
        static_assert(!SELF || (STAGES >= KB && EPI == EPI_QKV), "SELF needs every k block resident");
        const int t = tid - 288;
        float ss[4] = {0.f, 0.f, 0.f, 0.f}, sq[4] = {0.f, 0.f, 0.f, 0.f};
        auto row_stats = [&](int kb) {
            const uint32_t arow = sbase + kb * SM::STAGE + (t >> 1) * 128;
            uint32_t w[4][4];
#pragma unroll
            for (int j = 0; j < 4; j++)
                asm volatile("ld.shared.v4.u32 {%0,%1,%2,%3}, [%4];" : "=r"(w[j][0]), "=r"(w[j][1]), "=r"(w[j][2]), "=r"(w[j][3])
                             : "r"(arow + (((2 * j + (t & 1) + 2 * ((t >> 1) & 3)) & 7) << 4)));
#pragma unroll
            for (int j = 0; j < 4; j++)
#pragma unroll
                for (int i = 0; i < 4; i++) {
                    const float lo = bf_lo(w[j][i]), hi = bf_hi(w[j][i]);
                    ss[i] += lo + hi;
                    sq[i] = fmaf(lo, lo, fmaf(hi, hi, sq[i]));
                }
        };
        if ((warp >> 2) == 3) {
            float csum[BN / 2];
            const uint64_t dB0 = mkdesc(sbase + G::A_BYTES, G::B_LBO, G::B_SBO, G::B_SWZ);
            if constexpr (XKV) named_bar(6, 512);
#pragma unroll 1
            for (int kb = 0; kb < KB; kb++) {
                mbar_wait(bar_full + 8 * kb, 0);
                const uint64_t dB = dB0 + (uint64_t)(kb * (SM::STAGE >> 4));
                wg_fence();
#pragma unroll
                for (int k = 0; k < G::BK / 16; k++) {
                    if constexpr (SELF) wgmma_rs_ones<BN>(csum, dB + (uint64_t)(k * (G::B_KSTEP >> 4)), (kb | k) != 0);
                }
                wg_commit();
                row_stats(kb);
            }
            wg_wait<0>();
            fence_regs(csum);
            if (warp == 12 && lane < 4) {
#pragma unroll
                for (int j = 0; j < BN / 8; j++) {
                    const float2 v = make_float2(csum[4 * j], csum[4 * j + 1]);
                    *(float2*)(s_cs + 8 * j + 2 * lane) = v;
                    if (tile_m == 0) {
                        if (j < 8) *(float2*)(g_cs_q + n0 + 8 * j + 2 * lane) = v;
                        else *(float2*)(g_cs_kv + tile_n * 16 + 8 * (j - 8) + 2 * lane) = v;
                    }
                }
            }
        } else {
            if constexpr (XKV) named_bar(6, 512);
#pragma unroll 1
            for (int kb = 0; kb < KB; kb++) {
                mbar_wait(bar_full + 8 * kb, 0);
                row_stats(kb);
            }
        }
        float tsum = (ss[0] + ss[1]) + (ss[2] + ss[3]), tsq = (sq[0] + sq[1]) + (sq[2] + sq[3]);
        tsum += __shfl_xor_sync(0xffffffffu, tsum, 1);
        tsq += __shfl_xor_sync(0xffffffffu, tsq, 1);
        if ((t & 1) == 0) {
            const float md = tsum * (1.f / 512.f);
            const float var = fmaxf(tsq * (1.f / 512.f) - md * md, 0.f);
            *(float2*)(s_row + t) = make_float2(md, 1.0f / sqrtf(var + 1e-5f));
        }
        named_bar(4, 512);
    } else if (!INLINE_PROD && warp == 8) {
        prologue_loads();
        int s = PRE % STAGES, ph = (PRE / STAGES) & 1;
#pragma unroll 1
        for (int kb = PRE; kb < KB; kb++) {
            mbar_wait(bar_empty + 8 * s, ph ^ 1);
            if (elect_one()) {
                mbar_expect_tx(bar_full + 8 * s, STAGE_TX);
                loadB(kb, s);
                loadA(kb, s);
            }
            if (++s == STAGES) { s = 0; ph ^= 1; }
        }
        if constexpr (EPI == EPI_RES && KB >= STAGES) {
            mbar_wait(bar_empty + 8 * s, ph ^ 1);
            if (elect_one()) {
                mbar_expect_tx(bar_full + 8 * s, 16384);
                tma2d(sbase + s * SM::STAGE, mapR, n0, m0, bar_full + 8 * s);
            }
        }
    } else {
        if (INLINE_PROD && warp == 0) prologue_loads();
        const int wg = warp >> 2, g = lane >> 2, c = lane & 3;
        const int rloc = wg * 64 + (warp & 3) * 16 + g;
        const int row0 = m0 + rloc;
        float mean0 = 0.f, rstd0 = 1.f, mean1 = 0.f, rstd1 = 1.f;
        if constexpr (XKV) {
            static_assert(!XKV || STAGES >= KB, "the K / V weight block must stay resident");
            const __nv_bfloat16* wsrc = tile_n == 0 ? prm.wkv : prm.wv;
            uint4 v[4];
#pragma unroll
            for (int i = 0; i < 4; i++) v[i] = __ldg((const uint4*)wsrc + tid + 256 * i);
#pragma unroll
            for (int i = 0; i < 4; i++) {
                const int idx = tid + 256 * i, k = idx >> 1, kr = k & 63;
                const uint32_t dst = sbase + (k >> 6) * SM::STAGE + G::A_BYTES + 2 * G::BLK + kr * 64 + (((idx & 1) ^ ((kr >> 1) & 3)) << 4);
                asm volatile("st.shared.v4.u32 [%0], {%1,%2,%3,%4};" ::"r"(dst), "r"(v[i].x), "r"(v[i].y), "r"(v[i].z), "r"(v[i].w) : "memory");
            }
            fence_async_smem();
            if constexpr (SELF) named_bar(6, 512); else named_bar(6, 256);
        }
        RowStatRaw raw;
        float csv = 0.f;
        float2 cskv[2] = {make_float2(0.f, 0.f), make_float2(0.f, 0.f)};
        auto ln_inputs = [&]() {
            pdl_wait();
            if constexpr (EPI != EPI_RES) {
                raw = load_row_stats(prm.stats_in, row0, c);
                const float* cs = EPI == EPI_FFN1 ? g_cs_1 + n0 : g_cs_q + n0;
                if (tid < TN) csv = cs[tid];
                if constexpr (XKV) {
                    cskv[0] = *(const float2*)(g_cs_kv + tile_n * 16 + 2 * c);
                    cskv[1] = *(const float2*)(g_cs_kv + tile_n * 16 + 8 + 2 * c);
                }
            }
        };
        if (!SELF) ln_inputs();
        float acc[BN / 2];
        const uint64_t dA0 = mkdesc(sbase + wg * (G::A_BYTES / 2), 16, G::A_SBO, G::A_SWZ);
        const uint64_t dB0 = mkdesc(sbase + G::A_BYTES, G::B_LBO, G::B_SBO, G::B_SWZ);
        int s = 0, ph = 0;
#pragma unroll 1
        for (int kb = 0; kb < KB; kb++) {
            mbar_wait(bar_full + 8 * s, ph);
            const uint64_t dA = dA0 + (uint64_t)(s * (SM::STAGE >> 4)), dB = dB0 + (uint64_t)(s * (SM::STAGE >> 4));
            wg_fence();
#pragma unroll
            for (int k = 0; k < G::BK / 16; k++) wgmma_ss_tb<BN>(acc, dA + (uint64_t)(k * 2), dB + (uint64_t)(k * (G::B_KSTEP >> 4)), (kb | k) != 0);
            wg_commit();
            if constexpr (EPI == EPI_RES && RES_WAIT0) {
                wg_wait<0>();
                if ((warp & 3) == 0 && elect_one()) {
                    if (MC) { mbar_arrive_remote(bar_empty + 8 * s, 0); mbar_arrive_remote(bar_empty + 8 * s, 1); }
                    else mbar_arrive(bar_empty + 8 * s);
                }
            } else if (kb > 0) {
                wg_wait<1>();
                const int sp = s == 0 ? STAGES - 1 : s - 1;
                if ((warp & 3) == 0 && elect_one()) {
                    if (MC) { mbar_arrive_remote(bar_empty + 8 * sp, 0); mbar_arrive_remote(bar_empty + 8 * sp, 1); }
                    else mbar_arrive(bar_empty + 8 * sp);
                }
                if (INLINE_PROD && warp == 0 && kb >= LAG && kb - LAG + STAGES < KB) {
                    const int sq = LAG == 1 ? sp : (sp == 0 ? STAGES - 1 : sp - 1);
                    mbar_wait(bar_empty + 8 * sq, ((kb - LAG) / STAGES) & 1);
                    if (elect_one()) {
                        mbar_expect_tx(bar_full + 8 * sq, STAGE_TX);
                        loadB(kb - LAG + STAGES, sq);
                        loadA(kb - LAG + STAGES, sq);
                    }
                }
            }
            if (++s == STAGES) { s = 0; ph ^= 1; }
        }
        if constexpr (SELF) {
            named_bar(4, 512);
            const float2 r0 = *(const float2*)(s_row + 2 * rloc), r1 = *(const float2*)(s_row + 2 * rloc + 16);
            mean0 = r0.x; rstd0 = r0.y; mean1 = r1.x; rstd1 = r1.y;
        } else if constexpr (EPI != EPI_RES) {
            finish_row_stats(raw, mean0, rstd0, mean1, rstd1);
            if (tid < TN) s_cs[tid] = csv;
        }
        wg_wait<0>();
        fence_regs(acc);
        if (tid == 0) TL(prm.tk, 2);
        if constexpr (EPI != EPI_RES) named_bar(1, 256);

        if constexpr (EPI != EPI_FFN1) {
            const uint32_t stile = sbase + (EPI == EPI_RES ? s * SM::STAGE : 0);
            const int mrow = wg * 64 + (warp & 3) * 16 + (lane & 7) + ((lane >> 3) & 1) * 8;
            const uint32_t rbase = stile + mrow * 128;
            if constexpr (EPI == EPI_RES) {
                mbar_wait(bar_full + 8 * s, ph);
                float s0 = 0.f, s1 = 0.f;
#pragma unroll
                for (int jj = 0; jj < 4; jj++) {
                    uint32_t r0, r1, r2, r3;
                    const uint32_t addr = rbase + (((2 * jj + (lane >> 4)) ^ (mrow & 7)) << 4);
                    ldsm_x4(r0, r1, r2, r3, addr);
                    const uint32_t u0 = pack_bf16(acc[8 * jj] + bf_lo(r0), acc[8 * jj + 1] + bf_hi(r0));
                    const uint32_t u1 = pack_bf16(acc[8 * jj + 2] + bf_lo(r1), acc[8 * jj + 3] + bf_hi(r1));
                    const uint32_t u2 = pack_bf16(acc[8 * jj + 4] + bf_lo(r2), acc[8 * jj + 5] + bf_hi(r2));
                    const uint32_t u3 = pack_bf16(acc[8 * jj + 6] + bf_lo(r3), acc[8 * jj + 7] + bf_hi(r3));
                    stsm_x4(addr, u0, u1, u2, u3);
                    acc[8 * jj] = bf_lo(u0); acc[8 * jj + 1] = bf_hi(u0); acc[8 * jj + 4] = bf_lo(u2); acc[8 * jj + 5] = bf_hi(u2);
                    acc[8 * jj + 2] = bf_lo(u1); acc[8 * jj + 3] = bf_hi(u1); acc[8 * jj + 6] = bf_lo(u3); acc[8 * jj + 7] = bf_hi(u3);
                    s0 += (acc[8 * jj] + acc[8 * jj + 1]) + (acc[8 * jj + 4] + acc[8 * jj + 5]);
                    s1 += (acc[8 * jj + 2] + acc[8 * jj + 3]) + (acc[8 * jj + 6] + acc[8 * jj + 7]);
                }
                fence_async_smem();
                named_bar(2 + wg, 128);
                if ((warp & 3) == 0 && elect_one()) { tma2d_store(mapC, stile + wg * 8192, n0, m0 + wg * 64); bulk_commit(); }
                if (prm.stats_out) {
                    s0 += __shfl_xor_sync(0xffffffffu, s0, 1); s0 += __shfl_xor_sync(0xffffffffu, s0, 2);
                    s1 += __shfl_xor_sync(0xffffffffu, s1, 1); s1 += __shfl_xor_sync(0xffffffffu, s1, 2);
                    const float mu0 = s0 * (1.f / 64.f), mu1 = s1 * (1.f / 64.f);
                    float q0 = 0.f, q1 = 0.f;
#pragma unroll
                    for (int j = 0; j < 8; j++) {
                        float d;
                        d = acc[4 * j] - mu0; q0 += d * d; d = acc[4 * j + 1] - mu0; q0 += d * d;
                        d = acc[4 * j + 2] - mu1; q1 += d * d; d = acc[4 * j + 3] - mu1; q1 += d * d;
                    }
                    q0 += __shfl_xor_sync(0xffffffffu, q0, 1); q0 += __shfl_xor_sync(0xffffffffu, q0, 2);
                    q1 += __shfl_xor_sync(0xffffffffu, q1, 1); q1 += __shfl_xor_sync(0xffffffffu, q1, 2);
                    if (c == 0) {
                        prm.stats_out[tile_n * S_ + row0] = make_float2(mu0, q0);
                        prm.stats_out[tile_n * S_ + row0 + 8] = make_float2(mu1, q1);
                    }
                }
            } else {
                const float sc = 0.25f * 1.4426950408889634f;
                const float a0 = rstd0 * sc, a1 = rstd1 * sc, rm0 = a0 * mean0, rm1 = a1 * mean1;
#pragma unroll
                for (int jj = 0; jj < 4; jj++) {
                    const float2 ca = *(const float2*)(s_cs + 16 * jj + 2 * c), cb = *(const float2*)(s_cs + 16 * jj + 8 + 2 * c);
                    const uint32_t u0 = pack_bf16(acc[8 * jj] * a0 - rm0 * ca.x, acc[8 * jj + 1] * a0 - rm0 * ca.y);
                    const uint32_t u1 = pack_bf16(acc[8 * jj + 2] * a1 - rm1 * ca.x, acc[8 * jj + 3] * a1 - rm1 * ca.y);
                    const uint32_t u2 = pack_bf16(acc[8 * jj + 4] * a0 - rm0 * cb.x, acc[8 * jj + 5] * a0 - rm0 * cb.y);
                    const uint32_t u3 = pack_bf16(acc[8 * jj + 6] * a1 - rm1 * cb.x, acc[8 * jj + 7] * a1 - rm1 * cb.y);
                    stsm_x4(rbase + (((2 * jj + (lane >> 4)) ^ (mrow & 7)) << 4), u0, u1, u2, u3);
                }
                fence_async_smem();
                named_bar(2 + wg, 128);
                if ((warp & 3) == 0 && elect_one()) { tma2d_store(mapC, stile + wg * 8192, n0, m0 + wg * 64); bulk_commit(); }
            }
            if constexpr (XKV) {
                {
                    const float* acx = &acc[32];
                    const float rm0 = rstd0 * mean0, rm1 = rstd1 * mean1;
                    float n0s = 0.f, n1s = 0.f, vmax = 0.f;
#pragma unroll
                    for (int j = 0; j < 2; j++) {
                        const float2 cs2 = SELF ? *(const float2*)(s_cs + 64 + 8 * j + 2 * c) : cskv[j];
                        const uint32_t u0 = pack_bf16(acx[4 * j] * rstd0 - rm0 * cs2.x, acx[4 * j + 1] * rstd0 - rm0 * cs2.y);
                        const uint32_t u1 = pack_bf16(acx[4 * j + 2] * rstd1 - rm1 * cs2.x, acx[4 * j + 3] * rstd1 - rm1 * cs2.y);
                        n0s += bf_lo(u0) * bf_lo(u0) + bf_hi(u0) * bf_hi(u0);
                        n1s += bf_lo(u1) * bf_lo(u1) + bf_hi(u1) * bf_hi(u1);
                        vmax = fmaxf(vmax, fmaxf(fmaxf(fabsf(bf_lo(u0)), fabsf(bf_hi(u0))), fmaxf(fabsf(bf_lo(u1)), fabsf(bf_hi(u1)))));
                        if (tile_n == 0) {
                            *(uint32_t*)(g_kimg + (row0 >> 3) * 256 + j * 128 + g * 16 + c * 4) = u0;
                            *(uint32_t*)(g_kimg + ((row0 + 8) >> 3) * 256 + j * 128 + g * 16 + c * 4) = u1;
                        } else {
                            uint8_t* vb = g_vimg + (row0 >> 4) * 768 + j * 256 + g * 16 + c * 4;
                            *(uint32_t*)(vb) = u0;
                            *(uint32_t*)(vb + 128) = u1;
                        }
                    }
                    if (tile_n == 1) {
                        uint8_t* vb = g_vimg + (row0 >> 4) * 768 + 512 + g * 16 + c * 4;
                        const uint32_t one = c == 0 ? 0x00003F80u : 0u;
                        *(uint32_t*)(vb) = one;
                        *(uint32_t*)(vb + 128) = one;
                    }
                    n0s += __shfl_xor_sync(0xffffffffu, n0s, 1); n0s += __shfl_xor_sync(0xffffffffu, n0s, 2);
                    n1s += __shfl_xor_sync(0xffffffffu, n1s, 1); n1s += __shfl_xor_sync(0xffffffffu, n1s, 2);
                    float km = tile_n == 0 ? fmaxf(n0s, n1s) : vmax;
                    if (!(n0s + n1s < INFINITY)) km = INFINITY;
#pragma unroll
                    for (int o = 1; o < 32; o <<= 1) km = fmaxf(km, __shfl_xor_sync(0xffffffffu, km, o));
                    if (lane == 0) s_red[warp] = km;
                    named_bar(1, 256);
                    if (tid == 0) {
                        float a = 0.f;
                        for (int i = 0; i < 8; i++) a = fmaxf(a, s_red[i]);
                        g_kvmax[tile_n * 16 + tile_m] = a;
                    }
                }
            }
            if ((warp & 3) == 0) bulk_wait_read();
        } else {
            const uint32_t stile = sbase + wg * (7 * 4096);
            const int mrow = (warp & 3) * 16 + (lane & 7) + ((lane >> 3) & 1) * 8;
            const float a0 = 0.5f * rstd0, a1 = 0.5f * rstd1, rm0 = a0 * mean0, rm1 = a1 * mean1;
#pragma unroll
            for (int jj = 0; jj < 14; jj++) {
                const float2 ca = *(const float2*)(s_cs + 16 * jj + 2 * c), cb = *(const float2*)(s_cs + 16 * jj + 8 + 2 * c);
                float y[8] = {acc[8 * jj] * a0 - rm0 * ca.x,     acc[8 * jj + 1] * a0 - rm0 * ca.y,
                              acc[8 * jj + 2] * a1 - rm1 * ca.x, acc[8 * jj + 3] * a1 - rm1 * ca.y,
                              acc[8 * jj + 4] * a0 - rm0 * cb.x, acc[8 * jj + 5] * a0 - rm0 * cb.y,
                              acc[8 * jj + 6] * a1 - rm1 * cb.x, acc[8 * jj + 7] * a1 - rm1 * cb.y};
#pragma unroll
                for (int i = 0; i < 8; i++) {
                    float t;
                    asm("tanh.approx.f32 %0, %1;" : "=f"(t) : "f"(y[i]));
                    y[i] = fmaf(y[i], t, y[i]);
                }
                const int chunk = (2 * jj + (lane >> 4)) & 3, blk = jj >> 1;
                stsm_x4(stile + blk * 4096 + mrow * 64 + ((chunk ^ ((mrow >> 1) & 3)) << 4),
                        pack_bf16(y[0], y[1]), pack_bf16(y[2], y[3]), pack_bf16(y[4], y[5]), pack_bf16(y[6], y[7]));
                if (jj & 1) {
                    fence_async_smem();
                    __syncwarp();
                    if (elect_one()) {
                        tma2d_store(mapC, stile + blk * 4096 + (warp & 3) * 1024, n0 + blk * 32, m0 + wg * 64 + (warp & 3) * 16);
                        bulk_commit();
                    }
                }
            }
            bulk_wait_read();
        }
    }
    if (tid == 0) TL(prm.tk, 3);
    if (MC) cluster_sync();
}

#define WO_ST 9
#define F2_ST 6
#define F1_ST (F1_BK == 64 ? 5 : 9)
#define QKV_ST 8
constexpr int QKV_STAGES = QKV_ST, WO_STAGES = WO_ST, FFN2_STAGES = F2_ST, FFN1_STAGES = F1_ST;
template <bool SELF>
__global__ void __launch_bounds__(SELF ? 544 : 288) qkv_kernel(const __grid_constant__ CUtensorMap mapA, const __grid_constant__ CUtensorMap mapWq,
                                                  const __grid_constant__ CUtensorMap mapQ, const GemmParams prm) {
    extern __shared__ __align__(1024) uint8_t smem_raw[];
    const int tn = blockIdx.x & 7;
    if (tn < 2) gemm_body<80, 8, QKV_STAGES, EPI_QKV, QKV_MC, SELF>(&mapA, &mapWq, &mapWq, &mapA, &mapQ, prm, blockIdx.x >> 3, tn, smem_raw);
    else gemm_body<64, 8, QKV_STAGES, EPI_QKV, QKV_MC, SELF>(&mapA, &mapWq, &mapWq, &mapA, &mapQ, prm, blockIdx.x >> 3, tn, smem_raw);
}
template <int KB, int STAGES>
__global__ void __launch_bounds__(288) res_gemm_kernel(const __grid_constant__ CUtensorMap mapA, const __grid_constant__ CUtensorMap mapW,
                                                       const __grid_constant__ CUtensorMap mapR, const __grid_constant__ CUtensorMap mapC, const GemmParams prm) {
    extern __shared__ __align__(1024) uint8_t smem_raw[];
    gemm_body<64, KB, STAGES, EPI_RES, (KB == 8 ? WO_MC : F2_MC)>(&mapA, &mapW, &mapW, &mapR, &mapC, prm, blockIdx.x >> 3, blockIdx.x & 7, smem_raw);
}
__global__ void __launch_bounds__(F1_INLINE ? 256 : 288) ffn1_kernel(const __grid_constant__ CUtensorMap mapA, const __grid_constant__ CUtensorMap mapW4,
                                                   const __grid_constant__ CUtensorMap mapW3, const __grid_constant__ CUtensorMap mapH, const GemmParams prm) {
    extern __shared__ __align__(1024) uint8_t smem_raw[];
    const int pair = blockIdx.x >> 1, tile_n = pair & 7, tile_m = (pair >> 3) * 2 + (blockIdx.x & 1);
    gemm_body<224, 512 / F1_BK, FFN1_STAGES, EPI_FFN1, F1_MC>(&mapA, &mapW4, &mapW3, &mapA, &mapH, prm, tile_m, tile_n, smem_raw);
}

constexpr int NPOLY = 10;
__host__ __device__ constexpr bool is_mufu(int i) { return ((i + 1) * (16 - NPOLY)) / 16 != (i * (16 - NPOLY)) / 16; }

__device__ __forceinline__ float ex2(float x) { float r; asm("ex2.approx.ftz.f32 %0, %1;" : "=f"(r) : "f"(x)); return r; }
__device__ __forceinline__ uint32_t exp_pair_mufu(float a, float b) { return pack_bf16(ex2(a), ex2(b)); }
__device__ __forceinline__ uint32_t exp_pair_fma(float a, float b, uint32_t c3f) {
    constexpr float MAGIC = 98430.4140625f;
    const float ta = a + MAGIC, tb = b + (MAGIC - 143.5f);
    uint32_t y, m, r;
    asm("mad.lo.u32 %0, %1, 65536, %2;" : "=r"(y) : "r"(__float_as_uint(tb)), "r"(__float_as_uint(ta)));
    asm("lop3.b32 %0, %1, 0x007F007F, %2, 0xEA;" : "=r"(m) : "r"(y), "r"(c3f));
    const uint32_t e = y & 0xFF80FF80u;
    asm("fma.rn.bf16x2 %0, %1, %2, %3;" : "=r"(r) : "r"(y), "r"(m), "r"(e));
    return r;
}

constexpr int KCH = 256, NCH = S_ / KCH;
constexpr int K_BYTES = S_ * 32, V_BYTES = (S_ / 16) * 768;
constexpr int ATT_SMEM = K_BYTES + V_BYTES;

__global__ void __launch_bounds__(512, 1) attn_kernel(const __nv_bfloat16* __restrict__ wo, const __nv_bfloat16* __restrict__ w1,
                                                       const __nv_bfloat16* __restrict__ w2, int tk) {
    extern __shared__ __align__(1024) uint8_t smem[];
    __shared__ uint64_t bars[NCH];
    __shared__ int s_slow;
    const int tid = threadIdx.x, wg = tid >> 7, warp = (tid >> 5) & 3, lane = tid & 31;
    const uint32_t sK = smem_u32(smem), sV = sK + K_BYTES;
    if (blockIdx.x >= 128) {
        pdl_launch();
        side_job(blockIdx.x - 128, (float*)smem, wo, w1, w2);
        return;
    }
    if (tid == 0) TL(tk, 0);
    if (tid == 0) {
        for (int i = 0; i < NCH; i++) mbar_init(smem_u32(&bars[i]), 1);
        s_slow = 0;
        fence_mbar_init();
    }
    __syncthreads();
    pdl_launch();
    pdl_wait();
    if (tid == 0) TL(tk, 1);
    if (__shfl_sync(0xffffffffu, tid >> 5, 0) == 0 && elect_one()) {
#pragma unroll
        for (int i = 0; i < NCH; i++) {
            mbar_expect_tx(smem_u32(&bars[i]), KCH * 32 + (KCH / 16) * 768);
            bulk_load(sK + i * KCH * 32, g_kimg + i * KCH * 32, KCH * 32, smem_u32(&bars[i]));
            bulk_load(sV + i * (KCH / 16) * 768, g_vimg + i * (KCH / 16) * 768, (KCH / 16) * 768, smem_u32(&bars[i]));
        }
    }
    const int tb = blockIdx.x >> 3, hg = blockIdx.x & 7;
    const int head = hg * 4 + wg;
    const int g = lane >> 2, c = lane & 3;
    uint32_t qa[2][4];
    float qn = 0.f;
#pragma unroll
    for (int m = 0; m < 2; m++) {
        const int row = tb * 128 + m * 64 + warp * 16 + g;
        const uint32_t* p0 = (const uint32_t*)(g_q + (size_t)row * D_ + head * 16);
        const uint32_t* p1 = (const uint32_t*)(g_q + (size_t)(row + 8) * D_ + head * 16);
        qa[m][0] = p0[c]; qa[m][1] = p1[c]; qa[m][2] = p0[c + 4]; qa[m][3] = p1[c + 4];
        float n0 = bf_lo(qa[m][0]) * bf_lo(qa[m][0]) + bf_hi(qa[m][0]) * bf_hi(qa[m][0]) + bf_lo(qa[m][2]) * bf_lo(qa[m][2]) + bf_hi(qa[m][2]) * bf_hi(qa[m][2]);
        float n1 = bf_lo(qa[m][1]) * bf_lo(qa[m][1]) + bf_hi(qa[m][1]) * bf_hi(qa[m][1]) + bf_lo(qa[m][3]) * bf_lo(qa[m][3]) + bf_hi(qa[m][3]) * bf_hi(qa[m][3]);
        n0 += __shfl_xor_sync(0xffffffffu, n0, 1); n0 += __shfl_xor_sync(0xffffffffu, n0, 2);
        n1 += __shfl_xor_sync(0xffffffffu, n1, 1); n1 += __shfl_xor_sync(0xffffffffu, n1, 2);
        if (!(n0 == n0) || !(n1 == n1)) n0 = __int_as_float(0x7f800000);
        qn = fmaxf(qn, fmaxf(n0, n1));
    }
    {
        float km = 0.f, vm = 0.f;
#pragma unroll
        for (int i = 0; i < 16; i++) { km = fmaxf(km, g_kvmax[i]); vm = fmaxf(vm, g_kvmax[16 + i]); }
        const bool ok = (qn * km <= 10000.f) && (vm <= 16384.f);
        if (!ok) s_slow = 1;
    }
    float oacc[2][12];
#pragma unroll
    for (int m = 0; m < 2; m++)
#pragma unroll
        for (int i = 0; i < 12; i++) oacc[m][i] = 0.f;
    __syncthreads();
    const bool slow = s_slow != 0;

    const uint64_t dK0 = mkdesc(sK, 128, 256, 0);
    const uint64_t dV0 = mkdesc(sV, 128, 256, 0);
    uint32_t c3f;
    asm volatile("mov.b32 %0, 0x3F003F00;" : "=r"(c3f));
    if (!slow) {
#pragma unroll 1
        for (int t = 0; t < S_ / 64; t++) {
            if ((t & 3) == 0) mbar_wait(smem_u32(&bars[t >> 2]), 0);
            const uint64_t dK = dK0 + (uint64_t)(t * 64 * 32 / 16);
            const uint64_t dV = dV0 + (uint64_t)(t * 4 * 768 / 16);
#pragma unroll
            for (int m = 0; m < 2; m++) {
                float s[32];
                wg_fence();
                wgmma_rs_n64_z(s, qa[m][0], qa[m][1], qa[m][2], qa[m][3], dK);
                wg_commit();
                wg_wait<0>();
                fence_regs(s);
                uint32_t p[16];
#pragma unroll
                for (int i = 0; i < 16; i++) p[i] = is_mufu(i) ? exp_pair_mufu(s[2 * i], s[2 * i + 1]) : exp_pair_fma(s[2 * i], s[2 * i + 1], c3f);
                wg_fence();
#pragma unroll
                for (int kk = 0; kk < 4; kk++)
                    wgmma_rs_n24_tb(oacc[m], p[4 * kk], p[4 * kk + 1], p[4 * kk + 2], p[4 * kk + 3], dV + (uint64_t)(kk * 768 / 16));
                wg_commit();
            }
        }
        wg_wait<0>();
    } else {
        float mx[2][2] = {{-INFINITY, -INFINITY}, {-INFINITY, -INFINITY}};
#pragma unroll 1
        for (int t = 0; t < S_ / 64; t++) {
            if ((t & 3) == 0) mbar_wait(smem_u32(&bars[t >> 2]), 0);
            const uint64_t dK = dK0 + (uint64_t)(t * 64 * 32 / 16);
            const uint64_t dV = dV0 + (uint64_t)(t * 4 * 768 / 16);
#pragma unroll
            for (int m = 0; m < 2; m++) {
                float s[32];
                wg_fence();
                wgmma_rs_n64_z(s, qa[m][0], qa[m][1], qa[m][2], qa[m][3], dK);
                wg_commit();
                wg_wait<0>();
                fence_regs(s);
                fence_regs(oacc[m]);
                float r0 = mx[m][0], r1 = mx[m][1];
#pragma unroll
                for (int j = 0; j < 8; j++) {
                    r0 = fmaxf(r0, fmaxf(s[4 * j], s[4 * j + 1]));
                    r1 = fmaxf(r1, fmaxf(s[4 * j + 2], s[4 * j + 3]));
                }
                r0 = fmaxf(r0, __shfl_xor_sync(0xffffffffu, r0, 1)); r0 = fmaxf(r0, __shfl_xor_sync(0xffffffffu, r0, 2));
                r1 = fmaxf(r1, __shfl_xor_sync(0xffffffffu, r1, 1)); r1 = fmaxf(r1, __shfl_xor_sync(0xffffffffu, r1, 2));
                const float al0 = ex2(mx[m][0] - r0), al1 = ex2(mx[m][1] - r1);
                mx[m][0] = r0; mx[m][1] = r1;
#pragma unroll
                for (int j = 0; j < 3; j++) {
                    oacc[m][4 * j] *= al0; oacc[m][4 * j + 1] *= al0;
                    oacc[m][4 * j + 2] *= al1; oacc[m][4 * j + 3] *= al1;
                }
                uint32_t p[16];
#pragma unroll
                for (int j = 0; j < 8; j++) {
                    p[2 * j] = pack_bf16(ex2(s[4 * j] - r0), ex2(s[4 * j + 1] - r0));
                    p[2 * j + 1] = pack_bf16(ex2(s[4 * j + 2] - r1), ex2(s[4 * j + 3] - r1));
                }
                fence_regs(oacc[m]);
                wg_fence();
#pragma unroll
                for (int kk = 0; kk < 4; kk++)
                    wgmma_rs_n24_tb(oacc[m], p[4 * kk], p[4 * kk + 1], p[4 * kk + 2], p[4 * kk + 3], dV + (uint64_t)(kk * 768 / 16));
                wg_commit();
                wg_wait<0>();
            }
        }
    }
    fence_regs(oacc[0]); fence_regs(oacc[1]);
    if (tid == 0) TL(tk, 2);
#pragma unroll
    for (int m = 0; m < 2; m++) {
        const float l0 = __shfl_sync(0xffffffffu, oacc[m][8], lane & ~3);
        const float l1 = __shfl_sync(0xffffffffu, oacc[m][10], lane & ~3);
        const float r0 = 1.0f / l0, r1 = 1.0f / l1;
        const int row = tb * 128 + m * 64 + warp * 16 + g;
        uint32_t* p0 = (uint32_t*)(g_o + (size_t)row * D_ + head * 16);
        uint32_t* p1 = (uint32_t*)(g_o + (size_t)(row + 8) * D_ + head * 16);
        p0[c] = pack_bf16(oacc[m][0] * r0, oacc[m][1] * r0);
        p1[c] = pack_bf16(oacc[m][2] * r1, oacc[m][3] * r1);
        p0[c + 4] = pack_bf16(oacc[m][4] * r0, oacc[m][5] * r0);
        p1[c + 4] = pack_bf16(oacc[m][6] * r1, oacc[m][7] * r1);
    }
    if (tid == 0) TL(tk, 3);
}

typedef CUresult (*EncodeFn)(CUtensorMap*, CUtensorMapDataType, cuuint32_t, void*, const cuuint64_t*, const cuuint64_t*, const cuuint32_t*,
                             const cuuint32_t*, CUtensorMapInterleave, CUtensorMapSwizzle, CUtensorMapL2promotion, CUtensorMapFloatOOBfill);

EncodeFn get_encode() {
    static EncodeFn fn = nullptr;
    if (!fn) {
        void* p = nullptr;
        cudaDriverEntryPointQueryResult qr;
        cudaGetDriverEntryPoint("cuTensorMapEncodeTiled", &p, cudaEnableDefault, &qr);
        fn = (EncodeFn)p;
    }
    return fn;
}
CUtensorMap map2d(const void* ptr, uint64_t cols, uint64_t rows, uint32_t bc, uint32_t br, CUtensorMapSwizzle sw) {
    CUtensorMap m;
    cuuint64_t gd[2] = {cols, rows}, gs[1] = {cols * 2};
    cuuint32_t bx[2] = {bc, br}, es[2] = {1, 1};
    get_encode()(&m, CU_TENSOR_MAP_DATA_TYPE_BFLOAT16, 2, (void*)ptr, gd, gs, bx, es, CU_TENSOR_MAP_INTERLEAVE_NONE, sw,
                 CU_TENSOR_MAP_L2_PROMOTION_L2_128B, CU_TENSOR_MAP_FLOAT_OOB_FILL_NONE);
    return m;
}
CUtensorMap map3d32(const void* ptr, uint64_t cols, uint64_t rows, uint32_t br, uint32_t nb) {
    CUtensorMap m;
    cuuint64_t gd[3] = {32, rows, cols / 32}, gs[2] = {cols * 2, 64};
    cuuint32_t bx[3] = {32, br, nb}, es[3] = {1, 1, 1};
    get_encode()(&m, CU_TENSOR_MAP_DATA_TYPE_BFLOAT16, 3, (void*)ptr, gd, gs, bx, es, CU_TENSOR_MAP_INTERLEAVE_NONE, CU_TENSOR_MAP_SWIZZLE_64B,
                 CU_TENSOR_MAP_L2_PROMOTION_L2_128B, CU_TENSOR_MAP_FLOAT_OOB_FILL_NONE);
    return m;
}

template <typename... KArgs, typename... Args>
void launch(void (*kern)(KArgs...), int grid, int block, int smem, int cluster, bool pdl, Args... args) {
    cudaLaunchConfig_t cfg = {};
    cfg.gridDim = dim3(grid);
    cfg.blockDim = dim3(block);
    cfg.dynamicSmemBytes = smem;
    cfg.stream = cudaStreamPerThread;
    cudaLaunchAttribute at[2];
    int n = 0;
    if (cluster > 1) { at[n].id = cudaLaunchAttributeClusterDimension; at[n].val.clusterDim.x = cluster; at[n].val.clusterDim.y = 1; at[n].val.clusterDim.z = 1; n++; }
    if (pdl) { at[n].id = cudaLaunchAttributeProgrammaticStreamSerialization; at[n].val.programmaticStreamSerializationAllowed = 1; n++; }
    cfg.attrs = at;
    cfg.numAttrs = n;
    cudaLaunchKernelEx(&cfg, kern, KArgs(args)...);
}

template <typename T> void* sym(const T& s) { void* p = nullptr; cudaGetSymbolAddress(&p, s); return p; }

}

extern "C" void kernel_launch(void* const* d_in, const int* in_sizes, int n_in, void* d_out, int out_size) {
    const __nv_bfloat16* x = (const __nv_bfloat16*)d_in[0];
    const __nv_bfloat16* wq = (const __nv_bfloat16*)d_in[1];
    const __nv_bfloat16* wk = (const __nv_bfloat16*)d_in[2];
    const __nv_bfloat16* wv = (const __nv_bfloat16*)d_in[3];
    const __nv_bfloat16* wo = (const __nv_bfloat16*)d_in[4];
    const __nv_bfloat16* w1 = (const __nv_bfloat16*)d_in[6];
    const __nv_bfloat16* w2 = (const __nv_bfloat16*)d_in[7];

    constexpr int SM_QKV = GemmSmem<QKV_STAGES, EPI_QKV>::TOTAL, SM_QKV0 = GemmSmem<QKV_STAGES, EPI_QKV>::TOTAL_SELF;
    static_assert(SM_QKV0 <= 232448, "shared memory");
    constexpr int HALF_PLUS = 116736;
    constexpr int SM_WO = GemmSmem<WO_STAGES, EPI_RES>::TOTAL > HALF_PLUS ? GemmSmem<WO_STAGES, EPI_RES>::TOTAL : HALF_PLUS;
    constexpr int SM_FFN2 = GemmSmem<FFN2_STAGES, EPI_RES>::TOTAL > HALF_PLUS ? GemmSmem<FFN2_STAGES, EPI_RES>::TOTAL : HALF_PLUS;
    constexpr int SM_FFN1 = GemmSmem<FFN1_STAGES, EPI_FFN1>::TOTAL;
    cudaFuncSetAttribute(qkv_kernel<false>, cudaFuncAttributeMaxDynamicSharedMemorySize, SM_QKV);
    cudaFuncSetAttribute(qkv_kernel<true>, cudaFuncAttributeMaxDynamicSharedMemorySize, SM_QKV0);
    cudaFuncSetAttribute(res_gemm_kernel<8, WO_STAGES>, cudaFuncAttributeMaxDynamicSharedMemorySize, SM_WO);
    cudaFuncSetAttribute(ffn1_kernel, cudaFuncAttributeMaxDynamicSharedMemorySize, SM_FFN1);
    cudaFuncSetAttribute(res_gemm_kernel<28, FFN2_STAGES>, cudaFuncAttributeMaxDynamicSharedMemorySize, SM_FFN2);
    cudaFuncSetAttribute(attn_kernel, cudaFuncAttributeMaxDynamicSharedMemorySize, ATT_SMEM);
    cudaFuncSetAttribute(qkv_kernel<false>, cudaFuncAttributePreferredSharedMemoryCarveout, 100);
    cudaFuncSetAttribute(qkv_kernel<true>, cudaFuncAttributePreferredSharedMemoryCarveout, 100);
    cudaFuncSetAttribute(res_gemm_kernel<8, WO_STAGES>, cudaFuncAttributePreferredSharedMemoryCarveout, 100);
    cudaFuncSetAttribute(ffn1_kernel, cudaFuncAttributePreferredSharedMemoryCarveout, 100);
    cudaFuncSetAttribute(res_gemm_kernel<28, FFN2_STAGES>, cudaFuncAttributePreferredSharedMemoryCarveout, 100);
    cudaFuncSetAttribute(attn_kernel, cudaFuncAttributePreferredSharedMemoryCarveout, 100);

    void *q = sym(g_q), *o = sym(g_o), *x1 = sym(g_x1), *x2 = sym(g_x2), *x3 = sym(g_x3), *h = sym(g_h);
    float2* stats = (float2*)sym(g_stats);
    const void* xs[5] = {x, x1, x2, x3, d_out};

    const CUtensorMapSwizzle SW128 = CU_TENSOR_MAP_SWIZZLE_128B, SW64 = CU_TENSOR_MAP_SWIZZLE_64B;
    const CUtensorMap mWq = map3d32(wq, D_, D_, 64, 2);
    const CUtensorMap mWo = map2d(wo, D_, D_, 64, 64, SW128);
    const CUtensorMap mW1a = map3d32(w1, F_, D_, F1_BK, 4), mW1b = map3d32(w1, F_, D_, F1_BK, 3);
    const CUtensorMap mW2 = map2d(w2, D_, F_, 64, 64, SW128);
    const CUtensorMap mQ = map2d(q, D_, S_, 64, 64, SW128);
    const CUtensorMap mHst = map2d(h, F_, S_, 32, 16, SW64);
    CUtensorMap mXa[4], mXf[4], mXr[4], mXs[5];
    for (int i = 0; i < 4; i++) {
        mXa[i] = map2d(xs[i], D_, S_, 64, QKV_MC ? 64 : 128, SW128);
        mXf[i] = F1_BK == 64 ? map2d(xs[i], D_, S_, 64, 128, SW128) : map2d(xs[i], D_, S_, 32, 128, SW64);
        mXr[i] = map2d(xs[i], D_, S_, 64, 128, SW128);
    }
    for (int i = 0; i < 5; i++) mXs[i] = map2d(xs[i], D_, S_, 64, 64, SW128);
    const CUtensorMap mOa = map2d(o, D_, S_, 64, WO_MC ? 64 : 128, SW128);
    const CUtensorMap mHa = map2d(h, F_, S_, 64, F2_MC ? 64 : 128, SW128);

    for (int layer = 0; layer < 2; layer++) {
        const int xi = layer * 2;
        GemmParams p;
        p.wkv = wk; p.wv = wv;
        p.stats_in = stats + (size_t)xi * 8 * S_; p.stats_out = nullptr; p.tk = 1 + 5 * layer;
        if (layer == 0) launch(qkv_kernel<true>, 128, 544, SM_QKV0, QKV_MC ? 2 : 1, false, mXa[xi], mWq, mQ, p);
        else launch(qkv_kernel<false>, 128, 288, SM_QKV, QKV_MC ? 2 : 1, true, mXa[xi], mWq, mQ, p);
        launch(attn_kernel, layer == 0 ? 128 + SIDE_CTAS : 128, 512, ATT_SMEM, 1, true, wo, w1, w2, 2 + 5 * layer);
        p.stats_in = nullptr; p.stats_out = stats + (size_t)(xi + 1) * 8 * S_; p.tk = 3 + 5 * layer;
        launch(res_gemm_kernel<8, WO_STAGES>, 128, 288, SM_WO, WO_MC ? 2 : 1, true, mOa, mWo, mXr[xi], mXs[xi + 1], p);
        p.stats_in = stats + (size_t)(xi + 1) * 8 * S_; p.stats_out = nullptr; p.tk = 4 + 5 * layer;
        launch(ffn1_kernel, 128, F1_INLINE ? 256 : 288, SM_FFN1, F1_MC ? 2 : 1, true, mXf[xi + 1], mW1a, mW1b, mHst, p);
        p.stats_in = nullptr; p.stats_out = layer == 0 ? stats + (size_t)2 * 8 * S_ : nullptr; p.tk = 5 + 5 * layer;
        launch(res_gemm_kernel<28, FFN2_STAGES>, 128, 288, SM_FFN2, F2_MC ? 2 : 1, true, mHa, mW2, mXr[xi + 1], mXs[xi + 2], p);
    }
}
```

```cpp
#include <cuda_runtime.h>
#include <cuda_bf16.h>
#include <cuda.h>
#include <stdint.h>

#define F1_INLINE 0
#define QKV_MC 0
#define WO_MC 0
#define F2_MC 0
#define F1_MC 2
#define SELF_WAIT 1
#define PREB 1
#define RES_WAIT0 0

namespace {

constexpr int S_ = 2048, D_ = 512, H_ = 32, F_ = 1792;

__device__ __align__(1024) __nv_bfloat16 g_q[S_ * D_];
__device__ __align__(1024) __nv_bfloat16 g_o[S_ * D_];
__device__ __align__(1024) __nv_bfloat16 g_x1[S_ * D_];
__device__ __align__(1024) __nv_bfloat16 g_x2[S_ * D_];
__device__ __align__(1024) __nv_bfloat16 g_x3[S_ * D_];
__device__ __align__(1024) __nv_bfloat16 g_h[S_ * F_];
__device__ __align__(1024) uint8_t g_kimg[S_ * 32];
__device__ __align__(1024) uint8_t g_vimg[(S_ / 16) * 768];
__device__ __align__(1024) float2 g_stats[4][8 * S_];
__device__ __align__(16) float g_cs_q[D_];
__device__ __align__(16) float g_cs_kv[32];
__device__ __align__(16) float g_cs_1[F_];
__device__ __align__(16) float g_kvmax[32];

#define TL(k, slot)

__device__ __forceinline__ uint32_t smem_u32(const void* p) { return (uint32_t)__cvta_generic_to_shared(p); }
__device__ __forceinline__ void mbar_init(uint32_t bar, uint32_t cnt) {
    asm volatile("mbarrier.init.shared::cta.b64 [%0], %1;" ::"r"(bar), "r"(cnt));
}
__device__ __forceinline__ void mbar_expect_tx(uint32_t bar, uint32_t bytes) {
    asm volatile("mbarrier.arrive.expect_tx.shared::cta.b64 _, [%0], %1;" ::"r"(bar), "r"(bytes) : "memory");
}
__device__ __forceinline__ void mbar_arrive(uint32_t bar) {
    asm volatile("mbarrier.arrive.shared::cta.b64 _, [%0];" ::"r"(bar) : "memory");
}
__device__ __forceinline__ void mbar_arrive_remote(uint32_t bar, uint32_t cta) {
    asm volatile("{\n.reg .b32 ra;\nmapa.shared::cluster.u32 ra, %0, %1;\nmbarrier.arrive.shared::cluster.b64 _, [ra];\n}" ::"r"(bar), "r"(cta) : "memory");
}
__device__ __forceinline__ void mbar_wait(uint32_t bar, uint32_t parity) {
    asm volatile("{\n.reg .pred p;\nWAIT_%=:\nmbarrier.try_wait.parity.shared::cta.b64 p, [%0], %1;\n@p bra DONE_%=;\nbra WAIT_%=;\nDONE_%=:\n}" ::"r"(bar), "r"(parity) : "memory");
}
__device__ __forceinline__ void bulk_load(uint32_t dst, const void* src, uint32_t bytes, uint32_t bar) {
    asm volatile("cp.async.bulk.shared::cluster.global.mbarrier::complete_tx::bytes [%0], [%1], %2, [%3];" ::"r"(dst), "l"(src), "r"(bytes), "r"(bar) : "memory");
}
__device__ __forceinline__ void tma2d(uint32_t dst, const CUtensorMap* m, int c0, int c1, uint32_t bar) {
    asm volatile("cp.async.bulk.tensor.2d.shared::cluster.global.mbarrier::complete_tx::bytes [%0], [%1, {%3, %4}], [%2];" ::"r"(dst), "l"(m), "r"(bar), "r"(c0), "r"(c1) : "memory");
}
__device__ __forceinline__ void tma2d_mc(uint32_t dst, const CUtensorMap* m, int c0, int c1, uint32_t bar, uint16_t mask) {
    asm volatile("cp.async.bulk.tensor.2d.shared::cluster.global.mbarrier::complete_tx::bytes.multicast::cluster [%0], [%1, {%3, %4}], [%2], %5;" ::"r"(dst), "l"(m), "r"(bar), "r"(c0), "r"(c1), "h"(mask) : "memory");
}
__device__ __forceinline__ void tma3d(uint32_t dst, const CUtensorMap* m, int c0, int c1, int c2, uint32_t bar) {
    asm volatile("cp.async.bulk.tensor.3d.shared::cluster.global.mbarrier::complete_tx::bytes [%0], [%1, {%3, %4, %5}], [%2];" ::"r"(dst), "l"(m), "r"(bar), "r"(c0), "r"(c1), "r"(c2) : "memory");
}
__device__ __forceinline__ void tma3d_mc(uint32_t dst, const CUtensorMap* m, int c0, int c1, int c2, uint32_t bar, uint16_t mask) {
    asm volatile("cp.async.bulk.tensor.3d.shared::cluster.global.mbarrier::complete_tx::bytes.multicast::cluster [%0], [%1, {%3, %4, %5}], [%2], %6;" ::"r"(dst), "l"(m), "r"(bar), "r"(c0), "r"(c1), "r"(c2), "h"(mask) : "memory");
}
__device__ __forceinline__ void tma2d_store(const CUtensorMap* m, uint32_t src, int c0, int c1) {
    asm volatile("cp.async.bulk.tensor.2d.global.shared::cta.bulk_group [%0, {%2, %3}], [%1];" ::"l"(m), "r"(src), "r"(c0), "r"(c1) : "memory");
}
__device__ __forceinline__ void tma3d_store(const CUtensorMap* m, uint32_t src, int c0, int c1, int c2) {
    asm volatile("cp.async.bulk.tensor.3d.global.shared::cta.bulk_group [%0, {%2, %3, %4}], [%1];" ::"l"(m), "r"(src), "r"(c0), "r"(c1), "r"(c2) : "memory");
}
__device__ __forceinline__ void bulk_commit() { asm volatile("cp.async.bulk.commit_group;" ::: "memory"); }
__device__ __forceinline__ void bulk_wait_read() { asm volatile("cp.async.bulk.wait_group.read 0;" ::: "memory"); }
__device__ __forceinline__ void prefetch_tmap(const CUtensorMap* m) { asm volatile("prefetch.tensormap [%0];" ::"l"(m) : "memory"); }
__device__ __forceinline__ void fence_async_smem() { asm volatile("fence.proxy.async.shared::cta;" ::: "memory"); }
__device__ __forceinline__ void fence_mbar_init() { asm volatile("fence.mbarrier_init.release.cluster;" ::: "memory"); }
__device__ __forceinline__ void cluster_sync() { asm volatile("barrier.cluster.arrive.release.aligned;\nbarrier.cluster.wait.acquire.aligned;" ::: "memory"); }
__device__ __forceinline__ uint32_t cluster_rank() { uint32_t r; asm volatile("mov.u32 %0, %%cluster_ctarank;" : "=r"(r)); return r; }
__device__ __forceinline__ void pdl_wait() { asm volatile("griddepcontrol.wait;" ::: "memory"); }
__device__ __forceinline__ void pdl_launch() { asm volatile("griddepcontrol.launch_dependents;" ::: "memory"); }
__device__ __forceinline__ bool elect_one() {
    uint32_t p;
    asm volatile("{\n.reg .pred p;\nelect.sync _|p, 0xffffffff;\nselp.b32 %0, 1, 0, p;\n}" : "=r"(p));
    return p != 0;
}
__device__ __forceinline__ void named_bar(int id, int n) { asm volatile("bar.sync %0, %1;" ::"r"(id), "r"(n) : "memory"); }

__device__ __forceinline__ void wg_fence() { asm volatile("wgmma.fence.sync.aligned;" ::: "memory"); }
__device__ __forceinline__ void wg_commit() { asm volatile("wgmma.commit_group.sync.aligned;" ::: "memory"); }
template <int N> __device__ __forceinline__ void wg_wait() { asm volatile("wgmma.wait_group.sync.aligned %0;" ::"n"(N) : "memory"); }
template <int N> __device__ __forceinline__ void fence_regs(float (&d)[N]) {
#pragma unroll
    for (int i = 0; i < N; i++) asm volatile("" : "+f"(d[i])::"memory");
}
__device__ __forceinline__ uint64_t mkdesc(uint32_t addr, uint32_t lbo, uint32_t sbo, uint32_t swz) {
    uint64_t d = 0;
    d |= (uint64_t)((addr & 0x3FFFF) >> 4);
    d |= (uint64_t)((lbo & 0x3FFFF) >> 4) << 16;
    d |= (uint64_t)((sbo & 0x3FFFF) >> 4) << 32;
    d |= (uint64_t)swz << 62;
    return d;
}
__device__ __forceinline__ void ldsm_x4(uint32_t& r0, uint32_t& r1, uint32_t& r2, uint32_t& r3, uint32_t addr) {
    asm volatile("ldmatrix.sync.aligned.m8n8.x4.shared.b16 {%0,%1,%2,%3}, [%4];" : "=r"(r0), "=r"(r1), "=r"(r2), "=r"(r3) : "r"(addr) : "memory");
}
__device__ __forceinline__ void stsm_x4(uint32_t addr, uint32_t r0, uint32_t r1, uint32_t r2, uint32_t r3) {
    asm volatile("stmatrix.sync.aligned.m8n8.x4.shared.b16 [%0], {%1,%2,%3,%4};" ::"r"(addr), "r"(r0), "r"(r1), "r"(r2), "r"(r3) : "memory");
}
__device__ __forceinline__ void ldsm_x4_t(uint32_t& r0, uint32_t& r1, uint32_t& r2, uint32_t& r3, uint32_t addr) {
    asm volatile("ldmatrix.sync.aligned.m8n8.x4.trans.shared.b16 {%0,%1,%2,%3}, [%4];" : "=r"(r0), "=r"(r1), "=r"(r2), "=r"(r3) : "r"(addr) : "memory");
}
__device__ __forceinline__ void hmma(float (&d)[4], uint32_t a0, uint32_t a1, uint32_t a2, uint32_t a3, uint32_t b0, uint32_t b1) {
    asm volatile("mma.sync.aligned.m16n8k16.row.col.f32.bf16.bf16.f32 {%0,%1,%2,%3}, {%4,%5,%6,%7}, {%8,%9}, {%0,%1,%2,%3};"
                 : "+f"(d[0]), "+f"(d[1]), "+f"(d[2]), "+f"(d[3]) : "r"(a0), "r"(a1), "r"(a2), "r"(a3), "r"(b0), "r"(b1));
}
__device__ __forceinline__ uint32_t pack_bf16(float lo, float hi) {
    uint32_t r;
    asm("cvt.rn.bf16x2.f32 %0, %1, %2;" : "=r"(r) : "f"(hi), "f"(lo));
    return r;
}
__device__ __forceinline__ float bf_lo(uint32_t v) { return __uint_as_float(v << 16); }
__device__ __forceinline__ float bf_hi(uint32_t v) { return __uint_as_float(v & 0xFFFF0000u); }

#define WG_REGS_4(o) "+f"(d[o]), "+f"(d[o + 1]), "+f"(d[o + 2]), "+f"(d[o + 3])
#define WG_REGS_8(o) WG_REGS_4(o), WG_REGS_4(o + 4)
#define WG_REGS_16(o) WG_REGS_8(o), WG_REGS_8(o + 8)
#define WG_REGS_32(o) WG_REGS_16(o), WG_REGS_16(o + 16)

__device__ __forceinline__ void wgmma_ss_n80_tb(float (&d)[40], uint64_t dA, uint64_t dB, int sc) {
    asm volatile("{\n.reg .pred p;\nsetp.ne.b32 p, %42, 0;\n"
                 "wgmma.mma_async.sync.aligned.m64n80k16.f32.bf16.bf16 "
                 "{%0,%1,%2,%3,%4,%5,%6,%7,%8,%9,%10,%11,%12,%13,%14,%15,%16,%17,%18,%19,%20,%21,%22,%23,%24,%25,%26,%27,%28,%29,%30,%31,"
                 "%32,%33,%34,%35,%36,%37,%38,%39}, %40, %41, p, 1, 1, 0, 1;\n}\n"
                 : WG_REGS_32(0), WG_REGS_8(32) : "l"(dA), "l"(dB), "r"(sc));
}
__device__ __forceinline__ void wgmma_ss_n64_tb(float (&d)[32], uint64_t dA, uint64_t dB, int sc) {
    asm volatile("{\n.reg .pred p;\nsetp.ne.b32 p, %34, 0;\n"
                 "wgmma.mma_async.sync.aligned.m64n64k16.f32.bf16.bf16 "
                 "{%0,%1,%2,%3,%4,%5,%6,%7,%8,%9,%10,%11,%12,%13,%14,%15,%16,%17,%18,%19,%20,%21,%22,%23,%24,%25,%26,%27,%28,%29,%30,%31}, "
                 "%32, %33, p, 1, 1, 0, 1;\n}\n"
                 : WG_REGS_32(0) : "l"(dA), "l"(dB), "r"(sc));
}
__device__ __forceinline__ void wgmma_ss_n224_tb(float (&d)[112], uint64_t dA, uint64_t dB, int sc) {
    asm volatile("{\n.reg .pred p;\nsetp.ne.b32 p, %114, 0;\n"
                 "wgmma.mma_async.sync.aligned.m64n224k16.f32.bf16.bf16 "
                 "{%0,%1,%2,%3,%4,%5,%6,%7,%8,%9,%10,%11,%12,%13,%14,%15,%16,%17,%18,%19,%20,%21,%22,%23,%24,%25,%26,%27,%28,%29,%30,%31,"
                 "%32,%33,%34,%35,%36,%37,%38,%39,%40,%41,%42,%43,%44,%45,%46,%47,%48,%49,%50,%51,%52,%53,%54,%55,%56,%57,%58,%59,%60,%61,%62,%63,"
                 "%64,%65,%66,%67,%68,%69,%70,%71,%72,%73,%74,%75,%76,%77,%78,%79,%80,%81,%82,%83,%84,%85,%86,%87,%88,%89,%90,%91,%92,%93,%94,%95,"
                 "%96,%97,%98,%99,%100,%101,%102,%103,%104,%105,%106,%107,%108,%109,%110,%111}, "
                 "%112, %113, p, 1, 1, 0, 1;\n}\n"
                 : WG_REGS_32(0), WG_REGS_32(32), WG_REGS_32(64), WG_REGS_16(96) : "l"(dA), "l"(dB), "r"(sc));
}
template <int BN> __device__ __forceinline__ void wgmma_ss_tb(float (&d)[BN / 2], uint64_t dA, uint64_t dB, int sc) {
    if constexpr (BN == 64) wgmma_ss_n64_tb(d, dA, dB, sc);
    else if constexpr (BN == 80) wgmma_ss_n80_tb(d, dA, dB, sc);
    else wgmma_ss_n224_tb(d, dA, dB, sc);
}
__device__ __forceinline__ void wgmma_rs_n64_tb(float (&d)[32], uint32_t a, uint64_t dB, int sc) {
    asm volatile("{\n.reg .pred p;\nsetp.ne.b32 p, %34, 0;\n"
                 "wgmma.mma_async.sync.aligned.m64n64k16.f32.bf16.bf16 "
                 "{%0,%1,%2,%3,%4,%5,%6,%7,%8,%9,%10,%11,%12,%13,%14,%15,%16,%17,%18,%19,%20,%21,%22,%23,%24,%25,%26,%27,%28,%29,%30,%31}, "
                 "{%32,%32,%32,%32}, %33, p, 1, 1, 1;\n}\n"
                 : WG_REGS_32(0) : "r"(a), "l"(dB), "r"(sc));
}
__device__ __forceinline__ void wgmma_rs_n80_tb(float (&d)[40], uint32_t a, uint64_t dB, int sc) {
    asm volatile("{\n.reg .pred p;\nsetp.ne.b32 p, %42, 0;\n"
                 "wgmma.mma_async.sync.aligned.m64n80k16.f32.bf16.bf16 "
                 "{%0,%1,%2,%3,%4,%5,%6,%7,%8,%9,%10,%11,%12,%13,%14,%15,%16,%17,%18,%19,%20,%21,%22,%23,%24,%25,%26,%27,%28,%29,%30,%31,"
                 "%32,%33,%34,%35,%36,%37,%38,%39}, {%40,%40,%40,%40}, %41, p, 1, 1, 1;\n}\n"
                 : WG_REGS_32(0), WG_REGS_8(32) : "r"(a), "l"(dB), "r"(sc));
}
template <int BN> __device__ __forceinline__ void wgmma_rs_ones(float (&d)[BN / 2], uint64_t dB, int sc) {
    if constexpr (BN == 80) wgmma_rs_n80_tb(d, 0x3F803F80u, dB, sc);
    else if constexpr (BN == 64) wgmma_rs_n64_tb(d, 0x3F803F80u, dB, sc);
}
__device__ __forceinline__ void wgmma_rs_n64_z(float (&d)[32], uint32_t a0, uint32_t a1, uint32_t a2, uint32_t a3, uint64_t dB) {
    asm volatile("{\n.reg .pred p;\nsetp.ne.b32 p, 0, 0;\n"
                 "wgmma.mma_async.sync.aligned.m64n64k16.f32.bf16.bf16 "
                 "{%0,%1,%2,%3,%4,%5,%6,%7,%8,%9,%10,%11,%12,%13,%14,%15,%16,%17,%18,%19,%20,%21,%22,%23,%24,%25,%26,%27,%28,%29,%30,%31}, "
                 "{%32,%33,%34,%35}, %36, p, 1, 1, 0;\n}\n"
                 : "=f"(d[0]), "=f"(d[1]), "=f"(d[2]), "=f"(d[3]), "=f"(d[4]), "=f"(d[5]), "=f"(d[6]), "=f"(d[7]),
                   "=f"(d[8]), "=f"(d[9]), "=f"(d[10]), "=f"(d[11]), "=f"(d[12]), "=f"(d[13]), "=f"(d[14]), "=f"(d[15]),
                   "=f"(d[16]), "=f"(d[17]), "=f"(d[18]), "=f"(d[19]), "=f"(d[20]), "=f"(d[21]), "=f"(d[22]), "=f"(d[23]),
                   "=f"(d[24]), "=f"(d[25]), "=f"(d[26]), "=f"(d[27]), "=f"(d[28]), "=f"(d[29]), "=f"(d[30]), "=f"(d[31])
                 : "r"(a0), "r"(a1), "r"(a2), "r"(a3), "l"(dB));
}
__device__ __forceinline__ void wgmma_rs_n24_tb(float (&d)[12], uint32_t a0, uint32_t a1, uint32_t a2, uint32_t a3, uint64_t dB) {
    asm volatile("{\n.reg .pred p;\nsetp.eq.b32 p, 0, 0;\n"
                 "wgmma.mma_async.sync.aligned.m64n24k16.f32.bf16.bf16 "
                 "{%0,%1,%2,%3,%4,%5,%6,%7,%8,%9,%10,%11}, {%12,%13,%14,%15}, %16, p, 1, 1, 1;\n}\n"
                 : WG_REGS_8(0), WG_REGS_4(8) : "r"(a0), "r"(a1), "r"(a2), "r"(a3), "l"(dB));
}

constexpr int SIDE_CTAS = 4;
__device__ __forceinline__ void side_job(int cta, float* red  , const __nv_bfloat16* __restrict__ wo,
                                         const __nv_bfloat16* __restrict__ w1, const __nv_bfloat16* __restrict__ w2) {
    const int tid = threadIdx.x, warp = tid >> 5, lane = tid & 31;
    for (int line = cta * 512 + tid; line < 18432; line += SIDE_CTAS * 512) {
        const char* p = line < 4096 ? (const char*)wo + (size_t)line * 128 : (const char*)w2 + (size_t)(line - 4096) * 128;
        asm volatile("prefetch.global.L2 [%0];" ::"l"(p));
    }
    const int rg = lane >> 3, c8 = lane & 7;
    for (int slab = cta; slab < F_ / 64; slab += SIDE_CTAS) {
        const __nv_bfloat16* base = w1 + slab * 64 + c8 * 8;
        uint4 v[8];
#pragma unroll
        for (int i = 0; i < 8; i++) v[i] = __ldg((const uint4*)(base + (size_t)(warp * 32 + rg + 4 * i) * F_));
        float acc[8];
#pragma unroll
        for (int i = 0; i < 8; i++) acc[i] = 0.f;
#pragma unroll
        for (int i = 0; i < 8; i++) {
            acc[0] += bf_lo(v[i].x); acc[1] += bf_hi(v[i].x); acc[2] += bf_lo(v[i].y); acc[3] += bf_hi(v[i].y);
            acc[4] += bf_lo(v[i].z); acc[5] += bf_hi(v[i].z); acc[6] += bf_lo(v[i].w); acc[7] += bf_hi(v[i].w);
        }
#pragma unroll
        for (int i = 0; i < 8; i++) {
            acc[i] += __shfl_xor_sync(0xffffffffu, acc[i], 8);
            acc[i] += __shfl_xor_sync(0xffffffffu, acc[i], 16);
        }
        if (rg == 0) {
#pragma unroll
            for (int i = 0; i < 8; i++) red[warp * 64 + c8 * 8 + i] = acc[i];
        }
        __syncthreads();
        if (tid < 64) {
            float s = 0.f;
#pragma unroll
            for (int i = 0; i < 16; i++) s += red[i * 64 + tid];
            g_cs_1[slab * 64 + tid] = s;
        }
        __syncthreads();
    }
}

enum { EPI_QKV = 0, EPI_RES = 1, EPI_FFN1 = 2 };

struct GemmParams {
    const float2* stats_in;
    float2* stats_out;
    const __nv_bfloat16* wkv;
    const __nv_bfloat16* wv;
    int tk;
};

template <int BK_, int NBLK> struct Geo {
    static constexpr int BK = BK_, A_BYTES = 128 * BK * 2, A_SWZ = BK == 64 ? 1 : 2, A_SBO = BK * 16;
    static constexpr int BLK = BK * 64;
    static constexpr int B_BYTES = NBLK * BLK, B_SWZ = 2, B_LBO = BLK, B_SBO = 512, B_KSTEP = 1024;
};
template <> struct Geo<64, 0> {
    static constexpr int BK = 64, A_BYTES = 128 * 128, A_SWZ = 1, A_SBO = 1024, BLK = 8192;
    static constexpr int B_BYTES = 64 * 128, B_SWZ = 1, B_LBO = 8192, B_SBO = 1024, B_KSTEP = 2048;
};
#define F1_BK 32
template <int EPI> struct EpiGeo;
template <> struct EpiGeo<EPI_QKV> { using G = Geo<64, 3>; };
template <> struct EpiGeo<EPI_RES> { using G = Geo<64, 0>; };
template <> struct EpiGeo<EPI_FFN1> { using G = Geo<F1_BK, 7>; };

template <int STAGES, int EPI> struct GemmSmem {
    using G = typename EpiGeo<EPI>::G;
    static constexpr int STAGE = G::A_BYTES + G::B_BYTES;
    static constexpr int AUX_OFF = STAGES * STAGE;
    static constexpr int TOTAL = AUX_OFF + 1152;
    static constexpr int TOTAL_SELF = AUX_OFF + 704 + 1024 + 1280;
};

struct RowStatRaw { float2 a0, a1, b0, b1; };
__device__ __forceinline__ RowStatRaw load_row_stats(const float2* __restrict__ st, int row0, int c) {
    RowStatRaw r;
    r.a0 = st[(2 * c) * S_ + row0]; r.a1 = st[(2 * c + 1) * S_ + row0];
    r.b0 = st[(2 * c) * S_ + row0 + 8]; r.b1 = st[(2 * c + 1) * S_ + row0 + 8];
    return r;
}
__device__ __forceinline__ void finish_row_stats(const RowStatRaw& r, float& mean0, float& rstd0, float& mean1, float& rstd1) {
    float sa = r.a0.x + r.a1.x, sb = r.b0.x + r.b1.x;
    sa += __shfl_xor_sync(0xffffffffu, sa, 1); sa += __shfl_xor_sync(0xffffffffu, sa, 2);
    sb += __shfl_xor_sync(0xffffffffu, sb, 1); sb += __shfl_xor_sync(0xffffffffu, sb, 2);
    mean0 = sa * 0.125f; mean1 = sb * 0.125f;
    float ma = r.a0.y + r.a1.y + 64.f * ((r.a0.x - mean0) * (r.a0.x - mean0) + (r.a1.x - mean0) * (r.a1.x - mean0));
    float mb = r.b0.y + r.b1.y + 64.f * ((r.b0.x - mean1) * (r.b0.x - mean1) + (r.b1.x - mean1) * (r.b1.x - mean1));
    ma += __shfl_xor_sync(0xffffffffu, ma, 1); ma += __shfl_xor_sync(0xffffffffu, ma, 2);
    mb += __shfl_xor_sync(0xffffffffu, mb, 1); mb += __shfl_xor_sync(0xffffffffu, mb, 2);
    rstd0 = 1.0f / sqrtf(ma * (1.f / 512.f) + 1e-5f);
    rstd1 = 1.0f / sqrtf(mb * (1.f / 512.f) + 1e-5f);
}

template <int BN, int KB, int STAGES, int EPI, int MC, bool SELF = false>
__device__ __forceinline__ void gemm_body(const CUtensorMap* mapA, const CUtensorMap* mapB, const CUtensorMap* mapB2, const CUtensorMap* mapR,
                                          const CUtensorMap* mapC, const GemmParams& prm, int tile_m, int tile_n, uint8_t* smem_raw) {
    using SM = GemmSmem<STAGES, EPI>;
    using G = typename SM::G;
    constexpr bool XKV = BN == 80;
    constexpr int TN = EPI == EPI_QKV ? 64 : BN;
    pdl_launch();
    const uint32_t sbase = smem_u32(smem_raw);
    if (sbase & 1023) __trap();
    uint8_t* sgen = smem_raw;
    const uint32_t bar_full = sbase + SM::AUX_OFF, bar_empty = bar_full + 8 * STAGES;
    float* s_cs = (float*)(sgen + SM::AUX_OFF + 256);
    float* s_row = (float*)(sgen + SM::AUX_OFF + 704);
    float* s_red = (float*)(sgen + SM::AUX_OFF + 640);
    const int tid = threadIdx.x, lane = tid & 31;
    const int warp = __shfl_sync(0xffffffffu, tid >> 5, 0);
    const uint32_t rank = MC ? cluster_rank() : 0;
    if (tid == 0) TL(prm.tk, 0);

    constexpr bool INLINE_PROD = EPI == EPI_FFN1 && F1_INLINE;
    constexpr int PWARP = INLINE_PROD ? 0 : 8;
    if (warp == PWARP && elect_one()) {
        prefetch_tmap(mapB); prefetch_tmap(mapA); prefetch_tmap(mapC);
        for (int s = 0; s < STAGES; s++) { mbar_init(bar_full + 8 * s, 1); mbar_init(bar_empty + 8 * s, MC ? 4 : 2); }
        fence_mbar_init();
    }
    __syncthreads();
    if (MC) cluster_sync();

    const int m0 = tile_m * 128, n0 = tile_n * TN;
    constexpr uint32_t STAGE_TX = G::A_BYTES + (EPI == EPI_QKV ? 2 * G::BLK : G::B_BYTES);
    auto loadB = [&](int kb, int s) {
        const uint32_t dst = sbase + s * SM::STAGE + G::A_BYTES, bar = bar_full + 8 * s;
        if constexpr (EPI == EPI_RES) {
            tma2d(dst, mapB, n0, kb * 64, bar);
        } else if constexpr (EPI == EPI_QKV) {
            tma3d(dst, mapB, 0, kb * G::BK, tile_n * 2, bar);
        } else {
            if constexpr (MC == 2) {
                if (rank == 0) tma3d_mc(dst, mapB, 0, kb * G::BK, tile_n * 7, bar, 3);
                else tma3d_mc(dst + 4 * G::BLK, mapB2, 0, kb * G::BK, tile_n * 7 + 4, bar, 3);
            } else {
                tma3d(dst, mapB, 0, kb * G::BK, tile_n * 7, bar);
                tma3d(dst + 4 * G::BLK, mapB2, 0, kb * G::BK, tile_n * 7 + 4, bar);
            }
        }
    };
    auto loadA = [&](int kb, int s) {
        const uint32_t dst = sbase + s * SM::STAGE, bar = bar_full + 8 * s;
        if constexpr (MC == 1) tma2d_mc(dst + rank * (G::A_BYTES / 2), mapA, kb * G::BK, m0 + rank * 64, bar, 3);
        else tma2d(dst, mapA, kb * G::BK, m0, bar);
    };
    constexpr int PRE = STAGES < KB ? STAGES : KB;
#define F1_LAG 2
    constexpr int LAG = F1_LAG;
    constexpr int PRE_B = PRE < PREB ? PRE : PREB;
    auto prologue_loads = [&]() {
        if (elect_one()) {
#pragma unroll
            for (int kb = 0; kb < PRE; kb++) mbar_expect_tx(bar_full + 8 * kb, STAGE_TX);
#pragma unroll
            for (int kb = 0; kb < PRE_B; kb++) loadB(kb, kb);
        }
        if (!SELF) pdl_wait();
        if (elect_one()) {
#pragma unroll
            for (int kb = 0; kb < PRE; kb++) {
                loadA(kb, kb);
                if (kb + PRE_B < PRE) loadB(kb + PRE_B, kb + PRE_B);
            }
            if constexpr (EPI == EPI_RES && KB < STAGES) {
                mbar_expect_tx(bar_full + 8 * KB, 16384);
                tma2d(sbase + KB * SM::STAGE, mapR, n0, m0, bar_full + 8 * KB);
            }
        }
    };
    if (SELF && warp > 8) {
        static_assert(!SELF || (STAGES >= KB && EPI == EPI_QKV), "SELF needs every k block resident");
        const int t = tid - 288;
        float ss[4] = {0.f, 0.f, 0.f, 0.f}, sq[4] = {0.f, 0.f, 0.f, 0.f};
        auto row_stats = [&](int kb) {
            const uint32_t arow = sbase + kb * SM::STAGE + (t >> 1) * 128;
            uint32_t w[4][4];
#pragma unroll
            for (int j = 0; j < 4; j++)
                asm volatile("ld.shared.v4.u32 {%0,%1,%2,%3}, [%4];" : "=r"(w[j][0]), "=r"(w[j][1]), "=r"(w[j][2]), "=r"(w[j][3])
                             : "r"(arow + (((2 * j + (t & 1) + 2 * ((t >> 1) & 3)) & 7) << 4)));
#pragma unroll
            for (int j = 0; j < 4; j++)
#pragma unroll
                for (int i = 0; i < 4; i++) {
                    const float lo = bf_lo(w[j][i]), hi = bf_hi(w[j][i]);
                    ss[i] += lo + hi;
                    sq[i] = fmaf(lo, lo, fmaf(hi, hi, sq[i]));
                }
        };
        if ((warp >> 2) == 3) {
            float csum[BN / 2];
            const uint64_t dB0 = mkdesc(sbase + G::A_BYTES, G::B_LBO, G::B_SBO, G::B_SWZ);
            if constexpr (XKV) named_bar(6, 512);
#pragma unroll 1
            for (int kb = 0; kb < KB; kb++) {
                mbar_wait(bar_full + 8 * kb, 0);
                const uint64_t dB = dB0 + (uint64_t)(kb * (SM::STAGE >> 4));
                wg_fence();
#pragma unroll
                for (int k = 0; k < G::BK / 16; k++) {
                    if constexpr (SELF) wgmma_rs_ones<BN>(csum, dB + (uint64_t)(k * (G::B_KSTEP >> 4)), (kb | k) != 0);
                }
                wg_commit();
                wg_wait<0>();
                row_stats(kb);
            }
            wg_wait<0>();
            fence_regs(csum);
            if (warp == 12 && lane < 4) {
#pragma unroll
                for (int j = 0; j < BN / 8; j++) {
                    const float2 v = make_float2(csum[4 * j], csum[4 * j + 1]);
                    *(float2*)(s_cs + 8 * j + 2 * lane) = v;
                    if (tile_m == 0) {
                        if (j < 8) *(float2*)(g_cs_q + n0 + 8 * j + 2 * lane) = v;
                        else *(float2*)(g_cs_kv + tile_n * 16 + 8 * (j - 8) + 2 * lane) = v;
                    }
                }
            }
        } else {
            if constexpr (XKV) named_bar(6, 512);
#pragma unroll 1
            for (int kb = 0; kb < KB; kb++) {
                mbar_wait(bar_full + 8 * kb, 0);
                row_stats(kb);
            }
        }
        float tsum = (ss[0] + ss[1]) + (ss[2] + ss[3]), tsq = (sq[0] + sq[1]) + (sq[2] + sq[3]);
        tsum += __shfl_xor_sync(0xffffffffu, tsum, 1);
        tsq += __shfl_xor_sync(0xffffffffu, tsq, 1);
        if ((t & 1) == 0) {
            const float md = tsum * (1.f / 512.f);
            const float var = fmaxf(tsq * (1.f / 512.f) - md * md, 0.f);
            *(float2*)(s_row + t) = make_float2(md, 1.0f / sqrtf(var + 1e-5f));
        }
        named_bar(4, 512);
    } else if (!INLINE_PROD && warp == 8) {
        prologue_loads();
        int s = PRE % STAGES, ph = (PRE / STAGES) & 1;
#pragma unroll 1
        for (int kb = PRE; kb < KB; kb++) {
            mbar_wait(bar_empty + 8 * s, ph ^ 1);
            if (elect_one()) {
                mbar_expect_tx(bar_full + 8 * s, STAGE_TX);
                loadB(kb, s);
                loadA(kb, s);
            }
            if (++s == STAGES) { s = 0; ph ^= 1; }
        }
        if constexpr (EPI == EPI_RES && KB >= STAGES) {
            mbar_wait(bar_empty + 8 * s, ph ^ 1);
            if (elect_one()) {
                mbar_expect_tx(bar_full + 8 * s, 16384);
                tma2d(sbase + s * SM::STAGE, mapR, n0, m0, bar_full + 8 * s);
            }
        }
    } else {
        if (INLINE_PROD && warp == 0) prologue_loads();
        const int wg = warp >> 2, g = lane >> 2, c = lane & 3;
        const int rloc = wg * 64 + (warp & 3) * 16 + g;
        const int row0 = m0 + rloc;
        float mean0 = 0.f, rstd0 = 1.f, mean1 = 0.f, rstd1 = 1.f;
        if constexpr (XKV) {
            static_assert(!XKV || STAGES >= KB, "the K / V weight block must stay resident");
            const __nv_bfloat16* wsrc = tile_n == 0 ? prm.wkv : prm.wv;
            uint4 v[4];
#pragma unroll
            for (int i = 0; i < 4; i++) v[i] = __ldg((const uint4*)wsrc + tid + 256 * i);
#pragma unroll
            for (int i = 0; i < 4; i++) {
                const int idx = tid + 256 * i, k = idx >> 1, kr = k & 63;
                const uint32_t dst = sbase + (k >> 6) * SM::STAGE + G::A_BYTES + 2 * G::BLK + kr * 64 + (((idx & 1) ^ ((kr >> 1) & 3)) << 4);
                asm volatile("st.shared.v4.u32 [%0], {%1,%2,%3,%4};" ::"r"(dst), "r"(v[i].x), "r"(v[i].y), "r"(v[i].z), "r"(v[i].w) : "memory");
            }
            fence_async_smem();
            if constexpr (SELF) named_bar(6, 512); else named_bar(6, 256);
        }
        RowStatRaw raw;
        float csv = 0.f;
        float2 cskv[2] = {make_float2(0.f, 0.f), make_float2(0.f, 0.f)};
        auto ln_inputs = [&]() {
            pdl_wait();
            if constexpr (EPI != EPI_RES) {
                raw = load_row_stats(prm.stats_in, row0, c);
                const float* cs = EPI == EPI_FFN1 ? g_cs_1 + n0 : g_cs_q + n0;
                if (tid < TN) csv = cs[tid];
                if constexpr (XKV) {
                    cskv[0] = *(const float2*)(g_cs_kv + tile_n * 16 + 2 * c);
                    cskv[1] = *(const float2*)(g_cs_kv + tile_n * 16 + 8 + 2 * c);
                }
            }
        };
        if (!SELF) ln_inputs();
        float acc[BN / 2];
        const uint64_t dA0 = mkdesc(sbase + wg * (G::A_BYTES / 2), 16, G::A_SBO, G::A_SWZ);
        const uint64_t dB0 = mkdesc(sbase + G::A_BYTES, G::B_LBO, G::B_SBO, G::B_SWZ);
        int s = 0, ph = 0;
#pragma unroll 1
        for (int kb = 0; kb < KB; kb++) {
            mbar_wait(bar_full + 8 * s, ph);
            const uint64_t dA = dA0 + (uint64_t)(s * (SM::STAGE >> 4)), dB = dB0 + (uint64_t)(s * (SM::STAGE >> 4));
            wg_fence();
#pragma unroll
            for (int k = 0; k < G::BK / 16; k++) wgmma_ss_tb<BN>(acc, dA + (uint64_t)(k * 2), dB + (uint64_t)(k * (G::B_KSTEP >> 4)), (kb | k) != 0);
            wg_commit();
            if constexpr (EPI == EPI_RES && RES_WAIT0) {
                wg_wait<0>();
                if ((warp & 3) == 0 && elect_one()) {
                    if (MC) { mbar_arrive_remote(bar_empty + 8 * s, 0); mbar_arrive_remote(bar_empty + 8 * s, 1); }
                    else mbar_arrive(bar_empty + 8 * s);
                }
            } else if (kb > 0) {
                wg_wait<1>();
                const int sp = s == 0 ? STAGES - 1 : s - 1;
                if ((warp & 3) == 0 && elect_one()) {
                    if (MC) { mbar_arrive_remote(bar_empty + 8 * sp, 0); mbar_arrive_remote(bar_empty + 8 * sp, 1); }
                    else mbar_arrive(bar_empty + 8 * sp);
                }
                if (INLINE_PROD && warp == 0 && kb >= LAG && kb - LAG + STAGES < KB) {
                    const int sq = LAG == 1 ? sp : (sp == 0 ? STAGES - 1 : sp - 1);
                    mbar_wait(bar_empty + 8 * sq, ((kb - LAG) / STAGES) & 1);
                    if (elect_one()) {
                        mbar_expect_tx(bar_full + 8 * sq, STAGE_TX);
                        loadB(kb - LAG + STAGES, sq);
                        loadA(kb - LAG + STAGES, sq);
                    }
                }
            }
            if (++s == STAGES) { s = 0; ph ^= 1; }
        }
        if constexpr (SELF) {
            named_bar(4, 512);
            const float2 r0 = *(const float2*)(s_row + 2 * rloc), r1 = *(const float2*)(s_row + 2 * rloc + 16);
            mean0 = r0.x; rstd0 = r0.y; mean1 = r1.x; rstd1 = r1.y;
        } else if constexpr (EPI != EPI_RES) {
            finish_row_stats(raw, mean0, rstd0, mean1, rstd1);
            if (tid < TN) s_cs[tid] = csv;
        }
        wg_wait<0>();
        fence_regs(acc);
        if (tid == 0) TL(prm.tk, 2);
        if constexpr (EPI != EPI_RES) named_bar(1, 256);

        if constexpr (EPI != EPI_FFN1) {
            const uint32_t stile = sbase + (EPI == EPI_RES ? s * SM::STAGE : 0);
            const int mrow = wg * 64 + (warp & 3) * 16 + (lane & 7) + ((lane >> 3) & 1) * 8;
            const uint32_t rbase = stile + mrow * 128;
            if constexpr (EPI == EPI_RES) {
                mbar_wait(bar_full + 8 * s, ph);
                float s0 = 0.f, s1 = 0.f;
#pragma unroll
                for (int jj = 0; jj < 4; jj++) {
                    uint32_t r0, r1, r2, r3;
                    const uint32_t addr = rbase + (((2 * jj + (lane >> 4)) ^ (mrow & 7)) << 4);
                    ldsm_x4(r0, r1, r2, r3, addr);
                    const uint32_t u0 = pack_bf16(acc[8 * jj] + bf_lo(r0), acc[8 * jj + 1] + bf_hi(r0));
                    const uint32_t u1 = pack_bf16(acc[8 * jj + 2] + bf_lo(r1), acc[8 * jj + 3] + bf_hi(r1));
                    const uint32_t u2 = pack_bf16(acc[8 * jj + 4] + bf_lo(r2), acc[8 * jj + 5] + bf_hi(r2));
                    const uint32_t u3 = pack_bf16(acc[8 * jj + 6] + bf_lo(r3), acc[8 * jj + 7] + bf_hi(r3));
                    stsm_x4(addr, u0, u1, u2, u3);
                    acc[8 * jj] = bf_lo(u0); acc[8 * jj + 1] = bf_hi(u0); acc[8 * jj + 4] = bf_lo(u2); acc[8 * jj + 5] = bf_hi(u2);
                    acc[8 * jj + 2] = bf_lo(u1); acc[8 * jj + 3] = bf_hi(u1); acc[8 * jj + 6] = bf_lo(u3); acc[8 * jj + 7] = bf_hi(u3);
                    s0 += (acc[8 * jj] + acc[8 * jj + 1]) + (acc[8 * jj + 4] + acc[8 * jj + 5]);
                    s1 += (acc[8 * jj + 2] + acc[8 * jj + 3]) + (acc[8 * jj + 6] + acc[8 * jj + 7]);
                }
                fence_async_smem();
                named_bar(2 + wg, 128);
                if ((warp & 3) == 0 && elect_one()) { tma2d_store(mapC, stile + wg * 8192, n0, m0 + wg * 64); bulk_commit(); }
                if (prm.stats_out) {
                    s0 += __shfl_xor_sync(0xffffffffu, s0, 1); s0 += __shfl_xor_sync(0xffffffffu, s0, 2);
                    s1 += __shfl_xor_sync(0xffffffffu, s1, 1); s1 += __shfl_xor_sync(0xffffffffu, s1, 2);
                    const float mu0 = s0 * (1.f / 64.f), mu1 = s1 * (1.f / 64.f);
                    float q0 = 0.f, q1 = 0.f;
#pragma unroll
                    for (int j = 0; j < 8; j++) {
                        float d;
                        d = acc[4 * j] - mu0; q0 += d * d; d = acc[4 * j + 1] - mu0; q0 += d * d;
                        d = acc[4 * j + 2] - mu1; q1 += d * d; d = acc[4 * j + 3] - mu1; q1 += d * d;
                    }
                    q0 += __shfl_xor_sync(0xffffffffu, q0, 1); q0 += __shfl_xor_sync(0xffffffffu, q0, 2);
                    q1 += __shfl_xor_sync(0xffffffffu, q1, 1); q1 += __shfl_xor_sync(0xffffffffu, q1, 2);
                    if (c == 0) {
                        prm.stats_out[tile_n * S_ + row0] = make_float2(mu0, q0);
                        prm.stats_out[tile_n * S_ + row0 + 8] = make_float2(mu1, q1);
                    }
                }
            } else {
                const float sc = 0.25f * 1.4426950408889634f;
                const float a0 = rstd0 * sc, a1 = rstd1 * sc, rm0 = a0 * mean0, rm1 = a1 * mean1;
#pragma unroll
                for (int jj = 0; jj < 4; jj++) {
                    const float2 ca = *(const float2*)(s_cs + 16 * jj + 2 * c), cb = *(const float2*)(s_cs + 16 * jj + 8 + 2 * c);
                    const uint32_t u0 = pack_bf16(acc[8 * jj] * a0 - rm0 * ca.x, acc[8 * jj + 1] * a0 - rm0 * ca.y);
                    const uint32_t u1 = pack_bf16(acc[8 * jj + 2] * a1 - rm1 * ca.x, acc[8 * jj + 3] * a1 - rm1 * ca.y);
                    const uint32_t u2 = pack_bf16(acc[8 * jj + 4] * a0 - rm0 * cb.x, acc[8 * jj + 5] * a0 - rm0 * cb.y);
                    const uint32_t u3 = pack_bf16(acc[8 * jj + 6] * a1 - rm1 * cb.x, acc[8 * jj + 7] * a1 - rm1 * cb.y);
                    stsm_x4(rbase + (((2 * jj + (lane >> 4)) ^ (mrow & 7)) << 4), u0, u1, u2, u3);
                }
                fence_async_smem();
                named_bar(2 + wg, 128);
                if ((warp & 3) == 0 && elect_one()) { tma2d_store(mapC, stile + wg * 8192, n0, m0 + wg * 64); bulk_commit(); }
            }
            if constexpr (XKV) {
                {
                    const float* acx = &acc[32];
                    const float rm0 = rstd0 * mean0, rm1 = rstd1 * mean1;
                    float n0s = 0.f, n1s = 0.f, vmax = 0.f;
#pragma unroll
                    for (int j = 0; j < 2; j++) {
                        const float2 cs2 = SELF ? *(const float2*)(s_cs + 64 + 8 * j + 2 * c) : cskv[j];
                        const uint32_t u0 = pack_bf16(acx[4 * j] * rstd0 - rm0 * cs2.x, acx[4 * j + 1] * rstd0 - rm0 * cs2.y);
                        const uint32_t u1 = pack_bf16(acx[4 * j + 2] * rstd1 - rm1 * cs2.x, acx[4 * j + 3] * rstd1 - rm1 * cs2.y);
                        n0s += bf_lo(u0) * bf_lo(u0) + bf_hi(u0) * bf_hi(u0);
                        n1s += bf_lo(u1) * bf_lo(u1) + bf_hi(u1) * bf_hi(u1);
                        vmax = fmaxf(vmax, fmaxf(fmaxf(fabsf(bf_lo(u0)), fabsf(bf_hi(u0))), fmaxf(fabsf(bf_lo(u1)), fabsf(bf_hi(u1)))));
                        if (tile_n == 0) {
                            *(uint32_t*)(g_kimg + (row0 >> 3) * 256 + j * 128 + g * 16 + c * 4) = u0;
                            *(uint32_t*)(g_kimg + ((row0 + 8) >> 3) * 256 + j * 128 + g * 16 + c * 4) = u1;
                        } else {
                            uint8_t* vb = g_vimg + (row0 >> 4) * 768 + j * 256 + g * 16 + c * 4;
                            *(uint32_t*)(vb) = u0;
                            *(uint32_t*)(vb + 128) = u1;
                        }
                    }
                    if (tile_n == 1) {
                        uint8_t* vb = g_vimg + (row0 >> 4) * 768 + 512 + g * 16 + c * 4;
                        const uint32_t one = c == 0 ? 0x00003F80u : 0u;
                        *(uint32_t*)(vb) = one;
                        *(uint32_t*)(vb + 128) = one;
                    }
                    n0s += __shfl_xor_sync(0xffffffffu, n0s, 1); n0s += __shfl_xor_sync(0xffffffffu, n0s, 2);
                    n1s += __shfl_xor_sync(0xffffffffu, n1s, 1); n1s += __shfl_xor_sync(0xffffffffu, n1s, 2);
                    float km = tile_n == 0 ? fmaxf(n0s, n1s) : vmax;
                    if (!(n0s + n1s < INFINITY)) km = INFINITY;
#pragma unroll
                    for (int o = 1; o < 32; o <<= 1) km = fmaxf(km, __shfl_xor_sync(0xffffffffu, km, o));
                    if (lane == 0) s_red[warp] = km;
                    named_bar(1, 256);
                    if (tid == 0) {
                        float a = 0.f;
                        for (int i = 0; i < 8; i++) a = fmaxf(a, s_red[i]);
                        g_kvmax[tile_n * 16 + tile_m] = a;
                    }
                }
            }
            if ((warp & 3) == 0) bulk_wait_read();
        } else {
            const uint32_t stile = sbase + wg * (7 * 4096);
            const int mrow = (warp & 3) * 16 + (lane & 7) + ((lane >> 3) & 1) * 8;
            const float a0 = 0.5f * rstd0, a1 = 0.5f * rstd1, rm0 = a0 * mean0, rm1 = a1 * mean1;
#pragma unroll
            for (int jj = 0; jj < 14; jj++) {
                const float2 ca = *(const float2*)(s_cs + 16 * jj + 2 * c), cb = *(const float2*)(s_cs + 16 * jj + 8 + 2 * c);
                float y[8] = {acc[8 * jj] * a0 - rm0 * ca.x,     acc[8 * jj + 1] * a0 - rm0 * ca.y,
                              acc[8 * jj + 2] * a1 - rm1 * ca.x, acc[8 * jj + 3] * a1 - rm1 * ca.y,
                              acc[8 * jj + 4] * a0 - rm0 * cb.x, acc[8 * jj + 5] * a0 - rm0 * cb.y,
                              acc[8 * jj + 6] * a1 - rm1 * cb.x, acc[8 * jj + 7] * a1 - rm1 * cb.y};
#pragma unroll
                for (int i = 0; i < 8; i++) {
                    float t;
                    asm("tanh.approx.f32 %0, %1;" : "=f"(t) : "f"(y[i]));
                    y[i] = fmaf(y[i], t, y[i]);
                }
                const int chunk = (2 * jj + (lane >> 4)) & 3, blk = jj >> 1;
                stsm_x4(stile + blk * 4096 + mrow * 64 + ((chunk ^ ((mrow >> 1) & 3)) << 4),
                        pack_bf16(y[0], y[1]), pack_bf16(y[2], y[3]), pack_bf16(y[4], y[5]), pack_bf16(y[6], y[7]));
                if (jj & 1) {
                    fence_async_smem();
                    __syncwarp();
                    if (elect_one()) {
                        tma2d_store(mapC, stile + blk * 4096 + (warp & 3) * 1024, n0 + blk * 32, m0 + wg * 64 + (warp & 3) * 16);
                        bulk_commit();
                    }
                }
            }
            bulk_wait_read();
        }
    }
    if (tid == 0) TL(prm.tk, 3);
    if (MC) cluster_sync();
}

#define WO_ST 9
#define F2_ST 6
#define F1_ST (F1_BK == 64 ? 5 : 9)
#define QKV_ST 8
constexpr int QKV_STAGES = QKV_ST, WO_STAGES = WO_ST, FFN2_STAGES = F2_ST, FFN1_STAGES = F1_ST;
template <bool SELF>
__global__ void __launch_bounds__(SELF ? 544 : 288) qkv_kernel(const __grid_constant__ CUtensorMap mapA, const __grid_constant__ CUtensorMap mapWq,
                                                  const __grid_constant__ CUtensorMap mapQ, const GemmParams prm) {
    extern __shared__ __align__(1024) uint8_t smem_raw[];
    const int tn = blockIdx.x & 7;
    if (tn < 2) gemm_body<80, 8, QKV_STAGES, EPI_QKV, QKV_MC, SELF>(&mapA, &mapWq, &mapWq, &mapA, &mapQ, prm, blockIdx.x >> 3, tn, smem_raw);
    else gemm_body<64, 8, QKV_STAGES, EPI_QKV, QKV_MC, SELF>(&mapA, &mapWq, &mapWq, &mapA, &mapQ, prm, blockIdx.x >> 3, tn, smem_raw);
}
template <int KB, int STAGES>
__global__ void __launch_bounds__(288) res_gemm_kernel(const __grid_constant__ CUtensorMap mapA, const __grid_constant__ CUtensorMap mapW,
                                                       const __grid_constant__ CUtensorMap mapR, const __grid_constant__ CUtensorMap mapC, const GemmParams prm) {
    extern __shared__ __align__(1024) uint8_t smem_raw[];
    gemm_body<64, KB, STAGES, EPI_RES, (KB == 8 ? WO_MC : F2_MC)>(&mapA, &mapW, &mapW, &mapR, &mapC, prm, blockIdx.x >> 3, blockIdx.x & 7, smem_raw);
}
__global__ void __launch_bounds__(F1_INLINE ? 256 : 288) ffn1_kernel(const __grid_constant__ CUtensorMap mapA, const __grid_constant__ CUtensorMap mapW4,
                                                   const __grid_constant__ CUtensorMap mapW3, const __grid_constant__ CUtensorMap mapH, const GemmParams prm) {
    extern __shared__ __align__(1024) uint8_t smem_raw[];
    const int pair = blockIdx.x >> 1, tile_n = pair & 7, tile_m = (pair >> 3) * 2 + (blockIdx.x & 1);
    gemm_body<224, 512 / F1_BK, FFN1_STAGES, EPI_FFN1, F1_MC>(&mapA, &mapW4, &mapW3, &mapA, &mapH, prm, tile_m, tile_n, smem_raw);
}

constexpr int NPOLY = 10;
__host__ __device__ constexpr bool is_mufu(int i) { return ((i + 1) * (16 - NPOLY)) / 16 != (i * (16 - NPOLY)) / 16; }

__device__ __forceinline__ float ex2(float x) { float r; asm("ex2.approx.ftz.f32 %0, %1;" : "=f"(r) : "f"(x)); return r; }
__device__ __forceinline__ uint32_t exp_pair_mufu(float a, float b) { return pack_bf16(ex2(a), ex2(b)); }
__device__ __forceinline__ uint32_t exp_pair_fma(float a, float b, uint32_t c3f) {
    constexpr float MAGIC = 98430.4140625f;
    const float ta = a + MAGIC, tb = b + (MAGIC - 143.5f);
    uint32_t y, m, r;
    asm("mad.lo.u32 %0, %1, 65536, %2;" : "=r"(y) : "r"(__float_as_uint(tb)), "r"(__float_as_uint(ta)));
    asm("lop3.b32 %0, %1, 0x007F007F, %2, 0xEA;" : "=r"(m) : "r"(y), "r"(c3f));
    const uint32_t e = y & 0xFF80FF80u;
    asm("fma.rn.bf16x2 %0, %1, %2, %3;" : "=r"(r) : "r"(y), "r"(m), "r"(e));
    return r;
}

constexpr int KCH = 256, NCH = S_ / KCH;
constexpr int K_BYTES = S_ * 32, V_BYTES = (S_ / 16) * 768;
constexpr int ATT_SMEM = K_BYTES + V_BYTES;

__global__ void __launch_bounds__(512, 1) attn_kernel(const __nv_bfloat16* __restrict__ wo, const __nv_bfloat16* __restrict__ w1,
                                                       const __nv_bfloat16* __restrict__ w2, int tk) {
    extern __shared__ __align__(1024) uint8_t smem[];
    __shared__ uint64_t bars[NCH];
    __shared__ int s_slow;
    const int tid = threadIdx.x, wg = tid >> 7, warp = (tid >> 5) & 3, lane = tid & 31;
    const uint32_t sK = smem_u32(smem), sV = sK + K_BYTES;
    if (blockIdx.x >= 128) {
        pdl_launch();
        side_job(blockIdx.x - 128, (float*)smem, wo, w1, w2);
        return;
    }
    if (tid == 0) TL(tk, 0);
    if (tid == 0) {
        for (int i = 0; i < NCH; i++) mbar_init(smem_u32(&bars[i]), 1);
        s_slow = 0;
        fence_mbar_init();
    }
    __syncthreads();
    pdl_launch();
    pdl_wait();
    if (tid == 0) TL(tk, 1);
    {
        const int w = __shfl_sync(0xffffffffu, tid >> 5, 0);
        if (w < NCH && elect_one()) {
            const uint32_t bar = smem_u32(&bars[w]);
            mbar_expect_tx(bar, KCH * 32 + (KCH / 16) * 768);
            bulk_load(sK + w * KCH * 32, g_kimg + w * KCH * 32, KCH * 32, bar);
            bulk_load(sV + w * (KCH / 16) * 768, g_vimg + w * (KCH / 16) * 768, (KCH / 16) * 768, bar);
        }
    }
    const int tb = blockIdx.x >> 3, hg = blockIdx.x & 7;
    const int head = hg * 4 + wg;
    const int g = lane >> 2, c = lane & 3;
    uint32_t qa[2][4];
#pragma unroll
    for (int m = 0; m < 2; m++) {
        const int row = tb * 128 + m * 64 + warp * 16 + g;
        const uint32_t* p0 = (const uint32_t*)(g_q + (size_t)row * D_ + head * 16);
        const uint32_t* p1 = (const uint32_t*)(g_q + (size_t)(row + 8) * D_ + head * 16);
        qa[m][0] = p0[c]; qa[m][1] = p1[c]; qa[m][2] = p0[c + 4]; qa[m][3] = p1[c + 4];
    }
    float kvm = g_kvmax[lane];
    {
        float qn = 0.f;
#pragma unroll
        for (int m = 0; m < 2; m++) {
            float n0 = bf_lo(qa[m][0]) * bf_lo(qa[m][0]) + bf_hi(qa[m][0]) * bf_hi(qa[m][0]) + bf_lo(qa[m][2]) * bf_lo(qa[m][2]) + bf_hi(qa[m][2]) * bf_hi(qa[m][2]);
            float n1 = bf_lo(qa[m][1]) * bf_lo(qa[m][1]) + bf_hi(qa[m][1]) * bf_hi(qa[m][1]) + bf_lo(qa[m][3]) * bf_lo(qa[m][3]) + bf_hi(qa[m][3]) * bf_hi(qa[m][3]);
            n0 += __shfl_xor_sync(0xffffffffu, n0, 1); n0 += __shfl_xor_sync(0xffffffffu, n0, 2);
            n1 += __shfl_xor_sync(0xffffffffu, n1, 1); n1 += __shfl_xor_sync(0xffffffffu, n1, 2);
            if (!(n0 == n0) || !(n1 == n1)) n0 = INFINITY;
            qn = fmaxf(qn, fmaxf(n0, n1));
        }
#pragma unroll
        for (int o = 1; o < 16; o <<= 1) kvm = fmaxf(kvm, __shfl_xor_sync(0xffffffffu, kvm, o));
        const float km = __shfl_sync(0xffffffffu, kvm, 0), vm = __shfl_sync(0xffffffffu, kvm, 16);
        const bool ok = (qn * km <= 10000.f) && (vm <= 16384.f);
        if (!ok) s_slow = 1;
    }
    float oacc[2][12];
#pragma unroll
    for (int m = 0; m < 2; m++)
#pragma unroll
        for (int i = 0; i < 12; i++) oacc[m][i] = 0.f;
    __syncthreads();
    const bool slow = s_slow != 0;

    const uint64_t dK0 = mkdesc(sK, 128, 256, 0);
    const uint64_t dV0 = mkdesc(sV, 128, 256, 0);
    uint32_t c3f;
    asm volatile("mov.b32 %0, 0x3F003F00;" : "=r"(c3f));
    if (!slow) {
#pragma unroll 1
        for (int t = 0; t < S_ / 64; t++) {
            if ((t & 3) == 0) mbar_wait(smem_u32(&bars[t >> 2]), 0);
            const uint64_t dK = dK0 + (uint64_t)(t * 64 * 32 / 16);
            const uint64_t dV = dV0 + (uint64_t)(t * 4 * 768 / 16);
#pragma unroll
            for (int m = 0; m < 2; m++) {
                float s[32];
                wg_fence();
                wgmma_rs_n64_z(s, qa[m][0], qa[m][1], qa[m][2], qa[m][3], dK);
                wg_commit();
                wg_wait<0>();
                fence_regs(s);
                uint32_t p[16];
#pragma unroll
                for (int i = 0; i < 16; i++) p[i] = is_mufu(i) ? exp_pair_mufu(s[2 * i], s[2 * i + 1]) : exp_pair_fma(s[2 * i], s[2 * i + 1], c3f);
                wg_fence();
#pragma unroll
                for (int kk = 0; kk < 4; kk++)
                    wgmma_rs_n24_tb(oacc[m], p[4 * kk], p[4 * kk + 1], p[4 * kk + 2], p[4 * kk + 3], dV + (uint64_t)(kk * 768 / 16));
                wg_commit();
            }
        }
        wg_wait<0>();
    } else {
        float mx[2][2] = {{-INFINITY, -INFINITY}, {-INFINITY, -INFINITY}};
#pragma unroll 1
        for (int t = 0; t < S_ / 64; t++) {
            if ((t & 3) == 0) mbar_wait(smem_u32(&bars[t >> 2]), 0);
            const uint64_t dK = dK0 + (uint64_t)(t * 64 * 32 / 16);
            const uint64_t dV = dV0 + (uint64_t)(t * 4 * 768 / 16);
#pragma unroll
            for (int m = 0; m < 2; m++) {
                float s[32];
                wg_fence();
                wgmma_rs_n64_z(s, qa[m][0], qa[m][1], qa[m][2], qa[m][3], dK);
                wg_commit();
                wg_wait<0>();
                fence_regs(s);
                fence_regs(oacc[m]);
                float r0 = mx[m][0], r1 = mx[m][1];
#pragma unroll
                for (int j = 0; j < 8; j++) {
                    r0 = fmaxf(r0, fmaxf(s[4 * j], s[4 * j + 1]));
                    r1 = fmaxf(r1, fmaxf(s[4 * j + 2], s[4 * j + 3]));
                }
                r0 = fmaxf(r0, __shfl_xor_sync(0xffffffffu, r0, 1)); r0 = fmaxf(r0, __shfl_xor_sync(0xffffffffu, r0, 2));
                r1 = fmaxf(r1, __shfl_xor_sync(0xffffffffu, r1, 1)); r1 = fmaxf(r1, __shfl_xor_sync(0xffffffffu, r1, 2));
                const float al0 = ex2(mx[m][0] - r0), al1 = ex2(mx[m][1] - r1);
                mx[m][0] = r0; mx[m][1] = r1;
#pragma unroll
                for (int j = 0; j < 3; j++) {
                    oacc[m][4 * j] *= al0; oacc[m][4 * j + 1] *= al0;
                    oacc[m][4 * j + 2] *= al1; oacc[m][4 * j + 3] *= al1;
                }
                uint32_t p[16];
#pragma unroll
                for (int j = 0; j < 8; j++) {
                    p[2 * j] = pack_bf16(ex2(s[4 * j] - r0), ex2(s[4 * j + 1] - r0));
                    p[2 * j + 1] = pack_bf16(ex2(s[4 * j + 2] - r1), ex2(s[4 * j + 3] - r1));
                }
                fence_regs(oacc[m]);
                wg_fence();
#pragma unroll
                for (int kk = 0; kk < 4; kk++)
                    wgmma_rs_n24_tb(oacc[m], p[4 * kk], p[4 * kk + 1], p[4 * kk + 2], p[4 * kk + 3], dV + (uint64_t)(kk * 768 / 16));
                wg_commit();
                wg_wait<0>();
            }
        }
    }
    fence_regs(oacc[0]); fence_regs(oacc[1]);
    if (tid == 0) TL(tk, 2);
#pragma unroll
    for (int m = 0; m < 2; m++) {
        const float l0 = __shfl_sync(0xffffffffu, oacc[m][8], lane & ~3);
        const float l1 = __shfl_sync(0xffffffffu, oacc[m][10], lane & ~3);
        const float r0 = __fdividef(1.0f, l0), r1 = __fdividef(1.0f, l1);
        const int row = tb * 128 + m * 64 + warp * 16 + g;
        uint32_t* p0 = (uint32_t*)(g_o + (size_t)row * D_ + head * 16);
        uint32_t* p1 = (uint32_t*)(g_o + (size_t)(row + 8) * D_ + head * 16);
        p0[c] = pack_bf16(oacc[m][0] * r0, oacc[m][1] * r0);
        p1[c] = pack_bf16(oacc[m][2] * r1, oacc[m][3] * r1);
        p0[c + 4] = pack_bf16(oacc[m][4] * r0, oacc[m][5] * r0);
        p1[c + 4] = pack_bf16(oacc[m][6] * r1, oacc[m][7] * r1);
    }
    if (tid == 0) TL(tk, 3);
}

typedef CUresult (*EncodeFn)(CUtensorMap*, CUtensorMapDataType, cuuint32_t, void*, const cuuint64_t*, const cuuint64_t*, const cuuint32_t*,
                             const cuuint32_t*, CUtensorMapInterleave, CUtensorMapSwizzle, CUtensorMapL2promotion, CUtensorMapFloatOOBfill);

EncodeFn get_encode() {
    static EncodeFn fn = nullptr;
    if (!fn) {
        void* p = nullptr;
        cudaDriverEntryPointQueryResult qr;
        cudaGetDriverEntryPoint("cuTensorMapEncodeTiled", &p, cudaEnableDefault, &qr);
        fn = (EncodeFn)p;
    }
    return fn;
}
CUtensorMap map2d(const void* ptr, uint64_t cols, uint64_t rows, uint32_t bc, uint32_t br, CUtensorMapSwizzle sw) {
    CUtensorMap m;
    cuuint64_t gd[2] = {cols, rows}, gs[1] = {cols * 2};
    cuuint32_t bx[2] = {bc, br}, es[2] = {1, 1};
    get_encode()(&m, CU_TENSOR_MAP_DATA_TYPE_BFLOAT16, 2, (void*)ptr, gd, gs, bx, es, CU_TENSOR_MAP_INTERLEAVE_NONE, sw,
                 CU_TENSOR_MAP_L2_PROMOTION_L2_128B, CU_TENSOR_MAP_FLOAT_OOB_FILL_NONE);
    return m;
}
CUtensorMap map3d32(const void* ptr, uint64_t cols, uint64_t rows, uint32_t br, uint32_t nb) {
    CUtensorMap m;
    cuuint64_t gd[3] = {32, rows, cols / 32}, gs[2] = {cols * 2, 64};
    cuuint32_t bx[3] = {32, br, nb}, es[3] = {1, 1, 1};
    get_encode()(&m, CU_TENSOR_MAP_DATA_TYPE_BFLOAT16, 3, (void*)ptr, gd, gs, bx, es, CU_TENSOR_MAP_INTERLEAVE_NONE, CU_TENSOR_MAP_SWIZZLE_64B,
                 CU_TENSOR_MAP_L2_PROMOTION_L2_128B, CU_TENSOR_MAP_FLOAT_OOB_FILL_NONE);
    return m;
}

template <typename... KArgs, typename... Args>
void launch(void (*kern)(KArgs...), int grid, int block, int smem, int cluster, bool pdl, Args... args) {
    cudaLaunchConfig_t cfg = {};
    cfg.gridDim = dim3(grid);
    cfg.blockDim = dim3(block);
    cfg.dynamicSmemBytes = smem;
    cfg.stream = cudaStreamPerThread;
    cudaLaunchAttribute at[2];
    int n = 0;
    if (cluster > 1) { at[n].id = cudaLaunchAttributeClusterDimension; at[n].val.clusterDim.x = cluster; at[n].val.clusterDim.y = 1; at[n].val.clusterDim.z = 1; n++; }
    if (pdl) { at[n].id = cudaLaunchAttributeProgrammaticStreamSerialization; at[n].val.programmaticStreamSerializationAllowed = 1; n++; }
    cfg.attrs = at;
    cfg.numAttrs = n;
    cudaLaunchKernelEx(&cfg, kern, KArgs(args)...);
}

template <typename T> void* sym(const T& s) { void* p = nullptr; cudaGetSymbolAddress(&p, s); return p; }

}

extern "C" void kernel_launch(void* const* d_in, const int* in_sizes, int n_in, void* d_out, int out_size) {
    const __nv_bfloat16* x = (const __nv_bfloat16*)d_in[0];
    const __nv_bfloat16* wq = (const __nv_bfloat16*)d_in[1];
    const __nv_bfloat16* wk = (const __nv_bfloat16*)d_in[2];
    const __nv_bfloat16* wv = (const __nv_bfloat16*)d_in[3];
    const __nv_bfloat16* wo = (const __nv_bfloat16*)d_in[4];
    const __nv_bfloat16* w1 = (const __nv_bfloat16*)d_in[6];
    const __nv_bfloat16* w2 = (const __nv_bfloat16*)d_in[7];

    constexpr int SM_QKV = GemmSmem<QKV_STAGES, EPI_QKV>::TOTAL, SM_QKV0 = GemmSmem<QKV_STAGES, EPI_QKV>::TOTAL_SELF;
    static_assert(SM_QKV0 <= 232448, "shared memory");
    constexpr int HALF_PLUS = 116736;
    constexpr int SM_WO = GemmSmem<WO_STAGES, EPI_RES>::TOTAL > HALF_PLUS ? GemmSmem<WO_STAGES, EPI_RES>::TOTAL : HALF_PLUS;
    constexpr int SM_FFN2 = GemmSmem<FFN2_STAGES, EPI_RES>::TOTAL > HALF_PLUS ? GemmSmem<FFN2_STAGES, EPI_RES>::TOTAL : HALF_PLUS;
    constexpr int SM_FFN1 = GemmSmem<FFN1_STAGES, EPI_FFN1>::TOTAL;
    cudaFuncSetAttribute(qkv_kernel<false>, cudaFuncAttributeMaxDynamicSharedMemorySize, SM_QKV);
    cudaFuncSetAttribute(qkv_kernel<true>, cudaFuncAttributeMaxDynamicSharedMemorySize, SM_QKV0);
    cudaFuncSetAttribute(res_gemm_kernel<8, WO_STAGES>, cudaFuncAttributeMaxDynamicSharedMemorySize, SM_WO);
    cudaFuncSetAttribute(ffn1_kernel, cudaFuncAttributeMaxDynamicSharedMemorySize, SM_FFN1);
    cudaFuncSetAttribute(res_gemm_kernel<28, FFN2_STAGES>, cudaFuncAttributeMaxDynamicSharedMemorySize, SM_FFN2);
    cudaFuncSetAttribute(attn_kernel, cudaFuncAttributeMaxDynamicSharedMemorySize, ATT_SMEM);
    cudaFuncSetAttribute(qkv_kernel<false>, cudaFuncAttributePreferredSharedMemoryCarveout, 100);
    cudaFuncSetAttribute(qkv_kernel<true>, cudaFuncAttributePreferredSharedMemoryCarveout, 100);
    cudaFuncSetAttribute(res_gemm_kernel<8, WO_STAGES>, cudaFuncAttributePreferredSharedMemoryCarveout, 100);
    cudaFuncSetAttribute(ffn1_kernel, cudaFuncAttributePreferredSharedMemoryCarveout, 100);
    cudaFuncSetAttribute(res_gemm_kernel<28, FFN2_STAGES>, cudaFuncAttributePreferredSharedMemoryCarveout, 100);
    cudaFuncSetAttribute(attn_kernel, cudaFuncAttributePreferredSharedMemoryCarveout, 100);

    void *q = sym(g_q), *o = sym(g_o), *x1 = sym(g_x1), *x2 = sym(g_x2), *x3 = sym(g_x3), *h = sym(g_h);
    float2* stats = (float2*)sym(g_stats);
    const void* xs[5] = {x, x1, x2, x3, d_out};

    const CUtensorMapSwizzle SW128 = CU_TENSOR_MAP_SWIZZLE_128B, SW64 = CU_TENSOR_MAP_SWIZZLE_64B;
    const CUtensorMap mWq = map3d32(wq, D_, D_, 64, 2);
    const CUtensorMap mWo = map2d(wo, D_, D_, 64, 64, SW128);
    const CUtensorMap mW1a = map3d32(w1, F_, D_, F1_BK, 4), mW1b = map3d32(w1, F_, D_, F1_BK, 3);
    const CUtensorMap mW2 = map2d(w2, D_, F_, 64, 64, SW128);
    const CUtensorMap mQ = map2d(q, D_, S_, 64, 64, SW128);
    const CUtensorMap mHst = map2d(h, F_, S_, 32, 16, SW64);
    CUtensorMap mXa[4], mXf[4], mXr[4], mXs[5];
    for (int i = 0; i < 4; i++) {
        mXa[i] = map2d(xs[i], D_, S_, 64, QKV_MC ? 64 : 128, SW128);
        mXf[i] = F1_BK == 64 ? map2d(xs[i], D_, S_, 64, 128, SW128) : map2d(xs[i], D_, S_, 32, 128, SW64);
        mXr[i] = map2d(xs[i], D_, S_, 64, 128, SW128);
    }
    for (int i = 0; i < 5; i++) mXs[i] = map2d(xs[i], D_, S_, 64, 64, SW128);
    const CUtensorMap mOa = map2d(o, D_, S_, 64, WO_MC ? 64 : 128, SW128);
    const CUtensorMap mHa = map2d(h, F_, S_, 64, F2_MC ? 64 : 128, SW128);

    for (int layer = 0; layer < 2; layer++) {
        const int xi = layer * 2;
        GemmParams p;
        p.wkv = wk; p.wv = wv;
        p.stats_in = stats + (size_t)xi * 8 * S_; p.stats_out = nullptr; p.tk = 1 + 5 * layer;
        if (layer == 0) launch(qkv_kernel<true>, 128, 544, SM_QKV0, QKV_MC ? 2 : 1, false, mXa[xi], mWq, mQ, p);
        else launch(qkv_kernel<false>, 128, 288, SM_QKV, QKV_MC ? 2 : 1, true, mXa[xi], mWq, mQ, p);
        launch(attn_kernel, layer == 0 ? 128 + SIDE_CTAS : 128, 512, ATT_SMEM, 1, true, wo, w1, w2, 2 + 5 * layer);
        p.stats_in = nullptr; p.stats_out = stats + (size_t)(xi + 1) * 8 * S_; p.tk = 3 + 5 * layer;
        launch(res_gemm_kernel<8, WO_STAGES>, 128, 288, SM_WO, WO_MC ? 2 : 1, true, mOa, mWo, mXr[xi], mXs[xi + 1], p);
        p.stats_in = stats + (size_t)(xi + 1) * 8 * S_; p.stats_out = nullptr; p.tk = 4 + 5 * layer;
        launch(ffn1_kernel, 128, F1_INLINE ? 256 : 288, SM_FFN1, F1_MC ? 2 : 1, true, mXf[xi + 1], mW1a, mW1b, mHst, p);
        p.stats_in = nullptr; p.stats_out = layer == 0 ? stats + (size_t)2 * 8 * S_ : nullptr; p.tk = 5 + 5 * layer;
        launch(res_gemm_kernel<28, FFN2_STAGES>, 128, 288, SM_FFN2, F2_MC ? 2 : 1, true, mHa, mW2, mXr[xi + 1], mXs[xi + 2], p);
    }
}
```

```cpp
#include <cuda_runtime.h>
#include <cuda_bf16.h>
#include <cuda.h>
#include <stdint.h>

#define F1_INLINE 0
#define QKV_MC 0
#define WO_MC 0
#define F2_MC 0
#define F1_MC 2
#define SELF_WAIT 1
#define PREB 1
#define RES_WAIT0 0

namespace {

constexpr int S_ = 2048, D_ = 512, H_ = 32, F_ = 1792;

__device__ __align__(1024) __nv_bfloat16 g_q[S_ * D_];
__device__ __align__(1024) __nv_bfloat16 g_o[S_ * D_];
__device__ __align__(1024) __nv_bfloat16 g_x1[S_ * D_];
__device__ __align__(1024) __nv_bfloat16 g_x2[S_ * D_];
__device__ __align__(1024) __nv_bfloat16 g_x3[S_ * D_];
__device__ __align__(1024) __nv_bfloat16 g_h[S_ * F_];
__device__ __align__(1024) uint8_t g_kimg[S_ * 32];
__device__ __align__(1024) uint8_t g_vimg[(S_ / 16) * 768];
__device__ __align__(1024) float2 g_stats[4][8 * S_];
__device__ __align__(16) float g_cs_q[D_];
__device__ __align__(16) float g_cs_kv[32];
__device__ __align__(16) float g_cs_1[F_];
__device__ __align__(16) float g_kvmax[32];

#define TL(k, slot)
#define CK(k, i)

__device__ __forceinline__ uint32_t smem_u32(const void* p) { return (uint32_t)__cvta_generic_to_shared(p); }
__device__ __forceinline__ void mbar_init(uint32_t bar, uint32_t cnt) {
    asm volatile("mbarrier.init.shared::cta.b64 [%0], %1;" ::"r"(bar), "r"(cnt));
}
__device__ __forceinline__ void mbar_expect_tx(uint32_t bar, uint32_t bytes) {
    asm volatile("mbarrier.arrive.expect_tx.shared::cta.b64 _, [%0], %1;" ::"r"(bar), "r"(bytes) : "memory");
}
__device__ __forceinline__ void mbar_arrive(uint32_t bar) {
    asm volatile("mbarrier.arrive.shared::cta.b64 _, [%0];" ::"r"(bar) : "memory");
}
__device__ __forceinline__ void mbar_arrive_remote(uint32_t bar, uint32_t cta) {
    asm volatile("{\n.reg .b32 ra;\nmapa.shared::cluster.u32 ra, %0, %1;\nmbarrier.arrive.shared::cluster.b64 _, [ra];\n}" ::"r"(bar), "r"(cta) : "memory");
}
__device__ __forceinline__ void mbar_wait(uint32_t bar, uint32_t parity) {
    asm volatile("{\n.reg .pred p;\nWAIT_%=:\nmbarrier.try_wait.parity.shared::cta.b64 p, [%0], %1;\n@p bra DONE_%=;\nbra WAIT_%=;\nDONE_%=:\n}" ::"r"(bar), "r"(parity) : "memory");
}
__device__ __forceinline__ void bulk_load(uint32_t dst, const void* src, uint32_t bytes, uint32_t bar) {
    asm volatile("cp.async.bulk.shared::cluster.global.mbarrier::complete_tx::bytes [%0], [%1], %2, [%3];" ::"r"(dst), "l"(src), "r"(bytes), "r"(bar) : "memory");
}
__device__ __forceinline__ void tma2d(uint32_t dst, const CUtensorMap* m, int c0, int c1, uint32_t bar) {
    asm volatile("cp.async.bulk.tensor.2d.shared::cluster.global.mbarrier::complete_tx::bytes [%0], [%1, {%3, %4}], [%2];" ::"r"(dst), "l"(m), "r"(bar), "r"(c0), "r"(c1) : "memory");
}
__device__ __forceinline__ void tma2d_mc(uint32_t dst, const CUtensorMap* m, int c0, int c1, uint32_t bar, uint16_t mask) {
    asm volatile("cp.async.bulk.tensor.2d.shared::cluster.global.mbarrier::complete_tx::bytes.multicast::cluster [%0], [%1, {%3, %4}], [%2], %5;" ::"r"(dst), "l"(m), "r"(bar), "r"(c0), "r"(c1), "h"(mask) : "memory");
}
__device__ __forceinline__ void tma3d(uint32_t dst, const CUtensorMap* m, int c0, int c1, int c2, uint32_t bar) {
    asm volatile("cp.async.bulk.tensor.3d.shared::cluster.global.mbarrier::complete_tx::bytes [%0], [%1, {%3, %4, %5}], [%2];" ::"r"(dst), "l"(m), "r"(bar), "r"(c0), "r"(c1), "r"(c2) : "memory");
}
__device__ __forceinline__ void tma3d_mc(uint32_t dst, const CUtensorMap* m, int c0, int c1, int c2, uint32_t bar, uint16_t mask) {
    asm volatile("cp.async.bulk.tensor.3d.shared::cluster.global.mbarrier::complete_tx::bytes.multicast::cluster [%0], [%1, {%3, %4, %5}], [%2], %6;" ::"r"(dst), "l"(m), "r"(bar), "r"(c0), "r"(c1), "r"(c2), "h"(mask) : "memory");
}
__device__ __forceinline__ void tma2d_store(const CUtensorMap* m, uint32_t src, int c0, int c1) {
    asm volatile("cp.async.bulk.tensor.2d.global.shared::cta.bulk_group [%0, {%2, %3}], [%1];" ::"l"(m), "r"(src), "r"(c0), "r"(c1) : "memory");
}
__device__ __forceinline__ void tma3d_store(const CUtensorMap* m, uint32_t src, int c0, int c1, int c2) {
    asm volatile("cp.async.bulk.tensor.3d.global.shared::cta.bulk_group [%0, {%2, %3, %4}], [%1];" ::"l"(m), "r"(src), "r"(c0), "r"(c1), "r"(c2) : "memory");
}
__device__ __forceinline__ void bulk_commit() { asm volatile("cp.async.bulk.commit_group;" ::: "memory"); }
__device__ __forceinline__ void bulk_wait_read() { asm volatile("cp.async.bulk.wait_group.read 0;" ::: "memory"); }
__device__ __forceinline__ void prefetch_tmap(const CUtensorMap* m) { asm volatile("prefetch.tensormap [%0];" ::"l"(m) : "memory"); }
__device__ __forceinline__ void fence_async_smem() { asm volatile("fence.proxy.async.shared::cta;" ::: "memory"); }
__device__ __forceinline__ void fence_mbar_init() { asm volatile("fence.mbarrier_init.release.cluster;" ::: "memory"); }
__device__ __forceinline__ void cluster_sync() { asm volatile("barrier.cluster.arrive.release.aligned;\nbarrier.cluster.wait.acquire.aligned;" ::: "memory"); }
__device__ __forceinline__ uint32_t cluster_rank() { uint32_t r; asm volatile("mov.u32 %0, %%cluster_ctarank;" : "=r"(r)); return r; }
__device__ __forceinline__ void pdl_wait() { asm volatile("griddepcontrol.wait;" ::: "memory"); }
__device__ __forceinline__ void pdl_launch() { asm volatile("griddepcontrol.launch_dependents;" ::: "memory"); }
__device__ __forceinline__ bool elect_one() {
    uint32_t p;
    asm volatile("{\n.reg .pred p;\nelect.sync _|p, 0xffffffff;\nselp.b32 %0, 1, 0, p;\n}" : "=r"(p));
    return p != 0;
}
__device__ __forceinline__ void named_bar(int id, int n) { asm volatile("bar.sync %0, %1;" ::"r"(id), "r"(n) : "memory"); }

__device__ __forceinline__ void wg_fence() { asm volatile("wgmma.fence.sync.aligned;" ::: "memory"); }
__device__ __forceinline__ void wg_commit() { asm volatile("wgmma.commit_group.sync.aligned;" ::: "memory"); }
template <int N> __device__ __forceinline__ void wg_wait() { asm volatile("wgmma.wait_group.sync.aligned %0;" ::"n"(N) : "memory"); }
template <int N> __device__ __forceinline__ void fence_regs(float (&d)[N]) {
#pragma unroll
    for (int i = 0; i < N; i++) asm volatile("" : "+f"(d[i])::"memory");
}
__device__ __forceinline__ uint64_t mkdesc(uint32_t addr, uint32_t lbo, uint32_t sbo, uint32_t swz) {
    uint64_t d = 0;
    d |= (uint64_t)((addr & 0x3FFFF) >> 4);
    d |= (uint64_t)((lbo & 0x3FFFF) >> 4) << 16;
    d |= (uint64_t)((sbo & 0x3FFFF) >> 4) << 32;
    d |= (uint64_t)swz << 62;
    return d;
}
__device__ __forceinline__ void ldsm_x4(uint32_t& r0, uint32_t& r1, uint32_t& r2, uint32_t& r3, uint32_t addr) {
    asm volatile("ldmatrix.sync.aligned.m8n8.x4.shared.b16 {%0,%1,%2,%3}, [%4];" : "=r"(r0), "=r"(r1), "=r"(r2), "=r"(r3) : "r"(addr) : "memory");
}
__device__ __forceinline__ void stsm_x4(uint32_t addr, uint32_t r0, uint32_t r1, uint32_t r2, uint32_t r3) {
    asm volatile("stmatrix.sync.aligned.m8n8.x4.shared.b16 [%0], {%1,%2,%3,%4};" ::"r"(addr), "r"(r0), "r"(r1), "r"(r2), "r"(r3) : "memory");
}
__device__ __forceinline__ void ldsm_x4_t(uint32_t& r0, uint32_t& r1, uint32_t& r2, uint32_t& r3, uint32_t addr) {
    asm volatile("ldmatrix.sync.aligned.m8n8.x4.trans.shared.b16 {%0,%1,%2,%3}, [%4];" : "=r"(r0), "=r"(r1), "=r"(r2), "=r"(r3) : "r"(addr) : "memory");
}
__device__ __forceinline__ void hmma(float (&d)[4], uint32_t a0, uint32_t a1, uint32_t a2, uint32_t a3, uint32_t b0, uint32_t b1) {
    asm volatile("mma.sync.aligned.m16n8k16.row.col.f32.bf16.bf16.f32 {%0,%1,%2,%3}, {%4,%5,%6,%7}, {%8,%9}, {%0,%1,%2,%3};"
                 : "+f"(d[0]), "+f"(d[1]), "+f"(d[2]), "+f"(d[3]) : "r"(a0), "r"(a1), "r"(a2), "r"(a3), "r"(b0), "r"(b1));
}
__device__ __forceinline__ uint32_t pack_bf16(float lo, float hi) {
    uint32_t r;
    asm("cvt.rn.bf16x2.f32 %0, %1, %2;" : "=r"(r) : "f"(hi), "f"(lo));
    return r;
}
__device__ __forceinline__ float bf_lo(uint32_t v) { return __uint_as_float(v << 16); }
__device__ __forceinline__ float bf_hi(uint32_t v) { return __uint_as_float(v & 0xFFFF0000u); }

#define WG_REGS_4(o) "+f"(d[o]), "+f"(d[o + 1]), "+f"(d[o + 2]), "+f"(d[o + 3])
#define WG_REGS_8(o) WG_REGS_4(o), WG_REGS_4(o + 4)
#define WG_REGS_16(o) WG_REGS_8(o), WG_REGS_8(o + 8)
#define WG_REGS_32(o) WG_REGS_16(o), WG_REGS_16(o + 16)

__device__ __forceinline__ void wgmma_ss_n80_tb(float (&d)[40], uint64_t dA, uint64_t dB, int sc) {
    asm volatile("{\n.reg .pred p;\nsetp.ne.b32 p, %42, 0;\n"
                 "wgmma.mma_async.sync.aligned.m64n80k16.f32.bf16.bf16 "
                 "{%0,%1,%2,%3,%4,%5,%6,%7,%8,%9,%10,%11,%12,%13,%14,%15,%16,%17,%18,%19,%20,%21,%22,%23,%24,%25,%26,%27,%28,%29,%30,%31,"
                 "%32,%33,%34,%35,%36,%37,%38,%39}, %40, %41, p, 1, 1, 0, 1;\n}\n"
                 : WG_REGS_32(0), WG_REGS_8(32) : "l"(dA), "l"(dB), "r"(sc));
}
__device__ __forceinline__ void wgmma_ss_n64_tb(float (&d)[32], uint64_t dA, uint64_t dB, int sc) {
    asm volatile("{\n.reg .pred p;\nsetp.ne.b32 p, %34, 0;\n"
                 "wgmma.mma_async.sync.aligned.m64n64k16.f32.bf16.bf16 "
                 "{%0,%1,%2,%3,%4,%5,%6,%7,%8,%9,%10,%11,%12,%13,%14,%15,%16,%17,%18,%19,%20,%21,%22,%23,%24,%25,%26,%27,%28,%29,%30,%31}, "
                 "%32, %33, p, 1, 1, 0, 1;\n}\n"
                 : WG_REGS_32(0) : "l"(dA), "l"(dB), "r"(sc));
}
__device__ __forceinline__ void wgmma_ss_n224_tb(float (&d)[112], uint64_t dA, uint64_t dB, int sc) {
    asm volatile("{\n.reg .pred p;\nsetp.ne.b32 p, %114, 0;\n"
                 "wgmma.mma_async.sync.aligned.m64n224k16.f32.bf16.bf16 "
                 "{%0,%1,%2,%3,%4,%5,%6,%7,%8,%9,%10,%11,%12,%13,%14,%15,%16,%17,%18,%19,%20,%21,%22,%23,%24,%25,%26,%27,%28,%29,%30,%31,"
                 "%32,%33,%34,%35,%36,%37,%38,%39,%40,%41,%42,%43,%44,%45,%46,%47,%48,%49,%50,%51,%52,%53,%54,%55,%56,%57,%58,%59,%60,%61,%62,%63,"
                 "%64,%65,%66,%67,%68,%69,%70,%71,%72,%73,%74,%75,%76,%77,%78,%79,%80,%81,%82,%83,%84,%85,%86,%87,%88,%89,%90,%91,%92,%93,%94,%95,"
                 "%96,%97,%98,%99,%100,%101,%102,%103,%104,%105,%106,%107,%108,%109,%110,%111}, "
                 "%112, %113, p, 1, 1, 0, 1;\n}\n"
                 : WG_REGS_32(0), WG_REGS_32(32), WG_REGS_32(64), WG_REGS_16(96) : "l"(dA), "l"(dB), "r"(sc));
}
template <int BN> __device__ __forceinline__ void wgmma_ss_tb(float (&d)[BN / 2], uint64_t dA, uint64_t dB, int sc) {
    if constexpr (BN == 64) wgmma_ss_n64_tb(d, dA, dB, sc);
    else if constexpr (BN == 80) wgmma_ss_n80_tb(d, dA, dB, sc);
    else wgmma_ss_n224_tb(d, dA, dB, sc);
}
__device__ __forceinline__ void wgmma_rs_n64_tb(float (&d)[32], uint32_t a, uint64_t dB, int sc) {
    asm volatile("{\n.reg .pred p;\nsetp.ne.b32 p, %34, 0;\n"
                 "wgmma.mma_async.sync.aligned.m64n64k16.f32.bf16.bf16 "
                 "{%0,%1,%2,%3,%4,%5,%6,%7,%8,%9,%10,%11,%12,%13,%14,%15,%16,%17,%18,%19,%20,%21,%22,%23,%24,%25,%26,%27,%28,%29,%30,%31}, "
                 "{%32,%32,%32,%32}, %33, p, 1, 1, 1;\n}\n"
                 : WG_REGS_32(0) : "r"(a), "l"(dB), "r"(sc));
}
__device__ __forceinline__ void wgmma_rs_n80_tb(float (&d)[40], uint32_t a, uint64_t dB, int sc) {
    asm volatile("{\n.reg .pred p;\nsetp.ne.b32 p, %42, 0;\n"
                 "wgmma.mma_async.sync.aligned.m64n80k16.f32.bf16.bf16 "
                 "{%0,%1,%2,%3,%4,%5,%6,%7,%8,%9,%10,%11,%12,%13,%14,%15,%16,%17,%18,%19,%20,%21,%22,%23,%24,%25,%26,%27,%28,%29,%30,%31,"
                 "%32,%33,%34,%35,%36,%37,%38,%39}, {%40,%40,%40,%40}, %41, p, 1, 1, 1;\n}\n"
                 : WG_REGS_32(0), WG_REGS_8(32) : "r"(a), "l"(dB), "r"(sc));
}
template <int BN> __device__ __forceinline__ void wgmma_rs_ones(float (&d)[BN / 2], uint64_t dB, int sc) {
    if constexpr (BN == 80) wgmma_rs_n80_tb(d, 0x3F803F80u, dB, sc);
    else if constexpr (BN == 64) wgmma_rs_n64_tb(d, 0x3F803F80u, dB, sc);
}
__device__ __forceinline__ void wgmma_rs_n64_z(float (&d)[32], uint32_t a0, uint32_t a1, uint32_t a2, uint32_t a3, uint64_t dB) {
    asm volatile("{\n.reg .pred p;\nsetp.ne.b32 p, 0, 0;\n"
                 "wgmma.mma_async.sync.aligned.m64n64k16.f32.bf16.bf16 "
                 "{%0,%1,%2,%3,%4,%5,%6,%7,%8,%9,%10,%11,%12,%13,%14,%15,%16,%17,%18,%19,%20,%21,%22,%23,%24,%25,%26,%27,%28,%29,%30,%31}, "
                 "{%32,%33,%34,%35}, %36, p, 1, 1, 0;\n}\n"
                 : "=f"(d[0]), "=f"(d[1]), "=f"(d[2]), "=f"(d[3]), "=f"(d[4]), "=f"(d[5]), "=f"(d[6]), "=f"(d[7]),
                   "=f"(d[8]), "=f"(d[9]), "=f"(d[10]), "=f"(d[11]), "=f"(d[12]), "=f"(d[13]), "=f"(d[14]), "=f"(d[15]),
                   "=f"(d[16]), "=f"(d[17]), "=f"(d[18]), "=f"(d[19]), "=f"(d[20]), "=f"(d[21]), "=f"(d[22]), "=f"(d[23]),
                   "=f"(d[24]), "=f"(d[25]), "=f"(d[26]), "=f"(d[27]), "=f"(d[28]), "=f"(d[29]), "=f"(d[30]), "=f"(d[31])
                 : "r"(a0), "r"(a1), "r"(a2), "r"(a3), "l"(dB));
}
__device__ __forceinline__ void wgmma_rs_n24_tb(float (&d)[12], uint32_t a0, uint32_t a1, uint32_t a2, uint32_t a3, uint64_t dB) {
    asm volatile("{\n.reg .pred p;\nsetp.eq.b32 p, 0, 0;\n"
                 "wgmma.mma_async.sync.aligned.m64n24k16.f32.bf16.bf16 "
                 "{%0,%1,%2,%3,%4,%5,%6,%7,%8,%9,%10,%11}, {%12,%13,%14,%15}, %16, p, 1, 1, 1;\n}\n"
                 : WG_REGS_8(0), WG_REGS_4(8) : "r"(a0), "r"(a1), "r"(a2), "r"(a3), "l"(dB));
}

constexpr int SIDE_CTAS = 4;
__device__ __forceinline__ void side_job(int cta, float* red  , const __nv_bfloat16* __restrict__ wo,
                                         const __nv_bfloat16* __restrict__ w1, const __nv_bfloat16* __restrict__ w2) {
    const int tid = threadIdx.x, warp = tid >> 5, lane = tid & 31;
    for (int line = cta * 512 + tid; line < 18432; line += SIDE_CTAS * 512) {
        const char* p = line < 4096 ? (const char*)wo + (size_t)line * 128 : (const char*)w2 + (size_t)(line - 4096) * 128;
        asm volatile("prefetch.global.L2 [%0];" ::"l"(p));
    }
    const int rg = lane >> 3, c8 = lane & 7;
    for (int slab = cta; slab < F_ / 64; slab += SIDE_CTAS) {
        const __nv_bfloat16* base = w1 + slab * 64 + c8 * 8;
        uint4 v[8];
#pragma unroll
        for (int i = 0; i < 8; i++) v[i] = __ldg((const uint4*)(base + (size_t)(warp * 32 + rg + 4 * i) * F_));
        float acc[8];
#pragma unroll
        for (int i = 0; i < 8; i++) acc[i] = 0.f;
#pragma unroll
        for (int i = 0; i < 8; i++) {
            acc[0] += bf_lo(v[i].x); acc[1] += bf_hi(v[i].x); acc[2] += bf_lo(v[i].y); acc[3] += bf_hi(v[i].y);
            acc[4] += bf_lo(v[i].z); acc[5] += bf_hi(v[i].z); acc[6] += bf_lo(v[i].w); acc[7] += bf_hi(v[i].w);
        }
#pragma unroll
        for (int i = 0; i < 8; i++) {
            acc[i] += __shfl_xor_sync(0xffffffffu, acc[i], 8);
            acc[i] += __shfl_xor_sync(0xffffffffu, acc[i], 16);
        }
        if (rg == 0) {
#pragma unroll
            for (int i = 0; i < 8; i++) red[warp * 64 + c8 * 8 + i] = acc[i];
        }
        __syncthreads();
        if (tid < 64) {
            float s = 0.f;
#pragma unroll
            for (int i = 0; i < 16; i++) s += red[i * 64 + tid];
            g_cs_1[slab * 64 + tid] = s;
        }
        __syncthreads();
    }
}

enum { EPI_QKV = 0, EPI_RES = 1, EPI_FFN1 = 2 };

struct GemmParams {
    const float2* stats_in;
    float2* stats_out;
    const __nv_bfloat16* wkv;
    const __nv_bfloat16* wv;
    int tk;
};

template <int BK_, int NBLK> struct Geo {
    static constexpr int BK = BK_, A_BYTES = 128 * BK * 2, A_SWZ = BK == 64 ? 1 : 2, A_SBO = BK * 16;
    static constexpr int BLK = BK * 64;
    static constexpr int B_BYTES = NBLK * BLK, B_SWZ = 2, B_LBO = BLK, B_SBO = 512, B_KSTEP = 1024;
};
template <> struct Geo<64, 0> {
    static constexpr int BK = 64, A_BYTES = 128 * 128, A_SWZ = 1, A_SBO = 1024, BLK = 8192;
    static constexpr int B_BYTES = 64 * 128, B_SWZ = 1, B_LBO = 8192, B_SBO = 1024, B_KSTEP = 2048;
};
#define F1_BK 32
template <int EPI> struct EpiGeo;
template <> struct EpiGeo<EPI_QKV> { using G = Geo<64, 3>; };
template <> struct EpiGeo<EPI_RES> { using G = Geo<64, 0>; };
template <> struct EpiGeo<EPI_FFN1> { using G = Geo<F1_BK, 7>; };

template <int STAGES, int EPI> struct GemmSmem {
    using G = typename EpiGeo<EPI>::G;
    static constexpr int STAGE = G::A_BYTES + G::B_BYTES;
    static constexpr int AUX_OFF = STAGES * STAGE;
    static constexpr int TOTAL = AUX_OFF + 1152;
    static constexpr int TOTAL_SELF = AUX_OFF + 704 + 1024 + 1280;
};

struct RowStatRaw { float2 a0, a1, b0, b1; };
__device__ __forceinline__ RowStatRaw load_row_stats(const float2* __restrict__ st, int row0, int c) {
    RowStatRaw r;
    r.a0 = st[(2 * c) * S_ + row0]; r.a1 = st[(2 * c + 1) * S_ + row0];
    r.b0 = st[(2 * c) * S_ + row0 + 8]; r.b1 = st[(2 * c + 1) * S_ + row0 + 8];
    return r;
}
__device__ __forceinline__ void finish_row_stats(const RowStatRaw& r, float& mean0, float& rstd0, float& mean1, float& rstd1) {
    float sa = r.a0.x + r.a1.x, sb = r.b0.x + r.b1.x;
    sa += __shfl_xor_sync(0xffffffffu, sa, 1); sa += __shfl_xor_sync(0xffffffffu, sa, 2);
    sb += __shfl_xor_sync(0xffffffffu, sb, 1); sb += __shfl_xor_sync(0xffffffffu, sb, 2);
    mean0 = sa * 0.125f; mean1 = sb * 0.125f;
    float ma = r.a0.y + r.a1.y + 64.f * ((r.a0.x - mean0) * (r.a0.x - mean0) + (r.a1.x - mean0) * (r.a1.x - mean0));
    float mb = r.b0.y + r.b1.y + 64.f * ((r.b0.x - mean1) * (r.b0.x - mean1) + (r.b1.x - mean1) * (r.b1.x - mean1));
    ma += __shfl_xor_sync(0xffffffffu, ma, 1); ma += __shfl_xor_sync(0xffffffffu, ma, 2);
    mb += __shfl_xor_sync(0xffffffffu, mb, 1); mb += __shfl_xor_sync(0xffffffffu, mb, 2);
    rstd0 = 1.0f / sqrtf(ma * (1.f / 512.f) + 1e-5f);
    rstd1 = 1.0f / sqrtf(mb * (1.f / 512.f) + 1e-5f);
}

template <int BN, int KB, int STAGES, int EPI, int MC, bool SELF = false>
__device__ __forceinline__ void gemm_body(const CUtensorMap* mapA, const CUtensorMap* mapB, const CUtensorMap* mapB2, const CUtensorMap* mapR,
                                          const CUtensorMap* mapC, const GemmParams& prm, int tile_m, int tile_n, uint8_t* smem_raw) {
    using SM = GemmSmem<STAGES, EPI>;
    using G = typename SM::G;
    constexpr bool XKV = BN == 80;
    constexpr int TN = EPI == EPI_QKV ? 64 : BN;
    pdl_launch();
    const uint32_t sbase = smem_u32(smem_raw);
    if (sbase & 1023) __trap();
    uint8_t* sgen = smem_raw;
    const uint32_t bar_full = sbase + SM::AUX_OFF, bar_empty = bar_full + 8 * STAGES;
    float* s_cs = (float*)(sgen + SM::AUX_OFF + 256);
    float* s_row = (float*)(sgen + SM::AUX_OFF + 704);
    float* s_red = (float*)(sgen + SM::AUX_OFF + 640);
    const int tid = threadIdx.x, lane = tid & 31;
    const int warp = __shfl_sync(0xffffffffu, tid >> 5, 0);
    const uint32_t rank = MC ? cluster_rank() : 0;
    if (tid == 0) TL(prm.tk, 0);

    constexpr bool INLINE_PROD = EPI == EPI_FFN1 && F1_INLINE;
    constexpr int PWARP = INLINE_PROD ? 0 : 8;
    if (warp == PWARP && elect_one()) {
        prefetch_tmap(mapB); prefetch_tmap(mapA); prefetch_tmap(mapC);
        for (int s = 0; s < STAGES; s++) { mbar_init(bar_full + 8 * s, 1); mbar_init(bar_empty + 8 * s, MC ? 4 : 2); }
        fence_mbar_init();
    }
    __syncthreads();
    if (MC) cluster_sync();

    const int m0 = tile_m * 128, n0 = tile_n * TN;
    constexpr uint32_t STAGE_TX = G::A_BYTES + (EPI == EPI_QKV ? 2 * G::BLK : G::B_BYTES);
    auto loadB = [&](int kb, int s) {
        const uint32_t dst = sbase + s * SM::STAGE + G::A_BYTES, bar = bar_full + 8 * s;
        if constexpr (EPI == EPI_RES) {
            tma2d(dst, mapB, n0, kb * 64, bar);
        } else if constexpr (EPI == EPI_QKV) {
            tma3d(dst, mapB, 0, kb * G::BK, tile_n * 2, bar);
        } else {
            if constexpr (MC == 2) {
                if (rank == 0) tma3d_mc(dst, mapB, 0, kb * G::BK, tile_n * 7, bar, 3);
                else tma3d_mc(dst + 4 * G::BLK, mapB2, 0, kb * G::BK, tile_n * 7 + 4, bar, 3);
            } else {
                tma3d(dst, mapB, 0, kb * G::BK, tile_n * 7, bar);
                tma3d(dst + 4 * G::BLK, mapB2, 0, kb * G::BK, tile_n * 7 + 4, bar);
            }
        }
    };
    auto loadA = [&](int kb, int s) {
        const uint32_t dst = sbase + s * SM::STAGE, bar = bar_full + 8 * s;
        if constexpr (MC == 1) tma2d_mc(dst + rank * (G::A_BYTES / 2), mapA, kb * G::BK, m0 + rank * 64, bar, 3);
        else tma2d(dst, mapA, kb * G::BK, m0, bar);
    };
    constexpr int PRE = STAGES < KB ? STAGES : KB;
#define F1_LAG 2
    constexpr int LAG = F1_LAG;
    constexpr int PRE_B = PRE < PREB ? PRE : PREB;
    auto prologue_loads = [&]() {
        if (elect_one()) {
#pragma unroll
            for (int kb = 0; kb < PRE; kb++) mbar_expect_tx(bar_full + 8 * kb, STAGE_TX);
#pragma unroll
            for (int kb = 0; kb < PRE_B; kb++) loadB(kb, kb);
        }
        if (!SELF) pdl_wait();
        if (elect_one()) {
#pragma unroll
            for (int kb = 0; kb < PRE; kb++) {
                loadA(kb, kb);
                if (kb + PRE_B < PRE) loadB(kb + PRE_B, kb + PRE_B);
            }
            if constexpr (EPI == EPI_RES && KB < STAGES) {
                mbar_expect_tx(bar_full + 8 * KB, 16384);
                tma2d(sbase + KB * SM::STAGE, mapR, n0, m0, bar_full + 8 * KB);
            }
        }
    };
    if (SELF && warp > 8) {
        static_assert(!SELF || (STAGES >= KB && EPI == EPI_QKV), "SELF needs every k block resident");
        const int t = tid - 288;
        float ss[4] = {0.f, 0.f, 0.f, 0.f}, sq[4] = {0.f, 0.f, 0.f, 0.f};
        auto row_stats = [&](int kb) {
            const uint32_t arow = sbase + kb * SM::STAGE + (t >> 1) * 128;
            uint32_t w[4][4];
#pragma unroll
            for (int j = 0; j < 4; j++)
                asm volatile("ld.shared.v4.u32 {%0,%1,%2,%3}, [%4];" : "=r"(w[j][0]), "=r"(w[j][1]), "=r"(w[j][2]), "=r"(w[j][3])
                             : "r"(arow + (((2 * j + (t & 1) + 2 * ((t >> 1) & 3)) & 7) << 4)));
#pragma unroll
            for (int j = 0; j < 4; j++)
#pragma unroll
                for (int i = 0; i < 4; i++) {
                    const float lo = bf_lo(w[j][i]), hi = bf_hi(w[j][i]);
                    ss[i] += lo + hi;
                    sq[i] = fmaf(lo, lo, fmaf(hi, hi, sq[i]));
                }
        };
        if ((warp >> 2) == 3) {
            float csum[BN / 2];
            const uint64_t dB0 = mkdesc(sbase + G::A_BYTES, G::B_LBO, G::B_SBO, G::B_SWZ);
            if constexpr (XKV) named_bar(6, 512);
#pragma unroll 1
            for (int kb = 0; kb < KB; kb++) {
                mbar_wait(bar_full + 8 * kb, 0);
                const uint64_t dB = dB0 + (uint64_t)(kb * (SM::STAGE >> 4));
                wg_fence();
#pragma unroll
                for (int k = 0; k < G::BK / 16; k++) {
                    if constexpr (SELF) wgmma_rs_ones<BN>(csum, dB + (uint64_t)(k * (G::B_KSTEP >> 4)), (kb | k) != 0);
                }
                wg_commit();
                wg_wait<0>();
                row_stats(kb);
            }
            wg_wait<0>();
            fence_regs(csum);
            if (warp == 12 && lane < 4) {
#pragma unroll
                for (int j = 0; j < BN / 8; j++) {
                    const float2 v = make_float2(csum[4 * j], csum[4 * j + 1]);
                    *(float2*)(s_cs + 8 * j + 2 * lane) = v;
                    if (tile_m == 0) {
                        if (j < 8) *(float2*)(g_cs_q + n0 + 8 * j + 2 * lane) = v;
                        else *(float2*)(g_cs_kv + tile_n * 16 + 8 * (j - 8) + 2 * lane) = v;
                    }
                }
            }
        } else {
            if constexpr (XKV) named_bar(6, 512);
#pragma unroll 1
            for (int kb = 0; kb < KB; kb++) {
                mbar_wait(bar_full + 8 * kb, 0);
                row_stats(kb);
            }
        }
        float tsum = (ss[0] + ss[1]) + (ss[2] + ss[3]), tsq = (sq[0] + sq[1]) + (sq[2] + sq[3]);
        tsum += __shfl_xor_sync(0xffffffffu, tsum, 1);
        tsq += __shfl_xor_sync(0xffffffffu, tsq, 1);
        if ((t & 1) == 0) {
            const float md = tsum * (1.f / 512.f);
            const float var = fmaxf(tsq * (1.f / 512.f) - md * md, 0.f);
            *(float2*)(s_row + t) = make_float2(md, 1.0f / sqrtf(var + 1e-5f));
        }
        named_bar(4, 512);
    } else if (!INLINE_PROD && warp == 8) {
        prologue_loads();
        int s = PRE % STAGES, ph = (PRE / STAGES) & 1;
#pragma unroll 1
        for (int kb = PRE; kb < KB; kb++) {
            mbar_wait(bar_empty + 8 * s, ph ^ 1);
            if (elect_one()) {
                mbar_expect_tx(bar_full + 8 * s, STAGE_TX);
                loadB(kb, s);
                loadA(kb, s);
            }
            if (++s == STAGES) { s = 0; ph ^= 1; }
        }
        if constexpr (EPI == EPI_RES && KB >= STAGES) {
            mbar_wait(bar_empty + 8 * s, ph ^ 1);
            if (elect_one()) {
                mbar_expect_tx(bar_full + 8 * s, 16384);
                tma2d(sbase + s * SM::STAGE, mapR, n0, m0, bar_full + 8 * s);
            }
        }
    } else {
        if (INLINE_PROD && warp == 0) prologue_loads();
        const int wg = warp >> 2, g = lane >> 2, c = lane & 3;
        const int rloc = wg * 64 + (warp & 3) * 16 + g;
        const int row0 = m0 + rloc;
        float mean0 = 0.f, rstd0 = 1.f, mean1 = 0.f, rstd1 = 1.f;
        if constexpr (XKV) {
            static_assert(!XKV || STAGES >= KB, "the K / V weight block must stay resident");
            const __nv_bfloat16* wsrc = tile_n == 0 ? prm.wkv : prm.wv;
            uint4 v[4];
#pragma unroll
            for (int i = 0; i < 4; i++) v[i] = __ldg((const uint4*)wsrc + tid + 256 * i);
#pragma unroll
            for (int i = 0; i < 4; i++) {
                const int idx = tid + 256 * i, k = idx >> 1, kr = k & 63;
                const uint32_t dst = sbase + (k >> 6) * SM::STAGE + G::A_BYTES + 2 * G::BLK + kr * 64 + (((idx & 1) ^ ((kr >> 1) & 3)) << 4);
                asm volatile("st.shared.v4.u32 [%0], {%1,%2,%3,%4};" ::"r"(dst), "r"(v[i].x), "r"(v[i].y), "r"(v[i].z), "r"(v[i].w) : "memory");
            }
            fence_async_smem();
            if constexpr (SELF) named_bar(6, 512); else named_bar(6, 256);
        }
        RowStatRaw raw;
        float csv = 0.f;
        float2 cskv[2] = {make_float2(0.f, 0.f), make_float2(0.f, 0.f)};
        auto ln_inputs = [&]() {
            pdl_wait();
            if constexpr (EPI != EPI_RES) {
                raw = load_row_stats(prm.stats_in, row0, c);
                const float* cs = EPI == EPI_FFN1 ? g_cs_1 + n0 : g_cs_q + n0;
                if (tid < TN) csv = cs[tid];
                if constexpr (XKV) {
                    cskv[0] = *(const float2*)(g_cs_kv + tile_n * 16 + 2 * c);
                    cskv[1] = *(const float2*)(g_cs_kv + tile_n * 16 + 8 + 2 * c);
                }
            }
        };
        if (!SELF) ln_inputs();
        float acc[BN / 2];
        const uint64_t dA0 = mkdesc(sbase + wg * (G::A_BYTES / 2), 16, G::A_SBO, G::A_SWZ);
        const uint64_t dB0 = mkdesc(sbase + G::A_BYTES, G::B_LBO, G::B_SBO, G::B_SWZ);
        int s = 0, ph = 0;
#pragma unroll 1
        for (int kb = 0; kb < KB; kb++) {
            mbar_wait(bar_full + 8 * s, ph);
            const uint64_t dA = dA0 + (uint64_t)(s * (SM::STAGE >> 4)), dB = dB0 + (uint64_t)(s * (SM::STAGE >> 4));
            wg_fence();
#pragma unroll
            for (int k = 0; k < G::BK / 16; k++) wgmma_ss_tb<BN>(acc, dA + (uint64_t)(k * 2), dB + (uint64_t)(k * (G::B_KSTEP >> 4)), (kb | k) != 0);
            wg_commit();
            if constexpr (EPI == EPI_RES && RES_WAIT0) {
                wg_wait<0>();
                if ((warp & 3) == 0 && elect_one()) {
                    if (MC) { mbar_arrive_remote(bar_empty + 8 * s, 0); mbar_arrive_remote(bar_empty + 8 * s, 1); }
                    else mbar_arrive(bar_empty + 8 * s);
                }
            } else if (kb > 0) {
                wg_wait<1>();
                const int sp = s == 0 ? STAGES - 1 : s - 1;
                if ((warp & 3) == 0 && elect_one()) {
                    if (MC) { mbar_arrive_remote(bar_empty + 8 * sp, 0); mbar_arrive_remote(bar_empty + 8 * sp, 1); }
                    else mbar_arrive(bar_empty + 8 * sp);
                }
                if (INLINE_PROD && warp == 0 && kb >= LAG && kb - LAG + STAGES < KB) {
                    const int sq = LAG == 1 ? sp : (sp == 0 ? STAGES - 1 : sp - 1);
                    mbar_wait(bar_empty + 8 * sq, ((kb - LAG) / STAGES) & 1);
                    if (elect_one()) {
                        mbar_expect_tx(bar_full + 8 * sq, STAGE_TX);
                        loadB(kb - LAG + STAGES, sq);
                        loadA(kb - LAG + STAGES, sq);
                    }
                }
            }
            if (++s == STAGES) { s = 0; ph ^= 1; }
        }
        if constexpr (SELF) {
            named_bar(4, 512);
            const float2 r0 = *(const float2*)(s_row + 2 * rloc), r1 = *(const float2*)(s_row + 2 * rloc + 16);
            mean0 = r0.x; rstd0 = r0.y; mean1 = r1.x; rstd1 = r1.y;
        } else if constexpr (EPI != EPI_RES) {
            finish_row_stats(raw, mean0, rstd0, mean1, rstd1);
            if (tid < TN) s_cs[tid] = csv;
        }
        wg_wait<0>();
        fence_regs(acc);
        if (tid == 0) TL(prm.tk, 2);
        if constexpr (EPI != EPI_RES) named_bar(1, 256);

        if constexpr (EPI != EPI_FFN1) {
            const uint32_t stile = sbase + (EPI == EPI_RES ? s * SM::STAGE : 0);
            const int mrow = wg * 64 + (warp & 3) * 16 + (lane & 7) + ((lane >> 3) & 1) * 8;
            const uint32_t rbase = stile + mrow * 128;
            if constexpr (EPI == EPI_RES) {
                mbar_wait(bar_full + 8 * s, ph);
                float s0 = 0.f, s1 = 0.f;
#pragma unroll
                for (int jj = 0; jj < 4; jj++) {
                    uint32_t r0, r1, r2, r3;
                    const uint32_t addr = rbase + (((2 * jj + (lane >> 4)) ^ (mrow & 7)) << 4);
                    ldsm_x4(r0, r1, r2, r3, addr);
                    const uint32_t u0 = pack_bf16(acc[8 * jj] + bf_lo(r0), acc[8 * jj + 1] + bf_hi(r0));
                    const uint32_t u1 = pack_bf16(acc[8 * jj + 2] + bf_lo(r1), acc[8 * jj + 3] + bf_hi(r1));
                    const uint32_t u2 = pack_bf16(acc[8 * jj + 4] + bf_lo(r2), acc[8 * jj + 5] + bf_hi(r2));
                    const uint32_t u3 = pack_bf16(acc[8 * jj + 6] + bf_lo(r3), acc[8 * jj + 7] + bf_hi(r3));
                    stsm_x4(addr, u0, u1, u2, u3);
                    acc[8 * jj] = bf_lo(u0); acc[8 * jj + 1] = bf_hi(u0); acc[8 * jj + 4] = bf_lo(u2); acc[8 * jj + 5] = bf_hi(u2);
                    acc[8 * jj + 2] = bf_lo(u1); acc[8 * jj + 3] = bf_hi(u1); acc[8 * jj + 6] = bf_lo(u3); acc[8 * jj + 7] = bf_hi(u3);
                    s0 += (acc[8 * jj] + acc[8 * jj + 1]) + (acc[8 * jj + 4] + acc[8 * jj + 5]);
                    s1 += (acc[8 * jj + 2] + acc[8 * jj + 3]) + (acc[8 * jj + 6] + acc[8 * jj + 7]);
                }
                fence_async_smem();
                named_bar(2 + wg, 128);
                if ((warp & 3) == 0 && elect_one()) { tma2d_store(mapC, stile + wg * 8192, n0, m0 + wg * 64); bulk_commit(); }
                if (prm.stats_out) {
                    s0 += __shfl_xor_sync(0xffffffffu, s0, 1); s0 += __shfl_xor_sync(0xffffffffu, s0, 2);
                    s1 += __shfl_xor_sync(0xffffffffu, s1, 1); s1 += __shfl_xor_sync(0xffffffffu, s1, 2);
                    const float mu0 = s0 * (1.f / 64.f), mu1 = s1 * (1.f / 64.f);
                    float q0 = 0.f, q1 = 0.f;
#pragma unroll
                    for (int j = 0; j < 8; j++) {
                        float d;
                        d = acc[4 * j] - mu0; q0 += d * d; d = acc[4 * j + 1] - mu0; q0 += d * d;
                        d = acc[4 * j + 2] - mu1; q1 += d * d; d = acc[4 * j + 3] - mu1; q1 += d * d;
                    }
                    q0 += __shfl_xor_sync(0xffffffffu, q0, 1); q0 += __shfl_xor_sync(0xffffffffu, q0, 2);
                    q1 += __shfl_xor_sync(0xffffffffu, q1, 1); q1 += __shfl_xor_sync(0xffffffffu, q1, 2);
                    if (c == 0) {
                        prm.stats_out[tile_n * S_ + row0] = make_float2(mu0, q0);
                        prm.stats_out[tile_n * S_ + row0 + 8] = make_float2(mu1, q1);
                    }
                }
            } else {
                const float sc = 0.25f * 1.4426950408889634f;
                const float a0 = rstd0 * sc, a1 = rstd1 * sc, rm0 = a0 * mean0, rm1 = a1 * mean1;
#pragma unroll
                for (int jj = 0; jj < 4; jj++) {
                    const float2 ca = *(const float2*)(s_cs + 16 * jj + 2 * c), cb = *(const float2*)(s_cs + 16 * jj + 8 + 2 * c);
                    const uint32_t u0 = pack_bf16(acc[8 * jj] * a0 - rm0 * ca.x, acc[8 * jj + 1] * a0 - rm0 * ca.y);
                    const uint32_t u1 = pack_bf16(acc[8 * jj + 2] * a1 - rm1 * ca.x, acc[8 * jj + 3] * a1 - rm1 * ca.y);
                    const uint32_t u2 = pack_bf16(acc[8 * jj + 4] * a0 - rm0 * cb.x, acc[8 * jj + 5] * a0 - rm0 * cb.y);
                    const uint32_t u3 = pack_bf16(acc[8 * jj + 6] * a1 - rm1 * cb.x, acc[8 * jj + 7] * a1 - rm1 * cb.y);
                    stsm_x4(rbase + (((2 * jj + (lane >> 4)) ^ (mrow & 7)) << 4), u0, u1, u2, u3);
                }
                fence_async_smem();
                named_bar(2 + wg, 128);
                if ((warp & 3) == 0 && elect_one()) { tma2d_store(mapC, stile + wg * 8192, n0, m0 + wg * 64); bulk_commit(); }
            }
            if constexpr (XKV) {
                {
                    const float* acx = &acc[32];
                    const float rm0 = rstd0 * mean0, rm1 = rstd1 * mean1;
                    float n0s = 0.f, n1s = 0.f, vmax = 0.f;
#pragma unroll
                    for (int j = 0; j < 2; j++) {
                        const float2 cs2 = SELF ? *(const float2*)(s_cs + 64 + 8 * j + 2 * c) : cskv[j];
                        const uint32_t u0 = pack_bf16(acx[4 * j] * rstd0 - rm0 * cs2.x, acx[4 * j + 1] * rstd0 - rm0 * cs2.y);
                        const uint32_t u1 = pack_bf16(acx[4 * j + 2] * rstd1 - rm1 * cs2.x, acx[4 * j + 3] * rstd1 - rm1 * cs2.y);
                        n0s += bf_lo(u0) * bf_lo(u0) + bf_hi(u0) * bf_hi(u0);
                        n1s += bf_lo(u1) * bf_lo(u1) + bf_hi(u1) * bf_hi(u1);
                        vmax = fmaxf(vmax, fmaxf(fmaxf(fabsf(bf_lo(u0)), fabsf(bf_hi(u0))), fmaxf(fabsf(bf_lo(u1)), fabsf(bf_hi(u1)))));
                        if (tile_n == 0) {
                            *(uint32_t*)(g_kimg + (row0 >> 3) * 256 + j * 128 + g * 16 + c * 4) = u0;
                            *(uint32_t*)(g_kimg + ((row0 + 8) >> 3) * 256 + j * 128 + g * 16 + c * 4) = u1;
                        } else {
                            uint8_t* vb = g_vimg + (row0 >> 4) * 768 + j * 256 + g * 16 + c * 4;
                            *(uint32_t*)(vb) = u0;
                            *(uint32_t*)(vb + 128) = u1;
                        }
                    }
                    if (tile_n == 1) {
                        uint8_t* vb = g_vimg + (row0 >> 4) * 768 + 512 + g * 16 + c * 4;
                        const uint32_t one = c == 0 ? 0x00003F80u : 0u;
                        *(uint32_t*)(vb) = one;
                        *(uint32_t*)(vb + 128) = one;
                    }
                    n0s += __shfl_xor_sync(0xffffffffu, n0s, 1); n0s += __shfl_xor_sync(0xffffffffu, n0s, 2);
                    n1s += __shfl_xor_sync(0xffffffffu, n1s, 1); n1s += __shfl_xor_sync(0xffffffffu, n1s, 2);
                    float km = tile_n == 0 ? fmaxf(n0s, n1s) : vmax;
                    if (!(n0s + n1s < INFINITY)) km = INFINITY;
#pragma unroll
                    for (int o = 1; o < 32; o <<= 1) km = fmaxf(km, __shfl_xor_sync(0xffffffffu, km, o));
                    if (lane == 0) s_red[warp] = km;
                    named_bar(1, 256);
                    if (tid == 0) {
                        float a = 0.f;
                        for (int i = 0; i < 8; i++) a = fmaxf(a, s_red[i]);
                        g_kvmax[tile_n * 16 + tile_m] = a;
                    }
                }
            }
            if ((warp & 3) == 0) bulk_wait_read();
        } else {
            const uint32_t stile = sbase + wg * (7 * 4096);
            const int mrow = (warp & 3) * 16 + (lane & 7) + ((lane >> 3) & 1) * 8;
            const float a0 = 0.5f * rstd0, a1 = 0.5f * rstd1, rm0 = a0 * mean0, rm1 = a1 * mean1;
#pragma unroll
            for (int jj = 0; jj < 14; jj++) {
                const float2 ca = *(const float2*)(s_cs + 16 * jj + 2 * c), cb = *(const float2*)(s_cs + 16 * jj + 8 + 2 * c);
                float y[8] = {acc[8 * jj] * a0 - rm0 * ca.x,     acc[8 * jj + 1] * a0 - rm0 * ca.y,
                              acc[8 * jj + 2] * a1 - rm1 * ca.x, acc[8 * jj + 3] * a1 - rm1 * ca.y,
                              acc[8 * jj + 4] * a0 - rm0 * cb.x, acc[8 * jj + 5] * a0 - rm0 * cb.y,
                              acc[8 * jj + 6] * a1 - rm1 * cb.x, acc[8 * jj + 7] * a1 - rm1 * cb.y};
#pragma unroll
                for (int i = 0; i < 8; i++) {
                    float t;
                    asm("tanh.approx.f32 %0, %1;" : "=f"(t) : "f"(y[i]));
                    y[i] = fmaf(y[i], t, y[i]);
                }
                const int chunk = (2 * jj + (lane >> 4)) & 3, blk = jj >> 1;
                stsm_x4(stile + blk * 4096 + mrow * 64 + ((chunk ^ ((mrow >> 1) & 3)) << 4),
                        pack_bf16(y[0], y[1]), pack_bf16(y[2], y[3]), pack_bf16(y[4], y[5]), pack_bf16(y[6], y[7]));
                if (jj & 1) {
                    fence_async_smem();
                    __syncwarp();
                    if (elect_one()) {
                        tma2d_store(mapC, stile + blk * 4096 + (warp & 3) * 1024, n0 + blk * 32, m0 + wg * 64 + (warp & 3) * 16);
                        bulk_commit();
                    }
                }
            }
            bulk_wait_read();
        }
    }
    if (tid == 0) TL(prm.tk, 3);
    if (MC) cluster_sync();
}

#define WO_ST 9
#define F2_ST 6
#define F1_ST (F1_BK == 64 ? 5 : 9)
#define QKV_ST 8
constexpr int QKV_STAGES = QKV_ST, WO_STAGES = WO_ST, FFN2_STAGES = F2_ST, FFN1_STAGES = F1_ST;
template <bool SELF>
__global__ void __launch_bounds__(SELF ? 544 : 288) qkv_kernel(const __grid_constant__ CUtensorMap mapA, const __grid_constant__ CUtensorMap mapWq,
                                                  const __grid_constant__ CUtensorMap mapQ, const GemmParams prm) {
    extern __shared__ __align__(1024) uint8_t smem_raw[];
    const int tn = blockIdx.x & 7;
    if (tn < 2) gemm_body<80, 8, QKV_STAGES, EPI_QKV, QKV_MC, SELF>(&mapA, &mapWq, &mapWq, &mapA, &mapQ, prm, blockIdx.x >> 3, tn, smem_raw);
    else gemm_body<64, 8, QKV_STAGES, EPI_QKV, QKV_MC, SELF>(&mapA, &mapWq, &mapWq, &mapA, &mapQ, prm, blockIdx.x >> 3, tn, smem_raw);
}
template <int KB, int STAGES>
__global__ void __launch_bounds__(288) res_gemm_kernel(const __grid_constant__ CUtensorMap mapA, const __grid_constant__ CUtensorMap mapW,
                                                       const __grid_constant__ CUtensorMap mapR, const __grid_constant__ CUtensorMap mapC, const GemmParams prm) {
    extern __shared__ __align__(1024) uint8_t smem_raw[];
    gemm_body<64, KB, STAGES, EPI_RES, (KB == 8 ? WO_MC : F2_MC)>(&mapA, &mapW, &mapW, &mapR, &mapC, prm, blockIdx.x >> 3, blockIdx.x & 7, smem_raw);
}
__global__ void __launch_bounds__(F1_INLINE ? 256 : 288) ffn1_kernel(const __grid_constant__ CUtensorMap mapA, const __grid_constant__ CUtensorMap mapW4,
                                                   const __grid_constant__ CUtensorMap mapW3, const __grid_constant__ CUtensorMap mapH, const GemmParams prm) {
    extern __shared__ __align__(1024) uint8_t smem_raw[];
    const int pair = blockIdx.x >> 1, tile_n = pair & 7, tile_m = (pair >> 3) * 2 + (blockIdx.x & 1);
    gemm_body<224, 512 / F1_BK, FFN1_STAGES, EPI_FFN1, F1_MC>(&mapA, &mapW4, &mapW3, &mapA, &mapH, prm, tile_m, tile_n, smem_raw);
}

constexpr int NPOLY = 10;
__host__ __device__ constexpr bool is_mufu(int i) { return ((i + 1) * (16 - NPOLY)) / 16 != (i * (16 - NPOLY)) / 16; }

__device__ __forceinline__ float ex2(float x) { float r; asm("ex2.approx.ftz.f32 %0, %1;" : "=f"(r) : "f"(x)); return r; }
__device__ __forceinline__ uint32_t exp_pair_mufu(float a, float b) { return pack_bf16(ex2(a), ex2(b)); }
__device__ __forceinline__ uint32_t exp_pair_fma(float a, float b, uint32_t c3f) {
    constexpr float MAGIC = 98430.4140625f;
    const float ta = a + MAGIC, tb = b + (MAGIC - 143.5f);
    uint32_t y, m, r;
    asm("mad.lo.u32 %0, %1, 65536, %2;" : "=r"(y) : "r"(__float_as_uint(tb)), "r"(__float_as_uint(ta)));
    asm("lop3.b32 %0, %1, 0x007F007F, %2, 0xEA;" : "=r"(m) : "r"(y), "r"(c3f));
    const uint32_t e = y & 0xFF80FF80u;
    asm("fma.rn.bf16x2 %0, %1, %2, %3;" : "=r"(r) : "r"(y), "r"(m), "r"(e));
    return r;
}

constexpr int KCH = 256, NCH = S_ / KCH;
constexpr int K_BYTES = S_ * 32, V_BYTES = (S_ / 16) * 768;
constexpr int ATT_SMEM = K_BYTES + V_BYTES;

__global__ void __launch_bounds__(512, 1) attn_kernel(const __nv_bfloat16* __restrict__ wo, const __nv_bfloat16* __restrict__ w1,
                                                       const __nv_bfloat16* __restrict__ w2, int tk) {
    extern __shared__ __align__(1024) uint8_t smem[];
    __shared__ uint64_t bars[NCH];
    __shared__ int s_slow;
    const int tid = threadIdx.x, wg = tid >> 7, warp = (tid >> 5) & 3, lane = tid & 31;
    const uint32_t sK = smem_u32(smem), sV = sK + K_BYTES;
    if (blockIdx.x >= 128) {
        pdl_launch();
        side_job(blockIdx.x - 128, (float*)smem, wo, w1, w2);
        return;
    }
    CK(tk, 9);
    if (tid == 0) TL(tk, 0);
    if (tid == 0) {
        for (int i = 0; i < NCH; i++) mbar_init(smem_u32(&bars[i]), 1);
        s_slow = 0;
        fence_mbar_init();
    }
    __syncthreads();
    pdl_launch();
    CK(tk, 10);
    pdl_wait();
    CK(tk, 11);
    if (tid == 0) TL(tk, 1);
    const int wu = __shfl_sync(0xffffffffu, tid >> 5, 0);
    auto fetch_chunk = [&](int w) {
        if (elect_one()) {
            const uint32_t bar = smem_u32(&bars[w]);
            mbar_expect_tx(bar, KCH * 32 + (KCH / 16) * 768);
            bulk_load(sK + w * KCH * 32, g_kimg + w * KCH * 32, KCH * 32, bar);
            bulk_load(sV + w * (KCH / 16) * 768, g_vimg + w * (KCH / 16) * 768, (KCH / 16) * 768, bar);
        }
    };
    if (wu == 0) fetch_chunk(0);
    const int tb = blockIdx.x >> 3, hg = blockIdx.x & 7;
    const int head = hg * 4 + wg;
    const int g = lane >> 2, c = lane & 3;
    uint32_t qa[2][4];
#pragma unroll
    for (int m = 0; m < 2; m++) {
        const int row = tb * 128 + m * 64 + warp * 16 + g;
        const uint32_t* p0 = (const uint32_t*)(g_q + (size_t)row * D_ + head * 16);
        const uint32_t* p1 = (const uint32_t*)(g_q + (size_t)(row + 8) * D_ + head * 16);
        qa[m][0] = p0[c]; qa[m][1] = p1[c]; qa[m][2] = p0[c + 4]; qa[m][3] = p1[c + 4];
    }
    CK(tk, 12);
    float kvm = g_kvmax[lane];
    {
        float qn = 0.f;
#pragma unroll
        for (int m = 0; m < 2; m++) {
            float n0 = bf_lo(qa[m][0]) * bf_lo(qa[m][0]) + bf_hi(qa[m][0]) * bf_hi(qa[m][0]) + bf_lo(qa[m][2]) * bf_lo(qa[m][2]) + bf_hi(qa[m][2]) * bf_hi(qa[m][2]);
            float n1 = bf_lo(qa[m][1]) * bf_lo(qa[m][1]) + bf_hi(qa[m][1]) * bf_hi(qa[m][1]) + bf_lo(qa[m][3]) * bf_lo(qa[m][3]) + bf_hi(qa[m][3]) * bf_hi(qa[m][3]);
            n0 += __shfl_xor_sync(0xffffffffu, n0, 1); n0 += __shfl_xor_sync(0xffffffffu, n0, 2);
            n1 += __shfl_xor_sync(0xffffffffu, n1, 1); n1 += __shfl_xor_sync(0xffffffffu, n1, 2);
            if (!(n0 == n0) || !(n1 == n1)) n0 = INFINITY;
            qn = fmaxf(qn, fmaxf(n0, n1));
        }
        CK(tk, 13);
#pragma unroll
        for (int o = 1; o < 16; o <<= 1) kvm = fmaxf(kvm, __shfl_xor_sync(0xffffffffu, kvm, o));
        const float km = __shfl_sync(0xffffffffu, kvm, 0), vm = __shfl_sync(0xffffffffu, kvm, 16);
        const bool ok = (qn * km <= 10000.f) && (vm <= 16384.f);
        if (!ok) s_slow = 1;
    }
    CK(tk, 14);
    float oacc[2][12];
#pragma unroll
    for (int m = 0; m < 2; m++)
#pragma unroll
        for (int i = 0; i < 12; i++) oacc[m][i] = 0.f;
    __syncthreads();
    const bool slow = s_slow != 0;
    if (wu >= 1 && wu < NCH) fetch_chunk(wu);
    CK(tk, 15);

    const uint64_t dK0 = mkdesc(sK, 128, 256, 0);
    const uint64_t dV0 = mkdesc(sV, 128, 256, 0);
    uint32_t c3f;
    asm volatile("mov.b32 %0, 0x3F003F00;" : "=r"(c3f));
    if (!slow) {
#pragma unroll 1
        for (int t = 0; t < S_ / 64; t++) {
            if ((t & 3) == 0) mbar_wait(smem_u32(&bars[t >> 2]), 0);
            const uint64_t dK = dK0 + (uint64_t)(t * 64 * 32 / 16);
            const uint64_t dV = dV0 + (uint64_t)(t * 4 * 768 / 16);
#pragma unroll
            for (int m = 0; m < 2; m++) {
                float s[32];
                wg_fence();
                wgmma_rs_n64_z(s, qa[m][0], qa[m][1], qa[m][2], qa[m][3], dK);
                wg_commit();
                wg_wait<0>();
                fence_regs(s);
                uint32_t p[16];
#pragma unroll
                for (int i = 0; i < 16; i++) p[i] = is_mufu(i) ? exp_pair_mufu(s[2 * i], s[2 * i + 1]) : exp_pair_fma(s[2 * i], s[2 * i + 1], c3f);
                wg_fence();
#pragma unroll
                for (int kk = 0; kk < 4; kk++)
                    wgmma_rs_n24_tb(oacc[m], p[4 * kk], p[4 * kk + 1], p[4 * kk + 2], p[4 * kk + 3], dV + (uint64_t)(kk * 768 / 16));
                wg_commit();
            }
        }
        wg_wait<0>();
    } else {
        float mx[2][2] = {{-INFINITY, -INFINITY}, {-INFINITY, -INFINITY}};
#pragma unroll 1
        for (int t = 0; t < S_ / 64; t++) {
            if ((t & 3) == 0) mbar_wait(smem_u32(&bars[t >> 2]), 0);
            const uint64_t dK = dK0 + (uint64_t)(t * 64 * 32 / 16);
            const uint64_t dV = dV0 + (uint64_t)(t * 4 * 768 / 16);
#pragma unroll
            for (int m = 0; m < 2; m++) {
                float s[32];
                wg_fence();
                wgmma_rs_n64_z(s, qa[m][0], qa[m][1], qa[m][2], qa[m][3], dK);
                wg_commit();
                wg_wait<0>();
                fence_regs(s);
                fence_regs(oacc[m]);
                float r0 = mx[m][0], r1 = mx[m][1];
#pragma unroll
                for (int j = 0; j < 8; j++) {
                    r0 = fmaxf(r0, fmaxf(s[4 * j], s[4 * j + 1]));
                    r1 = fmaxf(r1, fmaxf(s[4 * j + 2], s[4 * j + 3]));
                }
                r0 = fmaxf(r0, __shfl_xor_sync(0xffffffffu, r0, 1)); r0 = fmaxf(r0, __shfl_xor_sync(0xffffffffu, r0, 2));
                r1 = fmaxf(r1, __shfl_xor_sync(0xffffffffu, r1, 1)); r1 = fmaxf(r1, __shfl_xor_sync(0xffffffffu, r1, 2));
                const float al0 = ex2(mx[m][0] - r0), al1 = ex2(mx[m][1] - r1);
                mx[m][0] = r0; mx[m][1] = r1;
#pragma unroll
                for (int j = 0; j < 3; j++) {
                    oacc[m][4 * j] *= al0; oacc[m][4 * j + 1] *= al0;
                    oacc[m][4 * j + 2] *= al1; oacc[m][4 * j + 3] *= al1;
                }
                uint32_t p[16];
#pragma unroll
                for (int j = 0; j < 8; j++) {
                    p[2 * j] = pack_bf16(ex2(s[4 * j] - r0), ex2(s[4 * j + 1] - r0));
                    p[2 * j + 1] = pack_bf16(ex2(s[4 * j + 2] - r1), ex2(s[4 * j + 3] - r1));
                }
                fence_regs(oacc[m]);
                wg_fence();
#pragma unroll
                for (int kk = 0; kk < 4; kk++)
                    wgmma_rs_n24_tb(oacc[m], p[4 * kk], p[4 * kk + 1], p[4 * kk + 2], p[4 * kk + 3], dV + (uint64_t)(kk * 768 / 16));
                wg_commit();
                wg_wait<0>();
            }
        }
    }
    fence_regs(oacc[0]); fence_regs(oacc[1]);
    if (tid == 0) TL(tk, 2);
#pragma unroll
    for (int m = 0; m < 2; m++) {
        const float l0 = __shfl_sync(0xffffffffu, oacc[m][8], lane & ~3);
        const float l1 = __shfl_sync(0xffffffffu, oacc[m][10], lane & ~3);
        const float r0 = __fdividef(1.0f, l0), r1 = __fdividef(1.0f, l1);
        const int row = tb * 128 + m * 64 + warp * 16 + g;
        uint32_t* p0 = (uint32_t*)(g_o + (size_t)row * D_ + head * 16);
        uint32_t* p1 = (uint32_t*)(g_o + (size_t)(row + 8) * D_ + head * 16);
        p0[c] = pack_bf16(oacc[m][0] * r0, oacc[m][1] * r0);
        p1[c] = pack_bf16(oacc[m][2] * r1, oacc[m][3] * r1);
        p0[c + 4] = pack_bf16(oacc[m][4] * r0, oacc[m][5] * r0);
        p1[c + 4] = pack_bf16(oacc[m][6] * r1, oacc[m][7] * r1);
    }
    if (tid == 0) TL(tk, 3);
}

typedef CUresult (*EncodeFn)(CUtensorMap*, CUtensorMapDataType, cuuint32_t, void*, const cuuint64_t*, const cuuint64_t*, const cuuint32_t*,
                             const cuuint32_t*, CUtensorMapInterleave, CUtensorMapSwizzle, CUtensorMapL2promotion, CUtensorMapFloatOOBfill);

EncodeFn get_encode() {
    static EncodeFn fn = nullptr;
    if (!fn) {
        void* p = nullptr;
        cudaDriverEntryPointQueryResult qr;
        cudaGetDriverEntryPoint("cuTensorMapEncodeTiled", &p, cudaEnableDefault, &qr);
        fn = (EncodeFn)p;
    }
    return fn;
}
CUtensorMap map2d(const void* ptr, uint64_t cols, uint64_t rows, uint32_t bc, uint32_t br, CUtensorMapSwizzle sw) {
    CUtensorMap m;
    cuuint64_t gd[2] = {cols, rows}, gs[1] = {cols * 2};
    cuuint32_t bx[2] = {bc, br}, es[2] = {1, 1};
    get_encode()(&m, CU_TENSOR_MAP_DATA_TYPE_BFLOAT16, 2, (void*)ptr, gd, gs, bx, es, CU_TENSOR_MAP_INTERLEAVE_NONE, sw,
                 CU_TENSOR_MAP_L2_PROMOTION_L2_128B, CU_TENSOR_MAP_FLOAT_OOB_FILL_NONE);
    return m;
}
CUtensorMap map3d32(const void* ptr, uint64_t cols, uint64_t rows, uint32_t br, uint32_t nb) {
    CUtensorMap m;
    cuuint64_t gd[3] = {32, rows, cols / 32}, gs[2] = {cols * 2, 64};
    cuuint32_t bx[3] = {32, br, nb}, es[3] = {1, 1, 1};
    get_encode()(&m, CU_TENSOR_MAP_DATA_TYPE_BFLOAT16, 3, (void*)ptr, gd, gs, bx, es, CU_TENSOR_MAP_INTERLEAVE_NONE, CU_TENSOR_MAP_SWIZZLE_64B,
                 CU_TENSOR_MAP_L2_PROMOTION_L2_128B, CU_TENSOR_MAP_FLOAT_OOB_FILL_NONE);
    return m;
}

template <typename... KArgs, typename... Args>
void launch(void (*kern)(KArgs...), int grid, int block, int smem, int cluster, bool pdl, Args... args) {
    cudaLaunchConfig_t cfg = {};
    cfg.gridDim = dim3(grid);
    cfg.blockDim = dim3(block);
    cfg.dynamicSmemBytes = smem;
    cfg.stream = cudaStreamPerThread;
    cudaLaunchAttribute at[2];
    int n = 0;
    if (cluster > 1) { at[n].id = cudaLaunchAttributeClusterDimension; at[n].val.clusterDim.x = cluster; at[n].val.clusterDim.y = 1; at[n].val.clusterDim.z = 1; n++; }
    if (pdl) { at[n].id = cudaLaunchAttributeProgrammaticStreamSerialization; at[n].val.programmaticStreamSerializationAllowed = 1; n++; }
    cfg.attrs = at;
    cfg.numAttrs = n;
    cudaLaunchKernelEx(&cfg, kern, KArgs(args)...);
}

template <typename T> void* sym(const T& s) { void* p = nullptr; cudaGetSymbolAddress(&p, s); return p; }

}

extern "C" void kernel_launch(void* const* d_in, const int* in_sizes, int n_in, void* d_out, int out_size) {
    const __nv_bfloat16* x = (const __nv_bfloat16*)d_in[0];
    const __nv_bfloat16* wq = (const __nv_bfloat16*)d_in[1];
    const __nv_bfloat16* wk = (const __nv_bfloat16*)d_in[2];
    const __nv_bfloat16* wv = (const __nv_bfloat16*)d_in[3];
    const __nv_bfloat16* wo = (const __nv_bfloat16*)d_in[4];
    const __nv_bfloat16* w1 = (const __nv_bfloat16*)d_in[6];
    const __nv_bfloat16* w2 = (const __nv_bfloat16*)d_in[7];

    constexpr int SM_QKV = GemmSmem<QKV_STAGES, EPI_QKV>::TOTAL, SM_QKV0 = GemmSmem<QKV_STAGES, EPI_QKV>::TOTAL_SELF;
    static_assert(SM_QKV0 <= 232448, "shared memory");
    constexpr int HALF_PLUS = 116736;
    constexpr int SM_WO = GemmSmem<WO_STAGES, EPI_RES>::TOTAL > HALF_PLUS ? GemmSmem<WO_STAGES, EPI_RES>::TOTAL : HALF_PLUS;
    constexpr int SM_FFN2 = GemmSmem<FFN2_STAGES, EPI_RES>::TOTAL > HALF_PLUS ? GemmSmem<FFN2_STAGES, EPI_RES>::TOTAL : HALF_PLUS;
    constexpr int SM_FFN1 = GemmSmem<FFN1_STAGES, EPI_FFN1>::TOTAL;
    cudaFuncSetAttribute(qkv_kernel<false>, cudaFuncAttributeMaxDynamicSharedMemorySize, SM_QKV);
    cudaFuncSetAttribute(qkv_kernel<true>, cudaFuncAttributeMaxDynamicSharedMemorySize, SM_QKV0);
    cudaFuncSetAttribute(res_gemm_kernel<8, WO_STAGES>, cudaFuncAttributeMaxDynamicSharedMemorySize, SM_WO);
    cudaFuncSetAttribute(ffn1_kernel, cudaFuncAttributeMaxDynamicSharedMemorySize, SM_FFN1);
    cudaFuncSetAttribute(res_gemm_kernel<28, FFN2_STAGES>, cudaFuncAttributeMaxDynamicSharedMemorySize, SM_FFN2);
    cudaFuncSetAttribute(attn_kernel, cudaFuncAttributeMaxDynamicSharedMemorySize, ATT_SMEM);
    cudaFuncSetAttribute(qkv_kernel<false>, cudaFuncAttributePreferredSharedMemoryCarveout, 100);
    cudaFuncSetAttribute(qkv_kernel<true>, cudaFuncAttributePreferredSharedMemoryCarveout, 100);
    cudaFuncSetAttribute(res_gemm_kernel<8, WO_STAGES>, cudaFuncAttributePreferredSharedMemoryCarveout, 100);
    cudaFuncSetAttribute(ffn1_kernel, cudaFuncAttributePreferredSharedMemoryCarveout, 100);
    cudaFuncSetAttribute(res_gemm_kernel<28, FFN2_STAGES>, cudaFuncAttributePreferredSharedMemoryCarveout, 100);
    cudaFuncSetAttribute(attn_kernel, cudaFuncAttributePreferredSharedMemoryCarveout, 100);

    void *q = sym(g_q), *o = sym(g_o), *x1 = sym(g_x1), *x2 = sym(g_x2), *x3 = sym(g_x3), *h = sym(g_h);
    float2* stats = (float2*)sym(g_stats);
    const void* xs[5] = {x, x1, x2, x3, d_out};

    const CUtensorMapSwizzle SW128 = CU_TENSOR_MAP_SWIZZLE_128B, SW64 = CU_TENSOR_MAP_SWIZZLE_64B;
    const CUtensorMap mWq = map3d32(wq, D_, D_, 64, 2);
    const CUtensorMap mWo = map2d(wo, D_, D_, 64, 64, SW128);
    const CUtensorMap mW1a = map3d32(w1, F_, D_, F1_BK, 4), mW1b = map3d32(w1, F_, D_, F1_BK, 3);
    const CUtensorMap mW2 = map2d(w2, D_, F_, 64, 64, SW128);
    const CUtensorMap mQ = map2d(q, D_, S_, 64, 64, SW128);
    const CUtensorMap mHst = map2d(h, F_, S_, 32, 16, SW64);
    CUtensorMap mXa[4], mXf[4], mXr[4], mXs[5];
    for (int i = 0; i < 4; i++) {
        mXa[i] = map2d(xs[i], D_, S_, 64, QKV_MC ? 64 : 128, SW128);
        mXf[i] = F1_BK == 64 ? map2d(xs[i], D_, S_, 64, 128, SW128) : map2d(xs[i], D_, S_, 32, 128, SW64);
        mXr[i] = map2d(xs[i], D_, S_, 64, 128, SW128);
    }
    for (int i = 0; i < 5; i++) mXs[i] = map2d(xs[i], D_, S_, 64, 64, SW128);
    const CUtensorMap mOa = map2d(o, D_, S_, 64, WO_MC ? 64 : 128, SW128);
    const CUtensorMap mHa = map2d(h, F_, S_, 64, F2_MC ? 64 : 128, SW128);

    for (int layer = 0; layer < 2; layer++) {
        const int xi = layer * 2;
        GemmParams p;
        p.wkv = wk; p.wv = wv;
        p.stats_in = stats + (size_t)xi * 8 * S_; p.stats_out = nullptr; p.tk = 1 + 5 * layer;
        if (layer == 0) launch(qkv_kernel<true>, 128, 544, SM_QKV0, QKV_MC ? 2 : 1, false, mXa[xi], mWq, mQ, p);
        else launch(qkv_kernel<false>, 128, 288, SM_QKV, QKV_MC ? 2 : 1, true, mXa[xi], mWq, mQ, p);
        launch(attn_kernel, layer == 0 ? 128 + SIDE_CTAS : 128, 512, ATT_SMEM, 1, true, wo, w1, w2, 2 + 5 * layer);
        p.stats_in = nullptr; p.stats_out = stats + (size_t)(xi + 1) * 8 * S_; p.tk = 3 + 5 * layer;
        launch(res_gemm_kernel<8, WO_STAGES>, 128, 288, SM_WO, WO_MC ? 2 : 1, true, mOa, mWo, mXr[xi], mXs[xi + 1], p);
        p.stats_in = stats + (size_t)(xi + 1) * 8 * S_; p.stats_out = nullptr; p.tk = 4 + 5 * layer;
        launch(ffn1_kernel, 128, F1_INLINE ? 256 : 288, SM_FFN1, F1_MC ? 2 : 1, true, mXf[xi + 1], mW1a, mW1b, mHst, p);
        p.stats_in = nullptr; p.stats_out = layer == 0 ? stats + (size_t)2 * 8 * S_ : nullptr; p.tk = 5 + 5 * layer;
        launch(res_gemm_kernel<28, FFN2_STAGES>, 128, 288, SM_FFN2, F2_MC ? 2 : 1, true, mHa, mW2, mXr[xi + 1], mXs[xi + 2], p);
    }
}
```

```cpp
#include <cuda_runtime.h>
#include <cuda_bf16.h>
#include <cuda.h>
#include <stdint.h>

#define F1_INLINE 0
#define QKV_MC 0
#define WO_MC 0
#define F2_MC 0
#define F1_MC 2
#define SELF_WAIT 1
#define PREB 1
#define RES_WAIT0 0

namespace {

constexpr int S_ = 2048, D_ = 512, H_ = 32, F_ = 1792;

__device__ __align__(1024) __nv_bfloat16 g_q[S_ * D_];
__device__ __align__(1024) __nv_bfloat16 g_o[S_ * D_];
__device__ __align__(1024) __nv_bfloat16 g_x1[S_ * D_];
__device__ __align__(1024) __nv_bfloat16 g_x2[S_ * D_];
__device__ __align__(1024) __nv_bfloat16 g_x3[S_ * D_];
__device__ __align__(1024) __nv_bfloat16 g_h[S_ * F_];
__device__ __align__(1024) uint8_t g_kimg[S_ * 32];
__device__ __align__(1024) uint8_t g_vimg[(S_ / 16) * 768];
__device__ __align__(1024) float2 g_stats[4][8 * S_];
__device__ __align__(16) float g_cs_q[D_];
__device__ __align__(16) float g_cs_kv[32];
__device__ __align__(16) float g_cs_1[F_];
__device__ __align__(16) float g_kvmax[32];

#define TL(k, slot)
#define CK(k, i)

__device__ __forceinline__ uint32_t smem_u32(const void* p) { return (uint32_t)__cvta_generic_to_shared(p); }
__device__ __forceinline__ void mbar_init(uint32_t bar, uint32_t cnt) {
    asm volatile("mbarrier.init.shared::cta.b64 [%0], %1;" ::"r"(bar), "r"(cnt));
}
__device__ __forceinline__ void mbar_expect_tx(uint32_t bar, uint32_t bytes) {
    asm volatile("mbarrier.arrive.expect_tx.shared::cta.b64 _, [%0], %1;" ::"r"(bar), "r"(bytes) : "memory");
}
__device__ __forceinline__ void mbar_arrive(uint32_t bar) {
    asm volatile("mbarrier.arrive.shared::cta.b64 _, [%0];" ::"r"(bar) : "memory");
}
__device__ __forceinline__ void mbar_arrive_remote(uint32_t bar, uint32_t cta) {
    asm volatile("{\n.reg .b32 ra;\nmapa.shared::cluster.u32 ra, %0, %1;\nmbarrier.arrive.shared::cluster.b64 _, [ra];\n}" ::"r"(bar), "r"(cta) : "memory");
}
__device__ __forceinline__ void mbar_wait(uint32_t bar, uint32_t parity) {
    asm volatile("{\n.reg .pred p;\nWAIT_%=:\nmbarrier.try_wait.parity.shared::cta.b64 p, [%0], %1;\n@p bra DONE_%=;\nbra WAIT_%=;\nDONE_%=:\n}" ::"r"(bar), "r"(parity) : "memory");
}
__device__ __forceinline__ void bulk_load(uint32_t dst, const void* src, uint32_t bytes, uint32_t bar) {
    asm volatile("cp.async.bulk.shared::cluster.global.mbarrier::complete_tx::bytes [%0], [%1], %2, [%3];" ::"r"(dst), "l"(src), "r"(bytes), "r"(bar) : "memory");
}
__device__ __forceinline__ void tma2d(uint32_t dst, const CUtensorMap* m, int c0, int c1, uint32_t bar) {
    asm volatile("cp.async.bulk.tensor.2d.shared::cluster.global.mbarrier::complete_tx::bytes [%0], [%1, {%3, %4}], [%2];" ::"r"(dst), "l"(m), "r"(bar), "r"(c0), "r"(c1) : "memory");
}
__device__ __forceinline__ void tma2d_mc(uint32_t dst, const CUtensorMap* m, int c0, int c1, uint32_t bar, uint16_t mask) {
    asm volatile("cp.async.bulk.tensor.2d.shared::cluster.global.mbarrier::complete_tx::bytes.multicast::cluster [%0], [%1, {%3, %4}], [%2], %5;" ::"r"(dst), "l"(m), "r"(bar), "r"(c0), "r"(c1), "h"(mask) : "memory");
}
__device__ __forceinline__ void tma3d(uint32_t dst, const CUtensorMap* m, int c0, int c1, int c2, uint32_t bar) {
    asm volatile("cp.async.bulk.tensor.3d.shared::cluster.global.mbarrier::complete_tx::bytes [%0], [%1, {%3, %4, %5}], [%2];" ::"r"(dst), "l"(m), "r"(bar), "r"(c0), "r"(c1), "r"(c2) : "memory");
}
__device__ __forceinline__ void tma3d_mc(uint32_t dst, const CUtensorMap* m, int c0, int c1, int c2, uint32_t bar, uint16_t mask) {
    asm volatile("cp.async.bulk.tensor.3d.shared::cluster.global.mbarrier::complete_tx::bytes.multicast::cluster [%0], [%1, {%3, %4, %5}], [%2], %6;" ::"r"(dst), "l"(m), "r"(bar), "r"(c0), "r"(c1), "r"(c2), "h"(mask) : "memory");
}
__device__ __forceinline__ void tma2d_store(const CUtensorMap* m, uint32_t src, int c0, int c1) {
    asm volatile("cp.async.bulk.tensor.2d.global.shared::cta.bulk_group [%0, {%2, %3}], [%1];" ::"l"(m), "r"(src), "r"(c0), "r"(c1) : "memory");
}
__device__ __forceinline__ void tma3d_store(const CUtensorMap* m, uint32_t src, int c0, int c1, int c2) {
    asm volatile("cp.async.bulk.tensor.3d.global.shared::cta.bulk_group [%0, {%2, %3, %4}], [%1];" ::"l"(m), "r"(src), "r"(c0), "r"(c1), "r"(c2) : "memory");
}
__device__ __forceinline__ void bulk_commit() { asm volatile("cp.async.bulk.commit_group;" ::: "memory"); }
__device__ __forceinline__ void bulk_wait_read() { asm volatile("cp.async.bulk.wait_group.read 0;" ::: "memory"); }
__device__ __forceinline__ void prefetch_tmap(const CUtensorMap* m) { asm volatile("prefetch.tensormap [%0];" ::"l"(m) : "memory"); }
__device__ __forceinline__ void fence_async_smem() { asm volatile("fence.proxy.async.shared::cta;" ::: "memory"); }
__device__ __forceinline__ void fence_mbar_init() { asm volatile("fence.mbarrier_init.release.cluster;" ::: "memory"); }
__device__ __forceinline__ void cluster_sync() { asm volatile("barrier.cluster.arrive.release.aligned;\nbarrier.cluster.wait.acquire.aligned;" ::: "memory"); }
__device__ __forceinline__ uint32_t cluster_rank() { uint32_t r; asm volatile("mov.u32 %0, %%cluster_ctarank;" : "=r"(r)); return r; }
__device__ __forceinline__ void pdl_wait() { asm volatile("griddepcontrol.wait;" ::: "memory"); }
__device__ __forceinline__ void pdl_launch() { asm volatile("griddepcontrol.launch_dependents;" ::: "memory"); }
__device__ __forceinline__ bool elect_one() {
    uint32_t p;
    asm volatile("{\n.reg .pred p;\nelect.sync _|p, 0xffffffff;\nselp.b32 %0, 1, 0, p;\n}" : "=r"(p));
    return p != 0;
}
__device__ __forceinline__ void named_bar(int id, int n) { asm volatile("bar.sync %0, %1;" ::"r"(id), "r"(n) : "memory"); }

__device__ __forceinline__ void wg_fence() { asm volatile("wgmma.fence.sync.aligned;" ::: "memory"); }
__device__ __forceinline__ void wg_commit() { asm volatile("wgmma.commit_group.sync.aligned;" ::: "memory"); }
template <int N> __device__ __forceinline__ void wg_wait() { asm volatile("wgmma.wait_group.sync.aligned %0;" ::"n"(N) : "memory"); }
template <int N> __device__ __forceinline__ void fence_regs(float (&d)[N]) {
#pragma unroll
    for (int i = 0; i < N; i++) asm volatile("" : "+f"(d[i])::"memory");
}
__device__ __forceinline__ uint64_t mkdesc(uint32_t addr, uint32_t lbo, uint32_t sbo, uint32_t swz) {
    uint64_t d = 0;
    d |= (uint64_t)((addr & 0x3FFFF) >> 4);
    d |= (uint64_t)((lbo & 0x3FFFF) >> 4) << 16;
    d |= (uint64_t)((sbo & 0x3FFFF) >> 4) << 32;
    d |= (uint64_t)swz << 62;
    return d;
}
__device__ __forceinline__ void ldsm_x4(uint32_t& r0, uint32_t& r1, uint32_t& r2, uint32_t& r3, uint32_t addr) {
    asm volatile("ldmatrix.sync.aligned.m8n8.x4.shared.b16 {%0,%1,%2,%3}, [%4];" : "=r"(r0), "=r"(r1), "=r"(r2), "=r"(r3) : "r"(addr) : "memory");
}
__device__ __forceinline__ void stsm_x4(uint32_t addr, uint32_t r0, uint32_t r1, uint32_t r2, uint32_t r3) {
    asm volatile("stmatrix.sync.aligned.m8n8.x4.shared.b16 [%0], {%1,%2,%3,%4};" ::"r"(addr), "r"(r0), "r"(r1), "r"(r2), "r"(r3) : "memory");
}
__device__ __forceinline__ void ldsm_x4_t(uint32_t& r0, uint32_t& r1, uint32_t& r2, uint32_t& r3, uint32_t addr) {
    asm volatile("ldmatrix.sync.aligned.m8n8.x4.trans.shared.b16 {%0,%1,%2,%3}, [%4];" : "=r"(r0), "=r"(r1), "=r"(r2), "=r"(r3) : "r"(addr) : "memory");
}
__device__ __forceinline__ void hmma(float (&d)[4], uint32_t a0, uint32_t a1, uint32_t a2, uint32_t a3, uint32_t b0, uint32_t b1) {
    asm volatile("mma.sync.aligned.m16n8k16.row.col.f32.bf16.bf16.f32 {%0,%1,%2,%3}, {%4,%5,%6,%7}, {%8,%9}, {%0,%1,%2,%3};"
                 : "+f"(d[0]), "+f"(d[1]), "+f"(d[2]), "+f"(d[3]) : "r"(a0), "r"(a1), "r"(a2), "r"(a3), "r"(b0), "r"(b1));
}
__device__ __forceinline__ uint32_t pack_bf16(float lo, float hi) {
    uint32_t r;
    asm("cvt.rn.bf16x2.f32 %0, %1, %2;" : "=r"(r) : "f"(hi), "f"(lo));
    return r;
}
__device__ __forceinline__ float bf_lo(uint32_t v) { return __uint_as_float(v << 16); }
__device__ __forceinline__ float bf_hi(uint32_t v) { return __uint_as_float(v & 0xFFFF0000u); }

#define WG_REGS_4(o) "+f"(d[o]), "+f"(d[o + 1]), "+f"(d[o + 2]), "+f"(d[o + 3])
#define WG_REGS_8(o) WG_REGS_4(o), WG_REGS_4(o + 4)
#define WG_REGS_16(o) WG_REGS_8(o), WG_REGS_8(o + 8)
#define WG_REGS_32(o) WG_REGS_16(o), WG_REGS_16(o + 16)

__device__ __forceinline__ void wgmma_ss_n80_tb(float (&d)[40], uint64_t dA, uint64_t dB, int sc) {
    asm volatile("{\n.reg .pred p;\nsetp.ne.b32 p, %42, 0;\n"
                 "wgmma.mma_async.sync.aligned.m64n80k16.f32.bf16.bf16 "
                 "{%0,%1,%2,%3,%4,%5,%6,%7,%8,%9,%10,%11,%12,%13,%14,%15,%16,%17,%18,%19,%20,%21,%22,%23,%24,%25,%26,%27,%28,%29,%30,%31,"
                 "%32,%33,%34,%35,%36,%37,%38,%39}, %40, %41, p, 1, 1, 0, 1;\n}\n"
                 : WG_REGS_32(0), WG_REGS_8(32) : "l"(dA), "l"(dB), "r"(sc));
}
__device__ __forceinline__ void wgmma_ss_n64_tb(float (&d)[32], uint64_t dA, uint64_t dB, int sc) {
    asm volatile("{\n.reg .pred p;\nsetp.ne.b32 p, %34, 0;\n"
                 "wgmma.mma_async.sync.aligned.m64n64k16.f32.bf16.bf16 "
                 "{%0,%1,%2,%3,%4,%5,%6,%7,%8,%9,%10,%11,%12,%13,%14,%15,%16,%17,%18,%19,%20,%21,%22,%23,%24,%25,%26,%27,%28,%29,%30,%31}, "
                 "%32, %33, p, 1, 1, 0, 1;\n}\n"
                 : WG_REGS_32(0) : "l"(dA), "l"(dB), "r"(sc));
}
__device__ __forceinline__ void wgmma_ss_n128_tb(float (&d)[64], uint64_t dA, uint64_t dB, int sc) {
    asm volatile("{\n.reg .pred p;\nsetp.ne.b32 p, %66, 0;\n"
                 "wgmma.mma_async.sync.aligned.m64n128k16.f32.bf16.bf16 "
                 "{%0,%1,%2,%3,%4,%5,%6,%7,%8,%9,%10,%11,%12,%13,%14,%15,%16,%17,%18,%19,%20,%21,%22,%23,%24,%25,%26,%27,%28,%29,%30,%31,"
                 "%32,%33,%34,%35,%36,%37,%38,%39,%40,%41,%42,%43,%44,%45,%46,%47,%48,%49,%50,%51,%52,%53,%54,%55,%56,%57,%58,%59,%60,%61,%62,%63}, "
                 "%64, %65, p, 1, 1, 0, 1;\n}\n"
                 : WG_REGS_32(0), WG_REGS_32(32) : "l"(dA), "l"(dB), "r"(sc));
}
__device__ __forceinline__ void wgmma_ss_n224_tb(float (&d)[112], uint64_t dA, uint64_t dB, int sc) {
    asm volatile("{\n.reg .pred p;\nsetp.ne.b32 p, %114, 0;\n"
                 "wgmma.mma_async.sync.aligned.m64n224k16.f32.bf16.bf16 "
                 "{%0,%1,%2,%3,%4,%5,%6,%7,%8,%9,%10,%11,%12,%13,%14,%15,%16,%17,%18,%19,%20,%21,%22,%23,%24,%25,%26,%27,%28,%29,%30,%31,"
                 "%32,%33,%34,%35,%36,%37,%38,%39,%40,%41,%42,%43,%44,%45,%46,%47,%48,%49,%50,%51,%52,%53,%54,%55,%56,%57,%58,%59,%60,%61,%62,%63,"
                 "%64,%65,%66,%67,%68,%69,%70,%71,%72,%73,%74,%75,%76,%77,%78,%79,%80,%81,%82,%83,%84,%85,%86,%87,%88,%89,%90,%91,%92,%93,%94,%95,"
                 "%96,%97,%98,%99,%100,%101,%102,%103,%104,%105,%106,%107,%108,%109,%110,%111}, "
                 "%112, %113, p, 1, 1, 0, 1;\n}\n"
                 : WG_REGS_32(0), WG_REGS_32(32), WG_REGS_32(64), WG_REGS_16(96) : "l"(dA), "l"(dB), "r"(sc));
}
template <int BN> __device__ __forceinline__ void wgmma_ss_tb(float (&d)[BN / 2], uint64_t dA, uint64_t dB, int sc) {
    if constexpr (BN == 64) wgmma_ss_n64_tb(d, dA, dB, sc);
    else if constexpr (BN == 80) wgmma_ss_n80_tb(d, dA, dB, sc);
    else wgmma_ss_n224_tb(d, dA, dB, sc);
}
__device__ __forceinline__ void wgmma_rs_n64_tb(float (&d)[32], uint32_t a, uint64_t dB, int sc) {
    asm volatile("{\n.reg .pred p;\nsetp.ne.b32 p, %34, 0;\n"
                 "wgmma.mma_async.sync.aligned.m64n64k16.f32.bf16.bf16 "
                 "{%0,%1,%2,%3,%4,%5,%6,%7,%8,%9,%10,%11,%12,%13,%14,%15,%16,%17,%18,%19,%20,%21,%22,%23,%24,%25,%26,%27,%28,%29,%30,%31}, "
                 "{%32,%32,%32,%32}, %33, p, 1, 1, 1;\n}\n"
                 : WG_REGS_32(0) : "r"(a), "l"(dB), "r"(sc));
}
__device__ __forceinline__ void wgmma_rs_n80_tb(float (&d)[40], uint32_t a, uint64_t dB, int sc) {
    asm volatile("{\n.reg .pred p;\nsetp.ne.b32 p, %42, 0;\n"
                 "wgmma.mma_async.sync.aligned.m64n80k16.f32.bf16.bf16 "
                 "{%0,%1,%2,%3,%4,%5,%6,%7,%8,%9,%10,%11,%12,%13,%14,%15,%16,%17,%18,%19,%20,%21,%22,%23,%24,%25,%26,%27,%28,%29,%30,%31,"
                 "%32,%33,%34,%35,%36,%37,%38,%39}, {%40,%40,%40,%40}, %41, p, 1, 1, 1;\n}\n"
                 : WG_REGS_32(0), WG_REGS_8(32) : "r"(a), "l"(dB), "r"(sc));
}
template <int BN> __device__ __forceinline__ void wgmma_rs_ones(float (&d)[BN / 2], uint64_t dB, int sc) {
    if constexpr (BN == 80) wgmma_rs_n80_tb(d, 0x3F803F80u, dB, sc);
    else if constexpr (BN == 64) wgmma_rs_n64_tb(d, 0x3F803F80u, dB, sc);
}
__device__ __forceinline__ void wgmma_rs_n64_z(float (&d)[32], uint32_t a0, uint32_t a1, uint32_t a2, uint32_t a3, uint64_t dB) {
    asm volatile("{\n.reg .pred p;\nsetp.ne.b32 p, 0, 0;\n"
                 "wgmma.mma_async.sync.aligned.m64n64k16.f32.bf16.bf16 "
                 "{%0,%1,%2,%3,%4,%5,%6,%7,%8,%9,%10,%11,%12,%13,%14,%15,%16,%17,%18,%19,%20,%21,%22,%23,%24,%25,%26,%27,%28,%29,%30,%31}, "
                 "{%32,%33,%34,%35}, %36, p, 1, 1, 0;\n}\n"
                 : "=f"(d[0]), "=f"(d[1]), "=f"(d[2]), "=f"(d[3]), "=f"(d[4]), "=f"(d[5]), "=f"(d[6]), "=f"(d[7]),
                   "=f"(d[8]), "=f"(d[9]), "=f"(d[10]), "=f"(d[11]), "=f"(d[12]), "=f"(d[13]), "=f"(d[14]), "=f"(d[15]),
                   "=f"(d[16]), "=f"(d[17]), "=f"(d[18]), "=f"(d[19]), "=f"(d[20]), "=f"(d[21]), "=f"(d[22]), "=f"(d[23]),
                   "=f"(d[24]), "=f"(d[25]), "=f"(d[26]), "=f"(d[27]), "=f"(d[28]), "=f"(d[29]), "=f"(d[30]), "=f"(d[31])
                 : "r"(a0), "r"(a1), "r"(a2), "r"(a3), "l"(dB));
}
__device__ __forceinline__ void wgmma_rs_n24_tb(float (&d)[12], uint32_t a0, uint32_t a1, uint32_t a2, uint32_t a3, uint64_t dB) {
    asm volatile("{\n.reg .pred p;\nsetp.eq.b32 p, 0, 0;\n"
                 "wgmma.mma_async.sync.aligned.m64n24k16.f32.bf16.bf16 "
                 "{%0,%1,%2,%3,%4,%5,%6,%7,%8,%9,%10,%11}, {%12,%13,%14,%15}, %16, p, 1, 1, 1;\n}\n"
                 : WG_REGS_8(0), WG_REGS_4(8) : "r"(a0), "r"(a1), "r"(a2), "r"(a3), "l"(dB));
}

constexpr int SIDE_CTAS = 4;
__device__ __forceinline__ void side_job(int cta, float* red  , const __nv_bfloat16* __restrict__ wo,
                                         const __nv_bfloat16* __restrict__ w1, const __nv_bfloat16* __restrict__ w2) {
    const int tid = threadIdx.x, warp = tid >> 5, lane = tid & 31;
    for (int line = cta * 512 + tid; line < 18432; line += SIDE_CTAS * 512) {
        const char* p = line < 4096 ? (const char*)wo + (size_t)line * 128 : (const char*)w2 + (size_t)(line - 4096) * 128;
        asm volatile("prefetch.global.L2 [%0];" ::"l"(p));
    }
    const int rg = lane >> 3, c8 = lane & 7;
    for (int slab = cta; slab < F_ / 64; slab += SIDE_CTAS) {
        const __nv_bfloat16* base = w1 + slab * 64 + c8 * 8;
        uint4 v[8];
#pragma unroll
        for (int i = 0; i < 8; i++) v[i] = __ldg((const uint4*)(base + (size_t)(warp * 32 + rg + 4 * i) * F_));
        float acc[8];
#pragma unroll
        for (int i = 0; i < 8; i++) acc[i] = 0.f;
#pragma unroll
        for (int i = 0; i < 8; i++) {
            acc[0] += bf_lo(v[i].x); acc[1] += bf_hi(v[i].x); acc[2] += bf_lo(v[i].y); acc[3] += bf_hi(v[i].y);
            acc[4] += bf_lo(v[i].z); acc[5] += bf_hi(v[i].z); acc[6] += bf_lo(v[i].w); acc[7] += bf_hi(v[i].w);
        }
#pragma unroll
        for (int i = 0; i < 8; i++) {
            acc[i] += __shfl_xor_sync(0xffffffffu, acc[i], 8);
            acc[i] += __shfl_xor_sync(0xffffffffu, acc[i], 16);
        }
        if (rg == 0) {
#pragma unroll
            for (int i = 0; i < 8; i++) red[warp * 64 + c8 * 8 + i] = acc[i];
        }
        __syncthreads();
        if (tid < 64) {
            float s = 0.f;
#pragma unroll
            for (int i = 0; i < 16; i++) s += red[i * 64 + tid];
            g_cs_1[slab * 64 + tid] = s;
        }
        __syncthreads();
    }
}

enum { EPI_QKV = 0, EPI_RES = 1, EPI_FFN1 = 2 };

struct GemmParams {
    const float2* stats_in;
    float2* stats_out;
    const __nv_bfloat16* wkv;
    const __nv_bfloat16* wv;
    int tk;
};

template <int BK_, int NBLK> struct Geo {
    static constexpr int BK = BK_, A_BYTES = 128 * BK * 2, A_SWZ = BK == 64 ? 1 : 2, A_SBO = BK * 16;
    static constexpr int BLK = BK * 64;
    static constexpr int B_BYTES = NBLK * BLK, B_SWZ = 2, B_LBO = BLK, B_SBO = 512, B_KSTEP = 1024;
};
template <> struct Geo<64, 0> {
    static constexpr int BK = 64, A_BYTES = 128 * 128, A_SWZ = 1, A_SBO = 1024, BLK = 8192;
    static constexpr int B_BYTES = 64 * 128, B_SWZ = 1, B_LBO = 8192, B_SBO = 1024, B_KSTEP = 2048;
};
#define F1_BK 32
template <int EPI> struct EpiGeo;
template <> struct EpiGeo<EPI_QKV> { using G = Geo<64, 3>; };
template <> struct EpiGeo<EPI_RES> { using G = Geo<64, 0>; };
template <> struct EpiGeo<EPI_FFN1> { using G = Geo<F1_BK, 7>; };

template <int STAGES, int EPI> struct GemmSmem {
    using G = typename EpiGeo<EPI>::G;
    static constexpr int STAGE = G::A_BYTES + G::B_BYTES;
    static constexpr int AUX_OFF = STAGES * STAGE;
    static constexpr int TOTAL = AUX_OFF + 1152;
    static constexpr int TOTAL_SELF = AUX_OFF + 704 + 1024 + 1280;
};

struct RowStatRaw { float2 a0, a1, b0, b1; };
__device__ __forceinline__ RowStatRaw load_row_stats(const float2* __restrict__ st, int row0, int c) {
    RowStatRaw r;
    r.a0 = st[(2 * c) * S_ + row0]; r.a1 = st[(2 * c + 1) * S_ + row0];
    r.b0 = st[(2 * c) * S_ + row0 + 8]; r.b1 = st[(2 * c + 1) * S_ + row0 + 8];
    return r;
}
__device__ __forceinline__ void finish_row_stats(const RowStatRaw& r, float& mean0, float& rstd0, float& mean1, float& rstd1) {
    float sa = r.a0.x + r.a1.x, sb = r.b0.x + r.b1.x;
    sa += __shfl_xor_sync(0xffffffffu, sa, 1); sa += __shfl_xor_sync(0xffffffffu, sa, 2);
    sb += __shfl_xor_sync(0xffffffffu, sb, 1); sb += __shfl_xor_sync(0xffffffffu, sb, 2);
    mean0 = sa * 0.125f; mean1 = sb * 0.125f;
    float ma = r.a0.y + r.a1.y + 64.f * ((r.a0.x - mean0) * (r.a0.x - mean0) + (r.a1.x - mean0) * (r.a1.x - mean0));
    float mb = r.b0.y + r.b1.y + 64.f * ((r.b0.x - mean1) * (r.b0.x - mean1) + (r.b1.x - mean1) * (r.b1.x - mean1));
    ma += __shfl_xor_sync(0xffffffffu, ma, 1); ma += __shfl_xor_sync(0xffffffffu, ma, 2);
    mb += __shfl_xor_sync(0xffffffffu, mb, 1); mb += __shfl_xor_sync(0xffffffffu, mb, 2);
    rstd0 = 1.0f / sqrtf(ma * (1.f / 512.f) + 1e-5f);
    rstd1 = 1.0f / sqrtf(mb * (1.f / 512.f) + 1e-5f);
}

template <int BN, int KB, int STAGES, int EPI, int MC, bool SELF = false>
__device__ __forceinline__ void gemm_body(const CUtensorMap* mapA, const CUtensorMap* mapB, const CUtensorMap* mapB2, const CUtensorMap* mapR,
                                          const CUtensorMap* mapC, const GemmParams& prm, int tile_m, int tile_n, uint8_t* smem_raw) {
    using SM = GemmSmem<STAGES, EPI>;
    using G = typename SM::G;
    constexpr bool XKV = BN == 80;
    constexpr int TN = EPI == EPI_QKV ? 64 : BN;
    pdl_launch();
    const uint32_t sbase = smem_u32(smem_raw);
    if (sbase & 1023) __trap();
    uint8_t* sgen = smem_raw;
    const uint32_t bar_full = sbase + SM::AUX_OFF, bar_empty = bar_full + 8 * STAGES;
    float* s_cs = (float*)(sgen + SM::AUX_OFF + 256);
    float* s_row = (float*)(sgen + SM::AUX_OFF + 704);
    float* s_red = (float*)(sgen + SM::AUX_OFF + 640);
    const int tid = threadIdx.x, lane = tid & 31;
    const int warp = __shfl_sync(0xffffffffu, tid >> 5, 0);
    const uint32_t rank = MC ? cluster_rank() : 0;
    if (tid == 0) TL(prm.tk, 0);

    constexpr bool INLINE_PROD = EPI == EPI_FFN1 && F1_INLINE;
    constexpr int PWARP = INLINE_PROD ? 0 : 8;
    if (warp == PWARP && elect_one()) {
        prefetch_tmap(mapB); prefetch_tmap(mapA); prefetch_tmap(mapC);
        for (int s = 0; s < STAGES; s++) { mbar_init(bar_full + 8 * s, 1); mbar_init(bar_empty + 8 * s, MC ? 4 : 2); }
        fence_mbar_init();
    }
    __syncthreads();
    if (MC) cluster_sync();

    const int m0 = tile_m * 128, n0 = tile_n * TN;
    constexpr uint32_t STAGE_TX = G::A_BYTES + (EPI == EPI_QKV ? 2 * G::BLK : G::B_BYTES);
    auto loadB = [&](int kb, int s) {
        const uint32_t dst = sbase + s * SM::STAGE + G::A_BYTES, bar = bar_full + 8 * s;
        if constexpr (EPI == EPI_RES) {
            tma2d(dst, mapB, n0, kb * 64, bar);
        } else if constexpr (EPI == EPI_QKV) {
            tma3d(dst, mapB, 0, kb * G::BK, tile_n * 2, bar);
        } else {
            if constexpr (MC == 2) {
                if (rank == 0) tma3d_mc(dst, mapB, 0, kb * G::BK, tile_n * 7, bar, 3);
                else tma3d_mc(dst + 4 * G::BLK, mapB2, 0, kb * G::BK, tile_n * 7 + 4, bar, 3);
            } else {
                tma3d(dst, mapB, 0, kb * G::BK, tile_n * 7, bar);
                tma3d(dst + 4 * G::BLK, mapB2, 0, kb * G::BK, tile_n * 7 + 4, bar);
            }
        }
    };
    auto loadA = [&](int kb, int s) {
        const uint32_t dst = sbase + s * SM::STAGE, bar = bar_full + 8 * s;
        if constexpr (MC == 1) tma2d_mc(dst + rank * (G::A_BYTES / 2), mapA, kb * G::BK, m0 + rank * 64, bar, 3);
        else tma2d(dst, mapA, kb * G::BK, m0, bar);
    };
    constexpr int PRE = STAGES < KB ? STAGES : KB;
#define F1_LAG 2
    constexpr int LAG = F1_LAG;
    constexpr int PRE_B = PRE < PREB ? PRE : PREB;
    auto prologue_loads = [&]() {
        if (elect_one()) {
#pragma unroll
            for (int kb = 0; kb < PRE; kb++) mbar_expect_tx(bar_full + 8 * kb, STAGE_TX);
#pragma unroll
            for (int kb = 0; kb < PRE_B; kb++) loadB(kb, kb);
        }
        if (!SELF) pdl_wait();
        if (elect_one()) {
#pragma unroll
            for (int kb = 0; kb < PRE; kb++) {
                loadA(kb, kb);
                if (kb + PRE_B < PRE) loadB(kb + PRE_B, kb + PRE_B);
            }
            if constexpr (EPI == EPI_RES && KB < STAGES) {
                mbar_expect_tx(bar_full + 8 * KB, 16384);
                tma2d(sbase + KB * SM::STAGE, mapR, n0, m0, bar_full + 8 * KB);
            }
        }
    };
    if (SELF && warp > 8) {
        static_assert(!SELF || (STAGES >= KB && EPI == EPI_QKV), "SELF needs every k block resident");
        const int t = tid - 288;
        float ss[4] = {0.f, 0.f, 0.f, 0.f}, sq[4] = {0.f, 0.f, 0.f, 0.f};
        auto row_stats = [&](int kb) {
            const uint32_t arow = sbase + kb * SM::STAGE + (t >> 1) * 128;
            uint32_t w[4][4];
#pragma unroll
            for (int j = 0; j < 4; j++)
                asm volatile("ld.shared.v4.u32 {%0,%1,%2,%3}, [%4];" : "=r"(w[j][0]), "=r"(w[j][1]), "=r"(w[j][2]), "=r"(w[j][3])
                             : "r"(arow + (((2 * j + (t & 1) + 2 * ((t >> 1) & 3)) & 7) << 4)));
#pragma unroll
            for (int j = 0; j < 4; j++)
#pragma unroll
                for (int i = 0; i < 4; i++) {
                    const float lo = bf_lo(w[j][i]), hi = bf_hi(w[j][i]);
                    ss[i] += lo + hi;
                    sq[i] = fmaf(lo, lo, fmaf(hi, hi, sq[i]));
                }
        };
        if ((warp >> 2) == 3) {
            float csum[BN / 2];
            const uint64_t dB0 = mkdesc(sbase + G::A_BYTES, G::B_LBO, G::B_SBO, G::B_SWZ);
            if constexpr (XKV) named_bar(6, 512);
#pragma unroll 1
            for (int kb = 0; kb < KB; kb++) {
                mbar_wait(bar_full + 8 * kb, 0);
                const uint64_t dB = dB0 + (uint64_t)(kb * (SM::STAGE >> 4));
                wg_fence();
#pragma unroll
                for (int k = 0; k < G::BK / 16; k++) {
                    if constexpr (SELF) wgmma_rs_ones<BN>(csum, dB + (uint64_t)(k * (G::B_KSTEP >> 4)), (kb | k) != 0);
                }
                wg_commit();
                wg_wait<0>();
                row_stats(kb);
            }
            wg_wait<0>();
            fence_regs(csum);
            if (warp == 12 && lane < 4) {
#pragma unroll
                for (int j = 0; j < BN / 8; j++) {
                    const float2 v = make_float2(csum[4 * j], csum[4 * j + 1]);
                    *(float2*)(s_cs + 8 * j + 2 * lane) = v;
                    if (tile_m == 0) {
                        if (j < 8) *(float2*)(g_cs_q + n0 + 8 * j + 2 * lane) = v;
                        else *(float2*)(g_cs_kv + tile_n * 16 + 8 * (j - 8) + 2 * lane) = v;
                    }
                }
            }
        } else {
            if constexpr (XKV) named_bar(6, 512);
#pragma unroll 1
            for (int kb = 0; kb < KB; kb++) {
                mbar_wait(bar_full + 8 * kb, 0);
                row_stats(kb);
            }
        }
        float tsum = (ss[0] + ss[1]) + (ss[2] + ss[3]), tsq = (sq[0] + sq[1]) + (sq[2] + sq[3]);
        tsum += __shfl_xor_sync(0xffffffffu, tsum, 1);
        tsq += __shfl_xor_sync(0xffffffffu, tsq, 1);
        if ((t & 1) == 0) {
            const float md = tsum * (1.f / 512.f);
            const float var = fmaxf(tsq * (1.f / 512.f) - md * md, 0.f);
            *(float2*)(s_row + t) = make_float2(md, 1.0f / sqrtf(var + 1e-5f));
        }
        named_bar(4, 512);
    } else if (!INLINE_PROD && warp == 8) {
        prologue_loads();
        int s = PRE % STAGES, ph = (PRE / STAGES) & 1;
#pragma unroll 1
        for (int kb = PRE; kb < KB; kb++) {
            mbar_wait(bar_empty + 8 * s, ph ^ 1);
            if (elect_one()) {
                mbar_expect_tx(bar_full + 8 * s, STAGE_TX);
                loadB(kb, s);
                loadA(kb, s);
            }
            if (++s == STAGES) { s = 0; ph ^= 1; }
        }
        if constexpr (EPI == EPI_RES && KB >= STAGES) {
            mbar_wait(bar_empty + 8 * s, ph ^ 1);
            if (elect_one()) {
                mbar_expect_tx(bar_full + 8 * s, 16384);
                tma2d(sbase + s * SM::STAGE, mapR, n0, m0, bar_full + 8 * s);
            }
        }
    } else {
        if (INLINE_PROD && warp == 0) prologue_loads();
        const int wg = warp >> 2, g = lane >> 2, c = lane & 3;
        const int rloc = wg * 64 + (warp & 3) * 16 + g;
        const int row0 = m0 + rloc;
        float mean0 = 0.f, rstd0 = 1.f, mean1 = 0.f, rstd1 = 1.f;
        if constexpr (XKV) {
            static_assert(!XKV || STAGES >= KB, "the K / V weight block must stay resident");
            const __nv_bfloat16* wsrc = tile_n == 0 ? prm.wkv : prm.wv;
            uint4 v[4];
#pragma unroll
            for (int i = 0; i < 4; i++) v[i] = __ldg((const uint4*)wsrc + tid + 256 * i);
#pragma unroll
            for (int i = 0; i < 4; i++) {
                const int idx = tid + 256 * i, k = idx >> 1, kr = k & 63;
                const uint32_t dst = sbase + (k >> 6) * SM::STAGE + G::A_BYTES + 2 * G::BLK + kr * 64 + (((idx & 1) ^ ((kr >> 1) & 3)) << 4);
                asm volatile("st.shared.v4.u32 [%0], {%1,%2,%3,%4};" ::"r"(dst), "r"(v[i].x), "r"(v[i].y), "r"(v[i].z), "r"(v[i].w) : "memory");
            }
            fence_async_smem();
            if constexpr (SELF) named_bar(6, 512); else named_bar(6, 256);
        }
        RowStatRaw raw;
        float csv = 0.f;
        float2 cskv[2] = {make_float2(0.f, 0.f), make_float2(0.f, 0.f)};
        auto ln_inputs = [&]() {
            pdl_wait();
            if constexpr (EPI != EPI_RES) {
                raw = load_row_stats(prm.stats_in, row0, c);
                const float* cs = EPI == EPI_FFN1 ? g_cs_1 + n0 : g_cs_q + n0;
                if (tid < TN) csv = cs[tid];
                if constexpr (XKV) {
                    cskv[0] = *(const float2*)(g_cs_kv + tile_n * 16 + 2 * c);
                    cskv[1] = *(const float2*)(g_cs_kv + tile_n * 16 + 8 + 2 * c);
                }
            }
        };
        if (!SELF) ln_inputs();
        float acc[BN / 2];
        const uint64_t dA0 = mkdesc(sbase + wg * (G::A_BYTES / 2), 16, G::A_SBO, G::A_SWZ);
        const uint64_t dB0 = mkdesc(sbase + G::A_BYTES, G::B_LBO, G::B_SBO, G::B_SWZ);
        int s = 0, ph = 0;
#pragma unroll 1
        for (int kb = 0; kb < KB; kb++) {
            mbar_wait(bar_full + 8 * s, ph);
            const uint64_t dA = dA0 + (uint64_t)(s * (SM::STAGE >> 4)), dB = dB0 + (uint64_t)(s * (SM::STAGE >> 4));
            wg_fence();
#pragma unroll
            for (int k = 0; k < G::BK / 16; k++) wgmma_ss_tb<BN>(acc, dA + (uint64_t)(k * 2), dB + (uint64_t)(k * (G::B_KSTEP >> 4)), (kb | k) != 0);
            wg_commit();
            if constexpr (EPI == EPI_RES && RES_WAIT0) {
                wg_wait<0>();
                if ((warp & 3) == 0 && elect_one()) {
                    if (MC) { mbar_arrive_remote(bar_empty + 8 * s, 0); mbar_arrive_remote(bar_empty + 8 * s, 1); }
                    else mbar_arrive(bar_empty + 8 * s);
                }
            } else if (kb > 0) {
                wg_wait<1>();
                const int sp = s == 0 ? STAGES - 1 : s - 1;
                if ((warp & 3) == 0 && elect_one()) {
                    if (MC) { mbar_arrive_remote(bar_empty + 8 * sp, 0); mbar_arrive_remote(bar_empty + 8 * sp, 1); }
                    else mbar_arrive(bar_empty + 8 * sp);
                }
                if (INLINE_PROD && warp == 0 && kb >= LAG && kb - LAG + STAGES < KB) {
                    const int sq = LAG == 1 ? sp : (sp == 0 ? STAGES - 1 : sp - 1);
                    mbar_wait(bar_empty + 8 * sq, ((kb - LAG) / STAGES) & 1);
                    if (elect_one()) {
                        mbar_expect_tx(bar_full + 8 * sq, STAGE_TX);
                        loadB(kb - LAG + STAGES, sq);
                        loadA(kb - LAG + STAGES, sq);
                    }
                }
            }
            if (++s == STAGES) { s = 0; ph ^= 1; }
        }
        if constexpr (SELF) {
            named_bar(4, 512);
            const float2 r0 = *(const float2*)(s_row + 2 * rloc), r1 = *(const float2*)(s_row + 2 * rloc + 16);
            mean0 = r0.x; rstd0 = r0.y; mean1 = r1.x; rstd1 = r1.y;
        } else if constexpr (EPI != EPI_RES) {
            finish_row_stats(raw, mean0, rstd0, mean1, rstd1);
            if (tid < TN) s_cs[tid] = csv;
        }
        wg_wait<0>();
        fence_regs(acc);
        if (tid == 0) TL(prm.tk, 2);
        if constexpr (EPI != EPI_RES) named_bar(1, 256);

        if constexpr (EPI != EPI_FFN1) {
            const uint32_t stile = sbase + (EPI == EPI_RES ? s * SM::STAGE : 0);
            const int mrow = wg * 64 + (warp & 3) * 16 + (lane & 7) + ((lane >> 3) & 1) * 8;
            const uint32_t rbase = stile + mrow * 128;
            if constexpr (EPI == EPI_RES) {
                mbar_wait(bar_full + 8 * s, ph);
                float s0 = 0.f, s1 = 0.f;
#pragma unroll
                for (int jj = 0; jj < 4; jj++) {
                    uint32_t r0, r1, r2, r3;
                    const uint32_t addr = rbase + (((2 * jj + (lane >> 4)) ^ (mrow & 7)) << 4);
                    ldsm_x4(r0, r1, r2, r3, addr);
                    const uint32_t u0 = pack_bf16(acc[8 * jj] + bf_lo(r0), acc[8 * jj + 1] + bf_hi(r0));
                    const uint32_t u1 = pack_bf16(acc[8 * jj + 2] + bf_lo(r1), acc[8 * jj + 3] + bf_hi(r1));
                    const uint32_t u2 = pack_bf16(acc[8 * jj + 4] + bf_lo(r2), acc[8 * jj + 5] + bf_hi(r2));
                    const uint32_t u3 = pack_bf16(acc[8 * jj + 6] + bf_lo(r3), acc[8 * jj + 7] + bf_hi(r3));
                    stsm_x4(addr, u0, u1, u2, u3);
                    acc[8 * jj] = bf_lo(u0); acc[8 * jj + 1] = bf_hi(u0); acc[8 * jj + 4] = bf_lo(u2); acc[8 * jj + 5] = bf_hi(u2);
                    acc[8 * jj + 2] = bf_lo(u1); acc[8 * jj + 3] = bf_hi(u1); acc[8 * jj + 6] = bf_lo(u3); acc[8 * jj + 7] = bf_hi(u3);
                    s0 += (acc[8 * jj] + acc[8 * jj + 1]) + (acc[8 * jj + 4] + acc[8 * jj + 5]);
                    s1 += (acc[8 * jj + 2] + acc[8 * jj + 3]) + (acc[8 * jj + 6] + acc[8 * jj + 7]);
                }
                fence_async_smem();
                named_bar(2 + wg, 128);
                if ((warp & 3) == 0 && elect_one()) { tma2d_store(mapC, stile + wg * 8192, n0, m0 + wg * 64); bulk_commit(); }
                if (prm.stats_out) {
                    s0 += __shfl_xor_sync(0xffffffffu, s0, 1); s0 += __shfl_xor_sync(0xffffffffu, s0, 2);
                    s1 += __shfl_xor_sync(0xffffffffu, s1, 1); s1 += __shfl_xor_sync(0xffffffffu, s1, 2);
                    const float mu0 = s0 * (1.f / 64.f), mu1 = s1 * (1.f / 64.f);
                    float q0 = 0.f, q1 = 0.f;
#pragma unroll
                    for (int j = 0; j < 8; j++) {
                        float d;
                        d = acc[4 * j] - mu0; q0 += d * d; d = acc[4 * j + 1] - mu0; q0 += d * d;
                        d = acc[4 * j + 2] - mu1; q1 += d * d; d = acc[4 * j + 3] - mu1; q1 += d * d;
                    }
                    q0 += __shfl_xor_sync(0xffffffffu, q0, 1); q0 += __shfl_xor_sync(0xffffffffu, q0, 2);
                    q1 += __shfl_xor_sync(0xffffffffu, q1, 1); q1 += __shfl_xor_sync(0xffffffffu, q1, 2);
                    if (c == 0) {
                        prm.stats_out[tile_n * S_ + row0] = make_float2(mu0, q0);
                        prm.stats_out[tile_n * S_ + row0 + 8] = make_float2(mu1, q1);
                    }
                }
            } else {
                const float sc = 0.25f * 1.4426950408889634f;
                const float a0 = rstd0 * sc, a1 = rstd1 * sc, rm0 = a0 * mean0, rm1 = a1 * mean1;
#pragma unroll
                for (int jj = 0; jj < 4; jj++) {
                    const float2 ca = *(const float2*)(s_cs + 16 * jj + 2 * c), cb = *(const float2*)(s_cs + 16 * jj + 8 + 2 * c);
                    const uint32_t u0 = pack_bf16(acc[8 * jj] * a0 - rm0 * ca.x, acc[8 * jj + 1] * a0 - rm0 * ca.y);
                    const uint32_t u1 = pack_bf16(acc[8 * jj + 2] * a1 - rm1 * ca.x, acc[8 * jj + 3] * a1 - rm1 * ca.y);
                    const uint32_t u2 = pack_bf16(acc[8 * jj + 4] * a0 - rm0 * cb.x, acc[8 * jj + 5] * a0 - rm0 * cb.y);
                    const uint32_t u3 = pack_bf16(acc[8 * jj + 6] * a1 - rm1 * cb.x, acc[8 * jj + 7] * a1 - rm1 * cb.y);
                    stsm_x4(rbase + (((2 * jj + (lane >> 4)) ^ (mrow & 7)) << 4), u0, u1, u2, u3);
                }
                fence_async_smem();
                named_bar(2 + wg, 128);
                if ((warp & 3) == 0 && elect_one()) { tma2d_store(mapC, stile + wg * 8192, n0, m0 + wg * 64); bulk_commit(); }
            }
            if constexpr (XKV) {
                {
                    const float* acx = &acc[32];
                    const float rm0 = rstd0 * mean0, rm1 = rstd1 * mean1;
                    float n0s = 0.f, n1s = 0.f, vmax = 0.f;
#pragma unroll
                    for (int j = 0; j < 2; j++) {
                        const float2 cs2 = SELF ? *(const float2*)(s_cs + 64 + 8 * j + 2 * c) : cskv[j];
                        const uint32_t u0 = pack_bf16(acx[4 * j] * rstd0 - rm0 * cs2.x, acx[4 * j + 1] * rstd0 - rm0 * cs2.y);
                        const uint32_t u1 = pack_bf16(acx[4 * j + 2] * rstd1 - rm1 * cs2.x, acx[4 * j + 3] * rstd1 - rm1 * cs2.y);
                        n0s += bf_lo(u0) * bf_lo(u0) + bf_hi(u0) * bf_hi(u0);
                        n1s += bf_lo(u1) * bf_lo(u1) + bf_hi(u1) * bf_hi(u1);
                        vmax = fmaxf(vmax, fmaxf(fmaxf(fabsf(bf_lo(u0)), fabsf(bf_hi(u0))), fmaxf(fabsf(bf_lo(u1)), fabsf(bf_hi(u1)))));
                        if (tile_n == 0) {
                            *(uint32_t*)(g_kimg + (row0 >> 3) * 256 + j * 128 + g * 16 + c * 4) = u0;
                            *(uint32_t*)(g_kimg + ((row0 + 8) >> 3) * 256 + j * 128 + g * 16 + c * 4) = u1;
                        } else {
                            uint8_t* vb = g_vimg + (row0 >> 4) * 768 + j * 256 + g * 16 + c * 4;
                            *(uint32_t*)(vb) = u0;
                            *(uint32_t*)(vb + 128) = u1;
                        }
                    }
                    if (tile_n == 1) {
                        uint8_t* vb = g_vimg + (row0 >> 4) * 768 + 512 + g * 16 + c * 4;
                        const uint32_t one = c == 0 ? 0x00003F80u : 0u;
                        *(uint32_t*)(vb) = one;
                        *(uint32_t*)(vb + 128) = one;
                    }
                    n0s += __shfl_xor_sync(0xffffffffu, n0s, 1); n0s += __shfl_xor_sync(0xffffffffu, n0s, 2);
                    n1s += __shfl_xor_sync(0xffffffffu, n1s, 1); n1s += __shfl_xor_sync(0xffffffffu, n1s, 2);
                    float km = tile_n == 0 ? fmaxf(n0s, n1s) : vmax;
                    if (!(n0s + n1s < INFINITY)) km = INFINITY;
#pragma unroll
                    for (int o = 1; o < 32; o <<= 1) km = fmaxf(km, __shfl_xor_sync(0xffffffffu, km, o));
                    if (lane == 0) s_red[warp] = km;
                    named_bar(1, 256);
                    if (tid == 0) {
                        float a = 0.f;
                        for (int i = 0; i < 8; i++) a = fmaxf(a, s_red[i]);
                        g_kvmax[tile_n * 16 + tile_m] = a;
                    }
                }
            }
            if ((warp & 3) == 0) bulk_wait_read();
        } else {
            const uint32_t stile = sbase + wg * (7 * 4096);
            const int mrow = (warp & 3) * 16 + (lane & 7) + ((lane >> 3) & 1) * 8;
            const float a0 = 0.5f * rstd0, a1 = 0.5f * rstd1, rm0 = a0 * mean0, rm1 = a1 * mean1;
#pragma unroll
            for (int jj = 0; jj < 14; jj++) {
                const float2 ca = *(const float2*)(s_cs + 16 * jj + 2 * c), cb = *(const float2*)(s_cs + 16 * jj + 8 + 2 * c);
                float y[8] = {acc[8 * jj] * a0 - rm0 * ca.x,     acc[8 * jj + 1] * a0 - rm0 * ca.y,
                              acc[8 * jj + 2] * a1 - rm1 * ca.x, acc[8 * jj + 3] * a1 - rm1 * ca.y,
                              acc[8 * jj + 4] * a0 - rm0 * cb.x, acc[8 * jj + 5] * a0 - rm0 * cb.y,
                              acc[8 * jj + 6] * a1 - rm1 * cb.x, acc[8 * jj + 7] * a1 - rm1 * cb.y};
#pragma unroll
                for (int i = 0; i < 8; i++) {
                    float t;
                    asm("tanh.approx.f32 %0, %1;" : "=f"(t) : "f"(y[i]));
                    y[i] = fmaf(y[i], t, y[i]);
                }
                const int chunk = (2 * jj + (lane >> 4)) & 3, blk = jj >> 1;
                stsm_x4(stile + blk * 4096 + mrow * 64 + ((chunk ^ ((mrow >> 1) & 3)) << 4),
                        pack_bf16(y[0], y[1]), pack_bf16(y[2], y[3]), pack_bf16(y[4], y[5]), pack_bf16(y[6], y[7]));
                if (jj & 1) {
                    fence_async_smem();
                    __syncwarp();
                    if (elect_one()) {
                        tma2d_store(mapC, stile + blk * 4096 + (warp & 3) * 1024, n0 + blk * 32, m0 + wg * 64 + (warp & 3) * 16);
                        bulk_commit();
                    }
                }
            }
            bulk_wait_read();
        }
    }
    if (tid == 0) TL(prm.tk, 3);
    if (MC) cluster_sync();
}

#define WO_ST 9
#define F2_ST 6
#define F1_ST (F1_BK == 64 ? 5 : 9)
#define QKV_ST 8
constexpr int QKV_STAGES = QKV_ST, WO_STAGES = WO_ST, FFN2_STAGES = F2_ST, FFN1_STAGES = F1_ST;
template <bool SELF>
__global__ void __launch_bounds__(SELF ? 544 : 288) qkv_kernel(const __grid_constant__ CUtensorMap mapA, const __grid_constant__ CUtensorMap mapWq,
                                                  const __grid_constant__ CUtensorMap mapQ, const GemmParams prm) {
    extern __shared__ __align__(1024) uint8_t smem_raw[];
    const int tn = blockIdx.x & 7;
    if (tn < 2) gemm_body<80, 8, QKV_STAGES, EPI_QKV, QKV_MC, SELF>(&mapA, &mapWq, &mapWq, &mapA, &mapQ, prm, blockIdx.x >> 3, tn, smem_raw);
    else gemm_body<64, 8, QKV_STAGES, EPI_QKV, QKV_MC, SELF>(&mapA, &mapWq, &mapWq, &mapA, &mapQ, prm, blockIdx.x >> 3, tn, smem_raw);
}
template <int STAGES> struct ResSmem {
    static constexpr int A_BYTES = 64 * 128, B_BYTES = 2 * 64 * 128, STAGE = A_BYTES + B_BYTES;
    static constexpr int AUX_OFF = STAGES * STAGE, TOTAL = AUX_OFF + 256;
};
#define RES_MAP 0
template <int KB, int STAGES>
__global__ void __launch_bounds__(288) res_gemm_kernel(const __grid_constant__ CUtensorMap mapA, const __grid_constant__ CUtensorMap mapW,
                                                       const __grid_constant__ CUtensorMap mapR, const __grid_constant__ CUtensorMap mapC, const GemmParams prm) {
    extern __shared__ __align__(1024) uint8_t smem_raw[];
    using SM = ResSmem<STAGES>;
    pdl_launch();
    const uint32_t sbase = smem_u32(smem_raw);
    if (sbase & 1023) __trap();
    const uint32_t bar_full = sbase + SM::AUX_OFF, bar_empty = bar_full + 8 * STAGES;
    const int tid = threadIdx.x, lane = tid & 31;
    const int warp = __shfl_sync(0xffffffffu, tid >> 5, 0);
    const int tile_m = RES_MAP == 0 ? blockIdx.x >> 2 : blockIdx.x & 31, tile_n = RES_MAP == 0 ? blockIdx.x & 3 : blockIdx.x >> 5;
    const int m0 = tile_m * 64, n0 = tile_n * 128;
    if (tid == 0) TL(prm.tk, 0);
    if (warp == 8 && elect_one()) {
        prefetch_tmap(&mapW); prefetch_tmap(&mapA); prefetch_tmap(&mapR); prefetch_tmap(&mapC);
        for (int s = 0; s < STAGES; s++) { mbar_init(bar_full + 8 * s, 1); mbar_init(bar_empty + 8 * s, 2); }
        fence_mbar_init();
    }
    __syncthreads();
    constexpr int PRE = STAGES < KB ? STAGES : KB;
    if (warp == 8) {
        auto loadB = [&](int kb, int s) { tma3d(sbase + s * SM::STAGE + SM::A_BYTES, &mapW, 0, kb * 64, tile_n * 2, bar_full + 8 * s); };
        auto loadA = [&](int kb, int s) { tma2d(sbase + s * SM::STAGE, &mapA, kb * 64, m0, bar_full + 8 * s); };
        auto loadR = [&](int s) {
            mbar_expect_tx(bar_full + 8 * s, 16384);
            tma3d(sbase + s * SM::STAGE, &mapR, 0, m0, tile_n * 2, bar_full + 8 * s);
        };
        if (elect_one()) {
#pragma unroll
            for (int kb = 0; kb < PRE; kb++) mbar_expect_tx(bar_full + 8 * kb, SM::STAGE);
            loadB(0, 0);
        }
        pdl_wait();
        if (elect_one()) {
#pragma unroll
            for (int kb = 0; kb < PRE; kb++) {
                loadA(kb, kb);
                if (kb + 1 < PRE) loadB(kb + 1, kb + 1);
            }
            if constexpr (KB < STAGES) loadR(KB);
        }
        int s = PRE % STAGES, ph = (PRE / STAGES) & 1;
#pragma unroll 1
        for (int kb = PRE; kb < KB; kb++) {
            mbar_wait(bar_empty + 8 * s, ph ^ 1);
            if (elect_one()) {
                mbar_expect_tx(bar_full + 8 * s, SM::STAGE);
                loadA(kb, s);
                loadB(kb, s);
            }
            if (++s == STAGES) { s = 0; ph ^= 1; }
        }
        if constexpr (KB >= STAGES) {
            mbar_wait(bar_empty + 8 * s, ph ^ 1);
            if (elect_one()) loadR(s);
        }
    } else {
        const int wg = warp >> 2, g = lane >> 2, c = lane & 3;
        float acc[64];
        const uint64_t dA0 = mkdesc(sbase + wg * 64, 16, 1024, 1);
        const uint64_t dB0 = mkdesc(sbase + SM::A_BYTES + wg * 4096, 8192, 1024, 1);
        int s = 0, ph = 0;
#pragma unroll 1
        for (int kb = 0; kb < KB; kb++) {
            mbar_wait(bar_full + 8 * s, ph);
            const uint64_t dA = dA0 + (uint64_t)(s * (SM::STAGE >> 4)), dB = dB0 + (uint64_t)(s * (SM::STAGE >> 4));
            wg_fence();
            wgmma_ss_n128_tb(acc, dA, dB, kb != 0);
            wgmma_ss_n128_tb(acc, dA + 2, dB + 128, 1);
            wg_commit();
            if (kb > 0) {
                wg_wait<1>();
                if ((warp & 3) == 0 && elect_one()) mbar_arrive(bar_empty + 8 * (s == 0 ? STAGES - 1 : s - 1));
            }
            if (++s == STAGES) { s = 0; ph ^= 1; }
        }
        wg_wait<0>();
        fence_regs(acc);
        if (tid == 0) TL(prm.tk, 2);
        pdl_wait();
        named_bar(1, 256);
        const int s1 = s + 1 == STAGES ? 0 : s + 1, s2 = s1 + 1 == STAGES ? 0 : s1 + 1;
        const uint32_t xw = sbase + (wg == 0 ? s1 : s2) * SM::STAGE + (tid & 127) * 16;
        const uint32_t xr = sbase + (wg == 0 ? s2 : s1) * SM::STAGE + (tid & 127) * 16;
        float v[32];
        if (wg == 0) {
#pragma unroll
            for (int i = 0; i < 8; i++)
                asm volatile("st.shared.v4.f32 [%0], {%1,%2,%3,%4};" ::"r"(xw + i * 2048), "f"(acc[32 + 4 * i]), "f"(acc[33 + 4 * i]), "f"(acc[34 + 4 * i]), "f"(acc[35 + 4 * i]) : "memory");
#pragma unroll
            for (int i = 0; i < 32; i++) v[i] = acc[i];
        } else {
#pragma unroll
            for (int i = 0; i < 8; i++)
                asm volatile("st.shared.v4.f32 [%0], {%1,%2,%3,%4};" ::"r"(xw + i * 2048), "f"(acc[4 * i]), "f"(acc[1 + 4 * i]), "f"(acc[2 + 4 * i]), "f"(acc[3 + 4 * i]) : "memory");
#pragma unroll
            for (int i = 0; i < 32; i++) v[i] = acc[32 + i];
        }
        named_bar(1, 256);
#pragma unroll
        for (int i = 0; i < 8; i++) {
            float t0, t1, t2, t3;
            asm volatile("ld.shared.v4.f32 {%0,%1,%2,%3}, [%4];" : "=f"(t0), "=f"(t1), "=f"(t2), "=f"(t3) : "r"(xr + i * 2048) : "memory");
            v[4 * i] += t0; v[4 * i + 1] += t1; v[4 * i + 2] += t2; v[4 * i + 3] += t3;
        }
        const uint32_t stile = sbase + s * SM::STAGE + wg * 8192;
        const int mrow = (warp & 3) * 16 + (lane & 7) + ((lane >> 3) & 1) * 8;
        mbar_wait(bar_full + 8 * s, ph);
        float s0 = 0.f, s1v = 0.f;
#pragma unroll
        for (int jj = 0; jj < 4; jj++) {
            uint32_t r0, r1, r2, r3;
            const uint32_t addr = stile + mrow * 128 + (((2 * jj + (lane >> 4)) ^ (mrow & 7)) << 4);
            ldsm_x4(r0, r1, r2, r3, addr);
            const uint32_t u0 = pack_bf16(v[8 * jj] + bf_lo(r0), v[8 * jj + 1] + bf_hi(r0));
            const uint32_t u1 = pack_bf16(v[8 * jj + 2] + bf_lo(r1), v[8 * jj + 3] + bf_hi(r1));
            const uint32_t u2 = pack_bf16(v[8 * jj + 4] + bf_lo(r2), v[8 * jj + 5] + bf_hi(r2));
            const uint32_t u3 = pack_bf16(v[8 * jj + 6] + bf_lo(r3), v[8 * jj + 7] + bf_hi(r3));
            stsm_x4(addr, u0, u1, u2, u3);
            v[8 * jj] = bf_lo(u0); v[8 * jj + 1] = bf_hi(u0); v[8 * jj + 4] = bf_lo(u2); v[8 * jj + 5] = bf_hi(u2);
            v[8 * jj + 2] = bf_lo(u1); v[8 * jj + 3] = bf_hi(u1); v[8 * jj + 6] = bf_lo(u3); v[8 * jj + 7] = bf_hi(u3);
            s0 += (v[8 * jj] + v[8 * jj + 1]) + (v[8 * jj + 4] + v[8 * jj + 5]);
            s1v += (v[8 * jj + 2] + v[8 * jj + 3]) + (v[8 * jj + 6] + v[8 * jj + 7]);
        }
        fence_async_smem();
        named_bar(2 + wg, 128);
        if ((warp & 3) == 0 && elect_one()) { tma2d_store(&mapC, stile, n0 + wg * 64, m0); bulk_commit(); }
        if (prm.stats_out) {
            const int row0 = m0 + (warp & 3) * 16 + g;
            s0 += __shfl_xor_sync(0xffffffffu, s0, 1); s0 += __shfl_xor_sync(0xffffffffu, s0, 2);
            s1v += __shfl_xor_sync(0xffffffffu, s1v, 1); s1v += __shfl_xor_sync(0xffffffffu, s1v, 2);
            const float mu0 = s0 * (1.f / 64.f), mu1 = s1v * (1.f / 64.f);
            float q0 = 0.f, q1 = 0.f;
#pragma unroll
            for (int j = 0; j < 8; j++) {
                float d;
                d = v[4 * j] - mu0; q0 += d * d; d = v[4 * j + 1] - mu0; q0 += d * d;
                d = v[4 * j + 2] - mu1; q1 += d * d; d = v[4 * j + 3] - mu1; q1 += d * d;
            }
            q0 += __shfl_xor_sync(0xffffffffu, q0, 1); q0 += __shfl_xor_sync(0xffffffffu, q0, 2);
            q1 += __shfl_xor_sync(0xffffffffu, q1, 1); q1 += __shfl_xor_sync(0xffffffffu, q1, 2);
            if (c == 0) {
                prm.stats_out[(tile_n * 2 + wg) * S_ + row0] = make_float2(mu0, q0);
                prm.stats_out[(tile_n * 2 + wg) * S_ + row0 + 8] = make_float2(mu1, q1);
            }
        }
        if ((warp & 3) == 0) bulk_wait_read();
    }
    if (tid == 0) TL(prm.tk, 3);
}
__global__ void __launch_bounds__(F1_INLINE ? 256 : 288) ffn1_kernel(const __grid_constant__ CUtensorMap mapA, const __grid_constant__ CUtensorMap mapW4,
                                                   const __grid_constant__ CUtensorMap mapW3, const __grid_constant__ CUtensorMap mapH, const GemmParams prm) {
    extern __shared__ __align__(1024) uint8_t smem_raw[];
    const int pair = blockIdx.x >> 1, tile_n = pair & 7, tile_m = (pair >> 3) * 2 + (blockIdx.x & 1);
    gemm_body<224, 512 / F1_BK, FFN1_STAGES, EPI_FFN1, F1_MC>(&mapA, &mapW4, &mapW3, &mapA, &mapH, prm, tile_m, tile_n, smem_raw);
}

constexpr int NPOLY = 10;
__host__ __device__ constexpr bool is_mufu(int i) { return ((i + 1) * (16 - NPOLY)) / 16 != (i * (16 - NPOLY)) / 16; }

__device__ __forceinline__ float ex2(float x) { float r; asm("ex2.approx.ftz.f32 %0, %1;" : "=f"(r) : "f"(x)); return r; }
__device__ __forceinline__ uint32_t exp_pair_mufu(float a, float b) { return pack_bf16(ex2(a), ex2(b)); }
__device__ __forceinline__ uint32_t exp_pair_fma(float a, float b, uint32_t c3f) {
    constexpr float MAGIC = 98430.4140625f;
    const float ta = a + MAGIC, tb = b + (MAGIC - 143.5f);
    uint32_t y, m, r;
    asm("mad.lo.u32 %0, %1, 65536, %2;" : "=r"(y) : "r"(__float_as_uint(tb)), "r"(__float_as_uint(ta)));
    asm("lop3.b32 %0, %1, 0x007F007F, %2, 0xEA;" : "=r"(m) : "r"(y), "r"(c3f));
    const uint32_t e = y & 0xFF80FF80u;
    asm("fma.rn.bf16x2 %0, %1, %2, %3;" : "=r"(r) : "r"(y), "r"(m), "r"(e));
    return r;
}

constexpr int KCH = 256, NCH = S_ / KCH;
constexpr int K_BYTES = S_ * 32, V_BYTES = (S_ / 16) * 768;
constexpr int ATT_SMEM = K_BYTES + V_BYTES;

__global__ void __launch_bounds__(512, 1) attn_kernel(const __nv_bfloat16* __restrict__ wo, const __nv_bfloat16* __restrict__ w1,
                                                       const __nv_bfloat16* __restrict__ w2, int tk) {
    extern __shared__ __align__(1024) uint8_t smem[];
    __shared__ uint64_t bars[NCH];
    __shared__ int s_slow;
    const int tid = threadIdx.x, wg = tid >> 7, warp = (tid >> 5) & 3, lane = tid & 31;
    const uint32_t sK = smem_u32(smem), sV = sK + K_BYTES;
    if (blockIdx.x >= 128) {
        pdl_launch();
        side_job(blockIdx.x - 128, (float*)smem, wo, w1, w2);
        return;
    }
    CK(tk, 9);
    if (tid == 0) TL(tk, 0);
    if (tid == 0) {
        for (int i = 0; i < NCH; i++) mbar_init(smem_u32(&bars[i]), 1);
        s_slow = 0;
        fence_mbar_init();
    }
    __syncthreads();
    pdl_launch();
    CK(tk, 10);
    pdl_wait();
    CK(tk, 11);
    if (tid == 0) TL(tk, 1);
    const int wu = __shfl_sync(0xffffffffu, tid >> 5, 0);
    auto fetch_chunk = [&](int w) {
        if (elect_one()) {
            const uint32_t bar = smem_u32(&bars[w]);
            mbar_expect_tx(bar, KCH * 32 + (KCH / 16) * 768);
            bulk_load(sK + w * KCH * 32, g_kimg + w * KCH * 32, KCH * 32, bar);
            bulk_load(sV + w * (KCH / 16) * 768, g_vimg + w * (KCH / 16) * 768, (KCH / 16) * 768, bar);
        }
    };
    if (wu == 0) fetch_chunk(0);
    const int tb = blockIdx.x >> 3, hg = blockIdx.x & 7;
    const int head = hg * 4 + wg;
    const int g = lane >> 2, c = lane & 3;
    uint32_t qa[2][4];
#pragma unroll
    for (int m = 0; m < 2; m++) {
        const int row = tb * 128 + m * 64 + warp * 16 + g;
        const uint32_t* p0 = (const uint32_t*)(g_q + (size_t)row * D_ + head * 16);
        const uint32_t* p1 = (const uint32_t*)(g_q + (size_t)(row + 8) * D_ + head * 16);
        qa[m][0] = p0[c]; qa[m][1] = p1[c]; qa[m][2] = p0[c + 4]; qa[m][3] = p1[c + 4];
    }
    CK(tk, 12);
    float kvm = g_kvmax[lane];
    {
        float qn = 0.f;
#pragma unroll
        for (int m = 0; m < 2; m++) {
            float n0 = bf_lo(qa[m][0]) * bf_lo(qa[m][0]) + bf_hi(qa[m][0]) * bf_hi(qa[m][0]) + bf_lo(qa[m][2]) * bf_lo(qa[m][2]) + bf_hi(qa[m][2]) * bf_hi(qa[m][2]);
            float n1 = bf_lo(qa[m][1]) * bf_lo(qa[m][1]) + bf_hi(qa[m][1]) * bf_hi(qa[m][1]) + bf_lo(qa[m][3]) * bf_lo(qa[m][3]) + bf_hi(qa[m][3]) * bf_hi(qa[m][3]);
            n0 += __shfl_xor_sync(0xffffffffu, n0, 1); n0 += __shfl_xor_sync(0xffffffffu, n0, 2);
            n1 += __shfl_xor_sync(0xffffffffu, n1, 1); n1 += __shfl_xor_sync(0xffffffffu, n1, 2);
            if (!(n0 == n0) || !(n1 == n1)) n0 = INFINITY;
            qn = fmaxf(qn, fmaxf(n0, n1));
        }
        CK(tk, 13);
#pragma unroll
        for (int o = 1; o < 16; o <<= 1) kvm = fmaxf(kvm, __shfl_xor_sync(0xffffffffu, kvm, o));
        const float km = __shfl_sync(0xffffffffu, kvm, 0), vm = __shfl_sync(0xffffffffu, kvm, 16);
        const bool ok = (qn * km <= 10000.f) && (vm <= 16384.f);
        if (!ok) s_slow = 1;
    }
    CK(tk, 14);
    float oacc[2][12];
#pragma unroll
    for (int m = 0; m < 2; m++)
#pragma unroll
        for (int i = 0; i < 12; i++) oacc[m][i] = 0.f;
    __syncthreads();
    const bool slow = s_slow != 0;
    if (wu >= 1 && wu < NCH) fetch_chunk(wu);
    CK(tk, 15);

    const uint64_t dK0 = mkdesc(sK, 128, 256, 0);
    const uint64_t dV0 = mkdesc(sV, 128, 256, 0);
    uint32_t c3f;
    asm volatile("mov.b32 %0, 0x3F003F00;" : "=r"(c3f));
    if (!slow) {
#pragma unroll 1
        for (int t = 0; t < S_ / 64; t++) {
            if ((t & 3) == 0) mbar_wait(smem_u32(&bars[t >> 2]), 0);
            const uint64_t dK = dK0 + (uint64_t)(t * 64 * 32 / 16);
            const uint64_t dV = dV0 + (uint64_t)(t * 4 * 768 / 16);
#pragma unroll
            for (int m = 0; m < 2; m++) {
                float s[32];
                wg_fence();
                wgmma_rs_n64_z(s, qa[m][0], qa[m][1], qa[m][2], qa[m][3], dK);
                wg_commit();
                wg_wait<0>();
                fence_regs(s);
                uint32_t p[16];
#pragma unroll
                for (int i = 0; i < 16; i++) p[i] = is_mufu(i) ? exp_pair_mufu(s[2 * i], s[2 * i + 1]) : exp_pair_fma(s[2 * i], s[2 * i + 1], c3f);
                wg_fence();
#pragma unroll
                for (int kk = 0; kk < 4; kk++)
                    wgmma_rs_n24_tb(oacc[m], p[4 * kk], p[4 * kk + 1], p[4 * kk + 2], p[4 * kk + 3], dV + (uint64_t)(kk * 768 / 16));
                wg_commit();
            }
        }
        wg_wait<0>();
    } else {
        float mx[2][2] = {{-INFINITY, -INFINITY}, {-INFINITY, -INFINITY}};
#pragma unroll 1
        for (int t = 0; t < S_ / 64; t++) {
            if ((t & 3) == 0) mbar_wait(smem_u32(&bars[t >> 2]), 0);
            const uint64_t dK = dK0 + (uint64_t)(t * 64 * 32 / 16);
            const uint64_t dV = dV0 + (uint64_t)(t * 4 * 768 / 16);
#pragma unroll
            for (int m = 0; m < 2; m++) {
                float s[32];
                wg_fence();
                wgmma_rs_n64_z(s, qa[m][0], qa[m][1], qa[m][2], qa[m][3], dK);
                wg_commit();
                wg_wait<0>();
                fence_regs(s);
                fence_regs(oacc[m]);
                float r0 = mx[m][0], r1 = mx[m][1];
#pragma unroll
                for (int j = 0; j < 8; j++) {
                    r0 = fmaxf(r0, fmaxf(s[4 * j], s[4 * j + 1]));
                    r1 = fmaxf(r1, fmaxf(s[4 * j + 2], s[4 * j + 3]));
                }
                r0 = fmaxf(r0, __shfl_xor_sync(0xffffffffu, r0, 1)); r0 = fmaxf(r0, __shfl_xor_sync(0xffffffffu, r0, 2));
                r1 = fmaxf(r1, __shfl_xor_sync(0xffffffffu, r1, 1)); r1 = fmaxf(r1, __shfl_xor_sync(0xffffffffu, r1, 2));
                const float al0 = ex2(mx[m][0] - r0), al1 = ex2(mx[m][1] - r1);
                mx[m][0] = r0; mx[m][1] = r1;
#pragma unroll
                for (int j = 0; j < 3; j++) {
                    oacc[m][4 * j] *= al0; oacc[m][4 * j + 1] *= al0;
                    oacc[m][4 * j + 2] *= al1; oacc[m][4 * j + 3] *= al1;
                }
                uint32_t p[16];
#pragma unroll
                for (int j = 0; j < 8; j++) {
                    p[2 * j] = pack_bf16(ex2(s[4 * j] - r0), ex2(s[4 * j + 1] - r0));
                    p[2 * j + 1] = pack_bf16(ex2(s[4 * j + 2] - r1), ex2(s[4 * j + 3] - r1));
                }
                fence_regs(oacc[m]);
                wg_fence();
#pragma unroll
                for (int kk = 0; kk < 4; kk++)
                    wgmma_rs_n24_tb(oacc[m], p[4 * kk], p[4 * kk + 1], p[4 * kk + 2], p[4 * kk + 3], dV + (uint64_t)(kk * 768 / 16));
                wg_commit();
                wg_wait<0>();
            }
        }
    }
    fence_regs(oacc[0]); fence_regs(oacc[1]);
    if (tid == 0) TL(tk, 2);
#pragma unroll
    for (int m = 0; m < 2; m++) {
        const float l0 = __shfl_sync(0xffffffffu, oacc[m][8], lane & ~3);
        const float l1 = __shfl_sync(0xffffffffu, oacc[m][10], lane & ~3);
        const float r0 = __fdividef(1.0f, l0), r1 = __fdividef(1.0f, l1);
        const int row = tb * 128 + m * 64 + warp * 16 + g;
        uint32_t* p0 = (uint32_t*)(g_o + (size_t)row * D_ + head * 16);
        uint32_t* p1 = (uint32_t*)(g_o + (size_t)(row + 8) * D_ + head * 16);
        p0[c] = pack_bf16(oacc[m][0] * r0, oacc[m][1] * r0);
        p1[c] = pack_bf16(oacc[m][2] * r1, oacc[m][3] * r1);
        p0[c + 4] = pack_bf16(oacc[m][4] * r0, oacc[m][5] * r0);
        p1[c + 4] = pack_bf16(oacc[m][6] * r1, oacc[m][7] * r1);
    }
    if (tid == 0) TL(tk, 3);
}

typedef CUresult (*EncodeFn)(CUtensorMap*, CUtensorMapDataType, cuuint32_t, void*, const cuuint64_t*, const cuuint64_t*, const cuuint32_t*,
                             const cuuint32_t*, CUtensorMapInterleave, CUtensorMapSwizzle, CUtensorMapL2promotion, CUtensorMapFloatOOBfill);

EncodeFn get_encode() {
    static EncodeFn fn = nullptr;
    if (!fn) {
        void* p = nullptr;
        cudaDriverEntryPointQueryResult qr;
        cudaGetDriverEntryPoint("cuTensorMapEncodeTiled", &p, cudaEnableDefault, &qr);
        fn = (EncodeFn)p;
    }
    return fn;
}
CUtensorMap map2d(const void* ptr, uint64_t cols, uint64_t rows, uint32_t bc, uint32_t br, CUtensorMapSwizzle sw) {
    CUtensorMap m;
    cuuint64_t gd[2] = {cols, rows}, gs[1] = {cols * 2};
    cuuint32_t bx[2] = {bc, br}, es[2] = {1, 1};
    get_encode()(&m, CU_TENSOR_MAP_DATA_TYPE_BFLOAT16, 2, (void*)ptr, gd, gs, bx, es, CU_TENSOR_MAP_INTERLEAVE_NONE, sw,
                 CU_TENSOR_MAP_L2_PROMOTION_L2_128B, CU_TENSOR_MAP_FLOAT_OOB_FILL_NONE);
    return m;
}
CUtensorMap map3d64(const void* ptr, uint64_t cols, uint64_t rows, uint32_t br, uint32_t nb) {
    CUtensorMap m;
    cuuint64_t gd[3] = {64, rows, cols / 64}, gs[2] = {cols * 2, 128};
    cuuint32_t bx[3] = {64, br, nb}, es[3] = {1, 1, 1};
    get_encode()(&m, CU_TENSOR_MAP_DATA_TYPE_BFLOAT16, 3, (void*)ptr, gd, gs, bx, es, CU_TENSOR_MAP_INTERLEAVE_NONE, CU_TENSOR_MAP_SWIZZLE_128B,
                 CU_TENSOR_MAP_L2_PROMOTION_L2_128B, CU_TENSOR_MAP_FLOAT_OOB_FILL_NONE);
    return m;
}
CUtensorMap map3d32(const void* ptr, uint64_t cols, uint64_t rows, uint32_t br, uint32_t nb) {
    CUtensorMap m;
    cuuint64_t gd[3] = {32, rows, cols / 32}, gs[2] = {cols * 2, 64};
    cuuint32_t bx[3] = {32, br, nb}, es[3] = {1, 1, 1};
    get_encode()(&m, CU_TENSOR_MAP_DATA_TYPE_BFLOAT16, 3, (void*)ptr, gd, gs, bx, es, CU_TENSOR_MAP_INTERLEAVE_NONE, CU_TENSOR_MAP_SWIZZLE_64B,
                 CU_TENSOR_MAP_L2_PROMOTION_L2_128B, CU_TENSOR_MAP_FLOAT_OOB_FILL_NONE);
    return m;
}

template <typename... KArgs, typename... Args>
void launch(void (*kern)(KArgs...), int grid, int block, int smem, int cluster, bool pdl, Args... args) {
    cudaLaunchConfig_t cfg = {};
    cfg.gridDim = dim3(grid);
    cfg.blockDim = dim3(block);
    cfg.dynamicSmemBytes = smem;
    cfg.stream = cudaStreamPerThread;
    cudaLaunchAttribute at[2];
    int n = 0;
    if (cluster > 1) { at[n].id = cudaLaunchAttributeClusterDimension; at[n].val.clusterDim.x = cluster; at[n].val.clusterDim.y = 1; at[n].val.clusterDim.z = 1; n++; }
    if (pdl) { at[n].id = cudaLaunchAttributeProgrammaticStreamSerialization; at[n].val.programmaticStreamSerializationAllowed = 1; n++; }
    cfg.attrs = at;
    cfg.numAttrs = n;
    cudaLaunchKernelEx(&cfg, kern, KArgs(args)...);
}

template <typename T> void* sym(const T& s) { void* p = nullptr; cudaGetSymbolAddress(&p, s); return p; }

}

extern "C" void kernel_launch(void* const* d_in, const int* in_sizes, int n_in, void* d_out, int out_size) {
    const __nv_bfloat16* x = (const __nv_bfloat16*)d_in[0];
    const __nv_bfloat16* wq = (const __nv_bfloat16*)d_in[1];
    const __nv_bfloat16* wk = (const __nv_bfloat16*)d_in[2];
    const __nv_bfloat16* wv = (const __nv_bfloat16*)d_in[3];
    const __nv_bfloat16* wo = (const __nv_bfloat16*)d_in[4];
    const __nv_bfloat16* w1 = (const __nv_bfloat16*)d_in[6];
    const __nv_bfloat16* w2 = (const __nv_bfloat16*)d_in[7];

    constexpr int SM_QKV = GemmSmem<QKV_STAGES, EPI_QKV>::TOTAL, SM_QKV0 = GemmSmem<QKV_STAGES, EPI_QKV>::TOTAL_SELF;
    static_assert(SM_QKV0 <= 232448, "shared memory");
    constexpr int SM_WO = ResSmem<WO_STAGES>::TOTAL, SM_FFN2 = ResSmem<FFN2_STAGES>::TOTAL;
    static_assert(SM_WO > 116736 && SM_FFN2 > 116736, "one CTA per SM");
    constexpr int SM_FFN1 = GemmSmem<FFN1_STAGES, EPI_FFN1>::TOTAL;
    cudaFuncSetAttribute(qkv_kernel<false>, cudaFuncAttributeMaxDynamicSharedMemorySize, SM_QKV);
    cudaFuncSetAttribute(qkv_kernel<true>, cudaFuncAttributeMaxDynamicSharedMemorySize, SM_QKV0);
    cudaFuncSetAttribute(res_gemm_kernel<8, WO_STAGES>, cudaFuncAttributeMaxDynamicSharedMemorySize, SM_WO);
    cudaFuncSetAttribute(ffn1_kernel, cudaFuncAttributeMaxDynamicSharedMemorySize, SM_FFN1);
    cudaFuncSetAttribute(res_gemm_kernel<28, FFN2_STAGES>, cudaFuncAttributeMaxDynamicSharedMemorySize, SM_FFN2);
    cudaFuncSetAttribute(attn_kernel, cudaFuncAttributeMaxDynamicSharedMemorySize, ATT_SMEM);
    cudaFuncSetAttribute(qkv_kernel<false>, cudaFuncAttributePreferredSharedMemoryCarveout, 100);
    cudaFuncSetAttribute(qkv_kernel<true>, cudaFuncAttributePreferredSharedMemoryCarveout, 100);
    cudaFuncSetAttribute(res_gemm_kernel<8, WO_STAGES>, cudaFuncAttributePreferredSharedMemoryCarveout, 100);
    cudaFuncSetAttribute(ffn1_kernel, cudaFuncAttributePreferredSharedMemoryCarveout, 100);
    cudaFuncSetAttribute(res_gemm_kernel<28, FFN2_STAGES>, cudaFuncAttributePreferredSharedMemoryCarveout, 100);
    cudaFuncSetAttribute(attn_kernel, cudaFuncAttributePreferredSharedMemoryCarveout, 100);

    void *q = sym(g_q), *o = sym(g_o), *x1 = sym(g_x1), *x2 = sym(g_x2), *x3 = sym(g_x3), *h = sym(g_h);
    float2* stats = (float2*)sym(g_stats);
    const void* xs[5] = {x, x1, x2, x3, d_out};

    const CUtensorMapSwizzle SW128 = CU_TENSOR_MAP_SWIZZLE_128B, SW64 = CU_TENSOR_MAP_SWIZZLE_64B;
    const CUtensorMap mWq = map3d32(wq, D_, D_, 64, 2);
    const CUtensorMap mWo = map3d64(wo, D_, D_, 64, 2);
    const CUtensorMap mW1a = map3d32(w1, F_, D_, F1_BK, 4), mW1b = map3d32(w1, F_, D_, F1_BK, 3);
    const CUtensorMap mW2 = map3d64(w2, D_, F_, 64, 2);
    const CUtensorMap mQ = map2d(q, D_, S_, 64, 64, SW128);
    const CUtensorMap mHst = map2d(h, F_, S_, 32, 16, SW64);
    CUtensorMap mXa[4], mXf[4], mXr[4], mXs[5];
    for (int i = 0; i < 4; i++) {
        mXa[i] = map2d(xs[i], D_, S_, 64, QKV_MC ? 64 : 128, SW128);
        mXf[i] = F1_BK == 64 ? map2d(xs[i], D_, S_, 64, 128, SW128) : map2d(xs[i], D_, S_, 32, 128, SW64);
        mXr[i] = map3d64(xs[i], D_, S_, 64, 2);
    }
    for (int i = 0; i < 5; i++) mXs[i] = map2d(xs[i], D_, S_, 64, 64, SW128);
    const CUtensorMap mOa = map2d(o, D_, S_, 64, 64, SW128);
    const CUtensorMap mHa = map2d(h, F_, S_, 64, 64, SW128);

    for (int layer = 0; layer < 2; layer++) {
        const int xi = layer * 2;
        GemmParams p;
        p.wkv = wk; p.wv = wv;
        p.stats_in = stats + (size_t)xi * 8 * S_; p.stats_out = nullptr; p.tk = 1 + 5 * layer;
        if (layer == 0) launch(qkv_kernel<true>, 128, 544, SM_QKV0, QKV_MC ? 2 : 1, false, mXa[xi], mWq, mQ, p);
        else launch(qkv_kernel<false>, 128, 288, SM_QKV, QKV_MC ? 2 : 1, true, mXa[xi], mWq, mQ, p);
        launch(attn_kernel, layer == 0 ? 128 + SIDE_CTAS : 128, 512, ATT_SMEM, 1, true, wo, w1, w2, 2 + 5 * layer);
        p.stats_in = nullptr; p.stats_out = stats + (size_t)(xi + 1) * 8 * S_; p.tk = 3 + 5 * layer;
        launch(res_gemm_kernel<8, WO_STAGES>, 128, 288, SM_WO, 1, true, mOa, mWo, mXr[xi], mXs[xi + 1], p);
        p.stats_in = stats + (size_t)(xi + 1) * 8 * S_; p.stats_out = nullptr; p.tk = 4 + 5 * layer;
        launch(ffn1_kernel, 128, F1_INLINE ? 256 : 288, SM_FFN1, F1_MC ? 2 : 1, true, mXf[xi + 1], mW1a, mW1b, mHst, p);
        p.stats_in = nullptr; p.stats_out = layer == 0 ? stats + (size_t)2 * 8 * S_ : nullptr; p.tk = 5 + 5 * layer;
        launch(res_gemm_kernel<28, FFN2_STAGES>, 128, 288, SM_FFN2, 1, true, mHa, mW2, mXr[xi + 1], mXs[xi + 2], p);
    }
}
```

```cpp
#include <cuda_runtime.h>
#include <cuda_bf16.h>
#include <cuda.h>
#include <stdint.h>

#define F1_INLINE 0
#define QKV_MC 0
#define WO_MC 0
#define F2_MC 0
#define F1_MC 2
#define SELF_WAIT 1
#define ATT_VAR 1
#define PREB 1
#define RES_WAIT0 0

namespace {

constexpr int S_ = 2048, D_ = 512, H_ = 32, F_ = 1792;

__device__ __align__(1024) __nv_bfloat16 g_q[S_ * D_];
__device__ __align__(1024) __nv_bfloat16 g_o[S_ * D_];
__device__ __align__(1024) __nv_bfloat16 g_x1[S_ * D_];
__device__ __align__(1024) __nv_bfloat16 g_x2[S_ * D_];
__device__ __align__(1024) __nv_bfloat16 g_x3[S_ * D_];
__device__ __align__(1024) __nv_bfloat16 g_h[S_ * F_];
__device__ __align__(1024) uint8_t g_kimg[S_ * 32];
__device__ __align__(1024) uint8_t g_vimg[(S_ / 16) * 768];
__device__ __align__(1024) float2 g_stats[4][8 * S_];
__device__ __align__(16) float g_cs_q[D_];
__device__ __align__(16) float g_cs_kv[32];
__device__ __align__(16) float g_cs_1[F_];
__device__ __align__(16) float g_kvmax[32];

#define TL(k, slot)
#define CK(k, i)

__device__ __forceinline__ uint32_t smem_u32(const void* p) { return (uint32_t)__cvta_generic_to_shared(p); }
__device__ __forceinline__ void mbar_init(uint32_t bar, uint32_t cnt) {
    asm volatile("mbarrier.init.shared::cta.b64 [%0], %1;" ::"r"(bar), "r"(cnt));
}
__device__ __forceinline__ void mbar_expect_tx(uint32_t bar, uint32_t bytes) {
    asm volatile("mbarrier.arrive.expect_tx.shared::cta.b64 _, [%0], %1;" ::"r"(bar), "r"(bytes) : "memory");
}
__device__ __forceinline__ void mbar_arrive(uint32_t bar) {
    asm volatile("mbarrier.arrive.shared::cta.b64 _, [%0];" ::"r"(bar) : "memory");
}
__device__ __forceinline__ void mbar_arrive_remote(uint32_t bar, uint32_t cta) {
    asm volatile("{\n.reg .b32 ra;\nmapa.shared::cluster.u32 ra, %0, %1;\nmbarrier.arrive.shared::cluster.b64 _, [ra];\n}" ::"r"(bar), "r"(cta) : "memory");
}
__device__ __forceinline__ void mbar_wait(uint32_t bar, uint32_t parity) {
    asm volatile("{\n.reg .pred p;\nWAIT_%=:\nmbarrier.try_wait.parity.shared::cta.b64 p, [%0], %1;\n@p bra DONE_%=;\nbra WAIT_%=;\nDONE_%=:\n}" ::"r"(bar), "r"(parity) : "memory");
}
__device__ __forceinline__ void bulk_load(uint32_t dst, const void* src, uint32_t bytes, uint32_t bar) {
    asm volatile("cp.async.bulk.shared::cluster.global.mbarrier::complete_tx::bytes [%0], [%1], %2, [%3];" ::"r"(dst), "l"(src), "r"(bytes), "r"(bar) : "memory");
}
__device__ __forceinline__ void tma2d(uint32_t dst, const CUtensorMap* m, int c0, int c1, uint32_t bar) {
    asm volatile("cp.async.bulk.tensor.2d.shared::cluster.global.mbarrier::complete_tx::bytes [%0], [%1, {%3, %4}], [%2];" ::"r"(dst), "l"(m), "r"(bar), "r"(c0), "r"(c1) : "memory");
}
__device__ __forceinline__ void tma2d_mc(uint32_t dst, const CUtensorMap* m, int c0, int c1, uint32_t bar, uint16_t mask) {
    asm volatile("cp.async.bulk.tensor.2d.shared::cluster.global.mbarrier::complete_tx::bytes.multicast::cluster [%0], [%1, {%3, %4}], [%2], %5;" ::"r"(dst), "l"(m), "r"(bar), "r"(c0), "r"(c1), "h"(mask) : "memory");
}
__device__ __forceinline__ void tma3d(uint32_t dst, const CUtensorMap* m, int c0, int c1, int c2, uint32_t bar) {
    asm volatile("cp.async.bulk.tensor.3d.shared::cluster.global.mbarrier::complete_tx::bytes [%0], [%1, {%3, %4, %5}], [%2];" ::"r"(dst), "l"(m), "r"(bar), "r"(c0), "r"(c1), "r"(c2) : "memory");
}
__device__ __forceinline__ void tma3d_mc(uint32_t dst, const CUtensorMap* m, int c0, int c1, int c2, uint32_t bar, uint16_t mask) {
    asm volatile("cp.async.bulk.tensor.3d.shared::cluster.global.mbarrier::complete_tx::bytes.multicast::cluster [%0], [%1, {%3, %4, %5}], [%2], %6;" ::"r"(dst), "l"(m), "r"(bar), "r"(c0), "r"(c1), "r"(c2), "h"(mask) : "memory");
}
__device__ __forceinline__ void tma2d_store(const CUtensorMap* m, uint32_t src, int c0, int c1) {
    asm volatile("cp.async.bulk.tensor.2d.global.shared::cta.bulk_group [%0, {%2, %3}], [%1];" ::"l"(m), "r"(src), "r"(c0), "r"(c1) : "memory");
}
__device__ __forceinline__ void tma3d_store(const CUtensorMap* m, uint32_t src, int c0, int c1, int c2) {
    asm volatile("cp.async.bulk.tensor.3d.global.shared::cta.bulk_group [%0, {%2, %3, %4}], [%1];" ::"l"(m), "r"(src), "r"(c0), "r"(c1), "r"(c2) : "memory");
}
__device__ __forceinline__ void bulk_commit() { asm volatile("cp.async.bulk.commit_group;" ::: "memory"); }
__device__ __forceinline__ void bulk_wait_read() { asm volatile("cp.async.bulk.wait_group.read 0;" ::: "memory"); }
__device__ __forceinline__ void prefetch_tmap(const CUtensorMap* m) { asm volatile("prefetch.tensormap [%0];" ::"l"(m) : "memory"); }
__device__ __forceinline__ void fence_async_smem() { asm volatile("fence.proxy.async.shared::cta;" ::: "memory"); }
__device__ __forceinline__ void fence_mbar_init() { asm volatile("fence.mbarrier_init.release.cluster;" ::: "memory"); }
__device__ __forceinline__ void cluster_sync() { asm volatile("barrier.cluster.arrive.release.aligned;\nbarrier.cluster.wait.acquire.aligned;" ::: "memory"); }
__device__ __forceinline__ uint32_t cluster_rank() { uint32_t r; asm volatile("mov.u32 %0, %%cluster_ctarank;" : "=r"(r)); return r; }
__device__ __forceinline__ void pdl_wait() { asm volatile("griddepcontrol.wait;" ::: "memory"); }
__device__ __forceinline__ void pdl_launch() { asm volatile("griddepcontrol.launch_dependents;" ::: "memory"); }
__device__ __forceinline__ bool elect_one() {
    uint32_t p;
    asm volatile("{\n.reg .pred p;\nelect.sync _|p, 0xffffffff;\nselp.b32 %0, 1, 0, p;\n}" : "=r"(p));
    return p != 0;
}
__device__ __forceinline__ void named_bar(int id, int n) { asm volatile("bar.sync %0, %1;" ::"r"(id), "r"(n) : "memory"); }

__device__ __forceinline__ void wg_fence() { asm volatile("wgmma.fence.sync.aligned;" ::: "memory"); }
__device__ __forceinline__ void wg_commit() { asm volatile("wgmma.commit_group.sync.aligned;" ::: "memory"); }
template <int N> __device__ __forceinline__ void wg_wait() { asm volatile("wgmma.wait_group.sync.aligned %0;" ::"n"(N) : "memory"); }
template <int N> __device__ __forceinline__ void fence_regs(float (&d)[N]) {
#pragma unroll
    for (int i = 0; i < N; i++) asm volatile("" : "+f"(d[i])::"memory");
}
__device__ __forceinline__ uint64_t mkdesc(uint32_t addr, uint32_t lbo, uint32_t sbo, uint32_t swz) {
    uint64_t d = 0;
    d |= (uint64_t)((addr & 0x3FFFF) >> 4);
    d |= (uint64_t)((lbo & 0x3FFFF) >> 4) << 16;
    d |= (uint64_t)((sbo & 0x3FFFF) >> 4) << 32;
    d |= (uint64_t)swz << 62;
    return d;
}
__device__ __forceinline__ void ldsm_x4(uint32_t& r0, uint32_t& r1, uint32_t& r2, uint32_t& r3, uint32_t addr) {
    asm volatile("ldmatrix.sync.aligned.m8n8.x4.shared.b16 {%0,%1,%2,%3}, [%4];" : "=r"(r0), "=r"(r1), "=r"(r2), "=r"(r3) : "r"(addr) : "memory");
}
__device__ __forceinline__ void stsm_x4(uint32_t addr, uint32_t r0, uint32_t r1, uint32_t r2, uint32_t r3) {
    asm volatile("stmatrix.sync.aligned.m8n8.x4.shared.b16 [%0], {%1,%2,%3,%4};" ::"r"(addr), "r"(r0), "r"(r1), "r"(r2), "r"(r3) : "memory");
}
__device__ __forceinline__ void ldsm_x4_t(uint32_t& r0, uint32_t& r1, uint32_t& r2, uint32_t& r3, uint32_t addr) {
    asm volatile("ldmatrix.sync.aligned.m8n8.x4.trans.shared.b16 {%0,%1,%2,%3}, [%4];" : "=r"(r0), "=r"(r1), "=r"(r2), "=r"(r3) : "r"(addr) : "memory");
}
__device__ __forceinline__ void hmma(float (&d)[4], uint32_t a0, uint32_t a1, uint32_t a2, uint32_t a3, uint32_t b0, uint32_t b1) {
    asm volatile("mma.sync.aligned.m16n8k16.row.col.f32.bf16.bf16.f32 {%0,%1,%2,%3}, {%4,%5,%6,%7}, {%8,%9}, {%0,%1,%2,%3};"
                 : "+f"(d[0]), "+f"(d[1]), "+f"(d[2]), "+f"(d[3]) : "r"(a0), "r"(a1), "r"(a2), "r"(a3), "r"(b0), "r"(b1));
}
__device__ __forceinline__ uint32_t pack_bf16(float lo, float hi) {
    uint32_t r;
    asm("cvt.rn.bf16x2.f32 %0, %1, %2;" : "=r"(r) : "f"(hi), "f"(lo));
    return r;
}
__device__ __forceinline__ float bf_lo(uint32_t v) { return __uint_as_float(v << 16); }
__device__ __forceinline__ float bf_hi(uint32_t v) { return __uint_as_float(v & 0xFFFF0000u); }

#define WG_REGS_4(o) "+f"(d[o]), "+f"(d[o + 1]), "+f"(d[o + 2]), "+f"(d[o + 3])
#define WG_REGS_8(o) WG_REGS_4(o), WG_REGS_4(o + 4)
#define WG_REGS_16(o) WG_REGS_8(o), WG_REGS_8(o + 8)
#define WG_REGS_32(o) WG_REGS_16(o), WG_REGS_16(o + 16)

__device__ __forceinline__ void wgmma_ss_n80_tb(float (&d)[40], uint64_t dA, uint64_t dB, int sc) {
    asm volatile("{\n.reg .pred p;\nsetp.ne.b32 p, %42, 0;\n"
                 "wgmma.mma_async.sync.aligned.m64n80k16.f32.bf16.bf16 "
                 "{%0,%1,%2,%3,%4,%5,%6,%7,%8,%9,%10,%11,%12,%13,%14,%15,%16,%17,%18,%19,%20,%21,%22,%23,%24,%25,%26,%27,%28,%29,%30,%31,"
                 "%32,%33,%34,%35,%36,%37,%38,%39}, %40, %41, p, 1, 1, 0, 1;\n}\n"
                 : WG_REGS_32(0), WG_REGS_8(32) : "l"(dA), "l"(dB), "r"(sc));
}
__device__ __forceinline__ void wgmma_ss_n64_tb(float (&d)[32], uint64_t dA, uint64_t dB, int sc) {
    asm volatile("{\n.reg .pred p;\nsetp.ne.b32 p, %34, 0;\n"
                 "wgmma.mma_async.sync.aligned.m64n64k16.f32.bf16.bf16 "
                 "{%0,%1,%2,%3,%4,%5,%6,%7,%8,%9,%10,%11,%12,%13,%14,%15,%16,%17,%18,%19,%20,%21,%22,%23,%24,%25,%26,%27,%28,%29,%30,%31}, "
                 "%32, %33, p, 1, 1, 0, 1;\n}\n"
                 : WG_REGS_32(0) : "l"(dA), "l"(dB), "r"(sc));
}
__device__ __forceinline__ void wgmma_ss_n224_tb(float (&d)[112], uint64_t dA, uint64_t dB, int sc) {
    asm volatile("{\n.reg .pred p;\nsetp.ne.b32 p, %114, 0;\n"
                 "wgmma.mma_async.sync.aligned.m64n224k16.f32.bf16.bf16 "
                 "{%0,%1,%2,%3,%4,%5,%6,%7,%8,%9,%10,%11,%12,%13,%14,%15,%16,%17,%18,%19,%20,%21,%22,%23,%24,%25,%26,%27,%28,%29,%30,%31,"
                 "%32,%33,%34,%35,%36,%37,%38,%39,%40,%41,%42,%43,%44,%45,%46,%47,%48,%49,%50,%51,%52,%53,%54,%55,%56,%57,%58,%59,%60,%61,%62,%63,"
                 "%64,%65,%66,%67,%68,%69,%70,%71,%72,%73,%74,%75,%76,%77,%78,%79,%80,%81,%82,%83,%84,%85,%86,%87,%88,%89,%90,%91,%92,%93,%94,%95,"
                 "%96,%97,%98,%99,%100,%101,%102,%103,%104,%105,%106,%107,%108,%109,%110,%111}, "
                 "%112, %113, p, 1, 1, 0, 1;\n}\n"
                 : WG_REGS_32(0), WG_REGS_32(32), WG_REGS_32(64), WG_REGS_16(96) : "l"(dA), "l"(dB), "r"(sc));
}
template <int BN> __device__ __forceinline__ void wgmma_ss_tb(float (&d)[BN / 2], uint64_t dA, uint64_t dB, int sc) {
    if constexpr (BN == 64) wgmma_ss_n64_tb(d, dA, dB, sc);
    else if constexpr (BN == 80) wgmma_ss_n80_tb(d, dA, dB, sc);
    else wgmma_ss_n224_tb(d, dA, dB, sc);
}
__device__ __forceinline__ void wgmma_rs_n64_tb(float (&d)[32], uint32_t a, uint64_t dB, int sc) {
    asm volatile("{\n.reg .pred p;\nsetp.ne.b32 p, %34, 0;\n"
                 "wgmma.mma_async.sync.aligned.m64n64k16.f32.bf16.bf16 "
                 "{%0,%1,%2,%3,%4,%5,%6,%7,%8,%9,%10,%11,%12,%13,%14,%15,%16,%17,%18,%19,%20,%21,%22,%23,%24,%25,%26,%27,%28,%29,%30,%31}, "
                 "{%32,%32,%32,%32}, %33, p, 1, 1, 1;\n}\n"
                 : WG_REGS_32(0) : "r"(a), "l"(dB), "r"(sc));
}
__device__ __forceinline__ void wgmma_rs_n80_tb(float (&d)[40], uint32_t a, uint64_t dB, int sc) {
    asm volatile("{\n.reg .pred p;\nsetp.ne.b32 p, %42, 0;\n"
                 "wgmma.mma_async.sync.aligned.m64n80k16.f32.bf16.bf16 "
                 "{%0,%1,%2,%3,%4,%5,%6,%7,%8,%9,%10,%11,%12,%13,%14,%15,%16,%17,%18,%19,%20,%21,%22,%23,%24,%25,%26,%27,%28,%29,%30,%31,"
                 "%32,%33,%34,%35,%36,%37,%38,%39}, {%40,%40,%40,%40}, %41, p, 1, 1, 1;\n}\n"
                 : WG_REGS_32(0), WG_REGS_8(32) : "r"(a), "l"(dB), "r"(sc));
}
template <int BN> __device__ __forceinline__ void wgmma_rs_ones(float (&d)[BN / 2], uint64_t dB, int sc) {
    if constexpr (BN == 80) wgmma_rs_n80_tb(d, 0x3F803F80u, dB, sc);
    else if constexpr (BN == 64) wgmma_rs_n64_tb(d, 0x3F803F80u, dB, sc);
}
__device__ __forceinline__ void wgmma_rs_n64_z(float (&d)[32], uint32_t a0, uint32_t a1, uint32_t a2, uint32_t a3, uint64_t dB) {
    asm volatile("{\n.reg .pred p;\nsetp.ne.b32 p, 0, 0;\n"
                 "wgmma.mma_async.sync.aligned.m64n64k16.f32.bf16.bf16 "
                 "{%0,%1,%2,%3,%4,%5,%6,%7,%8,%9,%10,%11,%12,%13,%14,%15,%16,%17,%18,%19,%20,%21,%22,%23,%24,%25,%26,%27,%28,%29,%30,%31}, "
                 "{%32,%33,%34,%35}, %36, p, 1, 1, 0;\n}\n"
                 : "=f"(d[0]), "=f"(d[1]), "=f"(d[2]), "=f"(d[3]), "=f"(d[4]), "=f"(d[5]), "=f"(d[6]), "=f"(d[7]),
                   "=f"(d[8]), "=f"(d[9]), "=f"(d[10]), "=f"(d[11]), "=f"(d[12]), "=f"(d[13]), "=f"(d[14]), "=f"(d[15]),
                   "=f"(d[16]), "=f"(d[17]), "=f"(d[18]), "=f"(d[19]), "=f"(d[20]), "=f"(d[21]), "=f"(d[22]), "=f"(d[23]),
                   "=f"(d[24]), "=f"(d[25]), "=f"(d[26]), "=f"(d[27]), "=f"(d[28]), "=f"(d[29]), "=f"(d[30]), "=f"(d[31])
                 : "r"(a0), "r"(a1), "r"(a2), "r"(a3), "l"(dB));
}
__device__ __forceinline__ void wgmma_rs_n24_tb(float (&d)[12], uint32_t a0, uint32_t a1, uint32_t a2, uint32_t a3, uint64_t dB) {
    asm volatile("{\n.reg .pred p;\nsetp.eq.b32 p, 0, 0;\n"
                 "wgmma.mma_async.sync.aligned.m64n24k16.f32.bf16.bf16 "
                 "{%0,%1,%2,%3,%4,%5,%6,%7,%8,%9,%10,%11}, {%12,%13,%14,%15}, %16, p, 1, 1, 1;\n}\n"
                 : WG_REGS_8(0), WG_REGS_4(8) : "r"(a0), "r"(a1), "r"(a2), "r"(a3), "l"(dB));
}

constexpr int SIDE_CTAS = 4;
__device__ __forceinline__ void side_job(int cta, float* red  , const __nv_bfloat16* __restrict__ wo,
                                         const __nv_bfloat16* __restrict__ w1, const __nv_bfloat16* __restrict__ w2) {
    const int tid = threadIdx.x, warp = tid >> 5, lane = tid & 31;
    for (int line = cta * 512 + tid; line < 18432; line += SIDE_CTAS * 512) {
        const char* p = line < 4096 ? (const char*)wo + (size_t)line * 128 : (const char*)w2 + (size_t)(line - 4096) * 128;
        asm volatile("prefetch.global.L2 [%0];" ::"l"(p));
    }
    const int rg = lane >> 3, c8 = lane & 7;
    for (int slab = cta; slab < F_ / 64; slab += SIDE_CTAS) {
        const __nv_bfloat16* base = w1 + slab * 64 + c8 * 8;
        uint4 v[8];
#pragma unroll
        for (int i = 0; i < 8; i++) v[i] = __ldg((const uint4*)(base + (size_t)(warp * 32 + rg + 4 * i) * F_));
        float acc[8];
#pragma unroll
        for (int i = 0; i < 8; i++) acc[i] = 0.f;
#pragma unroll
        for (int i = 0; i < 8; i++) {
            acc[0] += bf_lo(v[i].x); acc[1] += bf_hi(v[i].x); acc[2] += bf_lo(v[i].y); acc[3] += bf_hi(v[i].y);
            acc[4] += bf_lo(v[i].z); acc[5] += bf_hi(v[i].z); acc[6] += bf_lo(v[i].w); acc[7] += bf_hi(v[i].w);
        }
#pragma unroll
        for (int i = 0; i < 8; i++) {
            acc[i] += __shfl_xor_sync(0xffffffffu, acc[i], 8);
            acc[i] += __shfl_xor_sync(0xffffffffu, acc[i], 16);
        }
        if (rg == 0) {
#pragma unroll
            for (int i = 0; i < 8; i++) red[warp * 64 + c8 * 8 + i] = acc[i];
        }
        __syncthreads();
        if (tid < 64) {
            float s = 0.f;
#pragma unroll
            for (int i = 0; i < 16; i++) s += red[i * 64 + tid];
            g_cs_1[slab * 64 + tid] = s;
        }
        __syncthreads();
    }
}

enum { EPI_QKV = 0, EPI_RES = 1, EPI_FFN1 = 2 };

struct GemmParams {
    const float2* stats_in;
    float2* stats_out;
    const __nv_bfloat16* wkv;
    const __nv_bfloat16* wv;
    int tk;
};

template <int BK_, int NBLK> struct Geo {
    static constexpr int BK = BK_, A_BYTES = 128 * BK * 2, A_SWZ = BK == 64 ? 1 : 2, A_SBO = BK * 16;
    static constexpr int BLK = BK * 64;
    static constexpr int B_BYTES = NBLK * BLK, B_SWZ = 2, B_LBO = BLK, B_SBO = 512, B_KSTEP = 1024;
};
template <> struct Geo<64, 0> {
    static constexpr int BK = 64, A_BYTES = 128 * 128, A_SWZ = 1, A_SBO = 1024, BLK = 8192;
    static constexpr int B_BYTES = 64 * 128, B_SWZ = 1, B_LBO = 8192, B_SBO = 1024, B_KSTEP = 2048;
};
#define F1_BK 32
template <int EPI> struct EpiGeo;
template <> struct EpiGeo<EPI_QKV> { using G = Geo<64, 3>; };
template <> struct EpiGeo<EPI_RES> { using G = Geo<64, 0>; };
template <> struct EpiGeo<EPI_FFN1> { using G = Geo<F1_BK, 7>; };

template <int STAGES, int EPI> struct GemmSmem {
    using G = typename EpiGeo<EPI>::G;
    static constexpr int STAGE = G::A_BYTES + G::B_BYTES;
    static constexpr int AUX_OFF = STAGES * STAGE;
    static constexpr int TOTAL = AUX_OFF + 1152;
    static constexpr int TOTAL_SELF = AUX_OFF + 704 + 1024 + 1280;
};

struct RowStatRaw { float2 a0, a1, b0, b1; };
__device__ __forceinline__ RowStatRaw load_row_stats(const float2* __restrict__ st, int row0, int c) {
    RowStatRaw r;
    r.a0 = st[(2 * c) * S_ + row0]; r.a1 = st[(2 * c + 1) * S_ + row0];
    r.b0 = st[(2 * c) * S_ + row0 + 8]; r.b1 = st[(2 * c + 1) * S_ + row0 + 8];
    return r;
}
__device__ __forceinline__ void finish_row_stats(const RowStatRaw& r, float& mean0, float& rstd0, float& mean1, float& rstd1) {
    float sa = r.a0.x + r.a1.x, sb = r.b0.x + r.b1.x;
    sa += __shfl_xor_sync(0xffffffffu, sa, 1); sa += __shfl_xor_sync(0xffffffffu, sa, 2);
    sb += __shfl_xor_sync(0xffffffffu, sb, 1); sb += __shfl_xor_sync(0xffffffffu, sb, 2);
    mean0 = sa * 0.125f; mean1 = sb * 0.125f;
    float ma = r.a0.y + r.a1.y + 64.f * ((r.a0.x - mean0) * (r.a0.x - mean0) + (r.a1.x - mean0) * (r.a1.x - mean0));
    float mb = r.b0.y + r.b1.y + 64.f * ((r.b0.x - mean1) * (r.b0.x - mean1) + (r.b1.x - mean1) * (r.b1.x - mean1));
    ma += __shfl_xor_sync(0xffffffffu, ma, 1); ma += __shfl_xor_sync(0xffffffffu, ma, 2);
    mb += __shfl_xor_sync(0xffffffffu, mb, 1); mb += __shfl_xor_sync(0xffffffffu, mb, 2);
    rstd0 = 1.0f / sqrtf(ma * (1.f / 512.f) + 1e-5f);
    rstd1 = 1.0f / sqrtf(mb * (1.f / 512.f) + 1e-5f);
}

template <int BN, int KB, int STAGES, int EPI, int MC, bool SELF = false>
__device__ __forceinline__ void gemm_body(const CUtensorMap* mapA, const CUtensorMap* mapB, const CUtensorMap* mapB2, const CUtensorMap* mapR,
                                          const CUtensorMap* mapC, const GemmParams& prm, int tile_m, int tile_n, uint8_t* smem_raw) {
    using SM = GemmSmem<STAGES, EPI>;
    using G = typename SM::G;
    constexpr bool XKV = BN == 80;
    constexpr int TN = EPI == EPI_QKV ? 64 : BN;
    pdl_launch();
    const uint32_t sbase = smem_u32(smem_raw);
    if (sbase & 1023) __trap();
    uint8_t* sgen = smem_raw;
    const uint32_t bar_full = sbase + SM::AUX_OFF, bar_empty = bar_full + 8 * STAGES;
    float* s_cs = (float*)(sgen + SM::AUX_OFF + 256);
    float* s_row = (float*)(sgen + SM::AUX_OFF + 704);
    float* s_red = (float*)(sgen + SM::AUX_OFF + 640);
    const int tid = threadIdx.x, lane = tid & 31;
    const int warp = __shfl_sync(0xffffffffu, tid >> 5, 0);
    const uint32_t rank = MC ? cluster_rank() : 0;
    if (tid == 0) TL(prm.tk, 0);

    constexpr bool INLINE_PROD = EPI == EPI_FFN1 && F1_INLINE;
    constexpr int PWARP = INLINE_PROD ? 0 : 8;
    if (warp == PWARP && elect_one()) {
        prefetch_tmap(mapB); prefetch_tmap(mapA); prefetch_tmap(mapC);
        for (int s = 0; s < STAGES; s++) { mbar_init(bar_full + 8 * s, 1); mbar_init(bar_empty + 8 * s, MC ? 4 : 2); }
        fence_mbar_init();
    }
    __syncthreads();
    if (MC) asm volatile("barrier.cluster.arrive.release.aligned;" ::: "memory");
    auto cluster_wait = [&]() { if (MC) asm volatile("barrier.cluster.wait.acquire.aligned;" ::: "memory"); };

    const int m0 = tile_m * 128, n0 = tile_n * TN;
    constexpr uint32_t STAGE_TX = G::A_BYTES + (EPI == EPI_QKV ? 2 * G::BLK : G::B_BYTES);
    auto loadB = [&](int kb, int s) {
        const uint32_t dst = sbase + s * SM::STAGE + G::A_BYTES, bar = bar_full + 8 * s;
        if constexpr (EPI == EPI_RES) {
            tma2d(dst, mapB, n0, kb * 64, bar);
        } else if constexpr (EPI == EPI_QKV) {
            tma3d(dst, mapB, 0, kb * G::BK, tile_n * 2, bar);
        } else {
            if constexpr (MC == 2) {
                if (rank == 0) tma3d_mc(dst, mapB, 0, kb * G::BK, tile_n * 7, bar, 3);
                else tma3d_mc(dst + 4 * G::BLK, mapB2, 0, kb * G::BK, tile_n * 7 + 4, bar, 3);
            } else {
                tma3d(dst, mapB, 0, kb * G::BK, tile_n * 7, bar);
                tma3d(dst + 4 * G::BLK, mapB2, 0, kb * G::BK, tile_n * 7 + 4, bar);
            }
        }
    };
    auto loadA = [&](int kb, int s) {
        const uint32_t dst = sbase + s * SM::STAGE, bar = bar_full + 8 * s;
        if constexpr (MC == 1) tma2d_mc(dst + rank * (G::A_BYTES / 2), mapA, kb * G::BK, m0 + rank * 64, bar, 3);
        else tma2d(dst, mapA, kb * G::BK, m0, bar);
    };
    constexpr int PRE = STAGES < KB ? STAGES : KB;
#define F1_LAG 2
    constexpr int LAG = F1_LAG;
    constexpr int PRE_B = PRE < PREB ? PRE : PREB;
    auto prologue_loads = [&]() {
        if (elect_one()) {
#pragma unroll
            for (int kb = 0; kb < PRE; kb++) mbar_expect_tx(bar_full + 8 * kb, STAGE_TX);
        }
        cluster_wait();
        if (elect_one()) {
#pragma unroll
            for (int kb = 0; kb < PRE_B; kb++) loadB(kb, kb);
        }
        if (!SELF) pdl_wait();
        if (elect_one()) {
#pragma unroll
            for (int kb = 0; kb < PRE; kb++) {
                loadA(kb, kb);
                if (kb + PRE_B < PRE) loadB(kb + PRE_B, kb + PRE_B);
            }
            if constexpr (EPI == EPI_RES && KB < STAGES) {
                mbar_expect_tx(bar_full + 8 * KB, 16384);
                tma2d(sbase + KB * SM::STAGE, mapR, n0, m0, bar_full + 8 * KB);
            }
        }
    };
    if (SELF && warp > 8) {
        static_assert(!SELF || (STAGES >= KB && EPI == EPI_QKV), "SELF needs every k block resident");
        const int t = tid - 288;
        float ss[4] = {0.f, 0.f, 0.f, 0.f}, sq[4] = {0.f, 0.f, 0.f, 0.f};
        auto row_stats = [&](int kb) {
            const uint32_t arow = sbase + kb * SM::STAGE + (t >> 1) * 128;
            uint32_t w[4][4];
#pragma unroll
            for (int j = 0; j < 4; j++)
                asm volatile("ld.shared.v4.u32 {%0,%1,%2,%3}, [%4];" : "=r"(w[j][0]), "=r"(w[j][1]), "=r"(w[j][2]), "=r"(w[j][3])
                             : "r"(arow + (((2 * j + (t & 1) + 2 * ((t >> 1) & 3)) & 7) << 4)));
#pragma unroll
            for (int j = 0; j < 4; j++)
#pragma unroll
                for (int i = 0; i < 4; i++) {
                    const float lo = bf_lo(w[j][i]), hi = bf_hi(w[j][i]);
                    ss[i] += lo + hi;
                    sq[i] = fmaf(lo, lo, fmaf(hi, hi, sq[i]));
                }
        };
        if ((warp >> 2) == 3) {
            float csum[BN / 2];
            const uint64_t dB0 = mkdesc(sbase + G::A_BYTES, G::B_LBO, G::B_SBO, G::B_SWZ);
            if constexpr (XKV) named_bar(6, 512);
#pragma unroll 1
            for (int kb = 0; kb < KB; kb++) {
                mbar_wait(bar_full + 8 * kb, 0);
                const uint64_t dB = dB0 + (uint64_t)(kb * (SM::STAGE >> 4));
                wg_fence();
#pragma unroll
                for (int k = 0; k < G::BK / 16; k++) {
                    if constexpr (SELF) wgmma_rs_ones<BN>(csum, dB + (uint64_t)(k * (G::B_KSTEP >> 4)), (kb | k) != 0);
                }
                wg_commit();
                wg_wait<0>();
                row_stats(kb);
            }
            wg_wait<0>();
            fence_regs(csum);
            if (warp == 12 && lane < 4) {
#pragma unroll
                for (int j = 0; j < BN / 8; j++) {
                    const float2 v = make_float2(csum[4 * j], csum[4 * j + 1]);
                    *(float2*)(s_cs + 8 * j + 2 * lane) = v;
                    if (tile_m == 0) {
                        if (j < 8) *(float2*)(g_cs_q + n0 + 8 * j + 2 * lane) = v;
                        else *(float2*)(g_cs_kv + tile_n * 16 + 8 * (j - 8) + 2 * lane) = v;
                    }
                }
            }
        } else {
            if constexpr (XKV) named_bar(6, 512);
#pragma unroll 1
            for (int kb = 0; kb < KB; kb++) {
                mbar_wait(bar_full + 8 * kb, 0);
                row_stats(kb);
            }
        }
        float tsum = (ss[0] + ss[1]) + (ss[2] + ss[3]), tsq = (sq[0] + sq[1]) + (sq[2] + sq[3]);
        tsum += __shfl_xor_sync(0xffffffffu, tsum, 1);
        tsq += __shfl_xor_sync(0xffffffffu, tsq, 1);
        if ((t & 1) == 0) {
            const float md = tsum * (1.f / 512.f);
            const float var = fmaxf(tsq * (1.f / 512.f) - md * md, 0.f);
            *(float2*)(s_row + t) = make_float2(md, 1.0f / sqrtf(var + 1e-5f));
        }
        named_bar(4, 512);
    } else if (!INLINE_PROD && warp == 8) {
        prologue_loads();
        int s = PRE % STAGES, ph = (PRE / STAGES) & 1;
#pragma unroll 1
        for (int kb = PRE; kb < KB; kb++) {
            mbar_wait(bar_empty + 8 * s, ph ^ 1);
            if (elect_one()) {
                mbar_expect_tx(bar_full + 8 * s, STAGE_TX);
                loadB(kb, s);
                loadA(kb, s);
            }
            if (++s == STAGES) { s = 0; ph ^= 1; }
        }
        if constexpr (EPI == EPI_RES && KB >= STAGES) {
            mbar_wait(bar_empty + 8 * s, ph ^ 1);
            if (elect_one()) {
                mbar_expect_tx(bar_full + 8 * s, 16384);
                tma2d(sbase + s * SM::STAGE, mapR, n0, m0, bar_full + 8 * s);
            }
        }
    } else {
        if (INLINE_PROD && warp == 0) prologue_loads(); else cluster_wait();
        const int wg = warp >> 2, g = lane >> 2, c = lane & 3;
        const int rloc = wg * 64 + (warp & 3) * 16 + g;
        const int row0 = m0 + rloc;
        float mean0 = 0.f, rstd0 = 1.f, mean1 = 0.f, rstd1 = 1.f;
        if constexpr (XKV) {
            static_assert(!XKV || STAGES >= KB, "the K / V weight block must stay resident");
            const __nv_bfloat16* wsrc = tile_n == 0 ? prm.wkv : prm.wv;
            uint4 v[4];
#pragma unroll
            for (int i = 0; i < 4; i++) v[i] = __ldg((const uint4*)wsrc + tid + 256 * i);
#pragma unroll
            for (int i = 0; i < 4; i++) {
                const int idx = tid + 256 * i, k = idx >> 1, kr = k & 63;
                const uint32_t dst = sbase + (k >> 6) * SM::STAGE + G::A_BYTES + 2 * G::BLK + kr * 64 + (((idx & 1) ^ ((kr >> 1) & 3)) << 4);
                asm volatile("st.shared.v4.u32 [%0], {%1,%2,%3,%4};" ::"r"(dst), "r"(v[i].x), "r"(v[i].y), "r"(v[i].z), "r"(v[i].w) : "memory");
            }
            fence_async_smem();
            if constexpr (SELF) named_bar(6, 512); else named_bar(6, 256);
        }
        RowStatRaw raw;
        float csv = 0.f;
        float2 cskv[2] = {make_float2(0.f, 0.f), make_float2(0.f, 0.f)};
        auto ln_inputs = [&]() {
            pdl_wait();
            if constexpr (EPI != EPI_RES) {
                raw = load_row_stats(prm.stats_in, row0, c);
                const float* cs = EPI == EPI_FFN1 ? g_cs_1 + n0 : g_cs_q + n0;
                if (tid < TN) csv = cs[tid];
                if constexpr (XKV) {
                    cskv[0] = *(const float2*)(g_cs_kv + tile_n * 16 + 2 * c);
                    cskv[1] = *(const float2*)(g_cs_kv + tile_n * 16 + 8 + 2 * c);
                }
            }
        };
        if (!SELF) ln_inputs();
        float acc[BN / 2];
        const uint64_t dA0 = mkdesc(sbase + wg * (G::A_BYTES / 2), 16, G::A_SBO, G::A_SWZ);
        const uint64_t dB0 = mkdesc(sbase + G::A_BYTES, G::B_LBO, G::B_SBO, G::B_SWZ);
        int s = 0, ph = 0;
#pragma unroll 1
        for (int kb = 0; kb < KB; kb++) {
            mbar_wait(bar_full + 8 * s, ph);
            const uint64_t dA = dA0 + (uint64_t)(s * (SM::STAGE >> 4)), dB = dB0 + (uint64_t)(s * (SM::STAGE >> 4));
            wg_fence();
#pragma unroll
            for (int k = 0; k < G::BK / 16; k++) wgmma_ss_tb<BN>(acc, dA + (uint64_t)(k * 2), dB + (uint64_t)(k * (G::B_KSTEP >> 4)), (kb | k) != 0);
            wg_commit();
            if constexpr (EPI == EPI_RES && RES_WAIT0) {
                wg_wait<0>();
                if ((warp & 3) == 0 && elect_one()) {
                    if (MC) { mbar_arrive_remote(bar_empty + 8 * s, 0); mbar_arrive_remote(bar_empty + 8 * s, 1); }
                    else mbar_arrive(bar_empty + 8 * s);
                }
            } else if (kb > 0) {
                wg_wait<1>();
                const int sp = s == 0 ? STAGES - 1 : s - 1;
                if ((warp & 3) == 0 && elect_one()) {
                    if (MC) { mbar_arrive_remote(bar_empty + 8 * sp, 0); mbar_arrive_remote(bar_empty + 8 * sp, 1); }
                    else mbar_arrive(bar_empty + 8 * sp);
                }
                if (INLINE_PROD && warp == 0 && kb >= LAG && kb - LAG + STAGES < KB) {
                    const int sq = LAG == 1 ? sp : (sp == 0 ? STAGES - 1 : sp - 1);
                    mbar_wait(bar_empty + 8 * sq, ((kb - LAG) / STAGES) & 1);
                    if (elect_one()) {
                        mbar_expect_tx(bar_full + 8 * sq, STAGE_TX);
                        loadB(kb - LAG + STAGES, sq);
                        loadA(kb - LAG + STAGES, sq);
                    }
                }
            }
            if (++s == STAGES) { s = 0; ph ^= 1; }
        }
        if constexpr (SELF) {
            named_bar(4, 512);
            const float2 r0 = *(const float2*)(s_row + 2 * rloc), r1 = *(const float2*)(s_row + 2 * rloc + 16);
            mean0 = r0.x; rstd0 = r0.y; mean1 = r1.x; rstd1 = r1.y;
        } else if constexpr (EPI != EPI_RES) {
            finish_row_stats(raw, mean0, rstd0, mean1, rstd1);
            if (tid < TN) s_cs[tid] = csv;
        }
        wg_wait<0>();
        fence_regs(acc);
        if (tid == 0) TL(prm.tk, 2);
        if constexpr (EPI != EPI_RES) named_bar(1, 256);

        if constexpr (EPI != EPI_FFN1) {
            const uint32_t stile = sbase + (EPI == EPI_RES ? s * SM::STAGE : 0);
            const int mrow = wg * 64 + (warp & 3) * 16 + (lane & 7) + ((lane >> 3) & 1) * 8;
            const uint32_t rbase = stile + mrow * 128;
            if constexpr (EPI == EPI_RES) {
                mbar_wait(bar_full + 8 * s, ph);
                float s0 = 0.f, s1 = 0.f;
#pragma unroll
                for (int jj = 0; jj < 4; jj++) {
                    uint32_t r0, r1, r2, r3;
                    const uint32_t addr = rbase + (((2 * jj + (lane >> 4)) ^ (mrow & 7)) << 4);
                    ldsm_x4(r0, r1, r2, r3, addr);
                    const uint32_t u0 = pack_bf16(acc[8 * jj] + bf_lo(r0), acc[8 * jj + 1] + bf_hi(r0));
                    const uint32_t u1 = pack_bf16(acc[8 * jj + 2] + bf_lo(r1), acc[8 * jj + 3] + bf_hi(r1));
                    const uint32_t u2 = pack_bf16(acc[8 * jj + 4] + bf_lo(r2), acc[8 * jj + 5] + bf_hi(r2));
                    const uint32_t u3 = pack_bf16(acc[8 * jj + 6] + bf_lo(r3), acc[8 * jj + 7] + bf_hi(r3));
                    stsm_x4(addr, u0, u1, u2, u3);
                    acc[8 * jj] = bf_lo(u0); acc[8 * jj + 1] = bf_hi(u0); acc[8 * jj + 4] = bf_lo(u2); acc[8 * jj + 5] = bf_hi(u2);
                    acc[8 * jj + 2] = bf_lo(u1); acc[8 * jj + 3] = bf_hi(u1); acc[8 * jj + 6] = bf_lo(u3); acc[8 * jj + 7] = bf_hi(u3);
                    s0 += (acc[8 * jj] + acc[8 * jj + 1]) + (acc[8 * jj + 4] + acc[8 * jj + 5]);
                    s1 += (acc[8 * jj + 2] + acc[8 * jj + 3]) + (acc[8 * jj + 6] + acc[8 * jj + 7]);
                }
                fence_async_smem();
                named_bar(2 + wg, 128);
                if ((warp & 3) == 0 && elect_one()) { tma2d_store(mapC, stile + wg * 8192, n0, m0 + wg * 64); bulk_commit(); }
                if (prm.stats_out) {
                    s0 += __shfl_xor_sync(0xffffffffu, s0, 1); s0 += __shfl_xor_sync(0xffffffffu, s0, 2);
                    s1 += __shfl_xor_sync(0xffffffffu, s1, 1); s1 += __shfl_xor_sync(0xffffffffu, s1, 2);
                    const float mu0 = s0 * (1.f / 64.f), mu1 = s1 * (1.f / 64.f);
                    float q0 = 0.f, q1 = 0.f;
#pragma unroll
                    for (int j = 0; j < 8; j++) {
                        float d;
                        d = acc[4 * j] - mu0; q0 += d * d; d = acc[4 * j + 1] - mu0; q0 += d * d;
                        d = acc[4 * j + 2] - mu1; q1 += d * d; d = acc[4 * j + 3] - mu1; q1 += d * d;
                    }
                    q0 += __shfl_xor_sync(0xffffffffu, q0, 1); q0 += __shfl_xor_sync(0xffffffffu, q0, 2);
                    q1 += __shfl_xor_sync(0xffffffffu, q1, 1); q1 += __shfl_xor_sync(0xffffffffu, q1, 2);
                    if (c == 0) {
                        prm.stats_out[tile_n * S_ + row0] = make_float2(mu0, q0);
                        prm.stats_out[tile_n * S_ + row0 + 8] = make_float2(mu1, q1);
                    }
                }
            } else {
                const float sc = 0.25f * 1.4426950408889634f;
                const float a0 = rstd0 * sc, a1 = rstd1 * sc, rm0 = a0 * mean0, rm1 = a1 * mean1;
#pragma unroll
                for (int jj = 0; jj < 4; jj++) {
                    const float2 ca = *(const float2*)(s_cs + 16 * jj + 2 * c), cb = *(const float2*)(s_cs + 16 * jj + 8 + 2 * c);
                    const uint32_t u0 = pack_bf16(acc[8 * jj] * a0 - rm0 * ca.x, acc[8 * jj + 1] * a0 - rm0 * ca.y);
                    const uint32_t u1 = pack_bf16(acc[8 * jj + 2] * a1 - rm1 * ca.x, acc[8 * jj + 3] * a1 - rm1 * ca.y);
                    const uint32_t u2 = pack_bf16(acc[8 * jj + 4] * a0 - rm0 * cb.x, acc[8 * jj + 5] * a0 - rm0 * cb.y);
                    const uint32_t u3 = pack_bf16(acc[8 * jj + 6] * a1 - rm1 * cb.x, acc[8 * jj + 7] * a1 - rm1 * cb.y);
                    stsm_x4(rbase + (((2 * jj + (lane >> 4)) ^ (mrow & 7)) << 4), u0, u1, u2, u3);
                }
                fence_async_smem();
                named_bar(2 + wg, 128);
                if ((warp & 3) == 0 && elect_one()) { tma2d_store(mapC, stile + wg * 8192, n0, m0 + wg * 64); bulk_commit(); }
            }
            if constexpr (XKV) {
                {
                    const float* acx = &acc[32];
                    const float rm0 = rstd0 * mean0, rm1 = rstd1 * mean1;
                    float n0s = 0.f, n1s = 0.f, vmax = 0.f;
#pragma unroll
                    for (int j = 0; j < 2; j++) {
                        const float2 cs2 = SELF ? *(const float2*)(s_cs + 64 + 8 * j + 2 * c) : cskv[j];
                        const uint32_t u0 = pack_bf16(acx[4 * j] * rstd0 - rm0 * cs2.x, acx[4 * j + 1] * rstd0 - rm0 * cs2.y);
                        const uint32_t u1 = pack_bf16(acx[4 * j + 2] * rstd1 - rm1 * cs2.x, acx[4 * j + 3] * rstd1 - rm1 * cs2.y);
                        n0s += bf_lo(u0) * bf_lo(u0) + bf_hi(u0) * bf_hi(u0);
                        n1s += bf_lo(u1) * bf_lo(u1) + bf_hi(u1) * bf_hi(u1);
                        vmax = fmaxf(vmax, fmaxf(fmaxf(fabsf(bf_lo(u0)), fabsf(bf_hi(u0))), fmaxf(fabsf(bf_lo(u1)), fabsf(bf_hi(u1)))));
                        if (tile_n == 0) {
                            *(uint32_t*)(g_kimg + (row0 >> 3) * 256 + j * 128 + g * 16 + c * 4) = u0;
                            *(uint32_t*)(g_kimg + ((row0 + 8) >> 3) * 256 + j * 128 + g * 16 + c * 4) = u1;
                        } else {
                            uint8_t* vb = g_vimg + (row0 >> 4) * 768 + j * 256 + g * 16 + c * 4;
                            *(uint32_t*)(vb) = u0;
                            *(uint32_t*)(vb + 128) = u1;
                        }
                    }
                    if (tile_n == 1) {
                        uint8_t* vb = g_vimg + (row0 >> 4) * 768 + 512 + g * 16 + c * 4;
                        const uint32_t one = c == 0 ? 0x00003F80u : 0u;
                        *(uint32_t*)(vb) = one;
                        *(uint32_t*)(vb + 128) = one;
                    }
                    n0s += __shfl_xor_sync(0xffffffffu, n0s, 1); n0s += __shfl_xor_sync(0xffffffffu, n0s, 2);
                    n1s += __shfl_xor_sync(0xffffffffu, n1s, 1); n1s += __shfl_xor_sync(0xffffffffu, n1s, 2);
                    float km = tile_n == 0 ? fmaxf(n0s, n1s) : vmax;
                    if (!(n0s + n1s < INFINITY)) km = INFINITY;
#pragma unroll
                    for (int o = 1; o < 32; o <<= 1) km = fmaxf(km, __shfl_xor_sync(0xffffffffu, km, o));
                    if (lane == 0) s_red[warp] = km;
                    named_bar(1, 256);
                    if (tid == 0) {
                        float a = 0.f;
                        for (int i = 0; i < 8; i++) a = fmaxf(a, s_red[i]);
                        g_kvmax[tile_n * 16 + tile_m] = a;
                    }
                }
            }
            if ((warp & 3) == 0) bulk_wait_read();
        } else {
            const uint32_t stile = sbase + wg * (7 * 4096);
            const int mrow = (warp & 3) * 16 + (lane & 7) + ((lane >> 3) & 1) * 8;
            const float a0 = 0.5f * rstd0, a1 = 0.5f * rstd1, rm0 = a0 * mean0, rm1 = a1 * mean1;
#pragma unroll
            for (int jj = 0; jj < 14; jj++) {
                const float2 ca = *(const float2*)(s_cs + 16 * jj + 2 * c), cb = *(const float2*)(s_cs + 16 * jj + 8 + 2 * c);
                float y[8] = {acc[8 * jj] * a0 - rm0 * ca.x,     acc[8 * jj + 1] * a0 - rm0 * ca.y,
                              acc[8 * jj + 2] * a1 - rm1 * ca.x, acc[8 * jj + 3] * a1 - rm1 * ca.y,
                              acc[8 * jj + 4] * a0 - rm0 * cb.x, acc[8 * jj + 5] * a0 - rm0 * cb.y,
                              acc[8 * jj + 6] * a1 - rm1 * cb.x, acc[8 * jj + 7] * a1 - rm1 * cb.y};
#pragma unroll
                for (int i = 0; i < 8; i++) {
                    float t;
                    asm("tanh.approx.f32 %0, %1;" : "=f"(t) : "f"(y[i]));
                    y[i] = fmaf(y[i], t, y[i]);
                }
                const int chunk = (2 * jj + (lane >> 4)) & 3, blk = jj >> 1;
                stsm_x4(stile + blk * 4096 + mrow * 64 + ((chunk ^ ((mrow >> 1) & 3)) << 4),
                        pack_bf16(y[0], y[1]), pack_bf16(y[2], y[3]), pack_bf16(y[4], y[5]), pack_bf16(y[6], y[7]));
                if (jj & 1) {
                    fence_async_smem();
                    __syncwarp();
                    if (elect_one()) {
                        tma2d_store(mapC, stile + blk * 4096 + (warp & 3) * 1024, n0 + blk * 32, m0 + wg * 64 + (warp & 3) * 16);
                        bulk_commit();
                    }
                }
            }
            bulk_wait_read();
        }
    }
    if (tid == 0) TL(prm.tk, 3);
    if (MC) cluster_sync();
}

#define WO_ST 9
#define F2_ST 6
#define F1_ST (F1_BK == 64 ? 5 : 9)
#define QKV_ST 8
constexpr int QKV_STAGES = QKV_ST, WO_STAGES = WO_ST, FFN2_STAGES = F2_ST, FFN1_STAGES = F1_ST;
template <bool SELF>
__global__ void __launch_bounds__(SELF ? 544 : 288) qkv_kernel(const __grid_constant__ CUtensorMap mapA, const __grid_constant__ CUtensorMap mapWq,
                                                  const __grid_constant__ CUtensorMap mapQ, const GemmParams prm) {
    extern __shared__ __align__(1024) uint8_t smem_raw[];
    const int tn = blockIdx.x & 7;
    if (tn < 2) gemm_body<80, 8, QKV_STAGES, EPI_QKV, QKV_MC, SELF>(&mapA, &mapWq, &mapWq, &mapA, &mapQ, prm, blockIdx.x >> 3, tn, smem_raw);
    else gemm_body<64, 8, QKV_STAGES, EPI_QKV, QKV_MC, SELF>(&mapA, &mapWq, &mapWq, &mapA, &mapQ, prm, blockIdx.x >> 3, tn, smem_raw);
}
template <int KB, int STAGES>
__global__ void __launch_bounds__(288) res_gemm_kernel(const __grid_constant__ CUtensorMap mapA, const __grid_constant__ CUtensorMap mapW,
                                                       const __grid_constant__ CUtensorMap mapR, const __grid_constant__ CUtensorMap mapC, const GemmParams prm) {
    extern __shared__ __align__(1024) uint8_t smem_raw[];
#define RES_MAP 0
    gemm_body<64, KB, STAGES, EPI_RES, (KB == 8 ? WO_MC : F2_MC)>(&mapA, &mapW, &mapW, &mapR, &mapC, prm, RES_MAP ? blockIdx.x & 15 : blockIdx.x >> 3,
                                                                  RES_MAP ? blockIdx.x >> 4 : blockIdx.x & 7, smem_raw);
}
__global__ void __launch_bounds__(F1_INLINE ? 256 : 288) ffn1_kernel(const __grid_constant__ CUtensorMap mapA, const __grid_constant__ CUtensorMap mapW4,
                                                   const __grid_constant__ CUtensorMap mapW3, const __grid_constant__ CUtensorMap mapH, const GemmParams prm) {
    extern __shared__ __align__(1024) uint8_t smem_raw[];
#define F1_MAP 0
    const int pair = blockIdx.x >> 1;
    const int tile_n = F1_MAP == 0 ? (pair & 7) : F1_MAP == 1 ? (blockIdx.x >> 4) : (blockIdx.x & 7);
    const int tile_m = F1_MAP == 0 ? (pair >> 3) * 2 + (blockIdx.x & 1) : F1_MAP == 1 ? (blockIdx.x & 15) : (blockIdx.x >> 3);
    gemm_body<224, 512 / F1_BK, FFN1_STAGES, EPI_FFN1, F1_MC>(&mapA, &mapW4, &mapW3, &mapA, &mapH, prm, tile_m, tile_n, smem_raw);
}

#define ATT_NPOLY 11
constexpr int NPOLY = ATT_NPOLY;
__host__ __device__ constexpr bool is_mufu(int i) { return ((i + 1) * (16 - NPOLY)) / 16 != (i * (16 - NPOLY)) / 16; }

__device__ __forceinline__ float ex2(float x) { float r; asm("ex2.approx.ftz.f32 %0, %1;" : "=f"(r) : "f"(x)); return r; }
__device__ __forceinline__ uint32_t exp_pair_mufu(float a, float b) { return pack_bf16(ex2(a), ex2(b)); }
__device__ __forceinline__ uint32_t exp_pair_fma(float a, float b, uint32_t c3f) {
    constexpr float MAGIC = 98430.4140625f;
    const float ta = a + MAGIC, tb = b + (MAGIC - 143.5f);
    uint32_t y, m, r;
    asm("mad.lo.u32 %0, %1, 65536, %2;" : "=r"(y) : "r"(__float_as_uint(tb)), "r"(__float_as_uint(ta)));
    asm("lop3.b32 %0, %1, 0x007F007F, %2, 0xEA;" : "=r"(m) : "r"(y), "r"(c3f));
    const uint32_t e = y & 0xFF80FF80u;
    asm("fma.rn.bf16x2 %0, %1, %2, %3;" : "=r"(r) : "r"(y), "r"(m), "r"(e));
    return r;
}

constexpr int KCH = 256, NCH = S_ / KCH;
constexpr int K_BYTES = S_ * 32, V_BYTES = (S_ / 16) * 768;
constexpr int QO_BYTES = 128 * 128;
constexpr int ATT_SMEM = K_BYTES + V_BYTES + QO_BYTES;

__global__ void __launch_bounds__(512, 1) attn_kernel(const __grid_constant__ CUtensorMap mapQ, const __grid_constant__ CUtensorMap mapO,
                                                       const __nv_bfloat16* __restrict__ wo, const __nv_bfloat16* __restrict__ w1,
                                                       const __nv_bfloat16* __restrict__ w2, int tk) {
    extern __shared__ __align__(1024) uint8_t smem[];
    __shared__ uint64_t bars[NCH + 1];
    __shared__ int s_slow;
    const int tid = threadIdx.x, wg = tid >> 7, warp = (tid >> 5) & 3, lane = tid & 31;
    const uint32_t sK = smem_u32(smem), sV = sK + K_BYTES, sQ = sV + V_BYTES;
    if (blockIdx.x >= 128) {
        pdl_launch();
        side_job(blockIdx.x - 128, (float*)smem, wo, w1, w2);
        return;
    }
    CK(tk, 9);
    if (tid == 0) TL(tk, 0);
    if (tid == 0) {
        for (int i = 0; i <= NCH; i++) mbar_init(smem_u32(&bars[i]), 1);
        prefetch_tmap(&mapQ); prefetch_tmap(&mapO);
        s_slow = 0;
        fence_mbar_init();
    }
    __syncthreads();
    pdl_launch();
    CK(tk, 10);
    pdl_wait();
    CK(tk, 11);
    if (tid == 0) TL(tk, 1);
    const int wu = __shfl_sync(0xffffffffu, tid >> 5, 0);
    auto fetch_chunk = [&](int w) {
        if (elect_one()) {
            const uint32_t bar = smem_u32(&bars[w]);
            mbar_expect_tx(bar, KCH * 32 + (KCH / 16) * 768);
            bulk_load(sK + w * KCH * 32, g_kimg + w * KCH * 32, KCH * 32, bar);
            bulk_load(sV + w * (KCH / 16) * 768, g_vimg + w * (KCH / 16) * 768, (KCH / 16) * 768, bar);
        }
    };
    const int tb = blockIdx.x >> 3, hg = blockIdx.x & 7;
    if (wu == 1 && elect_one()) {
        mbar_expect_tx(smem_u32(&bars[NCH]), QO_BYTES);
        tma2d(sQ, &mapQ, hg * 64, tb * 128, smem_u32(&bars[NCH]));
    }
    if (wu == 0) fetch_chunk(0);
    const int g = lane >> 2;
    float kvm = g_kvmax[lane];
    const int lrow = warp * 16 + (lane & 7) + ((lane >> 3) & 1) * 8;
    const uint32_t qoff = lrow * 128 + (((2 * wg + (lane >> 4)) ^ (lrow & 7)) << 4);
    uint32_t qa[2][4];
    mbar_wait(smem_u32(&bars[NCH]), 0);
    ldsm_x4(qa[0][0], qa[0][1], qa[0][2], qa[0][3], sQ + qoff);
    ldsm_x4(qa[1][0], qa[1][1], qa[1][2], qa[1][3], sQ + 8192 + qoff);
    CK(tk, 12);
    {
        float qn = 0.f;
#pragma unroll
        for (int m = 0; m < 2; m++) {
            float n0 = bf_lo(qa[m][0]) * bf_lo(qa[m][0]) + bf_hi(qa[m][0]) * bf_hi(qa[m][0]) + bf_lo(qa[m][2]) * bf_lo(qa[m][2]) + bf_hi(qa[m][2]) * bf_hi(qa[m][2]);
            float n1 = bf_lo(qa[m][1]) * bf_lo(qa[m][1]) + bf_hi(qa[m][1]) * bf_hi(qa[m][1]) + bf_lo(qa[m][3]) * bf_lo(qa[m][3]) + bf_hi(qa[m][3]) * bf_hi(qa[m][3]);
            n0 += __shfl_xor_sync(0xffffffffu, n0, 1); n0 += __shfl_xor_sync(0xffffffffu, n0, 2);
            n1 += __shfl_xor_sync(0xffffffffu, n1, 1); n1 += __shfl_xor_sync(0xffffffffu, n1, 2);
            if (!(n0 == n0) || !(n1 == n1)) n0 = INFINITY;
            qn = fmaxf(qn, fmaxf(n0, n1));
        }
        CK(tk, 13);
#pragma unroll
        for (int o = 1; o < 16; o <<= 1) kvm = fmaxf(kvm, __shfl_xor_sync(0xffffffffu, kvm, o));
        const float km = __shfl_sync(0xffffffffu, kvm, 0), vm = __shfl_sync(0xffffffffu, kvm, 16);
        const bool ok = (qn * km <= 10000.f) && (vm <= 16384.f);
        if (!ok) s_slow = 1;
    }
    CK(tk, 14);
    float oacc[2][12];
#pragma unroll
    for (int m = 0; m < 2; m++)
#pragma unroll
        for (int i = 0; i < 12; i++) oacc[m][i] = 0.f;
    __syncthreads();
    const bool slow = s_slow != 0;
    if (wu >= 1 && wu < NCH) fetch_chunk(wu);
    CK(tk, 15);

    const uint64_t dK0 = mkdesc(sK, 128, 256, 0);
    const uint64_t dV0 = mkdesc(sV, 128, 256, 0);
    uint32_t c3f;
    asm volatile("mov.b32 %0, 0x3F003F00;" : "=r"(c3f));
    if (!slow) {
        uint64_t dK = dK0, dV = dV0;
        float s[32];
        fence_regs(oacc[0]); fence_regs(oacc[1]);
        mbar_wait(smem_u32(&bars[0]), 0);
        wg_fence();
        wgmma_rs_n64_z(s, qa[0][0], qa[0][1], qa[0][2], qa[0][3], dK);
        wg_commit();
#pragma unroll 1
        for (int ch = 0; ch < NCH; ch++) {
#pragma unroll
            for (int tt = 0; tt < KCH / 64; tt++) {
#pragma unroll
                for (int m = 0; m < 2; m++) {
                    wg_wait<0>();
                    fence_regs(s);
                    uint32_t p[16];
#pragma unroll
                    for (int i = 0; i < 16; i++) p[i] = is_mufu(i) ? exp_pair_mufu(s[2 * i], s[2 * i + 1]) : exp_pair_fma(s[2 * i], s[2 * i + 1], c3f);
                    if (m == 1 && tt == KCH / 64 - 1) mbar_wait(smem_u32(&bars[ch + 1 < NCH ? ch + 1 : ch]), 0);
                    wg_fence();
#pragma unroll
                    for (int kk = 0; kk < 4; kk++)
                        wgmma_rs_n24_tb(oacc[m], p[4 * kk], p[4 * kk + 1], p[4 * kk + 2], p[4 * kk + 3], dV + (uint64_t)((tt * 4 + kk) * (768 / 16)));
                    wgmma_rs_n64_z(s, qa[1 - m][0], qa[1 - m][1], qa[1 - m][2], qa[1 - m][3], dK + (uint64_t)((tt + m) * (64 * 32 / 16)));
                    wg_commit();
                }
            }
            dK += KCH * 32 / 16;
            dV += (KCH / 16) * (768 / 16);
        }
        wg_wait<0>();
        fence_regs(s);
    } else {
        float mx[2][2] = {{-INFINITY, -INFINITY}, {-INFINITY, -INFINITY}};
#pragma unroll 1
        for (int t = 0; t < S_ / 64; t++) {
            if ((t & 3) == 0) mbar_wait(smem_u32(&bars[t >> 2]), 0);
            const uint64_t dK = dK0 + (uint64_t)(t * 64 * 32 / 16);
            const uint64_t dV = dV0 + (uint64_t)(t * 4 * 768 / 16);
#pragma unroll
            for (int m = 0; m < 2; m++) {
                float s[32];
                wg_fence();
                wgmma_rs_n64_z(s, qa[m][0], qa[m][1], qa[m][2], qa[m][3], dK);
                wg_commit();
                wg_wait<0>();
                fence_regs(s);
                fence_regs(oacc[m]);
                float r0 = mx[m][0], r1 = mx[m][1];
#pragma unroll
                for (int j = 0; j < 8; j++) {
                    r0 = fmaxf(r0, fmaxf(s[4 * j], s[4 * j + 1]));
                    r1 = fmaxf(r1, fmaxf(s[4 * j + 2], s[4 * j + 3]));
                }
                r0 = fmaxf(r0, __shfl_xor_sync(0xffffffffu, r0, 1)); r0 = fmaxf(r0, __shfl_xor_sync(0xffffffffu, r0, 2));
                r1 = fmaxf(r1, __shfl_xor_sync(0xffffffffu, r1, 1)); r1 = fmaxf(r1, __shfl_xor_sync(0xffffffffu, r1, 2));
                const float al0 = ex2(mx[m][0] - r0), al1 = ex2(mx[m][1] - r1);
                mx[m][0] = r0; mx[m][1] = r1;
#pragma unroll
                for (int j = 0; j < 3; j++) {
                    oacc[m][4 * j] *= al0; oacc[m][4 * j + 1] *= al0;
                    oacc[m][4 * j + 2] *= al1; oacc[m][4 * j + 3] *= al1;
                }
                uint32_t p[16];
#pragma unroll
                for (int j = 0; j < 8; j++) {
                    p[2 * j] = pack_bf16(ex2(s[4 * j] - r0), ex2(s[4 * j + 1] - r0));
                    p[2 * j + 1] = pack_bf16(ex2(s[4 * j + 2] - r1), ex2(s[4 * j + 3] - r1));
                }
                fence_regs(oacc[m]);
                wg_fence();
#pragma unroll
                for (int kk = 0; kk < 4; kk++)
                    wgmma_rs_n24_tb(oacc[m], p[4 * kk], p[4 * kk + 1], p[4 * kk + 2], p[4 * kk + 3], dV + (uint64_t)(kk * 768 / 16));
                wg_commit();
                wg_wait<0>();
            }
        }
    }
    fence_regs(oacc[0]); fence_regs(oacc[1]);
    if (tid == 0) TL(tk, 2);
#pragma unroll
    for (int m = 0; m < 2; m++) {
        const float l0 = __shfl_sync(0xffffffffu, oacc[m][8], lane & ~3);
        const float l1 = __shfl_sync(0xffffffffu, oacc[m][10], lane & ~3);
        const float r0 = __fdividef(1.0f, l0), r1 = __fdividef(1.0f, l1);
        stsm_x4(sQ + m * 8192 + qoff, pack_bf16(oacc[m][0] * r0, oacc[m][1] * r0), pack_bf16(oacc[m][2] * r1, oacc[m][3] * r1),
                pack_bf16(oacc[m][4] * r0, oacc[m][5] * r0), pack_bf16(oacc[m][6] * r1, oacc[m][7] * r1));
    }
    fence_async_smem();
    __syncthreads();
    if (wu == 0 && elect_one()) {
        tma2d_store(&mapO, sQ, hg * 64, tb * 128);
        bulk_commit();
        bulk_wait_read();
    }
    if (tid == 0) TL(tk, 3);
}

typedef CUresult (*EncodeFn)(CUtensorMap*, CUtensorMapDataType, cuuint32_t, void*, const cuuint64_t*, const cuuint64_t*, const cuuint32_t*,
                             const cuuint32_t*, CUtensorMapInterleave, CUtensorMapSwizzle, CUtensorMapL2promotion, CUtensorMapFloatOOBfill);

EncodeFn get_encode() {
    static EncodeFn fn = nullptr;
    if (!fn) {
        void* p = nullptr;
        cudaDriverEntryPointQueryResult qr;
        cudaGetDriverEntryPoint("cuTensorMapEncodeTiled", &p, cudaEnableDefault, &qr);
        fn = (EncodeFn)p;
    }
    return fn;
}
CUtensorMap map2d(const void* ptr, uint64_t cols, uint64_t rows, uint32_t bc, uint32_t br, CUtensorMapSwizzle sw) {
    CUtensorMap m;
    cuuint64_t gd[2] = {cols, rows}, gs[1] = {cols * 2};
    cuuint32_t bx[2] = {bc, br}, es[2] = {1, 1};
    get_encode()(&m, CU_TENSOR_MAP_DATA_TYPE_BFLOAT16, 2, (void*)ptr, gd, gs, bx, es, CU_TENSOR_MAP_INTERLEAVE_NONE, sw,
                 CU_TENSOR_MAP_L2_PROMOTION_L2_128B, CU_TENSOR_MAP_FLOAT_OOB_FILL_NONE);
    return m;
}
CUtensorMap map3d32(const void* ptr, uint64_t cols, uint64_t rows, uint32_t br, uint32_t nb) {
    CUtensorMap m;
    cuuint64_t gd[3] = {32, rows, cols / 32}, gs[2] = {cols * 2, 64};
    cuuint32_t bx[3] = {32, br, nb}, es[3] = {1, 1, 1};
    get_encode()(&m, CU_TENSOR_MAP_DATA_TYPE_BFLOAT16, 3, (void*)ptr, gd, gs, bx, es, CU_TENSOR_MAP_INTERLEAVE_NONE, CU_TENSOR_MAP_SWIZZLE_64B,
                 CU_TENSOR_MAP_L2_PROMOTION_L2_128B, CU_TENSOR_MAP_FLOAT_OOB_FILL_NONE);
    return m;
}

template <typename... KArgs, typename... Args>
void launch(void (*kern)(KArgs...), int grid, int block, int smem, int cluster, bool pdl, Args... args) {
    cudaLaunchConfig_t cfg = {};
    cfg.gridDim = dim3(grid);
    cfg.blockDim = dim3(block);
    cfg.dynamicSmemBytes = smem;
    cfg.stream = cudaStreamPerThread;
    cudaLaunchAttribute at[2];
    int n = 0;
    if (cluster > 1) { at[n].id = cudaLaunchAttributeClusterDimension; at[n].val.clusterDim.x = cluster; at[n].val.clusterDim.y = 1; at[n].val.clusterDim.z = 1; n++; }
    if (pdl) { at[n].id = cudaLaunchAttributeProgrammaticStreamSerialization; at[n].val.programmaticStreamSerializationAllowed = 1; n++; }
    cfg.attrs = at;
    cfg.numAttrs = n;
    cudaLaunchKernelEx(&cfg, kern, KArgs(args)...);
}

template <typename T> void* sym(const T& s) { void* p = nullptr; cudaGetSymbolAddress(&p, s); return p; }

}

extern "C" void kernel_launch(void* const* d_in, const int* in_sizes, int n_in, void* d_out, int out_size) {
    const __nv_bfloat16* x = (const __nv_bfloat16*)d_in[0];
    const __nv_bfloat16* wq = (const __nv_bfloat16*)d_in[1];
    const __nv_bfloat16* wk = (const __nv_bfloat16*)d_in[2];
    const __nv_bfloat16* wv = (const __nv_bfloat16*)d_in[3];
    const __nv_bfloat16* wo = (const __nv_bfloat16*)d_in[4];
    const __nv_bfloat16* w1 = (const __nv_bfloat16*)d_in[6];
    const __nv_bfloat16* w2 = (const __nv_bfloat16*)d_in[7];

    constexpr int SM_QKV = GemmSmem<QKV_STAGES, EPI_QKV>::TOTAL, SM_QKV0 = GemmSmem<QKV_STAGES, EPI_QKV>::TOTAL_SELF;
    static_assert(SM_QKV0 <= 232448, "shared memory");
    constexpr int SM_WO = GemmSmem<WO_STAGES, EPI_RES>::TOTAL, SM_FFN2 = GemmSmem<FFN2_STAGES, EPI_RES>::TOTAL;
    static_assert(SM_WO > 116736 && SM_FFN2 > 116736, "one CTA per SM");
    constexpr int SM_FFN1 = GemmSmem<FFN1_STAGES, EPI_FFN1>::TOTAL;
    cudaFuncSetAttribute(qkv_kernel<false>, cudaFuncAttributeMaxDynamicSharedMemorySize, SM_QKV);
    cudaFuncSetAttribute(qkv_kernel<true>, cudaFuncAttributeMaxDynamicSharedMemorySize, SM_QKV0);
    cudaFuncSetAttribute(res_gemm_kernel<8, WO_STAGES>, cudaFuncAttributeMaxDynamicSharedMemorySize, SM_WO);
    cudaFuncSetAttribute(ffn1_kernel, cudaFuncAttributeMaxDynamicSharedMemorySize, SM_FFN1);
    cudaFuncSetAttribute(res_gemm_kernel<28, FFN2_STAGES>, cudaFuncAttributeMaxDynamicSharedMemorySize, SM_FFN2);
    cudaFuncSetAttribute(attn_kernel, cudaFuncAttributeMaxDynamicSharedMemorySize, ATT_SMEM);
    cudaFuncSetAttribute(qkv_kernel<false>, cudaFuncAttributePreferredSharedMemoryCarveout, 100);
    cudaFuncSetAttribute(qkv_kernel<true>, cudaFuncAttributePreferredSharedMemoryCarveout, 100);
    cudaFuncSetAttribute(res_gemm_kernel<8, WO_STAGES>, cudaFuncAttributePreferredSharedMemoryCarveout, 100);
    cudaFuncSetAttribute(ffn1_kernel, cudaFuncAttributePreferredSharedMemoryCarveout, 100);
    cudaFuncSetAttribute(res_gemm_kernel<28, FFN2_STAGES>, cudaFuncAttributePreferredSharedMemoryCarveout, 100);
    cudaFuncSetAttribute(attn_kernel, cudaFuncAttributePreferredSharedMemoryCarveout, 100);

    void *q = sym(g_q), *o = sym(g_o), *x1 = sym(g_x1), *x2 = sym(g_x2), *x3 = sym(g_x3), *h = sym(g_h);
    float2* stats = (float2*)sym(g_stats);
    const void* xs[5] = {x, x1, x2, x3, d_out};

    const CUtensorMapSwizzle SW128 = CU_TENSOR_MAP_SWIZZLE_128B, SW64 = CU_TENSOR_MAP_SWIZZLE_64B;
    const CUtensorMap mWq = map3d32(wq, D_, D_, 64, 2);
    const CUtensorMap mWo = map2d(wo, D_, D_, 64, 64, SW128);
    const CUtensorMap mW1a = map3d32(w1, F_, D_, F1_BK, 4), mW1b = map3d32(w1, F_, D_, F1_BK, 3);
    const CUtensorMap mW2 = map2d(w2, D_, F_, 64, 64, SW128);
    const CUtensorMap mQ = map2d(q, D_, S_, 64, 64, SW128);
    const CUtensorMap mQa = map2d(q, D_, S_, 64, 128, SW128), mOs = map2d(o, D_, S_, 64, 128, SW128);
    const CUtensorMap mHst = map2d(h, F_, S_, 32, 16, SW64);
    CUtensorMap mXa[4], mXf[4], mXr[4], mXs[5];
    for (int i = 0; i < 4; i++) {
        mXa[i] = map2d(xs[i], D_, S_, 64, QKV_MC ? 64 : 128, SW128);
        mXf[i] = F1_BK == 64 ? map2d(xs[i], D_, S_, 64, 128, SW128) : map2d(xs[i], D_, S_, 32, 128, SW64);
        mXr[i] = map2d(xs[i], D_, S_, 64, 128, SW128);
    }
    for (int i = 0; i < 5; i++) mXs[i] = map2d(xs[i], D_, S_, 64, 64, SW128);
    const CUtensorMap mOa = map2d(o, D_, S_, 64, WO_MC ? 64 : 128, SW128);
    const CUtensorMap mHa = map2d(h, F_, S_, 64, F2_MC ? 64 : 128, SW128);

    for (int layer = 0; layer < 2; layer++) {
        const int xi = layer * 2;
        GemmParams p;
        p.wkv = wk; p.wv = wv;
        p.stats_in = stats + (size_t)xi * 8 * S_; p.stats_out = nullptr; p.tk = 1 + 5 * layer;
        if (layer == 0) launch(qkv_kernel<true>, 128, 544, SM_QKV0, QKV_MC ? 2 : 1, false, mXa[xi], mWq, mQ, p);
        else launch(qkv_kernel<false>, 128, 288, SM_QKV, QKV_MC ? 2 : 1, true, mXa[xi], mWq, mQ, p);
        launch(attn_kernel, layer == 0 ? 128 + SIDE_CTAS : 128, 512, ATT_SMEM, 1, true, mQa, mOs, wo, w1, w2, 2 + 5 * layer);
        p.stats_in = nullptr; p.stats_out = stats + (size_t)(xi + 1) * 8 * S_; p.tk = 3 + 5 * layer;
        launch(res_gemm_kernel<8, WO_STAGES>, 128, 288, SM_WO, WO_MC ? 2 : 1, true, mOa, mWo, mXr[xi], mXs[xi + 1], p);
        p.stats_in = stats + (size_t)(xi + 1) * 8 * S_; p.stats_out = nullptr; p.tk = 4 + 5 * layer;
        launch(ffn1_kernel, 128, F1_INLINE ? 256 : 288, SM_FFN1, F1_MC ? 2 : 1, true, mXf[xi + 1], mW1a, mW1b, mHst, p);
        p.stats_in = nullptr; p.stats_out = layer == 0 ? stats + (size_t)2 * 8 * S_ : nullptr; p.tk = 5 + 5 * layer;
        launch(res_gemm_kernel<28, FFN2_STAGES>, 128, 288, SM_FFN2, F2_MC ? 2 : 1, true, mHa, mW2, mXr[xi + 1], mXs[xi + 2], p);
    }
}
```

```cpp
#include <cuda_runtime.h>
#include <cuda_bf16.h>
#include <cuda.h>
#include <stdint.h>

#define F1_INLINE 0
#define QKV_MC 0
#define WO_MC 0
#define F2_MC 0
#define F1_MC 2
#define SELF_WAIT 0
#define ATT_VAR 1
#define SIDE_WAIT 1
#define PREB 1
#define RES_WAIT0 0

namespace {

constexpr int S_ = 2048, D_ = 512, H_ = 32, F_ = 1792;

__device__ __align__(1024) __nv_bfloat16 g_q[S_ * D_];
__device__ __align__(1024) __nv_bfloat16 g_o[S_ * D_];
__device__ __align__(1024) __nv_bfloat16 g_x1[S_ * D_];
__device__ __align__(1024) __nv_bfloat16 g_x2[S_ * D_];
__device__ __align__(1024) __nv_bfloat16 g_x3[S_ * D_];
__device__ __align__(1024) __nv_bfloat16 g_h[S_ * F_];
__device__ __align__(1024) uint8_t g_kimg[S_ * 32];
__device__ __align__(1024) uint8_t g_vimg[(S_ / 16) * 768];
__device__ __align__(1024) float2 g_stats[4][8 * S_];
__device__ __align__(16) float g_cs_q[D_];
__device__ __align__(16) float g_cs_kv[32];
__device__ __align__(16) float g_cs_1[F_];
__device__ __align__(16) float g_kvmax[32];

#define TL(k, slot)
#define CK(k, i)

__device__ __forceinline__ uint32_t smem_u32(const void* p) { return (uint32_t)__cvta_generic_to_shared(p); }
__device__ __forceinline__ void mbar_init(uint32_t bar, uint32_t cnt) {
    asm volatile("mbarrier.init.shared::cta.b64 [%0], %1;" ::"r"(bar), "r"(cnt));
}
__device__ __forceinline__ void mbar_expect_tx(uint32_t bar, uint32_t bytes) {
    asm volatile("mbarrier.arrive.expect_tx.shared::cta.b64 _, [%0], %1;" ::"r"(bar), "r"(bytes) : "memory");
}
__device__ __forceinline__ void mbar_arrive(uint32_t bar) {
    asm volatile("mbarrier.arrive.shared::cta.b64 _, [%0];" ::"r"(bar) : "memory");
}
__device__ __forceinline__ void mbar_arrive_remote(uint32_t bar, uint32_t cta) {
    asm volatile("{\n.reg .b32 ra;\nmapa.shared::cluster.u32 ra, %0, %1;\nmbarrier.arrive.shared::cluster.b64 _, [ra];\n}" ::"r"(bar), "r"(cta) : "memory");
}
__device__ __forceinline__ void mbar_wait(uint32_t bar, uint32_t parity) {
    asm volatile("{\n.reg .pred p;\nWAIT_%=:\nmbarrier.try_wait.parity.shared::cta.b64 p, [%0], %1;\n@p bra DONE_%=;\nbra WAIT_%=;\nDONE_%=:\n}" ::"r"(bar), "r"(parity) : "memory");
}
__device__ __forceinline__ void bulk_load(uint32_t dst, const void* src, uint32_t bytes, uint32_t bar) {
    asm volatile("cp.async.bulk.shared::cluster.global.mbarrier::complete_tx::bytes [%0], [%1], %2, [%3];" ::"r"(dst), "l"(src), "r"(bytes), "r"(bar) : "memory");
}
__device__ __forceinline__ void tma2d(uint32_t dst, const CUtensorMap* m, int c0, int c1, uint32_t bar) {
    asm volatile("cp.async.bulk.tensor.2d.shared::cluster.global.mbarrier::complete_tx::bytes [%0], [%1, {%3, %4}], [%2];" ::"r"(dst), "l"(m), "r"(bar), "r"(c0), "r"(c1) : "memory");
}
__device__ __forceinline__ void tma2d_mc(uint32_t dst, const CUtensorMap* m, int c0, int c1, uint32_t bar, uint16_t mask) {
    asm volatile("cp.async.bulk.tensor.2d.shared::cluster.global.mbarrier::complete_tx::bytes.multicast::cluster [%0], [%1, {%3, %4}], [%2], %5;" ::"r"(dst), "l"(m), "r"(bar), "r"(c0), "r"(c1), "h"(mask) : "memory");
}
__device__ __forceinline__ void tma3d(uint32_t dst, const CUtensorMap* m, int c0, int c1, int c2, uint32_t bar) {
    asm volatile("cp.async.bulk.tensor.3d.shared::cluster.global.mbarrier::complete_tx::bytes [%0], [%1, {%3, %4, %5}], [%2];" ::"r"(dst), "l"(m), "r"(bar), "r"(c0), "r"(c1), "r"(c2) : "memory");
}
__device__ __forceinline__ void tma3d_mc(uint32_t dst, const CUtensorMap* m, int c0, int c1, int c2, uint32_t bar, uint16_t mask) {
    asm volatile("cp.async.bulk.tensor.3d.shared::cluster.global.mbarrier::complete_tx::bytes.multicast::cluster [%0], [%1, {%3, %4, %5}], [%2], %6;" ::"r"(dst), "l"(m), "r"(bar), "r"(c0), "r"(c1), "r"(c2), "h"(mask) : "memory");
}
__device__ __forceinline__ void tma2d_store(const CUtensorMap* m, uint32_t src, int c0, int c1) {
    asm volatile("cp.async.bulk.tensor.2d.global.shared::cta.bulk_group [%0, {%2, %3}], [%1];" ::"l"(m), "r"(src), "r"(c0), "r"(c1) : "memory");
}
__device__ __forceinline__ void tma3d_store(const CUtensorMap* m, uint32_t src, int c0, int c1, int c2) {
    asm volatile("cp.async.bulk.tensor.3d.global.shared::cta.bulk_group [%0, {%2, %3, %4}], [%1];" ::"l"(m), "r"(src), "r"(c0), "r"(c1), "r"(c2) : "memory");
}
__device__ __forceinline__ void bulk_commit() { asm volatile("cp.async.bulk.commit_group;" ::: "memory"); }
__device__ __forceinline__ void bulk_wait_read() { asm volatile("cp.async.bulk.wait_group.read 0;" ::: "memory"); }
__device__ __forceinline__ void prefetch_tmap(const CUtensorMap* m) { asm volatile("prefetch.tensormap [%0];" ::"l"(m) : "memory"); }
__device__ __forceinline__ void fence_async_smem() { asm volatile("fence.proxy.async.shared::cta;" ::: "memory"); }
__device__ __forceinline__ void fence_mbar_init() { asm volatile("fence.mbarrier_init.release.cluster;" ::: "memory"); }
__device__ __forceinline__ void cluster_sync() { asm volatile("barrier.cluster.arrive.release.aligned;\nbarrier.cluster.wait.acquire.aligned;" ::: "memory"); }
__device__ __forceinline__ uint32_t cluster_rank() { uint32_t r; asm volatile("mov.u32 %0, %%cluster_ctarank;" : "=r"(r)); return r; }
__device__ __forceinline__ void pdl_wait() { asm volatile("griddepcontrol.wait;" ::: "memory"); }
__device__ __forceinline__ void pdl_launch() { asm volatile("griddepcontrol.launch_dependents;" ::: "memory"); }
__device__ __forceinline__ bool elect_one() {
    uint32_t p;
    asm volatile("{\n.reg .pred p;\nelect.sync _|p, 0xffffffff;\nselp.b32 %0, 1, 0, p;\n}" : "=r"(p));
    return p != 0;
}
__device__ __forceinline__ void named_bar(int id, int n) { asm volatile("bar.sync %0, %1;" ::"r"(id), "r"(n) : "memory"); }

__device__ __forceinline__ void wg_fence() { asm volatile("wgmma.fence.sync.aligned;" ::: "memory"); }
__device__ __forceinline__ void wg_commit() { asm volatile("wgmma.commit_group.sync.aligned;" ::: "memory"); }
template <int N> __device__ __forceinline__ void wg_wait() { asm volatile("wgmma.wait_group.sync.aligned %0;" ::"n"(N) : "memory"); }
template <int N> __device__ __forceinline__ void fence_regs(float (&d)[N]) {
#pragma unroll
    for (int i = 0; i < N; i++) asm volatile("" : "+f"(d[i])::"memory");
}
__device__ __forceinline__ uint64_t mkdesc(uint32_t addr, uint32_t lbo, uint32_t sbo, uint32_t swz) {
    uint64_t d = 0;
    d |= (uint64_t)((addr & 0x3FFFF) >> 4);
    d |= (uint64_t)((lbo & 0x3FFFF) >> 4) << 16;
    d |= (uint64_t)((sbo & 0x3FFFF) >> 4) << 32;
    d |= (uint64_t)swz << 62;
    return d;
}
__device__ __forceinline__ void ldsm_x4(uint32_t& r0, uint32_t& r1, uint32_t& r2, uint32_t& r3, uint32_t addr) {
    asm volatile("ldmatrix.sync.aligned.m8n8.x4.shared.b16 {%0,%1,%2,%3}, [%4];" : "=r"(r0), "=r"(r1), "=r"(r2), "=r"(r3) : "r"(addr) : "memory");
}
__device__ __forceinline__ void stsm_x4(uint32_t addr, uint32_t r0, uint32_t r1, uint32_t r2, uint32_t r3) {
    asm volatile("stmatrix.sync.aligned.m8n8.x4.shared.b16 [%0], {%1,%2,%3,%4};" ::"r"(addr), "r"(r0), "r"(r1), "r"(r2), "r"(r3) : "memory");
}
__device__ __forceinline__ void ldsm_x4_t(uint32_t& r0, uint32_t& r1, uint32_t& r2, uint32_t& r3, uint32_t addr) {
    asm volatile("ldmatrix.sync.aligned.m8n8.x4.trans.shared.b16 {%0,%1,%2,%3}, [%4];" : "=r"(r0), "=r"(r1), "=r"(r2), "=r"(r3) : "r"(addr) : "memory");
}
__device__ __forceinline__ void hmma(float (&d)[4], uint32_t a0, uint32_t a1, uint32_t a2, uint32_t a3, uint32_t b0, uint32_t b1) {
    asm volatile("mma.sync.aligned.m16n8k16.row.col.f32.bf16.bf16.f32 {%0,%1,%2,%3}, {%4,%5,%6,%7}, {%8,%9}, {%0,%1,%2,%3};"
                 : "+f"(d[0]), "+f"(d[1]), "+f"(d[2]), "+f"(d[3]) : "r"(a0), "r"(a1), "r"(a2), "r"(a3), "r"(b0), "r"(b1));
}
__device__ __forceinline__ uint32_t pack_bf16(float lo, float hi) {
    uint32_t r;
    asm("cvt.rn.bf16x2.f32 %0, %1, %2;" : "=r"(r) : "f"(hi), "f"(lo));
    return r;
}
__device__ __forceinline__ float bf_lo(uint32_t v) { return __uint_as_float(v << 16); }
__device__ __forceinline__ float bf_hi(uint32_t v) { return __uint_as_float(v & 0xFFFF0000u); }

#define WG_REGS_4(o) "+f"(d[o]), "+f"(d[o + 1]), "+f"(d[o + 2]), "+f"(d[o + 3])
#define WG_REGS_8(o) WG_REGS_4(o), WG_REGS_4(o + 4)
#define WG_REGS_16(o) WG_REGS_8(o), WG_REGS_8(o + 8)
#define WG_REGS_32(o) WG_REGS_16(o), WG_REGS_16(o + 16)

__device__ __forceinline__ void wgmma_ss_n80_tb(float (&d)[40], uint64_t dA, uint64_t dB, int sc) {
    asm volatile("{\n.reg .pred p;\nsetp.ne.b32 p, %42, 0;\n"
                 "wgmma.mma_async.sync.aligned.m64n80k16.f32.bf16.bf16 "
                 "{%0,%1,%2,%3,%4,%5,%6,%7,%8,%9,%10,%11,%12,%13,%14,%15,%16,%17,%18,%19,%20,%21,%22,%23,%24,%25,%26,%27,%28,%29,%30,%31,"
                 "%32,%33,%34,%35,%36,%37,%38,%39}, %40, %41, p, 1, 1, 0, 1;\n}\n"
                 : WG_REGS_32(0), WG_REGS_8(32) : "l"(dA), "l"(dB), "r"(sc));
}
__device__ __forceinline__ void wgmma_ss_n64_tb(float (&d)[32], uint64_t dA, uint64_t dB, int sc) {
    asm volatile("{\n.reg .pred p;\nsetp.ne.b32 p, %34, 0;\n"
                 "wgmma.mma_async.sync.aligned.m64n64k16.f32.bf16.bf16 "
                 "{%0,%1,%2,%3,%4,%5,%6,%7,%8,%9,%10,%11,%12,%13,%14,%15,%16,%17,%18,%19,%20,%21,%22,%23,%24,%25,%26,%27,%28,%29,%30,%31}, "
                 "%32, %33, p, 1, 1, 0, 1;\n}\n"
                 : WG_REGS_32(0) : "l"(dA), "l"(dB), "r"(sc));
}
__device__ __forceinline__ void wgmma_ss_n224_tb(float (&d)[112], uint64_t dA, uint64_t dB, int sc) {
    asm volatile("{\n.reg .pred p;\nsetp.ne.b32 p, %114, 0;\n"
                 "wgmma.mma_async.sync.aligned.m64n224k16.f32.bf16.bf16 "
                 "{%0,%1,%2,%3,%4,%5,%6,%7,%8,%9,%10,%11,%12,%13,%14,%15,%16,%17,%18,%19,%20,%21,%22,%23,%24,%25,%26,%27,%28,%29,%30,%31,"
                 "%32,%33,%34,%35,%36,%37,%38,%39,%40,%41,%42,%43,%44,%45,%46,%47,%48,%49,%50,%51,%52,%53,%54,%55,%56,%57,%58,%59,%60,%61,%62,%63,"
                 "%64,%65,%66,%67,%68,%69,%70,%71,%72,%73,%74,%75,%76,%77,%78,%79,%80,%81,%82,%83,%84,%85,%86,%87,%88,%89,%90,%91,%92,%93,%94,%95,"
                 "%96,%97,%98,%99,%100,%101,%102,%103,%104,%105,%106,%107,%108,%109,%110,%111}, "
                 "%112, %113, p, 1, 1, 0, 1;\n}\n"
                 : WG_REGS_32(0), WG_REGS_32(32), WG_REGS_32(64), WG_REGS_16(96) : "l"(dA), "l"(dB), "r"(sc));
}
template <int BN> __device__ __forceinline__ void wgmma_ss_tb(float (&d)[BN / 2], uint64_t dA, uint64_t dB, int sc) {
    if constexpr (BN == 64) wgmma_ss_n64_tb(d, dA, dB, sc);
    else if constexpr (BN == 80) wgmma_ss_n80_tb(d, dA, dB, sc);
    else wgmma_ss_n224_tb(d, dA, dB, sc);
}
__device__ __forceinline__ void wgmma_rs_n64_tb(float (&d)[32], uint32_t a, uint64_t dB, int sc) {
    asm volatile("{\n.reg .pred p;\nsetp.ne.b32 p, %34, 0;\n"
                 "wgmma.mma_async.sync.aligned.m64n64k16.f32.bf16.bf16 "
                 "{%0,%1,%2,%3,%4,%5,%6,%7,%8,%9,%10,%11,%12,%13,%14,%15,%16,%17,%18,%19,%20,%21,%22,%23,%24,%25,%26,%27,%28,%29,%30,%31}, "
                 "{%32,%32,%32,%32}, %33, p, 1, 1, 1;\n}\n"
                 : WG_REGS_32(0) : "r"(a), "l"(dB), "r"(sc));
}
__device__ __forceinline__ void wgmma_rs_n80_tb(float (&d)[40], uint32_t a, uint64_t dB, int sc) {
    asm volatile("{\n.reg .pred p;\nsetp.ne.b32 p, %42, 0;\n"
                 "wgmma.mma_async.sync.aligned.m64n80k16.f32.bf16.bf16 "
                 "{%0,%1,%2,%3,%4,%5,%6,%7,%8,%9,%10,%11,%12,%13,%14,%15,%16,%17,%18,%19,%20,%21,%22,%23,%24,%25,%26,%27,%28,%29,%30,%31,"
                 "%32,%33,%34,%35,%36,%37,%38,%39}, {%40,%40,%40,%40}, %41, p, 1, 1, 1;\n}\n"
                 : WG_REGS_32(0), WG_REGS_8(32) : "r"(a), "l"(dB), "r"(sc));
}
template <int BN> __device__ __forceinline__ void wgmma_rs_ones(float (&d)[BN / 2], uint64_t dB, int sc) {
    if constexpr (BN == 80) wgmma_rs_n80_tb(d, 0x3F803F80u, dB, sc);
    else if constexpr (BN == 64) wgmma_rs_n64_tb(d, 0x3F803F80u, dB, sc);
}
__device__ __forceinline__ void wgmma_rs_n64_z(float (&d)[32], uint32_t a0, uint32_t a1, uint32_t a2, uint32_t a3, uint64_t dB) {
    asm volatile("{\n.reg .pred p;\nsetp.ne.b32 p, 0, 0;\n"
                 "wgmma.mma_async.sync.aligned.m64n64k16.f32.bf16.bf16 "
                 "{%0,%1,%2,%3,%4,%5,%6,%7,%8,%9,%10,%11,%12,%13,%14,%15,%16,%17,%18,%19,%20,%21,%22,%23,%24,%25,%26,%27,%28,%29,%30,%31}, "
                 "{%32,%33,%34,%35}, %36, p, 1, 1, 0;\n}\n"
                 : "=f"(d[0]), "=f"(d[1]), "=f"(d[2]), "=f"(d[3]), "=f"(d[4]), "=f"(d[5]), "=f"(d[6]), "=f"(d[7]),
                   "=f"(d[8]), "=f"(d[9]), "=f"(d[10]), "=f"(d[11]), "=f"(d[12]), "=f"(d[13]), "=f"(d[14]), "=f"(d[15]),
                   "=f"(d[16]), "=f"(d[17]), "=f"(d[18]), "=f"(d[19]), "=f"(d[20]), "=f"(d[21]), "=f"(d[22]), "=f"(d[23]),
                   "=f"(d[24]), "=f"(d[25]), "=f"(d[26]), "=f"(d[27]), "=f"(d[28]), "=f"(d[29]), "=f"(d[30]), "=f"(d[31])
                 : "r"(a0), "r"(a1), "r"(a2), "r"(a3), "l"(dB));
}
__device__ __forceinline__ void wgmma_rs_n24_tb(float (&d)[12], uint32_t a0, uint32_t a1, uint32_t a2, uint32_t a3, uint64_t dB) {
    asm volatile("{\n.reg .pred p;\nsetp.eq.b32 p, 0, 0;\n"
                 "wgmma.mma_async.sync.aligned.m64n24k16.f32.bf16.bf16 "
                 "{%0,%1,%2,%3,%4,%5,%6,%7,%8,%9,%10,%11}, {%12,%13,%14,%15}, %16, p, 1, 1, 1;\n}\n"
                 : WG_REGS_8(0), WG_REGS_4(8) : "r"(a0), "r"(a1), "r"(a2), "r"(a3), "l"(dB));
}

constexpr int SIDE_CTAS = 4;
__device__ __forceinline__ void side_job(int cta, float* red  , const __nv_bfloat16* __restrict__ wo,
                                         const __nv_bfloat16* __restrict__ w1, const __nv_bfloat16* __restrict__ w2) {
    const int tid = threadIdx.x, warp = tid >> 5, lane = tid & 31;
    for (int line = cta * 512 + tid; line < 18432; line += SIDE_CTAS * 512) {
        const char* p = line < 4096 ? (const char*)wo + (size_t)line * 128 : (const char*)w2 + (size_t)(line - 4096) * 128;
        asm volatile("prefetch.global.L2 [%0];" ::"l"(p));
    }
    const int rg = lane >> 3, c8 = lane & 7;
    for (int slab = cta; slab < F_ / 64; slab += SIDE_CTAS) {
        const __nv_bfloat16* base = w1 + slab * 64 + c8 * 8;
        uint4 v[8];
#pragma unroll
        for (int i = 0; i < 8; i++) v[i] = __ldg((const uint4*)(base + (size_t)(warp * 32 + rg + 4 * i) * F_));
        float acc[8];
#pragma unroll
        for (int i = 0; i < 8; i++) acc[i] = 0.f;
#pragma unroll
        for (int i = 0; i < 8; i++) {
            acc[0] += bf_lo(v[i].x); acc[1] += bf_hi(v[i].x); acc[2] += bf_lo(v[i].y); acc[3] += bf_hi(v[i].y);
            acc[4] += bf_lo(v[i].z); acc[5] += bf_hi(v[i].z); acc[6] += bf_lo(v[i].w); acc[7] += bf_hi(v[i].w);
        }
#pragma unroll
        for (int i = 0; i < 8; i++) {
            acc[i] += __shfl_xor_sync(0xffffffffu, acc[i], 8);
            acc[i] += __shfl_xor_sync(0xffffffffu, acc[i], 16);
        }
        if (rg == 0) {
#pragma unroll
            for (int i = 0; i < 8; i++) red[warp * 64 + c8 * 8 + i] = acc[i];
        }
        __syncthreads();
        if (tid < 64) {
            float s = 0.f;
#pragma unroll
            for (int i = 0; i < 16; i++) s += red[i * 64 + tid];
            g_cs_1[slab * 64 + tid] = s;
        }
        __syncthreads();
    }
}

enum { EPI_QKV = 0, EPI_RES = 1, EPI_FFN1 = 2 };

struct GemmParams {
    const float2* stats_in;
    float2* stats_out;
    const __nv_bfloat16* wkv;
    const __nv_bfloat16* wv;
    int tk;
};

template <int BK_, int NBLK> struct Geo {
    static constexpr int BK = BK_, A_BYTES = 128 * BK * 2, A_SWZ = BK == 64 ? 1 : 2, A_SBO = BK * 16;
    static constexpr int BLK = BK * 64;
    static constexpr int B_BYTES = NBLK * BLK, B_SWZ = 2, B_LBO = BLK, B_SBO = 512, B_KSTEP = 1024;
};
template <> struct Geo<64, 0> {
    static constexpr int BK = 64, A_BYTES = 128 * 128, A_SWZ = 1, A_SBO = 1024, BLK = 8192;
    static constexpr int B_BYTES = 64 * 128, B_SWZ = 1, B_LBO = 8192, B_SBO = 1024, B_KSTEP = 2048;
};
#define F1_BK 32
template <int EPI> struct EpiGeo;
template <> struct EpiGeo<EPI_QKV> { using G = Geo<64, 3>; };
template <> struct EpiGeo<EPI_RES> { using G = Geo<64, 0>; };
template <> struct EpiGeo<EPI_FFN1> { using G = Geo<F1_BK, 7>; };

template <int STAGES, int EPI> struct GemmSmem {
    using G = typename EpiGeo<EPI>::G;
    static constexpr int STAGE = G::A_BYTES + G::B_BYTES;
    static constexpr int AUX_OFF = STAGES * STAGE;
    static constexpr int TOTAL = AUX_OFF + 1152;
    static constexpr int TOTAL_SELF = AUX_OFF + 704 + 1024 + 1280;
};

struct RowStatRaw { float2 a0, a1, b0, b1; };
__device__ __forceinline__ RowStatRaw load_row_stats(const float2* __restrict__ st, int row0, int c) {
    RowStatRaw r;
    r.a0 = st[(2 * c) * S_ + row0]; r.a1 = st[(2 * c + 1) * S_ + row0];
    r.b0 = st[(2 * c) * S_ + row0 + 8]; r.b1 = st[(2 * c + 1) * S_ + row0 + 8];
    return r;
}
__device__ __forceinline__ void finish_row_stats(const RowStatRaw& r, float& mean0, float& rstd0, float& mean1, float& rstd1) {
    float sa = r.a0.x + r.a1.x, sb = r.b0.x + r.b1.x;
    sa += __shfl_xor_sync(0xffffffffu, sa, 1); sa += __shfl_xor_sync(0xffffffffu, sa, 2);
    sb += __shfl_xor_sync(0xffffffffu, sb, 1); sb += __shfl_xor_sync(0xffffffffu, sb, 2);
    mean0 = sa * 0.125f; mean1 = sb * 0.125f;
    float ma = r.a0.y + r.a1.y + 64.f * ((r.a0.x - mean0) * (r.a0.x - mean0) + (r.a1.x - mean0) * (r.a1.x - mean0));
    float mb = r.b0.y + r.b1.y + 64.f * ((r.b0.x - mean1) * (r.b0.x - mean1) + (r.b1.x - mean1) * (r.b1.x - mean1));
    ma += __shfl_xor_sync(0xffffffffu, ma, 1); ma += __shfl_xor_sync(0xffffffffu, ma, 2);
    mb += __shfl_xor_sync(0xffffffffu, mb, 1); mb += __shfl_xor_sync(0xffffffffu, mb, 2);
    rstd0 = 1.0f / sqrtf(ma * (1.f / 512.f) + 1e-5f);
    rstd1 = 1.0f / sqrtf(mb * (1.f / 512.f) + 1e-5f);
}

template <int BN, int KB, int STAGES, int EPI, int MC, bool SELF = false>
__device__ __forceinline__ void gemm_body(const CUtensorMap* mapA, const CUtensorMap* mapB, const CUtensorMap* mapB2, const CUtensorMap* mapR,
                                          const CUtensorMap* mapC, const GemmParams& prm, int tile_m, int tile_n, uint8_t* smem_raw) {
    using SM = GemmSmem<STAGES, EPI>;
    using G = typename SM::G;
    constexpr bool XKV = BN == 80;
    constexpr int TN = EPI == EPI_QKV ? 64 : BN;
    pdl_launch();
    const uint32_t sbase = smem_u32(smem_raw);
    if (sbase & 1023) __trap();
    uint8_t* sgen = smem_raw;
    const uint32_t bar_full = sbase + SM::AUX_OFF, bar_empty = bar_full + 8 * STAGES;
    float* s_cs = (float*)(sgen + SM::AUX_OFF + 256);
    float* s_row = (float*)(sgen + SM::AUX_OFF + 704);
    float* s_red = (float*)(sgen + SM::AUX_OFF + 640);
    const int tid = threadIdx.x, lane = tid & 31;
    const int warp = __shfl_sync(0xffffffffu, tid >> 5, 0);
    const uint32_t rank = MC ? cluster_rank() : 0;
    if (tid == 0) TL(prm.tk, 0);

    constexpr bool INLINE_PROD = EPI == EPI_FFN1 && F1_INLINE;
    constexpr int PWARP = INLINE_PROD ? 0 : 8;
    if (warp == PWARP && elect_one()) {
        prefetch_tmap(mapB); prefetch_tmap(mapA); prefetch_tmap(mapC);
        for (int s = 0; s < STAGES; s++) { mbar_init(bar_full + 8 * s, 1); mbar_init(bar_empty + 8 * s, MC ? 4 : 2); }
        fence_mbar_init();
    }
    __syncthreads();
    if (MC) asm volatile("barrier.cluster.arrive.release.aligned;" ::: "memory");
    auto cluster_wait = [&]() { if (MC) asm volatile("barrier.cluster.wait.acquire.aligned;" ::: "memory"); };

    const int m0 = tile_m * 128, n0 = tile_n * TN;
    constexpr uint32_t STAGE_TX = G::A_BYTES + (EPI == EPI_QKV ? 2 * G::BLK : G::B_BYTES);
    auto loadB = [&](int kb, int s) {
        const uint32_t dst = sbase + s * SM::STAGE + G::A_BYTES, bar = bar_full + 8 * s;
        if constexpr (EPI == EPI_RES) {
            tma2d(dst, mapB, n0, kb * 64, bar);
        } else if constexpr (EPI == EPI_QKV) {
            tma3d(dst, mapB, 0, kb * G::BK, tile_n * 2, bar);
        } else {
            if constexpr (MC == 2) {
                if (rank == 0) tma3d_mc(dst, mapB, 0, kb * G::BK, tile_n * 7, bar, 3);
                else tma3d_mc(dst + 4 * G::BLK, mapB2, 0, kb * G::BK, tile_n * 7 + 4, bar, 3);
            } else {
                tma3d(dst, mapB, 0, kb * G::BK, tile_n * 7, bar);
                tma3d(dst + 4 * G::BLK, mapB2, 0, kb * G::BK, tile_n * 7 + 4, bar);
            }
        }
    };
    auto loadA = [&](int kb, int s) {
        const uint32_t dst = sbase + s * SM::STAGE, bar = bar_full + 8 * s;
        if constexpr (MC == 1) tma2d_mc(dst + rank * (G::A_BYTES / 2), mapA, kb * G::BK, m0 + rank * 64, bar, 3);
        else tma2d(dst, mapA, kb * G::BK, m0, bar);
    };
    constexpr int PRE = STAGES < KB ? STAGES : KB;
#define F1_LAG 2
    constexpr int LAG = F1_LAG;
    constexpr int PRE_B = PRE < PREB ? PRE : PREB;
    auto prologue_loads = [&]() {
        if (elect_one()) {
#pragma unroll
            for (int kb = 0; kb < PRE; kb++) mbar_expect_tx(bar_full + 8 * kb, STAGE_TX);
        }
        cluster_wait();
        if (elect_one()) {
#pragma unroll
            for (int kb = 0; kb < PRE_B; kb++) loadB(kb, kb);
        }
        if (!SELF) pdl_wait();
        if (elect_one()) {
#pragma unroll
            for (int kb = 0; kb < PRE; kb++) {
                loadA(kb, kb);
                if (kb + PRE_B < PRE) loadB(kb + PRE_B, kb + PRE_B);
            }
            if constexpr (EPI == EPI_RES && KB < STAGES) {
                mbar_expect_tx(bar_full + 8 * KB, 16384);
                tma2d(sbase + KB * SM::STAGE, mapR, n0, m0, bar_full + 8 * KB);
            }
        }
    };
    if (SELF && warp > 8) {
        static_assert(!SELF || (STAGES >= KB && EPI == EPI_QKV), "SELF needs every k block resident");
        if ((warp >> 2) == 3) {
            float csum[BN / 2];
            const uint64_t dB0 = mkdesc(sbase + G::A_BYTES, G::B_LBO, G::B_SBO, G::B_SWZ);
            if constexpr (XKV) named_bar(6, 384);
#pragma unroll 1
            for (int kb = 0; kb < KB; kb++) {
                mbar_wait(bar_full + 8 * kb, 0);
                const uint64_t dB = dB0 + (uint64_t)(kb * (SM::STAGE >> 4));
                wg_fence();
#pragma unroll
                for (int k = 0; k < G::BK / 16; k++) {
                    if constexpr (SELF) wgmma_rs_ones<BN>(csum, dB + (uint64_t)(k * (G::B_KSTEP >> 4)), (kb | k) != 0);
                }
                wg_commit();
            }
            wg_wait<0>();
            fence_regs(csum);
            if (warp == 12 && lane < 4) {
#pragma unroll
                for (int j = 0; j < BN / 8; j++) {
                    const float2 v = make_float2(csum[4 * j], csum[4 * j + 1]);
                    *(float2*)(s_cs + 8 * j + 2 * lane) = v;
                    if (tile_m == 0) {
                        if (j < 8) *(float2*)(g_cs_q + n0 + 8 * j + 2 * lane) = v;
                        else *(float2*)(g_cs_kv + tile_n * 16 + 8 * (j - 8) + 2 * lane) = v;
                    }
                }
            }
        } else {
            const int t = (warp < 12 ? warp - 9 : warp - 13) * 32 + lane;
            float ss[4] = {0.f, 0.f, 0.f, 0.f}, sq[4] = {0.f, 0.f, 0.f, 0.f};
#pragma unroll 1
            for (int kb = 0; kb < KB; kb++) {
                mbar_wait(bar_full + 8 * kb, 0);
                const uint32_t arow = sbase + kb * SM::STAGE + (t >> 1) * 128;
                uint32_t w[4][4];
#pragma unroll
                for (int j = 0; j < 4; j++)
                    asm volatile("ld.shared.v4.u32 {%0,%1,%2,%3}, [%4];" : "=r"(w[j][0]), "=r"(w[j][1]), "=r"(w[j][2]), "=r"(w[j][3])
                                 : "r"(arow + (((2 * j + (t & 1) + 2 * ((t >> 1) & 3)) & 7) << 4)));
#pragma unroll
                for (int j = 0; j < 4; j++)
#pragma unroll
                    for (int i = 0; i < 4; i++) {
                        const float lo = bf_lo(w[j][i]), hi = bf_hi(w[j][i]);
                        ss[i] += lo + hi;
                        sq[i] = fmaf(lo, lo, fmaf(hi, hi, sq[i]));
                    }
            }
            float tsum = (ss[0] + ss[1]) + (ss[2] + ss[3]), tsq = (sq[0] + sq[1]) + (sq[2] + sq[3]);
            tsum += __shfl_xor_sync(0xffffffffu, tsum, 1);
            tsq += __shfl_xor_sync(0xffffffffu, tsq, 1);
            if ((t & 1) == 0) {
                const float md = tsum * (1.f / 512.f);
                const float var = fmaxf(tsq * (1.f / 512.f) - md * md, 0.f);
                *(float2*)(s_row + t) = make_float2(md, 1.0f / sqrtf(var + 1e-5f));
            }
        }
        named_bar(4, 640);
    } else if (!INLINE_PROD && warp == 8) {
        prologue_loads();
        int s = PRE % STAGES, ph = (PRE / STAGES) & 1;
#pragma unroll 1
        for (int kb = PRE; kb < KB; kb++) {
            mbar_wait(bar_empty + 8 * s, ph ^ 1);
            if (elect_one()) {
                mbar_expect_tx(bar_full + 8 * s, STAGE_TX);
                loadB(kb, s);
                loadA(kb, s);
            }
            if (++s == STAGES) { s = 0; ph ^= 1; }
        }
        if constexpr (EPI == EPI_RES && KB >= STAGES) {
            mbar_wait(bar_empty + 8 * s, ph ^ 1);
            if (elect_one()) {
                mbar_expect_tx(bar_full + 8 * s, 16384);
                tma2d(sbase + s * SM::STAGE, mapR, n0, m0, bar_full + 8 * s);
            }
        }
    } else {
        if (INLINE_PROD && warp == 0) prologue_loads(); else cluster_wait();
        const int wg = warp >> 2, g = lane >> 2, c = lane & 3;
        const int rloc = wg * 64 + (warp & 3) * 16 + g;
        const int row0 = m0 + rloc;
        float mean0 = 0.f, rstd0 = 1.f, mean1 = 0.f, rstd1 = 1.f;
        if constexpr (XKV) {
            static_assert(!XKV || STAGES >= KB, "the K / V weight block must stay resident");
            const __nv_bfloat16* wsrc = tile_n == 0 ? prm.wkv : prm.wv;
            uint4 v[4];
#pragma unroll
            for (int i = 0; i < 4; i++) v[i] = __ldg((const uint4*)wsrc + tid + 256 * i);
#pragma unroll
            for (int i = 0; i < 4; i++) {
                const int idx = tid + 256 * i, k = idx >> 1, kr = k & 63;
                const uint32_t dst = sbase + (k >> 6) * SM::STAGE + G::A_BYTES + 2 * G::BLK + kr * 64 + (((idx & 1) ^ ((kr >> 1) & 3)) << 4);
                asm volatile("st.shared.v4.u32 [%0], {%1,%2,%3,%4};" ::"r"(dst), "r"(v[i].x), "r"(v[i].y), "r"(v[i].z), "r"(v[i].w) : "memory");
            }
            fence_async_smem();
            if constexpr (SELF) named_bar(6, 384); else named_bar(6, 256);
        }
        RowStatRaw raw;
        float csv = 0.f;
        float2 cskv[2] = {make_float2(0.f, 0.f), make_float2(0.f, 0.f)};
        auto ln_inputs = [&]() {
            pdl_wait();
            if constexpr (EPI != EPI_RES) {
                raw = load_row_stats(prm.stats_in, row0, c);
                const float* cs = EPI == EPI_FFN1 ? g_cs_1 + n0 : g_cs_q + n0;
                if (tid < TN) csv = cs[tid];
                if constexpr (XKV) {
                    cskv[0] = *(const float2*)(g_cs_kv + tile_n * 16 + 2 * c);
                    cskv[1] = *(const float2*)(g_cs_kv + tile_n * 16 + 8 + 2 * c);
                }
            }
        };
        if (!SELF) ln_inputs();
        float acc[BN / 2];
        const uint64_t dA0 = mkdesc(sbase + wg * (G::A_BYTES / 2), 16, G::A_SBO, G::A_SWZ);
        const uint64_t dB0 = mkdesc(sbase + G::A_BYTES, G::B_LBO, G::B_SBO, G::B_SWZ);
        int s = 0, ph = 0;
#pragma unroll 1
        for (int kb = 0; kb < KB; kb++) {
            mbar_wait(bar_full + 8 * s, ph);
            const uint64_t dA = dA0 + (uint64_t)(s * (SM::STAGE >> 4)), dB = dB0 + (uint64_t)(s * (SM::STAGE >> 4));
            wg_fence();
#pragma unroll
            for (int k = 0; k < G::BK / 16; k++) wgmma_ss_tb<BN>(acc, dA + (uint64_t)(k * 2), dB + (uint64_t)(k * (G::B_KSTEP >> 4)), (kb | k) != 0);
            wg_commit();
            if constexpr (EPI == EPI_RES && RES_WAIT0) {
                wg_wait<0>();
                if ((warp & 3) == 0 && elect_one()) {
                    if (MC) { mbar_arrive_remote(bar_empty + 8 * s, 0); mbar_arrive_remote(bar_empty + 8 * s, 1); }
                    else mbar_arrive(bar_empty + 8 * s);
                }
            } else if (kb > 0) {
                wg_wait<1>();
                const int sp = s == 0 ? STAGES - 1 : s - 1;
                if ((warp & 3) == 0 && elect_one()) {
                    if (MC) { mbar_arrive_remote(bar_empty + 8 * sp, 0); mbar_arrive_remote(bar_empty + 8 * sp, 1); }
                    else mbar_arrive(bar_empty + 8 * sp);
                }
                if (INLINE_PROD && warp == 0 && kb >= LAG && kb - LAG + STAGES < KB) {
                    const int sq = LAG == 1 ? sp : (sp == 0 ? STAGES - 1 : sp - 1);
                    mbar_wait(bar_empty + 8 * sq, ((kb - LAG) / STAGES) & 1);
                    if (elect_one()) {
                        mbar_expect_tx(bar_full + 8 * sq, STAGE_TX);
                        loadB(kb - LAG + STAGES, sq);
                        loadA(kb - LAG + STAGES, sq);
                    }
                }
            }
            if (++s == STAGES) { s = 0; ph ^= 1; }
        }
        if constexpr (SELF) {
            named_bar(4, 640);
            const float2 r0 = *(const float2*)(s_row + 2 * rloc), r1 = *(const float2*)(s_row + 2 * rloc + 16);
            mean0 = r0.x; rstd0 = r0.y; mean1 = r1.x; rstd1 = r1.y;
        } else if constexpr (EPI != EPI_RES) {
            finish_row_stats(raw, mean0, rstd0, mean1, rstd1);
            if (tid < TN) s_cs[tid] = csv;
        }
        wg_wait<0>();
        fence_regs(acc);
        if (tid == 0) TL(prm.tk, 2);
        if constexpr (EPI != EPI_RES) named_bar(1, 256);

        if constexpr (EPI != EPI_FFN1) {
            const uint32_t stile = sbase + (EPI == EPI_RES ? s * SM::STAGE : 0);
            const int mrow = wg * 64 + (warp & 3) * 16 + (lane & 7) + ((lane >> 3) & 1) * 8;
            const uint32_t rbase = stile + mrow * 128;
            if constexpr (EPI == EPI_RES) {
                mbar_wait(bar_full + 8 * s, ph);
                float s0 = 0.f, s1 = 0.f;
#pragma unroll
                for (int jj = 0; jj < 4; jj++) {
                    uint32_t r0, r1, r2, r3;
                    const uint32_t addr = rbase + (((2 * jj + (lane >> 4)) ^ (mrow & 7)) << 4);
                    ldsm_x4(r0, r1, r2, r3, addr);
                    const uint32_t u0 = pack_bf16(acc[8 * jj] + bf_lo(r0), acc[8 * jj + 1] + bf_hi(r0));
                    const uint32_t u1 = pack_bf16(acc[8 * jj + 2] + bf_lo(r1), acc[8 * jj + 3] + bf_hi(r1));
                    const uint32_t u2 = pack_bf16(acc[8 * jj + 4] + bf_lo(r2), acc[8 * jj + 5] + bf_hi(r2));
                    const uint32_t u3 = pack_bf16(acc[8 * jj + 6] + bf_lo(r3), acc[8 * jj + 7] + bf_hi(r3));
                    stsm_x4(addr, u0, u1, u2, u3);
                    acc[8 * jj] = bf_lo(u0); acc[8 * jj + 1] = bf_hi(u0); acc[8 * jj + 4] = bf_lo(u2); acc[8 * jj + 5] = bf_hi(u2);
                    acc[8 * jj + 2] = bf_lo(u1); acc[8 * jj + 3] = bf_hi(u1); acc[8 * jj + 6] = bf_lo(u3); acc[8 * jj + 7] = bf_hi(u3);
                    s0 += (acc[8 * jj] + acc[8 * jj + 1]) + (acc[8 * jj + 4] + acc[8 * jj + 5]);
                    s1 += (acc[8 * jj + 2] + acc[8 * jj + 3]) + (acc[8 * jj + 6] + acc[8 * jj + 7]);
                }
                fence_async_smem();
                named_bar(2 + wg, 128);
                if ((warp & 3) == 0 && elect_one()) { tma2d_store(mapC, stile + wg * 8192, n0, m0 + wg * 64); bulk_commit(); }
                if (prm.stats_out) {
                    s0 += __shfl_xor_sync(0xffffffffu, s0, 1); s0 += __shfl_xor_sync(0xffffffffu, s0, 2);
                    s1 += __shfl_xor_sync(0xffffffffu, s1, 1); s1 += __shfl_xor_sync(0xffffffffu, s1, 2);
                    const float mu0 = s0 * (1.f / 64.f), mu1 = s1 * (1.f / 64.f);
                    float q0 = 0.f, q1 = 0.f;
#pragma unroll
                    for (int j = 0; j < 8; j++) {
                        float d;
                        d = acc[4 * j] - mu0; q0 += d * d; d = acc[4 * j + 1] - mu0; q0 += d * d;
                        d = acc[4 * j + 2] - mu1; q1 += d * d; d = acc[4 * j + 3] - mu1; q1 += d * d;
                    }
                    q0 += __shfl_xor_sync(0xffffffffu, q0, 1); q0 += __shfl_xor_sync(0xffffffffu, q0, 2);
                    q1 += __shfl_xor_sync(0xffffffffu, q1, 1); q1 += __shfl_xor_sync(0xffffffffu, q1, 2);
                    if (c == 0) {
                        prm.stats_out[tile_n * S_ + row0] = make_float2(mu0, q0);
                        prm.stats_out[tile_n * S_ + row0 + 8] = make_float2(mu1, q1);
                    }
                }
            } else {
                const float sc = 0.25f * 1.4426950408889634f;
                const float a0 = rstd0 * sc, a1 = rstd1 * sc, rm0 = a0 * mean0, rm1 = a1 * mean1;
#pragma unroll
                for (int jj = 0; jj < 4; jj++) {
                    const float2 ca = *(const float2*)(s_cs + 16 * jj + 2 * c), cb = *(const float2*)(s_cs + 16 * jj + 8 + 2 * c);
                    const uint32_t u0 = pack_bf16(acc[8 * jj] * a0 - rm0 * ca.x, acc[8 * jj + 1] * a0 - rm0 * ca.y);
                    const uint32_t u1 = pack_bf16(acc[8 * jj + 2] * a1 - rm1 * ca.x, acc[8 * jj + 3] * a1 - rm1 * ca.y);
                    const uint32_t u2 = pack_bf16(acc[8 * jj + 4] * a0 - rm0 * cb.x, acc[8 * jj + 5] * a0 - rm0 * cb.y);
                    const uint32_t u3 = pack_bf16(acc[8 * jj + 6] * a1 - rm1 * cb.x, acc[8 * jj + 7] * a1 - rm1 * cb.y);
                    stsm_x4(rbase + (((2 * jj + (lane >> 4)) ^ (mrow & 7)) << 4), u0, u1, u2, u3);
                }
                fence_async_smem();
                named_bar(2 + wg, 128);
                if ((warp & 3) == 0 && elect_one()) { tma2d_store(mapC, stile + wg * 8192, n0, m0 + wg * 64); bulk_commit(); }
            }
            if constexpr (XKV) {
                {
                    const float* acx = &acc[32];
                    const float rm0 = rstd0 * mean0, rm1 = rstd1 * mean1;
                    float n0s = 0.f, n1s = 0.f, vmax = 0.f;
#pragma unroll
                    for (int j = 0; j < 2; j++) {
                        const float2 cs2 = SELF ? *(const float2*)(s_cs + 64 + 8 * j + 2 * c) : cskv[j];
                        const uint32_t u0 = pack_bf16(acx[4 * j] * rstd0 - rm0 * cs2.x, acx[4 * j + 1] * rstd0 - rm0 * cs2.y);
                        const uint32_t u1 = pack_bf16(acx[4 * j + 2] * rstd1 - rm1 * cs2.x, acx[4 * j + 3] * rstd1 - rm1 * cs2.y);
                        n0s += bf_lo(u0) * bf_lo(u0) + bf_hi(u0) * bf_hi(u0);
                        n1s += bf_lo(u1) * bf_lo(u1) + bf_hi(u1) * bf_hi(u1);
                        vmax = fmaxf(vmax, fmaxf(fmaxf(fabsf(bf_lo(u0)), fabsf(bf_hi(u0))), fmaxf(fabsf(bf_lo(u1)), fabsf(bf_hi(u1)))));
                        if (tile_n == 0) {
                            *(uint32_t*)(g_kimg + (row0 >> 3) * 256 + j * 128 + g * 16 + c * 4) = u0;
                            *(uint32_t*)(g_kimg + ((row0 + 8) >> 3) * 256 + j * 128 + g * 16 + c * 4) = u1;
                        } else {
                            uint8_t* vb = g_vimg + (row0 >> 4) * 768 + j * 256 + g * 16 + c * 4;
                            *(uint32_t*)(vb) = u0;
                            *(uint32_t*)(vb + 128) = u1;
                        }
                    }
                    if (tile_n == 1) {
                        uint8_t* vb = g_vimg + (row0 >> 4) * 768 + 512 + g * 16 + c * 4;
                        const uint32_t one = c == 0 ? 0x00003F80u : 0u;
                        *(uint32_t*)(vb) = one;
                        *(uint32_t*)(vb + 128) = one;
                    }
                    n0s += __shfl_xor_sync(0xffffffffu, n0s, 1); n0s += __shfl_xor_sync(0xffffffffu, n0s, 2);
                    n1s += __shfl_xor_sync(0xffffffffu, n1s, 1); n1s += __shfl_xor_sync(0xffffffffu, n1s, 2);
                    float km = tile_n == 0 ? fmaxf(n0s, n1s) : vmax;
                    if (!(n0s + n1s < INFINITY)) km = INFINITY;
#pragma unroll
                    for (int o = 1; o < 32; o <<= 1) km = fmaxf(km, __shfl_xor_sync(0xffffffffu, km, o));
                    if (lane == 0) s_red[warp] = km;
                    named_bar(1, 256);
                    if (tid == 0) {
                        float a = 0.f;
                        for (int i = 0; i < 8; i++) a = fmaxf(a, s_red[i]);
                        g_kvmax[tile_n * 16 + tile_m] = a;
                    }
                }
            }
            if ((warp & 3) == 0) bulk_wait_read();
        } else {
            const uint32_t stile = sbase + wg * (7 * 4096);
            const int mrow = (warp & 3) * 16 + (lane & 7) + ((lane >> 3) & 1) * 8;
            const float a0 = 0.5f * rstd0, a1 = 0.5f * rstd1, rm0 = a0 * mean0, rm1 = a1 * mean1;
#pragma unroll
            for (int jj = 0; jj < 14; jj++) {
                const float2 ca = *(const float2*)(s_cs + 16 * jj + 2 * c), cb = *(const float2*)(s_cs + 16 * jj + 8 + 2 * c);
                float y[8] = {acc[8 * jj] * a0 - rm0 * ca.x,     acc[8 * jj + 1] * a0 - rm0 * ca.y,
                              acc[8 * jj + 2] * a1 - rm1 * ca.x, acc[8 * jj + 3] * a1 - rm1 * ca.y,
                              acc[8 * jj + 4] * a0 - rm0 * cb.x, acc[8 * jj + 5] * a0 - rm0 * cb.y,
                              acc[8 * jj + 6] * a1 - rm1 * cb.x, acc[8 * jj + 7] * a1 - rm1 * cb.y};
#pragma unroll
                for (int i = 0; i < 8; i++) {
                    float t;
                    asm("tanh.approx.f32 %0, %1;" : "=f"(t) : "f"(y[i]));
                    y[i] = fmaf(y[i], t, y[i]);
                }
                const int chunk = (2 * jj + (lane >> 4)) & 3, blk = jj >> 1;
                stsm_x4(stile + blk * 4096 + mrow * 64 + ((chunk ^ ((mrow >> 1) & 3)) << 4),
                        pack_bf16(y[0], y[1]), pack_bf16(y[2], y[3]), pack_bf16(y[4], y[5]), pack_bf16(y[6], y[7]));
                if (jj & 1) {
                    fence_async_smem();
                    __syncwarp();
                    if (elect_one()) {
                        tma2d_store(mapC, stile + blk * 4096 + (warp & 3) * 1024, n0 + blk * 32, m0 + wg * 64 + (warp & 3) * 16);
                        bulk_commit();
                    }
                }
            }
            bulk_wait_read();
        }
    }
    if (tid == 0) TL(prm.tk, 3);
    if (MC) cluster_sync();
}

#define WO_ST 9
#define F2_ST 6
#define F1_ST (F1_BK == 64 ? 5 : 9)
#define QKV_ST 8
constexpr int QKV_STAGES = QKV_ST, WO_STAGES = WO_ST, FFN2_STAGES = F2_ST, FFN1_STAGES = F1_ST;
template <bool SELF>
__global__ void __launch_bounds__(SELF ? 672 : 288) qkv_kernel(const __grid_constant__ CUtensorMap mapA, const __grid_constant__ CUtensorMap mapWq,
                                                  const __grid_constant__ CUtensorMap mapQ, const GemmParams prm) {
    extern __shared__ __align__(1024) uint8_t smem_raw[];
    const int tn = blockIdx.x & 7;
    if (tn < 2) gemm_body<80, 8, QKV_STAGES, EPI_QKV, QKV_MC, SELF>(&mapA, &mapWq, &mapWq, &mapA, &mapQ, prm, blockIdx.x >> 3, tn, smem_raw);
    else gemm_body<64, 8, QKV_STAGES, EPI_QKV, QKV_MC, SELF>(&mapA, &mapWq, &mapWq, &mapA, &mapQ, prm, blockIdx.x >> 3, tn, smem_raw);
}
template <int KB, int STAGES>
__global__ void __launch_bounds__(288) res_gemm_kernel(const __grid_constant__ CUtensorMap mapA, const __grid_constant__ CUtensorMap mapW,
                                                       const __grid_constant__ CUtensorMap mapR, const __grid_constant__ CUtensorMap mapC, const GemmParams prm) {
    extern __shared__ __align__(1024) uint8_t smem_raw[];
#define RES_MAP 0
    gemm_body<64, KB, STAGES, EPI_RES, (KB == 8 ? WO_MC : F2_MC)>(&mapA, &mapW, &mapW, &mapR, &mapC, prm, RES_MAP ? blockIdx.x & 15 : blockIdx.x >> 3,
                                                                  RES_MAP ? blockIdx.x >> 4 : blockIdx.x & 7, smem_raw);
}
__global__ void __launch_bounds__(F1_INLINE ? 256 : 288) ffn1_kernel(const __grid_constant__ CUtensorMap mapA, const __grid_constant__ CUtensorMap mapW4,
                                                   const __grid_constant__ CUtensorMap mapW3, const __grid_constant__ CUtensorMap mapH, const GemmParams prm) {
    extern __shared__ __align__(1024) uint8_t smem_raw[];
#define F1_MAP 0
    const int pair = blockIdx.x >> 1;
    const int tile_n = F1_MAP == 0 ? (pair & 7) : F1_MAP == 1 ? (blockIdx.x >> 4) : (blockIdx.x & 7);
    const int tile_m = F1_MAP == 0 ? (pair >> 3) * 2 + (blockIdx.x & 1) : F1_MAP == 1 ? (blockIdx.x & 15) : (blockIdx.x >> 3);
    gemm_body<224, 512 / F1_BK, FFN1_STAGES, EPI_FFN1, F1_MC>(&mapA, &mapW4, &mapW3, &mapA, &mapH, prm, tile_m, tile_n, smem_raw);
}

#define ATT_NPOLY 11
constexpr int NPOLY = ATT_NPOLY;
__host__ __device__ constexpr bool is_mufu(int i) { return ((i + 1) * (16 - NPOLY)) / 16 != (i * (16 - NPOLY)) / 16; }

__device__ __forceinline__ float ex2(float x) { float r; asm("ex2.approx.ftz.f32 %0, %1;" : "=f"(r) : "f"(x)); return r; }
__device__ __forceinline__ uint32_t exp_pair_mufu(float a, float b) { return pack_bf16(ex2(a), ex2(b)); }
__device__ __forceinline__ uint32_t exp_pair_fma(float a, float b, uint32_t c3f) {
    constexpr float MAGIC = 98430.4140625f;
    const float ta = a + MAGIC, tb = b + (MAGIC - 143.5f);
    uint32_t y, m, r;
    asm("mad.lo.u32 %0, %1, 65536, %2;" : "=r"(y) : "r"(__float_as_uint(tb)), "r"(__float_as_uint(ta)));
    asm("lop3.b32 %0, %1, 0x007F007F, %2, 0xEA;" : "=r"(m) : "r"(y), "r"(c3f));
    const uint32_t e = y & 0xFF80FF80u;
    asm("fma.rn.bf16x2 %0, %1, %2, %3;" : "=r"(r) : "r"(y), "r"(m), "r"(e));
    return r;
}

constexpr int KCH = 256, NCH = S_ / KCH;
constexpr int K_BYTES = S_ * 32, V_BYTES = (S_ / 16) * 768;
constexpr int QO_BYTES = 128 * 128;
constexpr int ATT_SMEM = K_BYTES + V_BYTES + QO_BYTES;

__global__ void __launch_bounds__(512, 1) attn_kernel(const __grid_constant__ CUtensorMap mapQ, const __grid_constant__ CUtensorMap mapO,
                                                       const __nv_bfloat16* __restrict__ wo, const __nv_bfloat16* __restrict__ w1,
                                                       const __nv_bfloat16* __restrict__ w2, int tk) {
    extern __shared__ __align__(1024) uint8_t smem[];
    __shared__ uint64_t bars[NCH + 1];
    __shared__ int s_slow;
    const int tid = threadIdx.x, wg = tid >> 7, warp = (tid >> 5) & 3, lane = tid & 31;
    const uint32_t sK = smem_u32(smem), sV = sK + K_BYTES, sQ = sV + V_BYTES;
    if (blockIdx.x >= 128) {
        pdl_launch();
        pdl_wait();
        side_job(blockIdx.x - 128, (float*)smem, wo, w1, w2);
        return;
    }
    CK(tk, 9);
    if (tid == 0) TL(tk, 0);
    if (tid == 0) {
        for (int i = 0; i <= NCH; i++) mbar_init(smem_u32(&bars[i]), 1);
        prefetch_tmap(&mapQ); prefetch_tmap(&mapO);
        s_slow = 0;
        fence_mbar_init();
    }
    __syncthreads();
    pdl_launch();
    CK(tk, 10);
    pdl_wait();
    CK(tk, 11);
    if (tid == 0) TL(tk, 1);
    const int wu = __shfl_sync(0xffffffffu, tid >> 5, 0);
    auto fetch_chunk = [&](int w) {
        if (elect_one()) {
            const uint32_t bar = smem_u32(&bars[w]);
            mbar_expect_tx(bar, KCH * 32 + (KCH / 16) * 768);
            bulk_load(sK + w * KCH * 32, g_kimg + w * KCH * 32, KCH * 32, bar);
            bulk_load(sV + w * (KCH / 16) * 768, g_vimg + w * (KCH / 16) * 768, (KCH / 16) * 768, bar);
        }
    };
    const int tb = blockIdx.x >> 3, hg = blockIdx.x & 7;
    if (wu == 1 && elect_one()) {
        mbar_expect_tx(smem_u32(&bars[NCH]), QO_BYTES);
        tma2d(sQ, &mapQ, hg * 64, tb * 128, smem_u32(&bars[NCH]));
    }
    if (wu == 0) fetch_chunk(0);
    const int g = lane >> 2;
    float kvm = g_kvmax[lane];
    const int lrow = warp * 16 + (lane & 7) + ((lane >> 3) & 1) * 8;
    const uint32_t qoff = lrow * 128 + (((2 * wg + (lane >> 4)) ^ (lrow & 7)) << 4);
    uint32_t qa[2][4];
    mbar_wait(smem_u32(&bars[NCH]), 0);
    ldsm_x4(qa[0][0], qa[0][1], qa[0][2], qa[0][3], sQ + qoff);
    ldsm_x4(qa[1][0], qa[1][1], qa[1][2], qa[1][3], sQ + 8192 + qoff);
    CK(tk, 12);
    {
        float qn = 0.f;
#pragma unroll
        for (int m = 0; m < 2; m++) {
            float n0 = bf_lo(qa[m][0]) * bf_lo(qa[m][0]) + bf_hi(qa[m][0]) * bf_hi(qa[m][0]) + bf_lo(qa[m][2]) * bf_lo(qa[m][2]) + bf_hi(qa[m][2]) * bf_hi(qa[m][2]);
            float n1 = bf_lo(qa[m][1]) * bf_lo(qa[m][1]) + bf_hi(qa[m][1]) * bf_hi(qa[m][1]) + bf_lo(qa[m][3]) * bf_lo(qa[m][3]) + bf_hi(qa[m][3]) * bf_hi(qa[m][3]);
            n0 += __shfl_xor_sync(0xffffffffu, n0, 1); n0 += __shfl_xor_sync(0xffffffffu, n0, 2);
            n1 += __shfl_xor_sync(0xffffffffu, n1, 1); n1 += __shfl_xor_sync(0xffffffffu, n1, 2);
            if (!(n0 == n0) || !(n1 == n1)) n0 = INFINITY;
            qn = fmaxf(qn, fmaxf(n0, n1));
        }
        CK(tk, 13);
#pragma unroll
        for (int o = 1; o < 16; o <<= 1) kvm = fmaxf(kvm, __shfl_xor_sync(0xffffffffu, kvm, o));
        const float km = __shfl_sync(0xffffffffu, kvm, 0), vm = __shfl_sync(0xffffffffu, kvm, 16);
        const bool ok = (qn * km <= 10000.f) && (vm <= 16384.f);
        if (!ok) s_slow = 1;
    }
    CK(tk, 14);
    float oacc[2][12];
#pragma unroll
    for (int m = 0; m < 2; m++)
#pragma unroll
        for (int i = 0; i < 12; i++) oacc[m][i] = 0.f;
    __syncthreads();
    const bool slow = s_slow != 0;
    if (wu >= 1 && wu < NCH) fetch_chunk(wu);
    CK(tk, 15);

    const uint64_t dK0 = mkdesc(sK, 128, 256, 0);
    const uint64_t dV0 = mkdesc(sV, 128, 256, 0);
    uint32_t c3f;
    asm volatile("mov.b32 %0, 0x3F003F00;" : "=r"(c3f));
    if (!slow) {
        uint64_t dK = dK0, dV = dV0;
        float s[32];
        fence_regs(oacc[0]); fence_regs(oacc[1]);
        mbar_wait(smem_u32(&bars[0]), 0);
        wg_fence();
        wgmma_rs_n64_z(s, qa[0][0], qa[0][1], qa[0][2], qa[0][3], dK);
        wg_commit();
#pragma unroll 1
        for (int ch = 0; ch < NCH; ch++) {
#pragma unroll
            for (int tt = 0; tt < KCH / 64; tt++) {
#pragma unroll
                for (int m = 0; m < 2; m++) {
                    wg_wait<0>();
                    fence_regs(s);
                    uint32_t p[16];
#pragma unroll
                    for (int i = 0; i < 16; i++) p[i] = is_mufu(i) ? exp_pair_mufu(s[2 * i], s[2 * i + 1]) : exp_pair_fma(s[2 * i], s[2 * i + 1], c3f);
                    if (m == 1 && tt == KCH / 64 - 1) mbar_wait(smem_u32(&bars[ch + 1 < NCH ? ch + 1 : ch]), 0);
                    wg_fence();
#pragma unroll
                    for (int kk = 0; kk < 4; kk++)
                        wgmma_rs_n24_tb(oacc[m], p[4 * kk], p[4 * kk + 1], p[4 * kk + 2], p[4 * kk + 3], dV + (uint64_t)((tt * 4 + kk) * (768 / 16)));
                    wgmma_rs_n64_z(s, qa[1 - m][0], qa[1 - m][1], qa[1 - m][2], qa[1 - m][3], dK + (uint64_t)((tt + m) * (64 * 32 / 16)));
                    wg_commit();
                }
            }
            dK += KCH * 32 / 16;
            dV += (KCH / 16) * (768 / 16);
        }
        wg_wait<0>();
        fence_regs(s);
    } else {
        float mx[2][2] = {{-INFINITY, -INFINITY}, {-INFINITY, -INFINITY}};
#pragma unroll 1
        for (int t = 0; t < S_ / 64; t++) {
            if ((t & 3) == 0) mbar_wait(smem_u32(&bars[t >> 2]), 0);
            const uint64_t dK = dK0 + (uint64_t)(t * 64 * 32 / 16);
            const uint64_t dV = dV0 + (uint64_t)(t * 4 * 768 / 16);
#pragma unroll
            for (int m = 0; m < 2; m++) {
                float s[32];
                wg_fence();
                wgmma_rs_n64_z(s, qa[m][0], qa[m][1], qa[m][2], qa[m][3], dK);
                wg_commit();
                wg_wait<0>();
                fence_regs(s);
                fence_regs(oacc[m]);
                float r0 = mx[m][0], r1 = mx[m][1];
#pragma unroll
                for (int j = 0; j < 8; j++) {
                    r0 = fmaxf(r0, fmaxf(s[4 * j], s[4 * j + 1]));
                    r1 = fmaxf(r1, fmaxf(s[4 * j + 2], s[4 * j + 3]));
                }
                r0 = fmaxf(r0, __shfl_xor_sync(0xffffffffu, r0, 1)); r0 = fmaxf(r0, __shfl_xor_sync(0xffffffffu, r0, 2));
                r1 = fmaxf(r1, __shfl_xor_sync(0xffffffffu, r1, 1)); r1 = fmaxf(r1, __shfl_xor_sync(0xffffffffu, r1, 2));
                const float al0 = ex2(mx[m][0] - r0), al1 = ex2(mx[m][1] - r1);
                mx[m][0] = r0; mx[m][1] = r1;
#pragma unroll
                for (int j = 0; j < 3; j++) {
                    oacc[m][4 * j] *= al0; oacc[m][4 * j + 1] *= al0;
                    oacc[m][4 * j + 2] *= al1; oacc[m][4 * j + 3] *= al1;
                }
                uint32_t p[16];
#pragma unroll
                for (int j = 0; j < 8; j++) {
                    p[2 * j] = pack_bf16(ex2(s[4 * j] - r0), ex2(s[4 * j + 1] - r0));
                    p[2 * j + 1] = pack_bf16(ex2(s[4 * j + 2] - r1), ex2(s[4 * j + 3] - r1));
                }
                fence_regs(oacc[m]);
                wg_fence();
#pragma unroll
                for (int kk = 0; kk < 4; kk++)
                    wgmma_rs_n24_tb(oacc[m], p[4 * kk], p[4 * kk + 1], p[4 * kk + 2], p[4 * kk + 3], dV + (uint64_t)(kk * 768 / 16));
                wg_commit();
                wg_wait<0>();
            }
        }
    }
    fence_regs(oacc[0]); fence_regs(oacc[1]);
    if (tid == 0) TL(tk, 2);
#pragma unroll
    for (int m = 0; m < 2; m++) {
        const float l0 = __shfl_sync(0xffffffffu, oacc[m][8], lane & ~3);
        const float l1 = __shfl_sync(0xffffffffu, oacc[m][10], lane & ~3);
        const float r0 = __fdividef(1.0f, l0), r1 = __fdividef(1.0f, l1);
        stsm_x4(sQ + m * 8192 + qoff, pack_bf16(oacc[m][0] * r0, oacc[m][1] * r0), pack_bf16(oacc[m][2] * r1, oacc[m][3] * r1),
                pack_bf16(oacc[m][4] * r0, oacc[m][5] * r0), pack_bf16(oacc[m][6] * r1, oacc[m][7] * r1));
    }
    fence_async_smem();
    __syncthreads();
    if (wu == 0 && elect_one()) {
        tma2d_store(&mapO, sQ, hg * 64, tb * 128);
        bulk_commit();
        bulk_wait_read();
    }
    if (tid == 0) TL(tk, 3);
}

typedef CUresult (*EncodeFn)(CUtensorMap*, CUtensorMapDataType, cuuint32_t, void*, const cuuint64_t*, const cuuint64_t*, const cuuint32_t*,
                             const cuuint32_t*, CUtensorMapInterleave, CUtensorMapSwizzle, CUtensorMapL2promotion, CUtensorMapFloatOOBfill);

EncodeFn get_encode() {
    static EncodeFn fn = nullptr;
    if (!fn) {
        void* p = nullptr;
        cudaDriverEntryPointQueryResult qr;
        cudaGetDriverEntryPoint("cuTensorMapEncodeTiled", &p, cudaEnableDefault, &qr);
        fn = (EncodeFn)p;
    }
    return fn;
}
CUtensorMap map2d(const void* ptr, uint64_t cols, uint64_t rows, uint32_t bc, uint32_t br, CUtensorMapSwizzle sw) {
    CUtensorMap m;
    cuuint64_t gd[2] = {cols, rows}, gs[1] = {cols * 2};
    cuuint32_t bx[2] = {bc, br}, es[2] = {1, 1};
    get_encode()(&m, CU_TENSOR_MAP_DATA_TYPE_BFLOAT16, 2, (void*)ptr, gd, gs, bx, es, CU_TENSOR_MAP_INTERLEAVE_NONE, sw,
                 CU_TENSOR_MAP_L2_PROMOTION_L2_128B, CU_TENSOR_MAP_FLOAT_OOB_FILL_NONE);
    return m;
}
CUtensorMap map3d32(const void* ptr, uint64_t cols, uint64_t rows, uint32_t br, uint32_t nb) {
    CUtensorMap m;
    cuuint64_t gd[3] = {32, rows, cols / 32}, gs[2] = {cols * 2, 64};
    cuuint32_t bx[3] = {32, br, nb}, es[3] = {1, 1, 1};
    get_encode()(&m, CU_TENSOR_MAP_DATA_TYPE_BFLOAT16, 3, (void*)ptr, gd, gs, bx, es, CU_TENSOR_MAP_INTERLEAVE_NONE, CU_TENSOR_MAP_SWIZZLE_64B,
                 CU_TENSOR_MAP_L2_PROMOTION_L2_128B, CU_TENSOR_MAP_FLOAT_OOB_FILL_NONE);
    return m;
}

template <typename... KArgs, typename... Args>
void launch(void (*kern)(KArgs...), int grid, int block, int smem, int cluster, bool pdl, Args... args) {
    cudaLaunchConfig_t cfg = {};
    cfg.gridDim = dim3(grid);
    cfg.blockDim = dim3(block);
    cfg.dynamicSmemBytes = smem;
    cfg.stream = cudaStreamPerThread;
    cudaLaunchAttribute at[2];
    int n = 0;
    if (cluster > 1) { at[n].id = cudaLaunchAttributeClusterDimension; at[n].val.clusterDim.x = cluster; at[n].val.clusterDim.y = 1; at[n].val.clusterDim.z = 1; n++; }
    if (pdl) { at[n].id = cudaLaunchAttributeProgrammaticStreamSerialization; at[n].val.programmaticStreamSerializationAllowed = 1; n++; }
    cfg.attrs = at;
    cfg.numAttrs = n;
    cudaLaunchKernelEx(&cfg, kern, KArgs(args)...);
}

template <typename T> void* sym(const T& s) { void* p = nullptr; cudaGetSymbolAddress(&p, s); return p; }

}

extern "C" void kernel_launch(void* const* d_in, const int* in_sizes, int n_in, void* d_out, int out_size) {
    const __nv_bfloat16* x = (const __nv_bfloat16*)d_in[0];
    const __nv_bfloat16* wq = (const __nv_bfloat16*)d_in[1];
    const __nv_bfloat16* wk = (const __nv_bfloat16*)d_in[2];
    const __nv_bfloat16* wv = (const __nv_bfloat16*)d_in[3];
    const __nv_bfloat16* wo = (const __nv_bfloat16*)d_in[4];
    const __nv_bfloat16* w1 = (const __nv_bfloat16*)d_in[6];
    const __nv_bfloat16* w2 = (const __nv_bfloat16*)d_in[7];

    constexpr int SM_QKV = GemmSmem<QKV_STAGES, EPI_QKV>::TOTAL, SM_QKV0 = GemmSmem<QKV_STAGES, EPI_QKV>::TOTAL_SELF;
    static_assert(SM_QKV0 <= 232448, "shared memory");
    constexpr int SM_WO = GemmSmem<WO_STAGES, EPI_RES>::TOTAL, SM_FFN2 = GemmSmem<FFN2_STAGES, EPI_RES>::TOTAL;
    static_assert(SM_WO > 116736 && SM_FFN2 > 116736, "one CTA per SM");
    constexpr int SM_FFN1 = GemmSmem<FFN1_STAGES, EPI_FFN1>::TOTAL;
    cudaFuncSetAttribute(qkv_kernel<false>, cudaFuncAttributeMaxDynamicSharedMemorySize, SM_QKV);
    cudaFuncSetAttribute(qkv_kernel<true>, cudaFuncAttributeMaxDynamicSharedMemorySize, SM_QKV0);
    cudaFuncSetAttribute(res_gemm_kernel<8, WO_STAGES>, cudaFuncAttributeMaxDynamicSharedMemorySize, SM_WO);
    cudaFuncSetAttribute(ffn1_kernel, cudaFuncAttributeMaxDynamicSharedMemorySize, SM_FFN1);
    cudaFuncSetAttribute(res_gemm_kernel<28, FFN2_STAGES>, cudaFuncAttributeMaxDynamicSharedMemorySize, SM_FFN2);
    cudaFuncSetAttribute(attn_kernel, cudaFuncAttributeMaxDynamicSharedMemorySize, ATT_SMEM);
    cudaFuncSetAttribute(qkv_kernel<false>, cudaFuncAttributePreferredSharedMemoryCarveout, 100);
    cudaFuncSetAttribute(qkv_kernel<true>, cudaFuncAttributePreferredSharedMemoryCarveout, 100);
    cudaFuncSetAttribute(res_gemm_kernel<8, WO_STAGES>, cudaFuncAttributePreferredSharedMemoryCarveout, 100);
    cudaFuncSetAttribute(ffn1_kernel, cudaFuncAttributePreferredSharedMemoryCarveout, 100);
    cudaFuncSetAttribute(res_gemm_kernel<28, FFN2_STAGES>, cudaFuncAttributePreferredSharedMemoryCarveout, 100);
    cudaFuncSetAttribute(attn_kernel, cudaFuncAttributePreferredSharedMemoryCarveout, 100);

    void *q = sym(g_q), *o = sym(g_o), *x1 = sym(g_x1), *x2 = sym(g_x2), *x3 = sym(g_x3), *h = sym(g_h);
    float2* stats = (float2*)sym(g_stats);
    const void* xs[5] = {x, x1, x2, x3, d_out};

    const CUtensorMapSwizzle SW128 = CU_TENSOR_MAP_SWIZZLE_128B, SW64 = CU_TENSOR_MAP_SWIZZLE_64B;
    const CUtensorMap mWq = map3d32(wq, D_, D_, 64, 2);
    const CUtensorMap mWo = map2d(wo, D_, D_, 64, 64, SW128);
    const CUtensorMap mW1a = map3d32(w1, F_, D_, F1_BK, 4), mW1b = map3d32(w1, F_, D_, F1_BK, 3);
    const CUtensorMap mW2 = map2d(w2, D_, F_, 64, 64, SW128);
    const CUtensorMap mQ = map2d(q, D_, S_, 64, 64, SW128);
    const CUtensorMap mQa = map2d(q, D_, S_, 64, 128, SW128), mOs = map2d(o, D_, S_, 64, 128, SW128);
    const CUtensorMap mHst = map2d(h, F_, S_, 32, 16, SW64);
    CUtensorMap mXa[4], mXf[4], mXr[4], mXs[5];
    for (int i = 0; i < 4; i++) {
        mXa[i] = map2d(xs[i], D_, S_, 64, QKV_MC ? 64 : 128, SW128);
        mXf[i] = F1_BK == 64 ? map2d(xs[i], D_, S_, 64, 128, SW128) : map2d(xs[i], D_, S_, 32, 128, SW64);
        mXr[i] = map2d(xs[i], D_, S_, 64, 128, SW128);
    }
    for (int i = 0; i < 5; i++) mXs[i] = map2d(xs[i], D_, S_, 64, 64, SW128);
    const CUtensorMap mOa = map2d(o, D_, S_, 64, WO_MC ? 64 : 128, SW128);
    const CUtensorMap mHa = map2d(h, F_, S_, 64, F2_MC ? 64 : 128, SW128);

    for (int layer = 0; layer < 2; layer++) {
        const int xi = layer * 2;
        GemmParams p;
        p.wkv = wk; p.wv = wv;
        p.stats_in = stats + (size_t)xi * 8 * S_; p.stats_out = nullptr; p.tk = 1 + 5 * layer;
        if (layer == 0) launch(qkv_kernel<true>, 128, 672, SM_QKV0, QKV_MC ? 2 : 1, false, mXa[xi], mWq, mQ, p);
        else launch(qkv_kernel<false>, 128, 288, SM_QKV, QKV_MC ? 2 : 1, true, mXa[xi], mWq, mQ, p);
        launch(attn_kernel, layer == 0 ? 128 + SIDE_CTAS : 128, 512, ATT_SMEM, 1, true, mQa, mOs, wo, w1, w2, 2 + 5 * layer);
        p.stats_in = nullptr; p.stats_out = stats + (size_t)(xi + 1) * 8 * S_; p.tk = 3 + 5 * layer;
        launch(res_gemm_kernel<8, WO_STAGES>, 128, 288, SM_WO, WO_MC ? 2 : 1, true, mOa, mWo, mXr[xi], mXs[xi + 1], p);
        p.stats_in = stats + (size_t)(xi + 1) * 8 * S_; p.stats_out = nullptr; p.tk = 4 + 5 * layer;
        launch(ffn1_kernel, 128, F1_INLINE ? 256 : 288, SM_FFN1, F1_MC ? 2 : 1, true, mXf[xi + 1], mW1a, mW1b, mHst, p);
        p.stats_in = nullptr; p.stats_out = layer == 0 ? stats + (size_t)2 * 8 * S_ : nullptr; p.tk = 5 + 5 * layer;
        launch(res_gemm_kernel<28, FFN2_STAGES>, 128, 288, SM_FFN2, F2_MC ? 2 : 1, true, mHa, mW2, mXr[xi + 1], mXs[xi + 2], p);
    }
}
```

```cpp
#include <cuda_runtime.h>
#include <cuda_bf16.h>
#include <cuda.h>
#include <stdint.h>

#define F1_INLINE 0
#define QKV_MC 0
#define WO_MC 0
#define F2_MC 0
#define F1_MC 2
#define SELF_WAIT 0
#define ATT_VAR 1
#define SIDE_WAIT 1
#define PREB 1
#define RES_WAIT0 0

namespace {

constexpr int S_ = 2048, D_ = 512, H_ = 32, F_ = 1792;

__device__ __align__(1024) __nv_bfloat16 g_q[S_ * D_];
__device__ __align__(1024) __nv_bfloat16 g_o[S_ * D_];
__device__ __align__(1024) __nv_bfloat16 g_x1[S_ * D_];
__device__ __align__(1024) __nv_bfloat16 g_x2[S_ * D_];
__device__ __align__(1024) __nv_bfloat16 g_x3[S_ * D_];
__device__ __align__(1024) __nv_bfloat16 g_h[S_ * F_];
__device__ __align__(1024) uint8_t g_kimg[S_ * 32];
__device__ __align__(1024) uint8_t g_vimg[(S_ / 16) * 768];
__device__ __align__(1024) float2 g_stats[4][8 * S_];
__device__ __align__(16) float g_cs_q[D_];
__device__ __align__(16) float g_cs_kv[32];
__device__ __align__(16) float g_cs_1[F_];
__device__ __align__(16) float g_kvmax[32];

#define TL(k, slot)
#define CK(k, i)

__device__ __forceinline__ uint32_t smem_u32(const void* p) { return (uint32_t)__cvta_generic_to_shared(p); }
__device__ __forceinline__ void mbar_init(uint32_t bar, uint32_t cnt) {
    asm volatile("mbarrier.init.shared::cta.b64 [%0], %1;" ::"r"(bar), "r"(cnt));
}
__device__ __forceinline__ void mbar_expect_tx(uint32_t bar, uint32_t bytes) {
    asm volatile("mbarrier.arrive.expect_tx.shared::cta.b64 _, [%0], %1;" ::"r"(bar), "r"(bytes) : "memory");
}
__device__ __forceinline__ void mbar_arrive(uint32_t bar) {
    asm volatile("mbarrier.arrive.shared::cta.b64 _, [%0];" ::"r"(bar) : "memory");
}
__device__ __forceinline__ void mbar_arrive_remote(uint32_t bar, uint32_t cta) {
    asm volatile("{\n.reg .b32 ra;\nmapa.shared::cluster.u32 ra, %0, %1;\nmbarrier.arrive.shared::cluster.b64 _, [ra];\n}" ::"r"(bar), "r"(cta) : "memory");
}
__device__ __forceinline__ void mbar_wait(uint32_t bar, uint32_t parity) {
    asm volatile("{\n.reg .pred p;\nWAIT_%=:\nmbarrier.try_wait.parity.shared::cta.b64 p, [%0], %1;\n@p bra DONE_%=;\nbra WAIT_%=;\nDONE_%=:\n}" ::"r"(bar), "r"(parity) : "memory");
}
__device__ __forceinline__ void bulk_load(uint32_t dst, const void* src, uint32_t bytes, uint32_t bar) {
    asm volatile("cp.async.bulk.shared::cluster.global.mbarrier::complete_tx::bytes [%0], [%1], %2, [%3];" ::"r"(dst), "l"(src), "r"(bytes), "r"(bar) : "memory");
}
__device__ __forceinline__ void tma2d(uint32_t dst, const CUtensorMap* m, int c0, int c1, uint32_t bar) {
    asm volatile("cp.async.bulk.tensor.2d.shared::cluster.global.mbarrier::complete_tx::bytes [%0], [%1, {%3, %4}], [%2];" ::"r"(dst), "l"(m), "r"(bar), "r"(c0), "r"(c1) : "memory");
}
__device__ __forceinline__ void tma2d_mc(uint32_t dst, const CUtensorMap* m, int c0, int c1, uint32_t bar, uint16_t mask) {
    asm volatile("cp.async.bulk.tensor.2d.shared::cluster.global.mbarrier::complete_tx::bytes.multicast::cluster [%0], [%1, {%3, %4}], [%2], %5;" ::"r"(dst), "l"(m), "r"(bar), "r"(c0), "r"(c1), "h"(mask) : "memory");
}
__device__ __forceinline__ void tma3d(uint32_t dst, const CUtensorMap* m, int c0, int c1, int c2, uint32_t bar) {
    asm volatile("cp.async.bulk.tensor.3d.shared::cluster.global.mbarrier::complete_tx::bytes [%0], [%1, {%3, %4, %5}], [%2];" ::"r"(dst), "l"(m), "r"(bar), "r"(c0), "r"(c1), "r"(c2) : "memory");
}
__device__ __forceinline__ void tma3d_mc(uint32_t dst, const CUtensorMap* m, int c0, int c1, int c2, uint32_t bar, uint16_t mask) {
    asm volatile("cp.async.bulk.tensor.3d.shared::cluster.global.mbarrier::complete_tx::bytes.multicast::cluster [%0], [%1, {%3, %4, %5}], [%2], %6;" ::"r"(dst), "l"(m), "r"(bar), "r"(c0), "r"(c1), "r"(c2), "h"(mask) : "memory");
}
__device__ __forceinline__ void tma2d_store(const CUtensorMap* m, uint32_t src, int c0, int c1) {
    asm volatile("cp.async.bulk.tensor.2d.global.shared::cta.bulk_group [%0, {%2, %3}], [%1];" ::"l"(m), "r"(src), "r"(c0), "r"(c1) : "memory");
}
__device__ __forceinline__ void tma3d_store(const CUtensorMap* m, uint32_t src, int c0, int c1, int c2) {
    asm volatile("cp.async.bulk.tensor.3d.global.shared::cta.bulk_group [%0, {%2, %3, %4}], [%1];" ::"l"(m), "r"(src), "r"(c0), "r"(c1), "r"(c2) : "memory");
}
__device__ __forceinline__ void bulk_commit() { asm volatile("cp.async.bulk.commit_group;" ::: "memory"); }
__device__ __forceinline__ void bulk_wait_read() { asm volatile("cp.async.bulk.wait_group.read 0;" ::: "memory"); }
__device__ __forceinline__ void prefetch_tmap(const CUtensorMap* m) { asm volatile("prefetch.tensormap [%0];" ::"l"(m) : "memory"); }
__device__ __forceinline__ void fence_async_smem() { asm volatile("fence.proxy.async.shared::cta;" ::: "memory"); }
__device__ __forceinline__ void fence_mbar_init() { asm volatile("fence.mbarrier_init.release.cluster;" ::: "memory"); }
__device__ __forceinline__ void cluster_sync() { asm volatile("barrier.cluster.arrive.release.aligned;\nbarrier.cluster.wait.acquire.aligned;" ::: "memory"); }
__device__ __forceinline__ uint32_t cluster_rank() { uint32_t r; asm volatile("mov.u32 %0, %%cluster_ctarank;" : "=r"(r)); return r; }
__device__ __forceinline__ void pdl_wait() { asm volatile("griddepcontrol.wait;" ::: "memory"); }
__device__ __forceinline__ void pdl_launch() { asm volatile("griddepcontrol.launch_dependents;" ::: "memory"); }
__device__ __forceinline__ bool elect_one() {
    uint32_t p;
    asm volatile("{\n.reg .pred p;\nelect.sync _|p, 0xffffffff;\nselp.b32 %0, 1, 0, p;\n}" : "=r"(p));
    return p != 0;
}
__device__ __forceinline__ void named_bar(int id, int n) { asm volatile("bar.sync %0, %1;" ::"r"(id), "r"(n) : "memory"); }

__device__ __forceinline__ void wg_fence() { asm volatile("wgmma.fence.sync.aligned;" ::: "memory"); }
__device__ __forceinline__ void wg_commit() { asm volatile("wgmma.commit_group.sync.aligned;" ::: "memory"); }
template <int N> __device__ __forceinline__ void wg_wait() { asm volatile("wgmma.wait_group.sync.aligned %0;" ::"n"(N) : "memory"); }
template <int N> __device__ __forceinline__ void fence_regs(float (&d)[N]) {
#pragma unroll
    for (int i = 0; i < N; i++) asm volatile("" : "+f"(d[i])::"memory");
}
__device__ __forceinline__ uint64_t mkdesc(uint32_t addr, uint32_t lbo, uint32_t sbo, uint32_t swz) {
    uint64_t d = 0;
    d |= (uint64_t)((addr & 0x3FFFF) >> 4);
    d |= (uint64_t)((lbo & 0x3FFFF) >> 4) << 16;
    d |= (uint64_t)((sbo & 0x3FFFF) >> 4) << 32;
    d |= (uint64_t)swz << 62;
    return d;
}
__device__ __forceinline__ void ldsm_x4(uint32_t& r0, uint32_t& r1, uint32_t& r2, uint32_t& r3, uint32_t addr) {
    asm volatile("ldmatrix.sync.aligned.m8n8.x4.shared.b16 {%0,%1,%2,%3}, [%4];" : "=r"(r0), "=r"(r1), "=r"(r2), "=r"(r3) : "r"(addr) : "memory");
}
__device__ __forceinline__ void stsm_x4(uint32_t addr, uint32_t r0, uint32_t r1, uint32_t r2, uint32_t r3) {
    asm volatile("stmatrix.sync.aligned.m8n8.x4.shared.b16 [%0], {%1,%2,%3,%4};" ::"r"(addr), "r"(r0), "r"(r1), "r"(r2), "r"(r3) : "memory");
}
__device__ __forceinline__ void ldsm_x4_t(uint32_t& r0, uint32_t& r1, uint32_t& r2, uint32_t& r3, uint32_t addr) {
    asm volatile("ldmatrix.sync.aligned.m8n8.x4.trans.shared.b16 {%0,%1,%2,%3}, [%4];" : "=r"(r0), "=r"(r1), "=r"(r2), "=r"(r3) : "r"(addr) : "memory");
}
__device__ __forceinline__ void hmma(float (&d)[4], uint32_t a0, uint32_t a1, uint32_t a2, uint32_t a3, uint32_t b0, uint32_t b1) {
    asm volatile("mma.sync.aligned.m16n8k16.row.col.f32.bf16.bf16.f32 {%0,%1,%2,%3}, {%4,%5,%6,%7}, {%8,%9}, {%0,%1,%2,%3};"
                 : "+f"(d[0]), "+f"(d[1]), "+f"(d[2]), "+f"(d[3]) : "r"(a0), "r"(a1), "r"(a2), "r"(a3), "r"(b0), "r"(b1));
}
__device__ __forceinline__ uint32_t pack_bf16(float lo, float hi) {
    uint32_t r;
    asm("cvt.rn.bf16x2.f32 %0, %1, %2;" : "=r"(r) : "f"(hi), "f"(lo));
    return r;
}
__device__ __forceinline__ float bf_lo(uint32_t v) { return __uint_as_float(v << 16); }
__device__ __forceinline__ float bf_hi(uint32_t v) { return __uint_as_float(v & 0xFFFF0000u); }

#define WG_REGS_4(o) "+f"(d[o]), "+f"(d[o + 1]), "+f"(d[o + 2]), "+f"(d[o + 3])
#define WG_REGS_8(o) WG_REGS_4(o), WG_REGS_4(o + 4)
#define WG_REGS_16(o) WG_REGS_8(o), WG_REGS_8(o + 8)
#define WG_REGS_32(o) WG_REGS_16(o), WG_REGS_16(o + 16)

__device__ __forceinline__ void wgmma_ss_n80_tb(float (&d)[40], uint64_t dA, uint64_t dB, int sc) {
    asm volatile("{\n.reg .pred p;\nsetp.ne.b32 p, %42, 0;\n"
                 "wgmma.mma_async.sync.aligned.m64n80k16.f32.bf16.bf16 "
                 "{%0,%1,%2,%3,%4,%5,%6,%7,%8,%9,%10,%11,%12,%13,%14,%15,%16,%17,%18,%19,%20,%21,%22,%23,%24,%25,%26,%27,%28,%29,%30,%31,"
                 "%32,%33,%34,%35,%36,%37,%38,%39}, %40, %41, p, 1, 1, 0, 1;\n}\n"
                 : WG_REGS_32(0), WG_REGS_8(32) : "l"(dA), "l"(dB), "r"(sc));
}
__device__ __forceinline__ void wgmma_ss_n64_tb(float (&d)[32], uint64_t dA, uint64_t dB, int sc) {
    asm volatile("{\n.reg .pred p;\nsetp.ne.b32 p, %34, 0;\n"
                 "wgmma.mma_async.sync.aligned.m64n64k16.f32.bf16.bf16 "
                 "{%0,%1,%2,%3,%4,%5,%6,%7,%8,%9,%10,%11,%12,%13,%14,%15,%16,%17,%18,%19,%20,%21,%22,%23,%24,%25,%26,%27,%28,%29,%30,%31}, "
                 "%32, %33, p, 1, 1, 0, 1;\n}\n"
                 : WG_REGS_32(0) : "l"(dA), "l"(dB), "r"(sc));
}
__device__ __forceinline__ void wgmma_ss_n224_tb(float (&d)[112], uint64_t dA, uint64_t dB, int sc) {
    asm volatile("{\n.reg .pred p;\nsetp.ne.b32 p, %114, 0;\n"
                 "wgmma.mma_async.sync.aligned.m64n224k16.f32.bf16.bf16 "
                 "{%0,%1,%2,%3,%4,%5,%6,%7,%8,%9,%10,%11,%12,%13,%14,%15,%16,%17,%18,%19,%20,%21,%22,%23,%24,%25,%26,%27,%28,%29,%30,%31,"
                 "%32,%33,%34,%35,%36,%37,%38,%39,%40,%41,%42,%43,%44,%45,%46,%47,%48,%49,%50,%51,%52,%53,%54,%55,%56,%57,%58,%59,%60,%61,%62,%63,"
                 "%64,%65,%66,%67,%68,%69,%70,%71,%72,%73,%74,%75,%76,%77,%78,%79,%80,%81,%82,%83,%84,%85,%86,%87,%88,%89,%90,%91,%92,%93,%94,%95,"
                 "%96,%97,%98,%99,%100,%101,%102,%103,%104,%105,%106,%107,%108,%109,%110,%111}, "
                 "%112, %113, p, 1, 1, 0, 1;\n}\n"
                 : WG_REGS_32(0), WG_REGS_32(32), WG_REGS_32(64), WG_REGS_16(96) : "l"(dA), "l"(dB), "r"(sc));
}
template <int BN> __device__ __forceinline__ void wgmma_ss_tb(float (&d)[BN / 2], uint64_t dA, uint64_t dB, int sc) {
    if constexpr (BN == 64) wgmma_ss_n64_tb(d, dA, dB, sc);
    else if constexpr (BN == 80) wgmma_ss_n80_tb(d, dA, dB, sc);
    else wgmma_ss_n224_tb(d, dA, dB, sc);
}
__device__ __forceinline__ void wgmma_rs_n64_tb(float (&d)[32], uint32_t a, uint64_t dB, int sc) {
    asm volatile("{\n.reg .pred p;\nsetp.ne.b32 p, %34, 0;\n"
                 "wgmma.mma_async.sync.aligned.m64n64k16.f32.bf16.bf16 "
                 "{%0,%1,%2,%3,%4,%5,%6,%7,%8,%9,%10,%11,%12,%13,%14,%15,%16,%17,%18,%19,%20,%21,%22,%23,%24,%25,%26,%27,%28,%29,%30,%31}, "
                 "{%32,%32,%32,%32}, %33, p, 1, 1, 1;\n}\n"
                 : WG_REGS_32(0) : "r"(a), "l"(dB), "r"(sc));
}
__device__ __forceinline__ void wgmma_rs_n80_tb(float (&d)[40], uint32_t a, uint64_t dB, int sc) {
    asm volatile("{\n.reg .pred p;\nsetp.ne.b32 p, %42, 0;\n"
                 "wgmma.mma_async.sync.aligned.m64n80k16.f32.bf16.bf16 "
                 "{%0,%1,%2,%3,%4,%5,%6,%7,%8,%9,%10,%11,%12,%13,%14,%15,%16,%17,%18,%19,%20,%21,%22,%23,%24,%25,%26,%27,%28,%29,%30,%31,"
                 "%32,%33,%34,%35,%36,%37,%38,%39}, {%40,%40,%40,%40}, %41, p, 1, 1, 1;\n}\n"
                 : WG_REGS_32(0), WG_REGS_8(32) : "r"(a), "l"(dB), "r"(sc));
}
template <int BN> __device__ __forceinline__ void wgmma_rs_ones(float (&d)[BN / 2], uint64_t dB, int sc) {
    if constexpr (BN == 80) wgmma_rs_n80_tb(d, 0x3F803F80u, dB, sc);
    else if constexpr (BN == 64) wgmma_rs_n64_tb(d, 0x3F803F80u, dB, sc);
}
__device__ __forceinline__ void wgmma_rs_n64_z(float (&d)[32], uint32_t a0, uint32_t a1, uint32_t a2, uint32_t a3, uint64_t dB) {
    asm volatile("{\n.reg .pred p;\nsetp.ne.b32 p, 0, 0;\n"
                 "wgmma.mma_async.sync.aligned.m64n64k16.f32.bf16.bf16 "
                 "{%0,%1,%2,%3,%4,%5,%6,%7,%8,%9,%10,%11,%12,%13,%14,%15,%16,%17,%18,%19,%20,%21,%22,%23,%24,%25,%26,%27,%28,%29,%30,%31}, "
                 "{%32,%33,%34,%35}, %36, p, 1, 1, 0;\n}\n"
                 : "=f"(d[0]), "=f"(d[1]), "=f"(d[2]), "=f"(d[3]), "=f"(d[4]), "=f"(d[5]), "=f"(d[6]), "=f"(d[7]),
                   "=f"(d[8]), "=f"(d[9]), "=f"(d[10]), "=f"(d[11]), "=f"(d[12]), "=f"(d[13]), "=f"(d[14]), "=f"(d[15]),
                   "=f"(d[16]), "=f"(d[17]), "=f"(d[18]), "=f"(d[19]), "=f"(d[20]), "=f"(d[21]), "=f"(d[22]), "=f"(d[23]),
                   "=f"(d[24]), "=f"(d[25]), "=f"(d[26]), "=f"(d[27]), "=f"(d[28]), "=f"(d[29]), "=f"(d[30]), "=f"(d[31])
                 : "r"(a0), "r"(a1), "r"(a2), "r"(a3), "l"(dB));
}
__device__ __forceinline__ void wgmma_rs_n24_tb(float (&d)[12], uint32_t a0, uint32_t a1, uint32_t a2, uint32_t a3, uint64_t dB) {
    asm volatile("{\n.reg .pred p;\nsetp.eq.b32 p, 0, 0;\n"
                 "wgmma.mma_async.sync.aligned.m64n24k16.f32.bf16.bf16 "
                 "{%0,%1,%2,%3,%4,%5,%6,%7,%8,%9,%10,%11}, {%12,%13,%14,%15}, %16, p, 1, 1, 1;\n}\n"
                 : WG_REGS_8(0), WG_REGS_4(8) : "r"(a0), "r"(a1), "r"(a2), "r"(a3), "l"(dB));
}

constexpr int SIDE_CTAS = 4;
__device__ __forceinline__ void side_job(int cta, float* red  , const __nv_bfloat16* __restrict__ wo,
                                         const __nv_bfloat16* __restrict__ w1, const __nv_bfloat16* __restrict__ w2) {
    const int tid = threadIdx.x, warp = tid >> 5, lane = tid & 31;
    for (int line = cta * 512 + tid; line < 18432; line += SIDE_CTAS * 512) {
        const char* p = line < 4096 ? (const char*)wo + (size_t)line * 128 : (const char*)w2 + (size_t)(line - 4096) * 128;
        asm volatile("prefetch.global.L2 [%0];" ::"l"(p));
    }
    const int rg = lane >> 3, c8 = lane & 7;
    for (int slab = cta; slab < F_ / 64; slab += SIDE_CTAS) {
        const __nv_bfloat16* base = w1 + slab * 64 + c8 * 8;
        uint4 v[8];
#pragma unroll
        for (int i = 0; i < 8; i++) v[i] = __ldg((const uint4*)(base + (size_t)(warp * 32 + rg + 4 * i) * F_));
        float acc[8];
#pragma unroll
        for (int i = 0; i < 8; i++) acc[i] = 0.f;
#pragma unroll
        for (int i = 0; i < 8; i++) {
            acc[0] += bf_lo(v[i].x); acc[1] += bf_hi(v[i].x); acc[2] += bf_lo(v[i].y); acc[3] += bf_hi(v[i].y);
            acc[4] += bf_lo(v[i].z); acc[5] += bf_hi(v[i].z); acc[6] += bf_lo(v[i].w); acc[7] += bf_hi(v[i].w);
        }
#pragma unroll
        for (int i = 0; i < 8; i++) {
            acc[i] += __shfl_xor_sync(0xffffffffu, acc[i], 8);
            acc[i] += __shfl_xor_sync(0xffffffffu, acc[i], 16);
        }
        if (rg == 0) {
#pragma unroll
            for (int i = 0; i < 8; i++) red[warp * 64 + c8 * 8 + i] = acc[i];
        }
        __syncthreads();
        if (tid < 64) {
            float s = 0.f;
#pragma unroll
            for (int i = 0; i < 16; i++) s += red[i * 64 + tid];
            g_cs_1[slab * 64 + tid] = s;
        }
        __syncthreads();
    }
}

enum { EPI_QKV = 0, EPI_RES = 1, EPI_FFN1 = 2 };

struct GemmParams {
    const float2* stats_in;
    float2* stats_out;
    const __nv_bfloat16* wkv;
    const __nv_bfloat16* wv;
    int tk;
};

template <int BK_, int NBLK> struct Geo {
    static constexpr int BK = BK_, A_BYTES = 128 * BK * 2, A_SWZ = BK == 64 ? 1 : 2, A_SBO = BK * 16;
    static constexpr int BLK = BK * 64;
    static constexpr int B_BYTES = NBLK * BLK, B_SWZ = 2, B_LBO = BLK, B_SBO = 512, B_KSTEP = 1024;
};
template <> struct Geo<64, 0> {
    static constexpr int BK = 64, A_BYTES = 128 * 128, A_SWZ = 1, A_SBO = 1024, BLK = 8192;
    static constexpr int B_BYTES = 64 * 128, B_SWZ = 1, B_LBO = 8192, B_SBO = 1024, B_KSTEP = 2048;
};
#define F1_BK 32
template <int EPI> struct EpiGeo;
template <> struct EpiGeo<EPI_QKV> { using G = Geo<64, 3>; };
template <> struct EpiGeo<EPI_RES> { using G = Geo<64, 0>; };
template <> struct EpiGeo<EPI_FFN1> { using G = Geo<F1_BK, 7>; };

template <int STAGES, int EPI> struct GemmSmem {
    using G = typename EpiGeo<EPI>::G;
    static constexpr int STAGE = G::A_BYTES + G::B_BYTES;
    static constexpr int AUX_OFF = STAGES * STAGE;
    static constexpr int TOTAL = AUX_OFF + 1152;
    static constexpr int TOTAL_SELF = AUX_OFF + 704 + 1024 + 1280;
};

struct RowStatRaw { float2 a0, a1, b0, b1; };
__device__ __forceinline__ RowStatRaw load_row_stats(const float2* __restrict__ st, int row0, int c) {
    RowStatRaw r;
    r.a0 = st[(2 * c) * S_ + row0]; r.a1 = st[(2 * c + 1) * S_ + row0];
    r.b0 = st[(2 * c) * S_ + row0 + 8]; r.b1 = st[(2 * c + 1) * S_ + row0 + 8];
    return r;
}
__device__ __forceinline__ void finish_row_stats(const RowStatRaw& r, float& mean0, float& rstd0, float& mean1, float& rstd1) {
    float sa = r.a0.x + r.a1.x, sb = r.b0.x + r.b1.x;
    sa += __shfl_xor_sync(0xffffffffu, sa, 1); sa += __shfl_xor_sync(0xffffffffu, sa, 2);
    sb += __shfl_xor_sync(0xffffffffu, sb, 1); sb += __shfl_xor_sync(0xffffffffu, sb, 2);
    mean0 = sa * 0.125f; mean1 = sb * 0.125f;
    float ma = r.a0.y + r.a1.y + 64.f * ((r.a0.x - mean0) * (r.a0.x - mean0) + (r.a1.x - mean0) * (r.a1.x - mean0));
    float mb = r.b0.y + r.b1.y + 64.f * ((r.b0.x - mean1) * (r.b0.x - mean1) + (r.b1.x - mean1) * (r.b1.x - mean1));
    ma += __shfl_xor_sync(0xffffffffu, ma, 1); ma += __shfl_xor_sync(0xffffffffu, ma, 2);
    mb += __shfl_xor_sync(0xffffffffu, mb, 1); mb += __shfl_xor_sync(0xffffffffu, mb, 2);
    rstd0 = 1.0f / sqrtf(ma * (1.f / 512.f) + 1e-5f);
    rstd1 = 1.0f / sqrtf(mb * (1.f / 512.f) + 1e-5f);
}

template <int BN, int KB, int STAGES, int EPI, int MC, bool SELF = false>
__device__ __forceinline__ void gemm_body(const CUtensorMap* mapA, const CUtensorMap* mapB, const CUtensorMap* mapB2, const CUtensorMap* mapR,
                                          const CUtensorMap* mapC, const GemmParams& prm, int tile_m, int tile_n, uint8_t* smem_raw) {
    using SM = GemmSmem<STAGES, EPI>;
    using G = typename SM::G;
    constexpr bool XKV = BN == 80;
    constexpr int TN = EPI == EPI_QKV ? 64 : BN;
    pdl_launch();
    const uint32_t sbase = smem_u32(smem_raw);
    if (sbase & 1023) __trap();
    uint8_t* sgen = smem_raw;
    const uint32_t bar_full = sbase + SM::AUX_OFF, bar_empty = bar_full + 8 * STAGES;
    float* s_cs = (float*)(sgen + SM::AUX_OFF + 256);
    float* s_row = (float*)(sgen + SM::AUX_OFF + 704);
    float* s_red = (float*)(sgen + SM::AUX_OFF + 640);
    const int tid = threadIdx.x, lane = tid & 31;
    const int warp = __shfl_sync(0xffffffffu, tid >> 5, 0);
    const uint32_t rank = MC ? cluster_rank() : 0;
    if (tid == 0) TL(prm.tk, 0);

    constexpr bool INLINE_PROD = EPI == EPI_FFN1 && F1_INLINE;
    constexpr int PWARP = INLINE_PROD ? 0 : 8;
    if (warp == PWARP && elect_one()) {
        prefetch_tmap(mapB); prefetch_tmap(mapA); prefetch_tmap(mapC);
        for (int s = 0; s < STAGES; s++) { mbar_init(bar_full + 8 * s, 1); mbar_init(bar_empty + 8 * s, MC ? 4 : 2); }
        fence_mbar_init();
    }
    __syncthreads();
    if (MC) asm volatile("barrier.cluster.arrive.release.aligned;" ::: "memory");
    auto cluster_wait = [&]() { if (MC) asm volatile("barrier.cluster.wait.acquire.aligned;" ::: "memory"); };

    const int m0 = tile_m * 128, n0 = tile_n * TN;
    constexpr uint32_t STAGE_TX = G::A_BYTES + (EPI == EPI_QKV ? 2 * G::BLK : G::B_BYTES);
    auto loadB = [&](int kb, int s) {
        const uint32_t dst = sbase + s * SM::STAGE + G::A_BYTES, bar = bar_full + 8 * s;
        if constexpr (EPI == EPI_RES) {
            tma2d(dst, mapB, n0, kb * 64, bar);
        } else if constexpr (EPI == EPI_QKV) {
            tma3d(dst, mapB, 0, kb * G::BK, tile_n * 2, bar);
        } else {
            if constexpr (MC == 2) {
                if (rank == 0) tma3d_mc(dst, mapB, 0, kb * G::BK, tile_n * 7, bar, 3);
                else tma3d_mc(dst + 4 * G::BLK, mapB2, 0, kb * G::BK, tile_n * 7 + 4, bar, 3);
            } else {
                tma3d(dst, mapB, 0, kb * G::BK, tile_n * 7, bar);
                tma3d(dst + 4 * G::BLK, mapB2, 0, kb * G::BK, tile_n * 7 + 4, bar);
            }
        }
    };
    auto loadA = [&](int kb, int s) {
        const uint32_t dst = sbase + s * SM::STAGE, bar = bar_full + 8 * s;
        if constexpr (MC == 1) tma2d_mc(dst + rank * (G::A_BYTES / 2), mapA, kb * G::BK, m0 + rank * 64, bar, 3);
        else tma2d(dst, mapA, kb * G::BK, m0, bar);
    };
    constexpr int PRE = STAGES < KB ? STAGES : KB;
#define F1_LAG 2
    constexpr int LAG = F1_LAG;
    constexpr int PRE_B = PRE < PREB ? PRE : PREB;
    auto prologue_loads = [&]() {
        if (elect_one()) {
#pragma unroll
            for (int kb = 0; kb < PRE; kb++) mbar_expect_tx(bar_full + 8 * kb, STAGE_TX);
        }
        cluster_wait();
        if (elect_one()) {
#pragma unroll
            for (int kb = 0; kb < PRE_B; kb++) loadB(kb, kb);
        }
        if (!SELF) pdl_wait();
        if (elect_one()) {
#pragma unroll
            for (int kb = 0; kb < PRE; kb++) {
                loadA(kb, kb);
                if (kb + PRE_B < PRE) loadB(kb + PRE_B, kb + PRE_B);
            }
            if constexpr (EPI == EPI_RES && KB < STAGES) {
                mbar_expect_tx(bar_full + 8 * KB, 16384);
                tma2d(sbase + KB * SM::STAGE, mapR, n0, m0, bar_full + 8 * KB);
            }
        }
    };
    if (SELF && warp >= 8) {
        if (warp == 8) prologue_loads();
        static_assert(!SELF || (STAGES >= KB && EPI == EPI_QKV), "SELF needs every k block resident");
        if ((warp >> 2) == 3) {
            float csum[BN / 2];
            const uint64_t dB0 = mkdesc(sbase + G::A_BYTES, G::B_LBO, G::B_SBO, G::B_SWZ);
            if constexpr (XKV) named_bar(6, 384);
#pragma unroll 1
            for (int kb = 0; kb < KB; kb++) {
                mbar_wait(bar_full + 8 * kb, 0);
                const uint64_t dB = dB0 + (uint64_t)(kb * (SM::STAGE >> 4));
                wg_fence();
#pragma unroll
                for (int k = 0; k < G::BK / 16; k++) {
                    if constexpr (SELF) wgmma_rs_ones<BN>(csum, dB + (uint64_t)(k * (G::B_KSTEP >> 4)), (kb | k) != 0);
                }
                wg_commit();
            }
            wg_wait<0>();
            fence_regs(csum);
            if (warp == 12 && lane < 4) {
#pragma unroll
                for (int j = 0; j < BN / 8; j++) {
                    const float2 v = make_float2(csum[4 * j], csum[4 * j + 1]);
                    *(float2*)(s_cs + 8 * j + 2 * lane) = v;
                    if (tile_m == 0) {
                        if (j < 8) *(float2*)(g_cs_q + n0 + 8 * j + 2 * lane) = v;
                        else *(float2*)(g_cs_kv + tile_n * 16 + 8 * (j - 8) + 2 * lane) = v;
                    }
                }
            }
        } else {
            const int t = (warp < 12 ? warp - 8 : warp - 12) * 32 + lane;
            float ss[4] = {0.f, 0.f, 0.f, 0.f}, sq[4] = {0.f, 0.f, 0.f, 0.f};
#pragma unroll 1
            for (int kb = 0; kb < KB; kb++) {
                mbar_wait(bar_full + 8 * kb, 0);
                const uint32_t arow = sbase + kb * SM::STAGE + (t >> 1) * 128;
                uint32_t w[4][4];
#pragma unroll
                for (int j = 0; j < 4; j++)
                    asm volatile("ld.shared.v4.u32 {%0,%1,%2,%3}, [%4];" : "=r"(w[j][0]), "=r"(w[j][1]), "=r"(w[j][2]), "=r"(w[j][3])
                                 : "r"(arow + (((2 * j + (t & 1) + 2 * ((t >> 1) & 3)) & 7) << 4)));
#pragma unroll
                for (int j = 0; j < 4; j++)
#pragma unroll
                    for (int i = 0; i < 4; i++) {
                        const float lo = bf_lo(w[j][i]), hi = bf_hi(w[j][i]);
                        ss[i] += lo + hi;
                        sq[i] = fmaf(lo, lo, fmaf(hi, hi, sq[i]));
                    }
            }
            float tsum = (ss[0] + ss[1]) + (ss[2] + ss[3]), tsq = (sq[0] + sq[1]) + (sq[2] + sq[3]);
            tsum += __shfl_xor_sync(0xffffffffu, tsum, 1);
            tsq += __shfl_xor_sync(0xffffffffu, tsq, 1);
            if ((t & 1) == 0) {
                const float md = tsum * (1.f / 512.f);
                const float var = fmaxf(tsq * (1.f / 512.f) - md * md, 0.f);
                *(float2*)(s_row + t) = make_float2(md, 1.0f / sqrtf(var + 1e-5f));
            }
        }
        named_bar(4, 640);
    } else if (!INLINE_PROD && warp == 8) {
        prologue_loads();
        int s = PRE % STAGES, ph = (PRE / STAGES) & 1;
#pragma unroll 1
        for (int kb = PRE; kb < KB; kb++) {
            mbar_wait(bar_empty + 8 * s, ph ^ 1);
            if (elect_one()) {
                mbar_expect_tx(bar_full + 8 * s, STAGE_TX);
                loadB(kb, s);
                loadA(kb, s);
            }
            if (++s == STAGES) { s = 0; ph ^= 1; }
        }
        if constexpr (EPI == EPI_RES && KB >= STAGES) {
            mbar_wait(bar_empty + 8 * s, ph ^ 1);
            if (elect_one()) {
                mbar_expect_tx(bar_full + 8 * s, 16384);
                tma2d(sbase + s * SM::STAGE, mapR, n0, m0, bar_full + 8 * s);
            }
        }
    } else {
        if (INLINE_PROD && warp == 0) prologue_loads(); else cluster_wait();
        const int wg = warp >> 2, g = lane >> 2, c = lane & 3;
        const int rloc = wg * 64 + (warp & 3) * 16 + g;
        const int row0 = m0 + rloc;
        float mean0 = 0.f, rstd0 = 1.f, mean1 = 0.f, rstd1 = 1.f;
        if constexpr (XKV) {
            static_assert(!XKV || STAGES >= KB, "the K / V weight block must stay resident");
            const __nv_bfloat16* wsrc = tile_n == 0 ? prm.wkv : prm.wv;
            uint4 v[4];
#pragma unroll
            for (int i = 0; i < 4; i++) v[i] = __ldg((const uint4*)wsrc + tid + 256 * i);
#pragma unroll
            for (int i = 0; i < 4; i++) {
                const int idx = tid + 256 * i, k = idx >> 1, kr = k & 63;
                const uint32_t dst = sbase + (k >> 6) * SM::STAGE + G::A_BYTES + 2 * G::BLK + kr * 64 + (((idx & 1) ^ ((kr >> 1) & 3)) << 4);
                asm volatile("st.shared.v4.u32 [%0], {%1,%2,%3,%4};" ::"r"(dst), "r"(v[i].x), "r"(v[i].y), "r"(v[i].z), "r"(v[i].w) : "memory");
            }
            fence_async_smem();
            if constexpr (SELF) named_bar(6, 384); else named_bar(6, 256);
        }
        RowStatRaw raw;
        float csv = 0.f;
        float2 cskv[2] = {make_float2(0.f, 0.f), make_float2(0.f, 0.f)};
        auto ln_inputs = [&]() {
            pdl_wait();
            if constexpr (EPI != EPI_RES) {
                raw = load_row_stats(prm.stats_in, row0, c);
                const float* cs = EPI == EPI_FFN1 ? g_cs_1 + n0 : g_cs_q + n0;
                if (tid < TN) csv = cs[tid];
                if constexpr (XKV) {
                    cskv[0] = *(const float2*)(g_cs_kv + tile_n * 16 + 2 * c);
                    cskv[1] = *(const float2*)(g_cs_kv + tile_n * 16 + 8 + 2 * c);
                }
            }
        };
        if (!SELF) ln_inputs();
        float acc[BN / 2];
        const uint64_t dA0 = mkdesc(sbase + wg * (G::A_BYTES / 2), 16, G::A_SBO, G::A_SWZ);
        const uint64_t dB0 = mkdesc(sbase + G::A_BYTES, G::B_LBO, G::B_SBO, G::B_SWZ);
        int s = 0, ph = 0;
#pragma unroll 1
        for (int kb = 0; kb < KB; kb++) {
            mbar_wait(bar_full + 8 * s, ph);
            const uint64_t dA = dA0 + (uint64_t)(s * (SM::STAGE >> 4)), dB = dB0 + (uint64_t)(s * (SM::STAGE >> 4));
            wg_fence();
#pragma unroll
            for (int k = 0; k < G::BK / 16; k++) wgmma_ss_tb<BN>(acc, dA + (uint64_t)(k * 2), dB + (uint64_t)(k * (G::B_KSTEP >> 4)), (kb | k) != 0);
            wg_commit();
            if constexpr (EPI == EPI_RES && RES_WAIT0) {
                wg_wait<0>();
                if ((warp & 3) == 0 && elect_one()) {
                    if (MC) { mbar_arrive_remote(bar_empty + 8 * s, 0); mbar_arrive_remote(bar_empty + 8 * s, 1); }
                    else mbar_arrive(bar_empty + 8 * s);
                }
            } else if (kb > 0) {
                wg_wait<1>();
                const int sp = s == 0 ? STAGES - 1 : s - 1;
                if ((warp & 3) == 0 && elect_one()) {
                    if (MC) { mbar_arrive_remote(bar_empty + 8 * sp, 0); mbar_arrive_remote(bar_empty + 8 * sp, 1); }
                    else mbar_arrive(bar_empty + 8 * sp);
                }
                if (INLINE_PROD && warp == 0 && kb >= LAG && kb - LAG + STAGES < KB) {
                    const int sq = LAG == 1 ? sp : (sp == 0 ? STAGES - 1 : sp - 1);
                    mbar_wait(bar_empty + 8 * sq, ((kb - LAG) / STAGES) & 1);
                    if (elect_one()) {
                        mbar_expect_tx(bar_full + 8 * sq, STAGE_TX);
                        loadB(kb - LAG + STAGES, sq);
                        loadA(kb - LAG + STAGES, sq);
                    }
                }
            }
            if (++s == STAGES) { s = 0; ph ^= 1; }
        }
        if constexpr (SELF) {
            named_bar(4, 640);
            const float2 r0 = *(const float2*)(s_row + 2 * rloc), r1 = *(const float2*)(s_row + 2 * rloc + 16);
            mean0 = r0.x; rstd0 = r0.y; mean1 = r1.x; rstd1 = r1.y;
        } else if constexpr (EPI != EPI_RES) {
            finish_row_stats(raw, mean0, rstd0, mean1, rstd1);
            if (tid < TN) s_cs[tid] = csv;
        }
        wg_wait<0>();
        fence_regs(acc);
        if (tid == 0) TL(prm.tk, 2);
        if constexpr (EPI != EPI_RES) named_bar(1, 256);

        if constexpr (EPI != EPI_FFN1) {
            const uint32_t stile = sbase + (EPI == EPI_RES ? s * SM::STAGE : 0);
            const int mrow = wg * 64 + (warp & 3) * 16 + (lane & 7) + ((lane >> 3) & 1) * 8;
            const uint32_t rbase = stile + mrow * 128;
            if constexpr (EPI == EPI_RES) {
                mbar_wait(bar_full + 8 * s, ph);
                float s0 = 0.f, s1 = 0.f;
#pragma unroll
                for (int jj = 0; jj < 4; jj++) {
                    uint32_t r0, r1, r2, r3;
                    const uint32_t addr = rbase + (((2 * jj + (lane >> 4)) ^ (mrow & 7)) << 4);
                    ldsm_x4(r0, r1, r2, r3, addr);
                    const uint32_t u0 = pack_bf16(acc[8 * jj] + bf_lo(r0), acc[8 * jj + 1] + bf_hi(r0));
                    const uint32_t u1 = pack_bf16(acc[8 * jj + 2] + bf_lo(r1), acc[8 * jj + 3] + bf_hi(r1));
                    const uint32_t u2 = pack_bf16(acc[8 * jj + 4] + bf_lo(r2), acc[8 * jj + 5] + bf_hi(r2));
                    const uint32_t u3 = pack_bf16(acc[8 * jj + 6] + bf_lo(r3), acc[8 * jj + 7] + bf_hi(r3));
                    stsm_x4(addr, u0, u1, u2, u3);
                    acc[8 * jj] = bf_lo(u0); acc[8 * jj + 1] = bf_hi(u0); acc[8 * jj + 4] = bf_lo(u2); acc[8 * jj + 5] = bf_hi(u2);
                    acc[8 * jj + 2] = bf_lo(u1); acc[8 * jj + 3] = bf_hi(u1); acc[8 * jj + 6] = bf_lo(u3); acc[8 * jj + 7] = bf_hi(u3);
                    s0 += (acc[8 * jj] + acc[8 * jj + 1]) + (acc[8 * jj + 4] + acc[8 * jj + 5]);
                    s1 += (acc[8 * jj + 2] + acc[8 * jj + 3]) + (acc[8 * jj + 6] + acc[8 * jj + 7]);
                }
                fence_async_smem();
                named_bar(2 + wg, 128);
                if ((warp & 3) == 0 && elect_one()) { tma2d_store(mapC, stile + wg * 8192, n0, m0 + wg * 64); bulk_commit(); }
                if (prm.stats_out) {
                    s0 += __shfl_xor_sync(0xffffffffu, s0, 1); s0 += __shfl_xor_sync(0xffffffffu, s0, 2);
                    s1 += __shfl_xor_sync(0xffffffffu, s1, 1); s1 += __shfl_xor_sync(0xffffffffu, s1, 2);
                    const float mu0 = s0 * (1.f / 64.f), mu1 = s1 * (1.f / 64.f);
                    float q0 = 0.f, q1 = 0.f;
#pragma unroll
                    for (int j = 0; j < 8; j++) {
                        float d;
                        d = acc[4 * j] - mu0; q0 += d * d; d = acc[4 * j + 1] - mu0; q0 += d * d;
                        d = acc[4 * j + 2] - mu1; q1 += d * d; d = acc[4 * j + 3] - mu1; q1 += d * d;
                    }
                    q0 += __shfl_xor_sync(0xffffffffu, q0, 1); q0 += __shfl_xor_sync(0xffffffffu, q0, 2);
                    q1 += __shfl_xor_sync(0xffffffffu, q1, 1); q1 += __shfl_xor_sync(0xffffffffu, q1, 2);
                    if (c == 0) {
                        prm.stats_out[tile_n * S_ + row0] = make_float2(mu0, q0);
                        prm.stats_out[tile_n * S_ + row0 + 8] = make_float2(mu1, q1);
                    }
                }
            } else {
                const float sc = 0.25f * 1.4426950408889634f;
                const float a0 = rstd0 * sc, a1 = rstd1 * sc, rm0 = a0 * mean0, rm1 = a1 * mean1;
#pragma unroll
                for (int jj = 0; jj < 4; jj++) {
                    const float2 ca = *(const float2*)(s_cs + 16 * jj + 2 * c), cb = *(const float2*)(s_cs + 16 * jj + 8 + 2 * c);
                    const uint32_t u0 = pack_bf16(acc[8 * jj] * a0 - rm0 * ca.x, acc[8 * jj + 1] * a0 - rm0 * ca.y);
                    const uint32_t u1 = pack_bf16(acc[8 * jj + 2] * a1 - rm1 * ca.x, acc[8 * jj + 3] * a1 - rm1 * ca.y);
                    const uint32_t u2 = pack_bf16(acc[8 * jj + 4] * a0 - rm0 * cb.x, acc[8 * jj + 5] * a0 - rm0 * cb.y);
                    const uint32_t u3 = pack_bf16(acc[8 * jj + 6] * a1 - rm1 * cb.x, acc[8 * jj + 7] * a1 - rm1 * cb.y);
                    stsm_x4(rbase + (((2 * jj + (lane >> 4)) ^ (mrow & 7)) << 4), u0, u1, u2, u3);
                }
                fence_async_smem();
                named_bar(2 + wg, 128);
                if ((warp & 3) == 0 && elect_one()) { tma2d_store(mapC, stile + wg * 8192, n0, m0 + wg * 64); bulk_commit(); }
            }
            if constexpr (XKV) {
                {
                    const float* acx = &acc[32];
                    const float rm0 = rstd0 * mean0, rm1 = rstd1 * mean1;
                    float n0s = 0.f, n1s = 0.f, vmax = 0.f;
#pragma unroll
                    for (int j = 0; j < 2; j++) {
                        const float2 cs2 = SELF ? *(const float2*)(s_cs + 64 + 8 * j + 2 * c) : cskv[j];
                        const uint32_t u0 = pack_bf16(acx[4 * j] * rstd0 - rm0 * cs2.x, acx[4 * j + 1] * rstd0 - rm0 * cs2.y);
                        const uint32_t u1 = pack_bf16(acx[4 * j + 2] * rstd1 - rm1 * cs2.x, acx[4 * j + 3] * rstd1 - rm1 * cs2.y);
                        n0s += bf_lo(u0) * bf_lo(u0) + bf_hi(u0) * bf_hi(u0);
                        n1s += bf_lo(u1) * bf_lo(u1) + bf_hi(u1) * bf_hi(u1);
                        vmax = fmaxf(vmax, fmaxf(fmaxf(fabsf(bf_lo(u0)), fabsf(bf_hi(u0))), fmaxf(fabsf(bf_lo(u1)), fabsf(bf_hi(u1)))));
                        if (tile_n == 0) {
                            *(uint32_t*)(g_kimg + (row0 >> 3) * 256 + j * 128 + g * 16 + c * 4) = u0;
                            *(uint32_t*)(g_kimg + ((row0 + 8) >> 3) * 256 + j * 128 + g * 16 + c * 4) = u1;
                        } else {
                            uint8_t* vb = g_vimg + (row0 >> 4) * 768 + j * 256 + g * 16 + c * 4;
                            *(uint32_t*)(vb) = u0;
                            *(uint32_t*)(vb + 128) = u1;
                        }
                    }
                    if (tile_n == 1) {
                        uint8_t* vb = g_vimg + (row0 >> 4) * 768 + 512 + g * 16 + c * 4;
                        const uint32_t one = c == 0 ? 0x00003F80u : 0u;
                        *(uint32_t*)(vb) = one;
                        *(uint32_t*)(vb + 128) = one;
                    }
                    n0s += __shfl_xor_sync(0xffffffffu, n0s, 1); n0s += __shfl_xor_sync(0xffffffffu, n0s, 2);
                    n1s += __shfl_xor_sync(0xffffffffu, n1s, 1); n1s += __shfl_xor_sync(0xffffffffu, n1s, 2);
                    float km = tile_n == 0 ? fmaxf(n0s, n1s) : vmax;
                    if (!(n0s + n1s < INFINITY)) km = INFINITY;
#pragma unroll
                    for (int o = 1; o < 32; o <<= 1) km = fmaxf(km, __shfl_xor_sync(0xffffffffu, km, o));
                    if (lane == 0) s_red[warp] = km;
                    named_bar(1, 256);
                    if (tid == 0) {
                        float a = 0.f;
                        for (int i = 0; i < 8; i++) a = fmaxf(a, s_red[i]);
                        g_kvmax[tile_n * 16 + tile_m] = a;
                    }
                }
            }
            if ((warp & 3) == 0) bulk_wait_read();
        } else {
            const uint32_t stile = sbase + wg * (7 * 4096);
            const int mrow = (warp & 3) * 16 + (lane & 7) + ((lane >> 3) & 1) * 8;
            const float a0 = 0.5f * rstd0, a1 = 0.5f * rstd1, rm0 = a0 * mean0, rm1 = a1 * mean1;
#pragma unroll
            for (int jj = 0; jj < 14; jj++) {
                const float2 ca = *(const float2*)(s_cs + 16 * jj + 2 * c), cb = *(const float2*)(s_cs + 16 * jj + 8 + 2 * c);
                float y[8] = {acc[8 * jj] * a0 - rm0 * ca.x,     acc[8 * jj + 1] * a0 - rm0 * ca.y,
                              acc[8 * jj + 2] * a1 - rm1 * ca.x, acc[8 * jj + 3] * a1 - rm1 * ca.y,
                              acc[8 * jj + 4] * a0 - rm0 * cb.x, acc[8 * jj + 5] * a0 - rm0 * cb.y,
                              acc[8 * jj + 6] * a1 - rm1 * cb.x, acc[8 * jj + 7] * a1 - rm1 * cb.y};
#pragma unroll
                for (int i = 0; i < 8; i++) {
                    float t;
                    asm("tanh.approx.f32 %0, %1;" : "=f"(t) : "f"(y[i]));
                    y[i] = fmaf(y[i], t, y[i]);
                }
                const int chunk = (2 * jj + (lane >> 4)) & 3, blk = jj >> 1;
                stsm_x4(stile + blk * 4096 + mrow * 64 + ((chunk ^ ((mrow >> 1) & 3)) << 4),
                        pack_bf16(y[0], y[1]), pack_bf16(y[2], y[3]), pack_bf16(y[4], y[5]), pack_bf16(y[6], y[7]));
                if (jj & 1) {
                    fence_async_smem();
                    __syncwarp();
                    if (elect_one()) {
                        tma2d_store(mapC, stile + blk * 4096 + (warp & 3) * 1024, n0 + blk * 32, m0 + wg * 64 + (warp & 3) * 16);
                        bulk_commit();
                    }
                }
            }
            bulk_wait_read();
        }
    }
    if (tid == 0) TL(prm.tk, 3);
    if (MC) cluster_sync();
}

#define WO_ST 9
#define F2_ST 6
#define F1_ST (F1_BK == 64 ? 5 : 9)
#define QKV_ST 8
constexpr int QKV_STAGES = QKV_ST, WO_STAGES = WO_ST, FFN2_STAGES = F2_ST, FFN1_STAGES = F1_ST;
template <bool SELF>
__global__ void __launch_bounds__(SELF ? 640 : 288) qkv_kernel(const __grid_constant__ CUtensorMap mapA, const __grid_constant__ CUtensorMap mapWq,
                                                  const __grid_constant__ CUtensorMap mapQ, const GemmParams prm) {
    extern __shared__ __align__(1024) uint8_t smem_raw[];
    const int tn = blockIdx.x & 7;
    if (tn < 2) gemm_body<80, 8, QKV_STAGES, EPI_QKV, QKV_MC, SELF>(&mapA, &mapWq, &mapWq, &mapA, &mapQ, prm, blockIdx.x >> 3, tn, smem_raw);
    else gemm_body<64, 8, QKV_STAGES, EPI_QKV, QKV_MC, SELF>(&mapA, &mapWq, &mapWq, &mapA, &mapQ, prm, blockIdx.x >> 3, tn, smem_raw);
}
template <int KB, int STAGES>
__global__ void __launch_bounds__(288) res_gemm_kernel(const __grid_constant__ CUtensorMap mapA, const __grid_constant__ CUtensorMap mapW,
                                                       const __grid_constant__ CUtensorMap mapR, const __grid_constant__ CUtensorMap mapC, const GemmParams prm) {
    extern __shared__ __align__(1024) uint8_t smem_raw[];
#define RES_MAP 0
    gemm_body<64, KB, STAGES, EPI_RES, (KB == 8 ? WO_MC : F2_MC)>(&mapA, &mapW, &mapW, &mapR, &mapC, prm, RES_MAP ? blockIdx.x & 15 : blockIdx.x >> 3,
                                                                  RES_MAP ? blockIdx.x >> 4 : blockIdx.x & 7, smem_raw);
}
__global__ void __launch_bounds__(F1_INLINE ? 256 : 288) ffn1_kernel(const __grid_constant__ CUtensorMap mapA, const __grid_constant__ CUtensorMap mapW4,
                                                   const __grid_constant__ CUtensorMap mapW3, const __grid_constant__ CUtensorMap mapH, const GemmParams prm) {
    extern __shared__ __align__(1024) uint8_t smem_raw[];
#define F1_MAP 0
    const int pair = blockIdx.x >> 1;
    const int tile_n = F1_MAP == 0 ? (pair & 7) : F1_MAP == 1 ? (blockIdx.x >> 4) : (blockIdx.x & 7);
    const int tile_m = F1_MAP == 0 ? (pair >> 3) * 2 + (blockIdx.x & 1) : F1_MAP == 1 ? (blockIdx.x & 15) : (blockIdx.x >> 3);
    gemm_body<224, 512 / F1_BK, FFN1_STAGES, EPI_FFN1, F1_MC>(&mapA, &mapW4, &mapW3, &mapA, &mapH, prm, tile_m, tile_n, smem_raw);
}

#define ATT_NPOLY 11
constexpr int NPOLY = ATT_NPOLY;
__host__ __device__ constexpr bool is_mufu(int i) { return ((i + 1) * (16 - NPOLY)) / 16 != (i * (16 - NPOLY)) / 16; }

__device__ __forceinline__ float ex2(float x) { float r; asm("ex2.approx.ftz.f32 %0, %1;" : "=f"(r) : "f"(x)); return r; }
__device__ __forceinline__ uint32_t exp_pair_mufu(float a, float b) { return pack_bf16(ex2(a), ex2(b)); }
__device__ __forceinline__ uint32_t exp_pair_fma(float a, float b, uint32_t c3f) {
    constexpr float MAGIC = 98430.4140625f;
    const float ta = a + MAGIC, tb = b + (MAGIC - 143.5f);
    uint32_t y, m, r;
    asm("mad.lo.u32 %0, %1, 65536, %2;" : "=r"(y) : "r"(__float_as_uint(tb)), "r"(__float_as_uint(ta)));
    asm("lop3.b32 %0, %1, 0x007F007F, %2, 0xEA;" : "=r"(m) : "r"(y), "r"(c3f));
    const uint32_t e = y & 0xFF80FF80u;
    asm("fma.rn.bf16x2 %0, %1, %2, %3;" : "=r"(r) : "r"(y), "r"(m), "r"(e));
    return r;
}

constexpr int KCH = 256, NCH = S_ / KCH;
constexpr int K_BYTES = S_ * 32, V_BYTES = (S_ / 16) * 768;
constexpr int QO_BYTES = 128 * 128;
constexpr int ATT_SMEM = K_BYTES + V_BYTES + QO_BYTES;

__global__ void __launch_bounds__(512, 1) attn_kernel(const __grid_constant__ CUtensorMap mapQ, const __grid_constant__ CUtensorMap mapO,
                                                       const __nv_bfloat16* __restrict__ wo, const __nv_bfloat16* __restrict__ w1,
                                                       const __nv_bfloat16* __restrict__ w2, int tk) {
    extern __shared__ __align__(1024) uint8_t smem[];
    __shared__ uint64_t bars[NCH + 1];
    __shared__ int s_slow;
    const int tid = threadIdx.x, wg = tid >> 7, warp = (tid >> 5) & 3, lane = tid & 31;
    const uint32_t sK = smem_u32(smem), sV = sK + K_BYTES, sQ = sV + V_BYTES;
    if (blockIdx.x >= 128) {
        pdl_launch();
        pdl_wait();
        side_job(blockIdx.x - 128, (float*)smem, wo, w1, w2);
        return;
    }
    CK(tk, 9);
    if (tid == 0) TL(tk, 0);
    if (tid == 0) {
        for (int i = 0; i <= NCH; i++) mbar_init(smem_u32(&bars[i]), 1);
        prefetch_tmap(&mapQ); prefetch_tmap(&mapO);
        s_slow = 0;
        fence_mbar_init();
    }
    __syncthreads();
    pdl_launch();
    CK(tk, 10);
    pdl_wait();
    CK(tk, 11);
    if (tid == 0) TL(tk, 1);
    const int wu = __shfl_sync(0xffffffffu, tid >> 5, 0);
    auto fetch_chunk = [&](int w) {
        if (elect_one()) {
            const uint32_t bar = smem_u32(&bars[w]);
            mbar_expect_tx(bar, KCH * 32 + (KCH / 16) * 768);
            bulk_load(sK + w * KCH * 32, g_kimg + w * KCH * 32, KCH * 32, bar);
            bulk_load(sV + w * (KCH / 16) * 768, g_vimg + w * (KCH / 16) * 768, (KCH / 16) * 768, bar);
        }
    };
    const int tb = blockIdx.x >> 3, hg = blockIdx.x & 7;
    if (wu == 1 && elect_one()) {
        mbar_expect_tx(smem_u32(&bars[NCH]), QO_BYTES);
        tma2d(sQ, &mapQ, hg * 64, tb * 128, smem_u32(&bars[NCH]));
    }
    if (wu == 0) fetch_chunk(0);
    const int g = lane >> 2;
    float kvm = g_kvmax[lane];
    const int lrow = warp * 16 + (lane & 7) + ((lane >> 3) & 1) * 8;
    const uint32_t qoff = lrow * 128 + (((2 * wg + (lane >> 4)) ^ (lrow & 7)) << 4);
    uint32_t qa[2][4];
    mbar_wait(smem_u32(&bars[NCH]), 0);
    ldsm_x4(qa[0][0], qa[0][1], qa[0][2], qa[0][3], sQ + qoff);
    ldsm_x4(qa[1][0], qa[1][1], qa[1][2], qa[1][3], sQ + 8192 + qoff);
    CK(tk, 12);
    {
        float qn = 0.f;
#pragma unroll
        for (int m = 0; m < 2; m++) {
            float n0 = bf_lo(qa[m][0]) * bf_lo(qa[m][0]) + bf_hi(qa[m][0]) * bf_hi(qa[m][0]) + bf_lo(qa[m][2]) * bf_lo(qa[m][2]) + bf_hi(qa[m][2]) * bf_hi(qa[m][2]);
            float n1 = bf_lo(qa[m][1]) * bf_lo(qa[m][1]) + bf_hi(qa[m][1]) * bf_hi(qa[m][1]) + bf_lo(qa[m][3]) * bf_lo(qa[m][3]) + bf_hi(qa[m][3]) * bf_hi(qa[m][3]);
            n0 += __shfl_xor_sync(0xffffffffu, n0, 1); n0 += __shfl_xor_sync(0xffffffffu, n0, 2);
            n1 += __shfl_xor_sync(0xffffffffu, n1, 1); n1 += __shfl_xor_sync(0xffffffffu, n1, 2);
            if (!(n0 == n0) || !(n1 == n1)) n0 = INFINITY;
            qn = fmaxf(qn, fmaxf(n0, n1));
        }
        CK(tk, 13);
#pragma unroll
        for (int o = 1; o < 16; o <<= 1) kvm = fmaxf(kvm, __shfl_xor_sync(0xffffffffu, kvm, o));
        const float km = __shfl_sync(0xffffffffu, kvm, 0), vm = __shfl_sync(0xffffffffu, kvm, 16);
        const bool ok = (qn * km <= 10000.f) && (vm <= 16384.f);
        if (!ok) s_slow = 1;
    }
    CK(tk, 14);
    float oacc[2][12];
#pragma unroll
    for (int m = 0; m < 2; m++)
#pragma unroll
        for (int i = 0; i < 12; i++) oacc[m][i] = 0.f;
    __syncthreads();
    const bool slow = s_slow != 0;
    if (wu >= 1 && wu < NCH) fetch_chunk(wu);
    CK(tk, 15);

    const uint64_t dK0 = mkdesc(sK, 128, 256, 0);
    const uint64_t dV0 = mkdesc(sV, 128, 256, 0);
    uint32_t c3f;
    asm volatile("mov.b32 %0, 0x3F003F00;" : "=r"(c3f));
    if (!slow) {
        uint64_t dK = dK0, dV = dV0;
        float s[32];
        fence_regs(oacc[0]); fence_regs(oacc[1]);
        mbar_wait(smem_u32(&bars[0]), 0);
        wg_fence();
        wgmma_rs_n64_z(s, qa[0][0], qa[0][1], qa[0][2], qa[0][3], dK);
        wg_commit();
#pragma unroll 1
        for (int ch = 0; ch < NCH; ch++) {
#pragma unroll
            for (int tt = 0; tt < KCH / 64; tt++) {
#pragma unroll
                for (int m = 0; m < 2; m++) {
                    wg_wait<0>();
                    fence_regs(s);
                    uint32_t p[16];
#pragma unroll
                    for (int i = 0; i < 16; i++) p[i] = is_mufu(i) ? exp_pair_mufu(s[2 * i], s[2 * i + 1]) : exp_pair_fma(s[2 * i], s[2 * i + 1], c3f);
                    if (m == 1 && tt == KCH / 64 - 1) mbar_wait(smem_u32(&bars[ch + 1 < NCH ? ch + 1 : ch]), 0);
                    wg_fence();
#pragma unroll
                    for (int kk = 0; kk < 4; kk++)
                        wgmma_rs_n24_tb(oacc[m], p[4 * kk], p[4 * kk + 1], p[4 * kk + 2], p[4 * kk + 3], dV + (uint64_t)((tt * 4 + kk) * (768 / 16)));
                    wgmma_rs_n64_z(s, qa[1 - m][0], qa[1 - m][1], qa[1 - m][2], qa[1 - m][3], dK + (uint64_t)((tt + m) * (64 * 32 / 16)));
                    wg_commit();
                }
            }
            dK += KCH * 32 / 16;
            dV += (KCH / 16) * (768 / 16);
        }
        wg_wait<0>();
        fence_regs(s);
    } else {
        float mx[2][2] = {{-INFINITY, -INFINITY}, {-INFINITY, -INFINITY}};
#pragma unroll 1
        for (int t = 0; t < S_ / 64; t++) {
            if ((t & 3) == 0) mbar_wait(smem_u32(&bars[t >> 2]), 0);
            const uint64_t dK = dK0 + (uint64_t)(t * 64 * 32 / 16);
            const uint64_t dV = dV0 + (uint64_t)(t * 4 * 768 / 16);
#pragma unroll
            for (int m = 0; m < 2; m++) {
                float s[32];
                wg_fence();
                wgmma_rs_n64_z(s, qa[m][0], qa[m][1], qa[m][2], qa[m][3], dK);
                wg_commit();
                wg_wait<0>();
                fence_regs(s);
                fence_regs(oacc[m]);
                float r0 = mx[m][0], r1 = mx[m][1];
#pragma unroll
                for (int j = 0; j < 8; j++) {
                    r0 = fmaxf(r0, fmaxf(s[4 * j], s[4 * j + 1]));
                    r1 = fmaxf(r1, fmaxf(s[4 * j + 2], s[4 * j + 3]));
                }
                r0 = fmaxf(r0, __shfl_xor_sync(0xffffffffu, r0, 1)); r0 = fmaxf(r0, __shfl_xor_sync(0xffffffffu, r0, 2));
                r1 = fmaxf(r1, __shfl_xor_sync(0xffffffffu, r1, 1)); r1 = fmaxf(r1, __shfl_xor_sync(0xffffffffu, r1, 2));
                const float al0 = ex2(mx[m][0] - r0), al1 = ex2(mx[m][1] - r1);
                mx[m][0] = r0; mx[m][1] = r1;
#pragma unroll
                for (int j = 0; j < 3; j++) {
                    oacc[m][4 * j] *= al0; oacc[m][4 * j + 1] *= al0;
                    oacc[m][4 * j + 2] *= al1; oacc[m][4 * j + 3] *= al1;
                }
                uint32_t p[16];
#pragma unroll
                for (int j = 0; j < 8; j++) {
                    p[2 * j] = pack_bf16(ex2(s[4 * j] - r0), ex2(s[4 * j + 1] - r0));
                    p[2 * j + 1] = pack_bf16(ex2(s[4 * j + 2] - r1), ex2(s[4 * j + 3] - r1));
                }
                fence_regs(oacc[m]);
                wg_fence();
#pragma unroll
                for (int kk = 0; kk < 4; kk++)
                    wgmma_rs_n24_tb(oacc[m], p[4 * kk], p[4 * kk + 1], p[4 * kk + 2], p[4 * kk + 3], dV + (uint64_t)(kk * 768 / 16));
                wg_commit();
                wg_wait<0>();
            }
        }
    }
    fence_regs(oacc[0]); fence_regs(oacc[1]);
    if (tid == 0) TL(tk, 2);
#pragma unroll
    for (int m = 0; m < 2; m++) {
        const float l0 = __shfl_sync(0xffffffffu, oacc[m][8], lane & ~3);
        const float l1 = __shfl_sync(0xffffffffu, oacc[m][10], lane & ~3);
        const float r0 = __fdividef(1.0f, l0), r1 = __fdividef(1.0f, l1);
        stsm_x4(sQ + m * 8192 + qoff, pack_bf16(oacc[m][0] * r0, oacc[m][1] * r0), pack_bf16(oacc[m][2] * r1, oacc[m][3] * r1),
                pack_bf16(oacc[m][4] * r0, oacc[m][5] * r0), pack_bf16(oacc[m][6] * r1, oacc[m][7] * r1));
    }
    fence_async_smem();
    __syncthreads();
    if (wu == 0 && elect_one()) {
        tma2d_store(&mapO, sQ, hg * 64, tb * 128);
        bulk_commit();
        bulk_wait_read();
    }
    if (tid == 0) TL(tk, 3);
}

typedef CUresult (*EncodeFn)(CUtensorMap*, CUtensorMapDataType, cuuint32_t, void*, const cuuint64_t*, const cuuint64_t*, const cuuint32_t*,
                             const cuuint32_t*, CUtensorMapInterleave, CUtensorMapSwizzle, CUtensorMapL2promotion, CUtensorMapFloatOOBfill);

EncodeFn get_encode() {
    static EncodeFn fn = nullptr;
    if (!fn) {
        void* p = nullptr;
        cudaDriverEntryPointQueryResult qr;
        cudaGetDriverEntryPoint("cuTensorMapEncodeTiled", &p, cudaEnableDefault, &qr);
        fn = (EncodeFn)p;
    }
    return fn;
}
CUtensorMap map2d(const void* ptr, uint64_t cols, uint64_t rows, uint32_t bc, uint32_t br, CUtensorMapSwizzle sw) {
    CUtensorMap m;
    cuuint64_t gd[2] = {cols, rows}, gs[1] = {cols * 2};
    cuuint32_t bx[2] = {bc, br}, es[2] = {1, 1};
    get_encode()(&m, CU_TENSOR_MAP_DATA_TYPE_BFLOAT16, 2, (void*)ptr, gd, gs, bx, es, CU_TENSOR_MAP_INTERLEAVE_NONE, sw,
                 CU_TENSOR_MAP_L2_PROMOTION_L2_128B, CU_TENSOR_MAP_FLOAT_OOB_FILL_NONE);
    return m;
}
CUtensorMap map3d32(const void* ptr, uint64_t cols, uint64_t rows, uint32_t br, uint32_t nb) {
    CUtensorMap m;
    cuuint64_t gd[3] = {32, rows, cols / 32}, gs[2] = {cols * 2, 64};
    cuuint32_t bx[3] = {32, br, nb}, es[3] = {1, 1, 1};
    get_encode()(&m, CU_TENSOR_MAP_DATA_TYPE_BFLOAT16, 3, (void*)ptr, gd, gs, bx, es, CU_TENSOR_MAP_INTERLEAVE_NONE, CU_TENSOR_MAP_SWIZZLE_64B,
                 CU_TENSOR_MAP_L2_PROMOTION_L2_128B, CU_TENSOR_MAP_FLOAT_OOB_FILL_NONE);
    return m;
}

template <typename... KArgs, typename... Args>
void launch(void (*kern)(KArgs...), int grid, int block, int smem, int cluster, bool pdl, Args... args) {
    cudaLaunchConfig_t cfg = {};
    cfg.gridDim = dim3(grid);
    cfg.blockDim = dim3(block);
    cfg.dynamicSmemBytes = smem;
    cfg.stream = cudaStreamPerThread;
    cudaLaunchAttribute at[2];
    int n = 0;
    if (cluster > 1) { at[n].id = cudaLaunchAttributeClusterDimension; at[n].val.clusterDim.x = cluster; at[n].val.clusterDim.y = 1; at[n].val.clusterDim.z = 1; n++; }
    if (pdl) { at[n].id = cudaLaunchAttributeProgrammaticStreamSerialization; at[n].val.programmaticStreamSerializationAllowed = 1; n++; }
    cfg.attrs = at;
    cfg.numAttrs = n;
    cudaLaunchKernelEx(&cfg, kern, KArgs(args)...);
}

template <typename T> void* sym(const T& s) { void* p = nullptr; cudaGetSymbolAddress(&p, s); return p; }

}

extern "C" void kernel_launch(void* const* d_in, const int* in_sizes, int n_in, void* d_out, int out_size) {
    const __nv_bfloat16* x = (const __nv_bfloat16*)d_in[0];
    const __nv_bfloat16* wq = (const __nv_bfloat16*)d_in[1];
    const __nv_bfloat16* wk = (const __nv_bfloat16*)d_in[2];
    const __nv_bfloat16* wv = (const __nv_bfloat16*)d_in[3];
    const __nv_bfloat16* wo = (const __nv_bfloat16*)d_in[4];
    const __nv_bfloat16* w1 = (const __nv_bfloat16*)d_in[6];
    const __nv_bfloat16* w2 = (const __nv_bfloat16*)d_in[7];

    constexpr int SM_QKV = GemmSmem<QKV_STAGES, EPI_QKV>::TOTAL, SM_QKV0 = GemmSmem<QKV_STAGES, EPI_QKV>::TOTAL_SELF;
    static_assert(SM_QKV0 <= 232448, "shared memory");
    constexpr int SM_WO = GemmSmem<WO_STAGES, EPI_RES>::TOTAL, SM_FFN2 = GemmSmem<FFN2_STAGES, EPI_RES>::TOTAL;
    static_assert(SM_WO > 116736 && SM_FFN2 > 116736, "one CTA per SM");
    constexpr int SM_FFN1 = GemmSmem<FFN1_STAGES, EPI_FFN1>::TOTAL;
    cudaFuncSetAttribute(qkv_kernel<false>, cudaFuncAttributeMaxDynamicSharedMemorySize, SM_QKV);
    cudaFuncSetAttribute(qkv_kernel<true>, cudaFuncAttributeMaxDynamicSharedMemorySize, SM_QKV0);
    cudaFuncSetAttribute(res_gemm_kernel<8, WO_STAGES>, cudaFuncAttributeMaxDynamicSharedMemorySize, SM_WO);
    cudaFuncSetAttribute(ffn1_kernel, cudaFuncAttributeMaxDynamicSharedMemorySize, SM_FFN1);
    cudaFuncSetAttribute(res_gemm_kernel<28, FFN2_STAGES>, cudaFuncAttributeMaxDynamicSharedMemorySize, SM_FFN2);
    cudaFuncSetAttribute(attn_kernel, cudaFuncAttributeMaxDynamicSharedMemorySize, ATT_SMEM);
    cudaFuncSetAttribute(qkv_kernel<false>, cudaFuncAttributePreferredSharedMemoryCarveout, 100);
    cudaFuncSetAttribute(qkv_kernel<true>, cudaFuncAttributePreferredSharedMemoryCarveout, 100);
    cudaFuncSetAttribute(res_gemm_kernel<8, WO_STAGES>, cudaFuncAttributePreferredSharedMemoryCarveout, 100);
    cudaFuncSetAttribute(ffn1_kernel, cudaFuncAttributePreferredSharedMemoryCarveout, 100);
    cudaFuncSetAttribute(res_gemm_kernel<28, FFN2_STAGES>, cudaFuncAttributePreferredSharedMemoryCarveout, 100);
    cudaFuncSetAttribute(attn_kernel, cudaFuncAttributePreferredSharedMemoryCarveout, 100);

    void *q = sym(g_q), *o = sym(g_o), *x1 = sym(g_x1), *x2 = sym(g_x2), *x3 = sym(g_x3), *h = sym(g_h);
    float2* stats = (float2*)sym(g_stats);
    const void* xs[5] = {x, x1, x2, x3, d_out};

    const CUtensorMapSwizzle SW128 = CU_TENSOR_MAP_SWIZZLE_128B, SW64 = CU_TENSOR_MAP_SWIZZLE_64B;
    const CUtensorMap mWq = map3d32(wq, D_, D_, 64, 2);
    const CUtensorMap mWo = map2d(wo, D_, D_, 64, 64, SW128);
    const CUtensorMap mW1a = map3d32(w1, F_, D_, F1_BK, 4), mW1b = map3d32(w1, F_, D_, F1_BK, 3);
    const CUtensorMap mW2 = map2d(w2, D_, F_, 64, 64, SW128);
    const CUtensorMap mQ = map2d(q, D_, S_, 64, 64, SW128);
    const CUtensorMap mQa = map2d(q, D_, S_, 64, 128, SW128), mOs = map2d(o, D_, S_, 64, 128, SW128);
    const CUtensorMap mHst = map2d(h, F_, S_, 32, 16, SW64);
    CUtensorMap mXa[4], mXf[4], mXr[4], mXs[5];
    for (int i = 0; i < 4; i++) {
        mXa[i] = map2d(xs[i], D_, S_, 64, QKV_MC ? 64 : 128, SW128);
        mXf[i] = F1_BK == 64 ? map2d(xs[i], D_, S_, 64, 128, SW128) : map2d(xs[i], D_, S_, 32, 128, SW64);
        mXr[i] = map2d(xs[i], D_, S_, 64, 128, SW128);
    }
    for (int i = 0; i < 5; i++) mXs[i] = map2d(xs[i], D_, S_, 64, 64, SW128);
    const CUtensorMap mOa = map2d(o, D_, S_, 64, WO_MC ? 64 : 128, SW128);
    const CUtensorMap mHa = map2d(h, F_, S_, 64, F2_MC ? 64 : 128, SW128);

    for (int layer = 0; layer < 2; layer++) {
        const int xi = layer * 2;
        GemmParams p;
        p.wkv = wk; p.wv = wv;
        p.stats_in = stats + (size_t)xi * 8 * S_; p.stats_out = nullptr; p.tk = 1 + 5 * layer;
        if (layer == 0) launch(qkv_kernel<true>, 128, 640, SM_QKV0, QKV_MC ? 2 : 1, false, mXa[xi], mWq, mQ, p);
        else launch(qkv_kernel<false>, 128, 288, SM_QKV, QKV_MC ? 2 : 1, true, mXa[xi], mWq, mQ, p);
        launch(attn_kernel, layer == 0 ? 128 + SIDE_CTAS : 128, 512, ATT_SMEM, 1, true, mQa, mOs, wo, w1, w2, 2 + 5 * layer);
        p.stats_in = nullptr; p.stats_out = stats + (size_t)(xi + 1) * 8 * S_; p.tk = 3 + 5 * layer;
        launch(res_gemm_kernel<8, WO_STAGES>, 128, 288, SM_WO, WO_MC ? 2 : 1, true, mOa, mWo, mXr[xi], mXs[xi + 1], p);
        p.stats_in = stats + (size_t)(xi + 1) * 8 * S_; p.stats_out = nullptr; p.tk = 4 + 5 * layer;
        launch(ffn1_kernel, 128, F1_INLINE ? 256 : 288, SM_FFN1, F1_MC ? 2 : 1, true, mXf[xi + 1], mW1a, mW1b, mHst, p);
        p.stats_in = nullptr; p.stats_out = layer == 0 ? stats + (size_t)2 * 8 * S_ : nullptr; p.tk = 5 + 5 * layer;
        launch(res_gemm_kernel<28, FFN2_STAGES>, 128, 288, SM_FFN2, F2_MC ? 2 : 1, true, mHa, mW2, mXr[xi + 1], mXs[xi + 2], p);
    }
}
```

```cpp
#include <cuda_runtime.h>
#include <cuda_bf16.h>
#include <cuda.h>
#include <stdint.h>

#define F1_INLINE 0
#define QKV_MC 0
#define WO_MC 0
#define F2_MC 0
#define F1_MC 2
#define SELF_WAIT 0
#define ATT_VAR 1
#define SIDE_WAIT 1
#define L2PROMO CU_TENSOR_MAP_L2_PROMOTION_L2_128B
#define PREB 1
#define RES_WAIT0 0

namespace {

constexpr int S_ = 2048, D_ = 512, H_ = 32, F_ = 1792;

__device__ __align__(1024) __nv_bfloat16 g_q[S_ * D_];
__device__ __align__(1024) __nv_bfloat16 g_o[S_ * D_];
__device__ __align__(1024) __nv_bfloat16 g_x1[S_ * D_];
__device__ __align__(1024) __nv_bfloat16 g_x2[S_ * D_];
__device__ __align__(1024) __nv_bfloat16 g_x3[S_ * D_];
__device__ __align__(1024) __nv_bfloat16 g_h[S_ * F_];
__device__ __align__(1024) uint8_t g_kimg[S_ * 32];
__device__ __align__(1024) uint8_t g_vimg[(S_ / 16) * 768];
__device__ __align__(1024) float2 g_stats[4][8 * S_];
__device__ __align__(16) float g_cs_q[D_];
__device__ __align__(16) float g_cs_kv[32];
__device__ __align__(16) float g_cs_1[F_];
__device__ __align__(16) float g_kvmax[32];

#define TL(k, slot)
#define CK(k, i)
#define CP(k, i)

__device__ __forceinline__ uint32_t smem_u32(const void* p) { return (uint32_t)__cvta_generic_to_shared(p); }
__device__ __forceinline__ void mbar_init(uint32_t bar, uint32_t cnt) {
    asm volatile("mbarrier.init.shared::cta.b64 [%0], %1;" ::"r"(bar), "r"(cnt));
}
__device__ __forceinline__ void mbar_expect_tx(uint32_t bar, uint32_t bytes) {
    asm volatile("mbarrier.arrive.expect_tx.shared::cta.b64 _, [%0], %1;" ::"r"(bar), "r"(bytes) : "memory");
}
__device__ __forceinline__ void mbar_arrive(uint32_t bar) {
    asm volatile("mbarrier.arrive.shared::cta.b64 _, [%0];" ::"r"(bar) : "memory");
}
__device__ __forceinline__ void mbar_arrive_remote(uint32_t bar, uint32_t cta) {
    asm volatile("{\n.reg .b32 ra;\nmapa.shared::cluster.u32 ra, %0, %1;\nmbarrier.arrive.shared::cluster.b64 _, [ra];\n}" ::"r"(bar), "r"(cta) : "memory");
}
__device__ __forceinline__ void mbar_wait(uint32_t bar, uint32_t parity) {
    asm volatile("{\n.reg .pred p;\nWAIT_%=:\nmbarrier.try_wait.parity.shared::cta.b64 p, [%0], %1;\n@p bra DONE_%=;\nbra WAIT_%=;\nDONE_%=:\n}" ::"r"(bar), "r"(parity) : "memory");
}
__device__ __forceinline__ void bulk_load(uint32_t dst, const void* src, uint32_t bytes, uint32_t bar) {
    asm volatile("cp.async.bulk.shared::cluster.global.mbarrier::complete_tx::bytes [%0], [%1], %2, [%3];" ::"r"(dst), "l"(src), "r"(bytes), "r"(bar) : "memory");
}
__device__ __forceinline__ void tma2d(uint32_t dst, const CUtensorMap* m, int c0, int c1, uint32_t bar) {
    asm volatile("cp.async.bulk.tensor.2d.shared::cluster.global.mbarrier::complete_tx::bytes [%0], [%1, {%3, %4}], [%2];" ::"r"(dst), "l"(m), "r"(bar), "r"(c0), "r"(c1) : "memory");
}
__device__ __forceinline__ void tma2d_mc(uint32_t dst, const CUtensorMap* m, int c0, int c1, uint32_t bar, uint16_t mask) {
    asm volatile("cp.async.bulk.tensor.2d.shared::cluster.global.mbarrier::complete_tx::bytes.multicast::cluster [%0], [%1, {%3, %4}], [%2], %5;" ::"r"(dst), "l"(m), "r"(bar), "r"(c0), "r"(c1), "h"(mask) : "memory");
}
__device__ __forceinline__ void tma3d(uint32_t dst, const CUtensorMap* m, int c0, int c1, int c2, uint32_t bar) {
    asm volatile("cp.async.bulk.tensor.3d.shared::cluster.global.mbarrier::complete_tx::bytes [%0], [%1, {%3, %4, %5}], [%2];" ::"r"(dst), "l"(m), "r"(bar), "r"(c0), "r"(c1), "r"(c2) : "memory");
}
__device__ __forceinline__ void tma3d_mc(uint32_t dst, const CUtensorMap* m, int c0, int c1, int c2, uint32_t bar, uint16_t mask) {
    asm volatile("cp.async.bulk.tensor.3d.shared::cluster.global.mbarrier::complete_tx::bytes.multicast::cluster [%0], [%1, {%3, %4, %5}], [%2], %6;" ::"r"(dst), "l"(m), "r"(bar), "r"(c0), "r"(c1), "r"(c2), "h"(mask) : "memory");
}
__device__ __forceinline__ void tma2d_store(const CUtensorMap* m, uint32_t src, int c0, int c1) {
    asm volatile("cp.async.bulk.tensor.2d.global.shared::cta.bulk_group [%0, {%2, %3}], [%1];" ::"l"(m), "r"(src), "r"(c0), "r"(c1) : "memory");
}
__device__ __forceinline__ void tma3d_store(const CUtensorMap* m, uint32_t src, int c0, int c1, int c2) {
    asm volatile("cp.async.bulk.tensor.3d.global.shared::cta.bulk_group [%0, {%2, %3, %4}], [%1];" ::"l"(m), "r"(src), "r"(c0), "r"(c1), "r"(c2) : "memory");
}
__device__ __forceinline__ void bulk_commit() { asm volatile("cp.async.bulk.commit_group;" ::: "memory"); }
__device__ __forceinline__ void bulk_wait_read() { asm volatile("cp.async.bulk.wait_group.read 0;" ::: "memory"); }
__device__ __forceinline__ void prefetch_tmap(const CUtensorMap* m) { asm volatile("prefetch.tensormap [%0];" ::"l"(m) : "memory"); }
__device__ __forceinline__ void fence_async_smem() { asm volatile("fence.proxy.async.shared::cta;" ::: "memory"); }
__device__ __forceinline__ void fence_mbar_init() { asm volatile("fence.mbarrier_init.release.cluster;" ::: "memory"); }
__device__ __forceinline__ void cluster_sync() { asm volatile("barrier.cluster.arrive.release.aligned;\nbarrier.cluster.wait.acquire.aligned;" ::: "memory"); }
__device__ __forceinline__ uint32_t cluster_rank() { uint32_t r; asm volatile("mov.u32 %0, %%cluster_ctarank;" : "=r"(r)); return r; }
__device__ __forceinline__ void pdl_wait() { asm volatile("griddepcontrol.wait;" ::: "memory"); }
__device__ __forceinline__ void pdl_launch() { asm volatile("griddepcontrol.launch_dependents;" ::: "memory"); }
__device__ __forceinline__ bool elect_one() {
    uint32_t p;
    asm volatile("{\n.reg .pred p;\nelect.sync _|p, 0xffffffff;\nselp.b32 %0, 1, 0, p;\n}" : "=r"(p));
    return p != 0;
}
__device__ __forceinline__ void named_bar(int id, int n) { asm volatile("bar.sync %0, %1;" ::"r"(id), "r"(n) : "memory"); }

__device__ __forceinline__ void wg_fence() { asm volatile("wgmma.fence.sync.aligned;" ::: "memory"); }
__device__ __forceinline__ void wg_commit() { asm volatile("wgmma.commit_group.sync.aligned;" ::: "memory"); }
template <int N> __device__ __forceinline__ void wg_wait() { asm volatile("wgmma.wait_group.sync.aligned %0;" ::"n"(N) : "memory"); }
template <int N> __device__ __forceinline__ void fence_regs(float (&d)[N]) {
#pragma unroll
    for (int i = 0; i < N; i++) asm volatile("" : "+f"(d[i])::"memory");
}
__device__ __forceinline__ uint64_t mkdesc(uint32_t addr, uint32_t lbo, uint32_t sbo, uint32_t swz) {
    uint64_t d = 0;
    d |= (uint64_t)((addr & 0x3FFFF) >> 4);
    d |= (uint64_t)((lbo & 0x3FFFF) >> 4) << 16;
    d |= (uint64_t)((sbo & 0x3FFFF) >> 4) << 32;
    d |= (uint64_t)swz << 62;
    return d;
}
__device__ __forceinline__ void ldsm_x4(uint32_t& r0, uint32_t& r1, uint32_t& r2, uint32_t& r3, uint32_t addr) {
    asm volatile("ldmatrix.sync.aligned.m8n8.x4.shared.b16 {%0,%1,%2,%3}, [%4];" : "=r"(r0), "=r"(r1), "=r"(r2), "=r"(r3) : "r"(addr) : "memory");
}
__device__ __forceinline__ void stsm_x4(uint32_t addr, uint32_t r0, uint32_t r1, uint32_t r2, uint32_t r3) {
    asm volatile("stmatrix.sync.aligned.m8n8.x4.shared.b16 [%0], {%1,%2,%3,%4};" ::"r"(addr), "r"(r0), "r"(r1), "r"(r2), "r"(r3) : "memory");
}
__device__ __forceinline__ void ldsm_x4_t(uint32_t& r0, uint32_t& r1, uint32_t& r2, uint32_t& r3, uint32_t addr) {
    asm volatile("ldmatrix.sync.aligned.m8n8.x4.trans.shared.b16 {%0,%1,%2,%3}, [%4];" : "=r"(r0), "=r"(r1), "=r"(r2), "=r"(r3) : "r"(addr) : "memory");
}
__device__ __forceinline__ void hmma(float (&d)[4], uint32_t a0, uint32_t a1, uint32_t a2, uint32_t a3, uint32_t b0, uint32_t b1) {
    asm volatile("mma.sync.aligned.m16n8k16.row.col.f32.bf16.bf16.f32 {%0,%1,%2,%3}, {%4,%5,%6,%7}, {%8,%9}, {%0,%1,%2,%3};"
                 : "+f"(d[0]), "+f"(d[1]), "+f"(d[2]), "+f"(d[3]) : "r"(a0), "r"(a1), "r"(a2), "r"(a3), "r"(b0), "r"(b1));
}
__device__ __forceinline__ uint32_t pack_bf16(float lo, float hi) {
    uint32_t r;
    asm("cvt.rn.bf16x2.f32 %0, %1, %2;" : "=r"(r) : "f"(hi), "f"(lo));
    return r;
}
__device__ __forceinline__ float bf_lo(uint32_t v) { return __uint_as_float(v << 16); }
__device__ __forceinline__ float bf_hi(uint32_t v) { return __uint_as_float(v & 0xFFFF0000u); }

#define WG_REGS_4(o) "+f"(d[o]), "+f"(d[o + 1]), "+f"(d[o + 2]), "+f"(d[o + 3])
#define WG_REGS_8(o) WG_REGS_4(o), WG_REGS_4(o + 4)
#define WG_REGS_16(o) WG_REGS_8(o), WG_REGS_8(o + 8)
#define WG_REGS_32(o) WG_REGS_16(o), WG_REGS_16(o + 16)

__device__ __forceinline__ void wgmma_ss_n80_tb(float (&d)[40], uint64_t dA, uint64_t dB, int sc) {
    asm volatile("{\n.reg .pred p;\nsetp.ne.b32 p, %42, 0;\n"
                 "wgmma.mma_async.sync.aligned.m64n80k16.f32.bf16.bf16 "
                 "{%0,%1,%2,%3,%4,%5,%6,%7,%8,%9,%10,%11,%12,%13,%14,%15,%16,%17,%18,%19,%20,%21,%22,%23,%24,%25,%26,%27,%28,%29,%30,%31,"
                 "%32,%33,%34,%35,%36,%37,%38,%39}, %40, %41, p, 1, 1, 0, 1;\n}\n"
                 : WG_REGS_32(0), WG_REGS_8(32) : "l"(dA), "l"(dB), "r"(sc));
}
__device__ __forceinline__ void wgmma_ss_n64_tb(float (&d)[32], uint64_t dA, uint64_t dB, int sc) {
    asm volatile("{\n.reg .pred p;\nsetp.ne.b32 p, %34, 0;\n"
                 "wgmma.mma_async.sync.aligned.m64n64k16.f32.bf16.bf16 "
                 "{%0,%1,%2,%3,%4,%5,%6,%7,%8,%9,%10,%11,%12,%13,%14,%15,%16,%17,%18,%19,%20,%21,%22,%23,%24,%25,%26,%27,%28,%29,%30,%31}, "
                 "%32, %33, p, 1, 1, 0, 1;\n}\n"
                 : WG_REGS_32(0) : "l"(dA), "l"(dB), "r"(sc));
}
__device__ __forceinline__ void wgmma_ss_n224_tb(float (&d)[112], uint64_t dA, uint64_t dB, int sc) {
    asm volatile("{\n.reg .pred p;\nsetp.ne.b32 p, %114, 0;\n"
                 "wgmma.mma_async.sync.aligned.m64n224k16.f32.bf16.bf16 "
                 "{%0,%1,%2,%3,%4,%5,%6,%7,%8,%9,%10,%11,%12,%13,%14,%15,%16,%17,%18,%19,%20,%21,%22,%23,%24,%25,%26,%27,%28,%29,%30,%31,"
                 "%32,%33,%34,%35,%36,%37,%38,%39,%40,%41,%42,%43,%44,%45,%46,%47,%48,%49,%50,%51,%52,%53,%54,%55,%56,%57,%58,%59,%60,%61,%62,%63,"
                 "%64,%65,%66,%67,%68,%69,%70,%71,%72,%73,%74,%75,%76,%77,%78,%79,%80,%81,%82,%83,%84,%85,%86,%87,%88,%89,%90,%91,%92,%93,%94,%95,"
                 "%96,%97,%98,%99,%100,%101,%102,%103,%104,%105,%106,%107,%108,%109,%110,%111}, "
                 "%112, %113, p, 1, 1, 0, 1;\n}\n"
                 : WG_REGS_32(0), WG_REGS_32(32), WG_REGS_32(64), WG_REGS_16(96) : "l"(dA), "l"(dB), "r"(sc));
}
template <int BN> __device__ __forceinline__ void wgmma_ss_tb(float (&d)[BN / 2], uint64_t dA, uint64_t dB, int sc) {
    if constexpr (BN == 64) wgmma_ss_n64_tb(d, dA, dB, sc);
    else if constexpr (BN == 80) wgmma_ss_n80_tb(d, dA, dB, sc);
    else wgmma_ss_n224_tb(d, dA, dB, sc);
}
__device__ __forceinline__ void wgmma_rs_n64_tb(float (&d)[32], uint32_t a, uint64_t dB, int sc) {
    asm volatile("{\n.reg .pred p;\nsetp.ne.b32 p, %34, 0;\n"
                 "wgmma.mma_async.sync.aligned.m64n64k16.f32.bf16.bf16 "
                 "{%0,%1,%2,%3,%4,%5,%6,%7,%8,%9,%10,%11,%12,%13,%14,%15,%16,%17,%18,%19,%20,%21,%22,%23,%24,%25,%26,%27,%28,%29,%30,%31}, "
                 "{%32,%32,%32,%32}, %33, p, 1, 1, 1;\n}\n"
                 : WG_REGS_32(0) : "r"(a), "l"(dB), "r"(sc));
}
__device__ __forceinline__ void wgmma_rs_n80_tb(float (&d)[40], uint32_t a, uint64_t dB, int sc) {
    asm volatile("{\n.reg .pred p;\nsetp.ne.b32 p, %42, 0;\n"
                 "wgmma.mma_async.sync.aligned.m64n80k16.f32.bf16.bf16 "
                 "{%0,%1,%2,%3,%4,%5,%6,%7,%8,%9,%10,%11,%12,%13,%14,%15,%16,%17,%18,%19,%20,%21,%22,%23,%24,%25,%26,%27,%28,%29,%30,%31,"
                 "%32,%33,%34,%35,%36,%37,%38,%39}, {%40,%40,%40,%40}, %41, p, 1, 1, 1;\n}\n"
                 : WG_REGS_32(0), WG_REGS_8(32) : "r"(a), "l"(dB), "r"(sc));
}
template <int BN> __device__ __forceinline__ void wgmma_rs_ones(float (&d)[BN / 2], uint64_t dB, int sc) {
    if constexpr (BN == 80) wgmma_rs_n80_tb(d, 0x3F803F80u, dB, sc);
    else if constexpr (BN == 64) wgmma_rs_n64_tb(d, 0x3F803F80u, dB, sc);
}
__device__ __forceinline__ void wgmma_rs_n64_z(float (&d)[32], uint32_t a0, uint32_t a1, uint32_t a2, uint32_t a3, uint64_t dB) {
    asm volatile("{\n.reg .pred p;\nsetp.ne.b32 p, 0, 0;\n"
                 "wgmma.mma_async.sync.aligned.m64n64k16.f32.bf16.bf16 "
                 "{%0,%1,%2,%3,%4,%5,%6,%7,%8,%9,%10,%11,%12,%13,%14,%15,%16,%17,%18,%19,%20,%21,%22,%23,%24,%25,%26,%27,%28,%29,%30,%31}, "
                 "{%32,%33,%34,%35}, %36, p, 1, 1, 0;\n}\n"
                 : "=f"(d[0]), "=f"(d[1]), "=f"(d[2]), "=f"(d[3]), "=f"(d[4]), "=f"(d[5]), "=f"(d[6]), "=f"(d[7]),
                   "=f"(d[8]), "=f"(d[9]), "=f"(d[10]), "=f"(d[11]), "=f"(d[12]), "=f"(d[13]), "=f"(d[14]), "=f"(d[15]),
                   "=f"(d[16]), "=f"(d[17]), "=f"(d[18]), "=f"(d[19]), "=f"(d[20]), "=f"(d[21]), "=f"(d[22]), "=f"(d[23]),
                   "=f"(d[24]), "=f"(d[25]), "=f"(d[26]), "=f"(d[27]), "=f"(d[28]), "=f"(d[29]), "=f"(d[30]), "=f"(d[31])
                 : "r"(a0), "r"(a1), "r"(a2), "r"(a3), "l"(dB));
}
__device__ __forceinline__ void wgmma_rs_n24_tb(float (&d)[12], uint32_t a0, uint32_t a1, uint32_t a2, uint32_t a3, uint64_t dB) {
    asm volatile("{\n.reg .pred p;\nsetp.eq.b32 p, 0, 0;\n"
                 "wgmma.mma_async.sync.aligned.m64n24k16.f32.bf16.bf16 "
                 "{%0,%1,%2,%3,%4,%5,%6,%7,%8,%9,%10,%11}, {%12,%13,%14,%15}, %16, p, 1, 1, 1;\n}\n"
                 : WG_REGS_8(0), WG_REGS_4(8) : "r"(a0), "r"(a1), "r"(a2), "r"(a3), "l"(dB));
}

constexpr int SIDE_CTAS = 4;
__device__ __forceinline__ void side_job(int cta, float* red  , const __nv_bfloat16* __restrict__ wo,
                                         const __nv_bfloat16* __restrict__ w1, const __nv_bfloat16* __restrict__ w2) {
    const int tid = threadIdx.x, warp = tid >> 5, lane = tid & 31;
    for (int line = cta * 512 + tid; line < 18432; line += SIDE_CTAS * 512) {
        const char* p = line < 4096 ? (const char*)wo + (size_t)line * 128 : (const char*)w2 + (size_t)(line - 4096) * 128;
        asm volatile("prefetch.global.L2 [%0];" ::"l"(p));
    }
    const int rg = lane >> 3, c8 = lane & 7;
    for (int slab = cta; slab < F_ / 64; slab += SIDE_CTAS) {
        const __nv_bfloat16* base = w1 + slab * 64 + c8 * 8;
        uint4 v[8];
#pragma unroll
        for (int i = 0; i < 8; i++) v[i] = __ldg((const uint4*)(base + (size_t)(warp * 32 + rg + 4 * i) * F_));
        float acc[8];
#pragma unroll
        for (int i = 0; i < 8; i++) acc[i] = 0.f;
#pragma unroll
        for (int i = 0; i < 8; i++) {
            acc[0] += bf_lo(v[i].x); acc[1] += bf_hi(v[i].x); acc[2] += bf_lo(v[i].y); acc[3] += bf_hi(v[i].y);
            acc[4] += bf_lo(v[i].z); acc[5] += bf_hi(v[i].z); acc[6] += bf_lo(v[i].w); acc[7] += bf_hi(v[i].w);
        }
#pragma unroll
        for (int i = 0; i < 8; i++) {
            acc[i] += __shfl_xor_sync(0xffffffffu, acc[i], 8);
            acc[i] += __shfl_xor_sync(0xffffffffu, acc[i], 16);
        }
        if (rg == 0) {
#pragma unroll
            for (int i = 0; i < 8; i++) red[warp * 64 + c8 * 8 + i] = acc[i];
        }
        __syncthreads();
        if (tid < 64) {
            float s = 0.f;
#pragma unroll
            for (int i = 0; i < 16; i++) s += red[i * 64 + tid];
            g_cs_1[slab * 64 + tid] = s;
        }
        __syncthreads();
    }
}

enum { EPI_QKV = 0, EPI_RES = 1, EPI_FFN1 = 2 };

struct GemmParams {
    const float2* stats_in;
    float2* stats_out;
    const __nv_bfloat16* wkv;
    const __nv_bfloat16* wv;
    int tk;
};

template <int BK_, int NBLK> struct Geo {
    static constexpr int BK = BK_, A_BYTES = 128 * BK * 2, A_SWZ = BK == 64 ? 1 : 2, A_SBO = BK * 16;
    static constexpr int BLK = BK * 64;
    static constexpr int B_BYTES = NBLK * BLK, B_SWZ = 2, B_LBO = BLK, B_SBO = 512, B_KSTEP = 1024;
};
template <> struct Geo<64, 0> {
    static constexpr int BK = 64, A_BYTES = 128 * 128, A_SWZ = 1, A_SBO = 1024, BLK = 8192;
    static constexpr int B_BYTES = 64 * 128, B_SWZ = 1, B_LBO = 8192, B_SBO = 1024, B_KSTEP = 2048;
};
#define F1_BK 32
template <int EPI> struct EpiGeo;
template <> struct EpiGeo<EPI_QKV> { using G = Geo<64, 3>; };
template <> struct EpiGeo<EPI_RES> { using G = Geo<64, 0>; };
template <> struct EpiGeo<EPI_FFN1> { using G = Geo<F1_BK, 7>; };

template <int STAGES, int EPI> struct GemmSmem {
    using G = typename EpiGeo<EPI>::G;
    static constexpr int STAGE = G::A_BYTES + G::B_BYTES;
    static constexpr int AUX_OFF = STAGES * STAGE;
    static constexpr int TOTAL = AUX_OFF + 1152;
    static constexpr int TOTAL_SELF = AUX_OFF + 704 + 1024 + 1280;
};

struct RowStatRaw { float2 a0, a1, b0, b1; };
__device__ __forceinline__ RowStatRaw load_row_stats(const float2* __restrict__ st, int row0, int c) {
    RowStatRaw r;
    r.a0 = st[(2 * c) * S_ + row0]; r.a1 = st[(2 * c + 1) * S_ + row0];
    r.b0 = st[(2 * c) * S_ + row0 + 8]; r.b1 = st[(2 * c + 1) * S_ + row0 + 8];
    return r;
}
__device__ __forceinline__ void finish_row_stats(const RowStatRaw& r, float& mean0, float& rstd0, float& mean1, float& rstd1) {
    float sa = r.a0.x + r.a1.x, sb = r.b0.x + r.b1.x;
    sa += __shfl_xor_sync(0xffffffffu, sa, 1); sa += __shfl_xor_sync(0xffffffffu, sa, 2);
    sb += __shfl_xor_sync(0xffffffffu, sb, 1); sb += __shfl_xor_sync(0xffffffffu, sb, 2);
    mean0 = sa * 0.125f; mean1 = sb * 0.125f;
    float ma = r.a0.y + r.a1.y + 64.f * ((r.a0.x - mean0) * (r.a0.x - mean0) + (r.a1.x - mean0) * (r.a1.x - mean0));
    float mb = r.b0.y + r.b1.y + 64.f * ((r.b0.x - mean1) * (r.b0.x - mean1) + (r.b1.x - mean1) * (r.b1.x - mean1));
    ma += __shfl_xor_sync(0xffffffffu, ma, 1); ma += __shfl_xor_sync(0xffffffffu, ma, 2);
    mb += __shfl_xor_sync(0xffffffffu, mb, 1); mb += __shfl_xor_sync(0xffffffffu, mb, 2);
    rstd0 = 1.0f / sqrtf(ma * (1.f / 512.f) + 1e-5f);
    rstd1 = 1.0f / sqrtf(mb * (1.f / 512.f) + 1e-5f);
}

template <int BN, int KB, int STAGES, int EPI, int MC, bool SELF = false>
__device__ __forceinline__ void gemm_body(const CUtensorMap* mapA, const CUtensorMap* mapB, const CUtensorMap* mapB2, const CUtensorMap* mapR,
                                          const CUtensorMap* mapC, const GemmParams& prm, int tile_m, int tile_n, uint8_t* smem_raw) {
    using SM = GemmSmem<STAGES, EPI>;
    using G = typename SM::G;
    constexpr bool XKV = BN == 80;
    constexpr int TN = EPI == EPI_QKV ? 64 : BN;
    CP(prm.tk, 0);
    pdl_launch();
    const uint32_t sbase = smem_u32(smem_raw);
    if (sbase & 1023) __trap();
    uint8_t* sgen = smem_raw;
    const uint32_t bar_full = sbase + SM::AUX_OFF, bar_empty = bar_full + 8 * STAGES;
    float* s_cs = (float*)(sgen + SM::AUX_OFF + 256);
    float* s_row = (float*)(sgen + SM::AUX_OFF + 704);
    float* s_red = (float*)(sgen + SM::AUX_OFF + 640);
    const int tid = threadIdx.x, lane = tid & 31;
    const int warp = __shfl_sync(0xffffffffu, tid >> 5, 0);
    const uint32_t rank = MC ? cluster_rank() : 0;
    if (tid == 0) TL(prm.tk, 0);

    constexpr bool INLINE_PROD = EPI == EPI_FFN1 && F1_INLINE;
    constexpr int PWARP = INLINE_PROD ? 0 : 8;
    if (warp == PWARP) {
        if (lane < STAGES) { mbar_init(bar_full + 8 * lane, 1); mbar_init(bar_empty + 8 * lane, MC ? 4 : 2); }
        else if (lane == 29) prefetch_tmap(mapC);
        else if (lane == 30) prefetch_tmap(mapA);
        else if (lane == 31) prefetch_tmap(mapB);
        fence_mbar_init();
    }
    CP(prm.tk, 1);
    __syncthreads();
    CP(prm.tk, 2);
    if (MC) asm volatile("barrier.cluster.arrive.relaxed.aligned;" ::: "memory");
    auto cluster_wait = [&]() { if (MC) asm volatile("barrier.cluster.wait.acquire.aligned;" ::: "memory"); };

    const int m0 = tile_m * 128, n0 = tile_n * TN;
    constexpr uint32_t STAGE_TX = G::A_BYTES + (EPI == EPI_QKV ? 2 * G::BLK : G::B_BYTES);
    auto loadB = [&](int kb, int s) {
        const uint32_t dst = sbase + s * SM::STAGE + G::A_BYTES, bar = bar_full + 8 * s;
        if constexpr (EPI == EPI_RES) {
            tma2d(dst, mapB, n0, kb * 64, bar);
        } else if constexpr (EPI == EPI_QKV) {
            tma3d(dst, mapB, 0, kb * G::BK, tile_n * 2, bar);
        } else {
            if constexpr (MC == 2) {
                if (rank == 0) tma3d_mc(dst, mapB, 0, kb * G::BK, tile_n * 7, bar, 3);
                else tma3d_mc(dst + 4 * G::BLK, mapB2, 0, kb * G::BK, tile_n * 7 + 4, bar, 3);
            } else {
                tma3d(dst, mapB, 0, kb * G::BK, tile_n * 7, bar);
                tma3d(dst + 4 * G::BLK, mapB2, 0, kb * G::BK, tile_n * 7 + 4, bar);
            }
        }
    };
    auto loadA = [&](int kb, int s) {
        const uint32_t dst = sbase + s * SM::STAGE, bar = bar_full + 8 * s;
        if constexpr (MC == 1) tma2d_mc(dst + rank * (G::A_BYTES / 2), mapA, kb * G::BK, m0 + rank * 64, bar, 3);
        else tma2d(dst, mapA, kb * G::BK, m0, bar);
    };
    constexpr int PRE = STAGES < KB ? STAGES : KB;
#define F1_LAG 2
    constexpr int LAG = F1_LAG;
    constexpr int PRE_B = PRE < PREB ? PRE : PREB;
    auto prologue_loads = [&]() {
        if (lane < PRE) mbar_expect_tx(bar_full + 8 * lane, STAGE_TX);
        __syncwarp();
        CP(prm.tk, 3);
        cluster_wait();
        CP(prm.tk, 4);
        if (elect_one()) {
#pragma unroll
            for (int kb = 0; kb < PRE_B; kb++) loadB(kb, kb);
        }
        CP(prm.tk, 5);
        if (!SELF) pdl_wait();
        CP(prm.tk, 6);
        if (elect_one()) {
#pragma unroll
            for (int kb = 0; kb < PRE; kb++) {
                loadA(kb, kb);
                if (kb + PRE_B < PRE) loadB(kb + PRE_B, kb + PRE_B);
            }
            if constexpr (EPI == EPI_RES && KB < STAGES) {
                mbar_expect_tx(bar_full + 8 * KB, 16384);
                tma2d(sbase + KB * SM::STAGE, mapR, n0, m0, bar_full + 8 * KB);
            }
        }
    };
    if (SELF && warp >= 8) {
        if (warp == 8) prologue_loads();
        static_assert(!SELF || (STAGES >= KB && EPI == EPI_QKV), "SELF needs every k block resident");
        if ((warp >> 2) == 3) {
            float csum[BN / 2];
            const uint64_t dB0 = mkdesc(sbase + G::A_BYTES, G::B_LBO, G::B_SBO, G::B_SWZ);
            if constexpr (XKV) named_bar(6, 384);
#pragma unroll 1
            for (int kb = 0; kb < KB; kb++) {
                mbar_wait(bar_full + 8 * kb, 0);
                const uint64_t dB = dB0 + (uint64_t)(kb * (SM::STAGE >> 4));
                wg_fence();
#pragma unroll
                for (int k = 0; k < G::BK / 16; k++) {
                    if constexpr (SELF) wgmma_rs_ones<BN>(csum, dB + (uint64_t)(k * (G::B_KSTEP >> 4)), (kb | k) != 0);
                }
                wg_commit();
            }
            wg_wait<0>();
            fence_regs(csum);
            if (warp == 12 && lane < 4) {
#pragma unroll
                for (int j = 0; j < BN / 8; j++) {
                    const float2 v = make_float2(csum[4 * j], csum[4 * j + 1]);
                    *(float2*)(s_cs + 8 * j + 2 * lane) = v;
                    if (tile_m == 0) {
                        if (j < 8) *(float2*)(g_cs_q + n0 + 8 * j + 2 * lane) = v;
                        else *(float2*)(g_cs_kv + tile_n * 16 + 8 * (j - 8) + 2 * lane) = v;
                    }
                }
            }
        } else {
            const int t = (warp < 12 ? warp - 8 : warp - 12) * 32 + lane;
            float ss[4] = {0.f, 0.f, 0.f, 0.f}, sq[4] = {0.f, 0.f, 0.f, 0.f};
#pragma unroll 1
            for (int kb = 0; kb < KB; kb++) {
                mbar_wait(bar_full + 8 * kb, 0);
                const uint32_t arow = sbase + kb * SM::STAGE + (t >> 1) * 128;
                uint32_t w[4][4];
#pragma unroll
                for (int j = 0; j < 4; j++)
                    asm volatile("ld.shared.v4.u32 {%0,%1,%2,%3}, [%4];" : "=r"(w[j][0]), "=r"(w[j][1]), "=r"(w[j][2]), "=r"(w[j][3])
                                 : "r"(arow + (((2 * j + (t & 1) + 2 * ((t >> 1) & 3)) & 7) << 4)));
#pragma unroll
                for (int j = 0; j < 4; j++)
#pragma unroll
                    for (int i = 0; i < 4; i++) {
                        const float lo = bf_lo(w[j][i]), hi = bf_hi(w[j][i]);
                        ss[i] += lo + hi;
                        sq[i] = fmaf(lo, lo, fmaf(hi, hi, sq[i]));
                    }
            }
            float tsum = (ss[0] + ss[1]) + (ss[2] + ss[3]), tsq = (sq[0] + sq[1]) + (sq[2] + sq[3]);
            tsum += __shfl_xor_sync(0xffffffffu, tsum, 1);
            tsq += __shfl_xor_sync(0xffffffffu, tsq, 1);
            if ((t & 1) == 0) {
                const float md = tsum * (1.f / 512.f);
                const float var = fmaxf(tsq * (1.f / 512.f) - md * md, 0.f);
                *(float2*)(s_row + t) = make_float2(md, 1.0f / sqrtf(var + 1e-5f));
            }
        }
        named_bar(4, 640);
    } else if (!INLINE_PROD && warp == 8) {
        prologue_loads();
        int s = PRE % STAGES, ph = (PRE / STAGES) & 1;
#pragma unroll 1
        for (int kb = PRE; kb < KB; kb++) {
            mbar_wait(bar_empty + 8 * s, ph ^ 1);
            if (elect_one()) {
                mbar_expect_tx(bar_full + 8 * s, STAGE_TX);
                loadB(kb, s);
                loadA(kb, s);
            }
            if (++s == STAGES) { s = 0; ph ^= 1; }
        }
        if constexpr (EPI == EPI_RES && KB >= STAGES) {
            mbar_wait(bar_empty + 8 * s, ph ^ 1);
            if (elect_one()) {
                mbar_expect_tx(bar_full + 8 * s, 16384);
                tma2d(sbase + s * SM::STAGE, mapR, n0, m0, bar_full + 8 * s);
            }
        }
    } else {
        if (INLINE_PROD && warp == 0) prologue_loads(); else cluster_wait();
        const int wg = warp >> 2, g = lane >> 2, c = lane & 3;
        const int rloc = wg * 64 + (warp & 3) * 16 + g;
        const int row0 = m0 + rloc;
        float mean0 = 0.f, rstd0 = 1.f, mean1 = 0.f, rstd1 = 1.f;
        if constexpr (XKV) {
            static_assert(!XKV || STAGES >= KB, "the K / V weight block must stay resident");
            const __nv_bfloat16* wsrc = tile_n == 0 ? prm.wkv : prm.wv;
            uint4 v[4];
#pragma unroll
            for (int i = 0; i < 4; i++) v[i] = __ldg((const uint4*)wsrc + tid + 256 * i);
#pragma unroll
            for (int i = 0; i < 4; i++) {
                const int idx = tid + 256 * i, k = idx >> 1, kr = k & 63;
                const uint32_t dst = sbase + (k >> 6) * SM::STAGE + G::A_BYTES + 2 * G::BLK + kr * 64 + (((idx & 1) ^ ((kr >> 1) & 3)) << 4);
                asm volatile("st.shared.v4.u32 [%0], {%1,%2,%3,%4};" ::"r"(dst), "r"(v[i].x), "r"(v[i].y), "r"(v[i].z), "r"(v[i].w) : "memory");
            }
            fence_async_smem();
            if constexpr (SELF) named_bar(6, 384); else named_bar(6, 256);
        }
        RowStatRaw raw;
        float csv = 0.f;
        float2 cskv[2] = {make_float2(0.f, 0.f), make_float2(0.f, 0.f)};
        auto ln_inputs = [&]() {
            pdl_wait();
            if constexpr (EPI != EPI_RES) {
                raw = load_row_stats(prm.stats_in, row0, c);
                const float* cs = EPI == EPI_FFN1 ? g_cs_1 + n0 : g_cs_q + n0;
                if (tid < TN) csv = cs[tid];
                if constexpr (XKV) {
                    cskv[0] = *(const float2*)(g_cs_kv + tile_n * 16 + 2 * c);
                    cskv[1] = *(const float2*)(g_cs_kv + tile_n * 16 + 8 + 2 * c);
                }
            }
        };
        if (!SELF) ln_inputs();
        float acc[BN / 2];
        const uint64_t dA0 = mkdesc(sbase + wg * (G::A_BYTES / 2), 16, G::A_SBO, G::A_SWZ);
        const uint64_t dB0 = mkdesc(sbase + G::A_BYTES, G::B_LBO, G::B_SBO, G::B_SWZ);
        int s = 0, ph = 0;
#pragma unroll 1
        for (int kb = 0; kb < KB; kb++) {
            mbar_wait(bar_full + 8 * s, ph);
            const uint64_t dA = dA0 + (uint64_t)(s * (SM::STAGE >> 4)), dB = dB0 + (uint64_t)(s * (SM::STAGE >> 4));
            wg_fence();
#pragma unroll
            for (int k = 0; k < G::BK / 16; k++) wgmma_ss_tb<BN>(acc, dA + (uint64_t)(k * 2), dB + (uint64_t)(k * (G::B_KSTEP >> 4)), (kb | k) != 0);
            wg_commit();
            if constexpr (EPI == EPI_RES && RES_WAIT0) {
                wg_wait<0>();
                if ((warp & 3) == 0 && elect_one()) {
                    if (MC) { mbar_arrive_remote(bar_empty + 8 * s, 0); mbar_arrive_remote(bar_empty + 8 * s, 1); }
                    else mbar_arrive(bar_empty + 8 * s);
                }
            } else if (kb > 0) {
                wg_wait<1>();
                const int sp = s == 0 ? STAGES - 1 : s - 1;
                if ((warp & 3) == 0 && elect_one()) {
                    if (MC) { mbar_arrive_remote(bar_empty + 8 * sp, 0); mbar_arrive_remote(bar_empty + 8 * sp, 1); }
                    else mbar_arrive(bar_empty + 8 * sp);
                }
                if (INLINE_PROD && warp == 0 && kb >= LAG && kb - LAG + STAGES < KB) {
                    const int sq = LAG == 1 ? sp : (sp == 0 ? STAGES - 1 : sp - 1);
                    mbar_wait(bar_empty + 8 * sq, ((kb - LAG) / STAGES) & 1);
                    if (elect_one()) {
                        mbar_expect_tx(bar_full + 8 * sq, STAGE_TX);
                        loadB(kb - LAG + STAGES, sq);
                        loadA(kb - LAG + STAGES, sq);
                    }
                }
            }
            if (++s == STAGES) { s = 0; ph ^= 1; }
        }
        if constexpr (SELF) {
            named_bar(4, 640);
            const float2 r0 = *(const float2*)(s_row + 2 * rloc), r1 = *(const float2*)(s_row + 2 * rloc + 16);
            mean0 = r0.x; rstd0 = r0.y; mean1 = r1.x; rstd1 = r1.y;
        } else if constexpr (EPI != EPI_RES) {
            finish_row_stats(raw, mean0, rstd0, mean1, rstd1);
            if (tid < TN) s_cs[tid] = csv;
        }
        wg_wait<0>();
        fence_regs(acc);
        if (tid == 0) TL(prm.tk, 2);
        if constexpr (EPI != EPI_RES) named_bar(1, 256);

        if constexpr (EPI != EPI_FFN1) {
            const uint32_t stile = sbase + (EPI == EPI_RES ? s * SM::STAGE : 0);
            const int mrow = wg * 64 + (warp & 3) * 16 + (lane & 7) + ((lane >> 3) & 1) * 8;
            const uint32_t rbase = stile + mrow * 128;
            if constexpr (EPI == EPI_RES) {
                mbar_wait(bar_full + 8 * s, ph);
                float s0 = 0.f, s1 = 0.f;
#pragma unroll
                for (int jj = 0; jj < 4; jj++) {
                    uint32_t r0, r1, r2, r3;
                    const uint32_t addr = rbase + (((2 * jj + (lane >> 4)) ^ (mrow & 7)) << 4);
                    ldsm_x4(r0, r1, r2, r3, addr);
                    const uint32_t u0 = pack_bf16(acc[8 * jj] + bf_lo(r0), acc[8 * jj + 1] + bf_hi(r0));
                    const uint32_t u1 = pack_bf16(acc[8 * jj + 2] + bf_lo(r1), acc[8 * jj + 3] + bf_hi(r1));
                    const uint32_t u2 = pack_bf16(acc[8 * jj + 4] + bf_lo(r2), acc[8 * jj + 5] + bf_hi(r2));
                    const uint32_t u3 = pack_bf16(acc[8 * jj + 6] + bf_lo(r3), acc[8 * jj + 7] + bf_hi(r3));
                    stsm_x4(addr, u0, u1, u2, u3);
                    acc[8 * jj] = bf_lo(u0); acc[8 * jj + 1] = bf_hi(u0); acc[8 * jj + 4] = bf_lo(u2); acc[8 * jj + 5] = bf_hi(u2);
                    acc[8 * jj + 2] = bf_lo(u1); acc[8 * jj + 3] = bf_hi(u1); acc[8 * jj + 6] = bf_lo(u3); acc[8 * jj + 7] = bf_hi(u3);
                    s0 += (acc[8 * jj] + acc[8 * jj + 1]) + (acc[8 * jj + 4] + acc[8 * jj + 5]);
                    s1 += (acc[8 * jj + 2] + acc[8 * jj + 3]) + (acc[8 * jj + 6] + acc[8 * jj + 7]);
                }
                fence_async_smem();
                named_bar(2 + wg, 128);
                if ((warp & 3) == 0 && elect_one()) { tma2d_store(mapC, stile + wg * 8192, n0, m0 + wg * 64); bulk_commit(); }
                if (prm.stats_out) {
                    s0 += __shfl_xor_sync(0xffffffffu, s0, 1); s0 += __shfl_xor_sync(0xffffffffu, s0, 2);
                    s1 += __shfl_xor_sync(0xffffffffu, s1, 1); s1 += __shfl_xor_sync(0xffffffffu, s1, 2);
                    const float mu0 = s0 * (1.f / 64.f), mu1 = s1 * (1.f / 64.f);
                    float q0 = 0.f, q1 = 0.f;
#pragma unroll
                    for (int j = 0; j < 8; j++) {
                        float d;
                        d = acc[4 * j] - mu0; q0 += d * d; d = acc[4 * j + 1] - mu0; q0 += d * d;
                        d = acc[4 * j + 2] - mu1; q1 += d * d; d = acc[4 * j + 3] - mu1; q1 += d * d;
                    }
                    q0 += __shfl_xor_sync(0xffffffffu, q0, 1); q0 += __shfl_xor_sync(0xffffffffu, q0, 2);
                    q1 += __shfl_xor_sync(0xffffffffu, q1, 1); q1 += __shfl_xor_sync(0xffffffffu, q1, 2);
                    if (c == 0) {
                        prm.stats_out[tile_n * S_ + row0] = make_float2(mu0, q0);
                        prm.stats_out[tile_n * S_ + row0 + 8] = make_float2(mu1, q1);
                    }
                }
            } else {
                const float sc = 0.25f * 1.4426950408889634f;
                const float a0 = rstd0 * sc, a1 = rstd1 * sc, rm0 = a0 * mean0, rm1 = a1 * mean1;
#pragma unroll
                for (int jj = 0; jj < 4; jj++) {
                    const float2 ca = *(const float2*)(s_cs + 16 * jj + 2 * c), cb = *(const float2*)(s_cs + 16 * jj + 8 + 2 * c);
                    const uint32_t u0 = pack_bf16(acc[8 * jj] * a0 - rm0 * ca.x, acc[8 * jj + 1] * a0 - rm0 * ca.y);
                    const uint32_t u1 = pack_bf16(acc[8 * jj + 2] * a1 - rm1 * ca.x, acc[8 * jj + 3] * a1 - rm1 * ca.y);
                    const uint32_t u2 = pack_bf16(acc[8 * jj + 4] * a0 - rm0 * cb.x, acc[8 * jj + 5] * a0 - rm0 * cb.y);
                    const uint32_t u3 = pack_bf16(acc[8 * jj + 6] * a1 - rm1 * cb.x, acc[8 * jj + 7] * a1 - rm1 * cb.y);
                    stsm_x4(rbase + (((2 * jj + (lane >> 4)) ^ (mrow & 7)) << 4), u0, u1, u2, u3);
                }
                fence_async_smem();
                named_bar(2 + wg, 128);
                if ((warp & 3) == 0 && elect_one()) { tma2d_store(mapC, stile + wg * 8192, n0, m0 + wg * 64); bulk_commit(); }
            }
            if constexpr (XKV) {
                {
                    const float* acx = &acc[32];
                    const float rm0 = rstd0 * mean0, rm1 = rstd1 * mean1;
                    float n0s = 0.f, n1s = 0.f, vmax = 0.f;
#pragma unroll
                    for (int j = 0; j < 2; j++) {
                        const float2 cs2 = SELF ? *(const float2*)(s_cs + 64 + 8 * j + 2 * c) : cskv[j];
                        const uint32_t u0 = pack_bf16(acx[4 * j] * rstd0 - rm0 * cs2.x, acx[4 * j + 1] * rstd0 - rm0 * cs2.y);
                        const uint32_t u1 = pack_bf16(acx[4 * j + 2] * rstd1 - rm1 * cs2.x, acx[4 * j + 3] * rstd1 - rm1 * cs2.y);
                        n0s += bf_lo(u0) * bf_lo(u0) + bf_hi(u0) * bf_hi(u0);
                        n1s += bf_lo(u1) * bf_lo(u1) + bf_hi(u1) * bf_hi(u1);
                        vmax = fmaxf(vmax, fmaxf(fmaxf(fabsf(bf_lo(u0)), fabsf(bf_hi(u0))), fmaxf(fabsf(bf_lo(u1)), fabsf(bf_hi(u1)))));
                        if (tile_n == 0) {
                            *(uint32_t*)(g_kimg + (row0 >> 3) * 256 + j * 128 + g * 16 + c * 4) = u0;
                            *(uint32_t*)(g_kimg + ((row0 + 8) >> 3) * 256 + j * 128 + g * 16 + c * 4) = u1;
                        } else {
                            uint8_t* vb = g_vimg + (row0 >> 4) * 768 + j * 256 + g * 16 + c * 4;
                            *(uint32_t*)(vb) = u0;
                            *(uint32_t*)(vb + 128) = u1;
                        }
                    }
                    if (tile_n == 1) {
                        uint8_t* vb = g_vimg + (row0 >> 4) * 768 + 512 + g * 16 + c * 4;
                        const uint32_t one = c == 0 ? 0x00003F80u : 0u;
                        *(uint32_t*)(vb) = one;
                        *(uint32_t*)(vb + 128) = one;
                    }
                    n0s += __shfl_xor_sync(0xffffffffu, n0s, 1); n0s += __shfl_xor_sync(0xffffffffu, n0s, 2);
                    n1s += __shfl_xor_sync(0xffffffffu, n1s, 1); n1s += __shfl_xor_sync(0xffffffffu, n1s, 2);
                    float km = tile_n == 0 ? fmaxf(n0s, n1s) : vmax;
                    if (!(n0s + n1s < INFINITY)) km = INFINITY;
#pragma unroll
                    for (int o = 1; o < 32; o <<= 1) km = fmaxf(km, __shfl_xor_sync(0xffffffffu, km, o));
                    if (lane == 0) s_red[warp] = km;
                    named_bar(1, 256);
                    if (tid == 0) {
                        float a = 0.f;
                        for (int i = 0; i < 8; i++) a = fmaxf(a, s_red[i]);
                        g_kvmax[tile_n * 16 + tile_m] = a;
                    }
                }
            }
            if ((warp & 3) == 0) bulk_wait_read();
        } else {
            const uint32_t stile = sbase + wg * (7 * 4096);
            const int mrow = (warp & 3) * 16 + (lane & 7) + ((lane >> 3) & 1) * 8;
            const float a0 = 0.5f * rstd0, a1 = 0.5f * rstd1, rm0 = a0 * mean0, rm1 = a1 * mean1;
#pragma unroll
            for (int jj = 0; jj < 14; jj++) {
                const float2 ca = *(const float2*)(s_cs + 16 * jj + 2 * c), cb = *(const float2*)(s_cs + 16 * jj + 8 + 2 * c);
                float y[8] = {acc[8 * jj] * a0 - rm0 * ca.x,     acc[8 * jj + 1] * a0 - rm0 * ca.y,
                              acc[8 * jj + 2] * a1 - rm1 * ca.x, acc[8 * jj + 3] * a1 - rm1 * ca.y,
                              acc[8 * jj + 4] * a0 - rm0 * cb.x, acc[8 * jj + 5] * a0 - rm0 * cb.y,
                              acc[8 * jj + 6] * a1 - rm1 * cb.x, acc[8 * jj + 7] * a1 - rm1 * cb.y};
#pragma unroll
                for (int i = 0; i < 8; i++) {
                    float t;
                    asm("tanh.approx.f32 %0, %1;" : "=f"(t) : "f"(y[i]));
                    y[i] = fmaf(y[i], t, y[i]);
                }
                const int chunk = (2 * jj + (lane >> 4)) & 3, blk = jj >> 1;
                stsm_x4(stile + blk * 4096 + mrow * 64 + ((chunk ^ ((mrow >> 1) & 3)) << 4),
                        pack_bf16(y[0], y[1]), pack_bf16(y[2], y[3]), pack_bf16(y[4], y[5]), pack_bf16(y[6], y[7]));
                if (jj & 1) {
                    fence_async_smem();
                    __syncwarp();
                    if (elect_one()) {
                        tma2d_store(mapC, stile + blk * 4096 + (warp & 3) * 1024, n0 + blk * 32, m0 + wg * 64 + (warp & 3) * 16);
                        bulk_commit();
                    }
                }
            }
            bulk_wait_read();
        }
    }
    if (tid == 0) TL(prm.tk, 3);
    if (MC) cluster_sync();
}

#define WO_ST 9
#define F2_ST 6
#define F1_ST (F1_BK == 64 ? 5 : 9)
#define QKV_ST 8
constexpr int QKV_STAGES = QKV_ST, WO_STAGES = WO_ST, FFN2_STAGES = F2_ST, FFN1_STAGES = F1_ST;
template <bool SELF>
__global__ void __launch_bounds__(SELF ? 640 : 288) qkv_kernel(const __grid_constant__ CUtensorMap mapA, const __grid_constant__ CUtensorMap mapWq,
                                                  const __grid_constant__ CUtensorMap mapQ, const GemmParams prm) {
    extern __shared__ __align__(1024) uint8_t smem_raw[];
    const int tn = blockIdx.x & 7;
    if (tn < 2) gemm_body<80, 8, QKV_STAGES, EPI_QKV, QKV_MC, SELF>(&mapA, &mapWq, &mapWq, &mapA, &mapQ, prm, blockIdx.x >> 3, tn, smem_raw);
    else gemm_body<64, 8, QKV_STAGES, EPI_QKV, QKV_MC, SELF>(&mapA, &mapWq, &mapWq, &mapA, &mapQ, prm, blockIdx.x >> 3, tn, smem_raw);
}
template <int KB, int STAGES>
__global__ void __launch_bounds__(288) res_gemm_kernel(const __grid_constant__ CUtensorMap mapA, const __grid_constant__ CUtensorMap mapW,
                                                       const __grid_constant__ CUtensorMap mapR, const __grid_constant__ CUtensorMap mapC, const GemmParams prm) {
    extern __shared__ __align__(1024) uint8_t smem_raw[];
#define RES_MAP 0
    gemm_body<64, KB, STAGES, EPI_RES, (KB == 8 ? WO_MC : F2_MC)>(&mapA, &mapW, &mapW, &mapR, &mapC, prm, RES_MAP ? blockIdx.x & 15 : blockIdx.x >> 3,
                                                                  RES_MAP ? blockIdx.x >> 4 : blockIdx.x & 7, smem_raw);
}
__global__ void __launch_bounds__(F1_INLINE ? 256 : 288) ffn1_kernel(const __grid_constant__ CUtensorMap mapA, const __grid_constant__ CUtensorMap mapW4,
                                                   const __grid_constant__ CUtensorMap mapW3, const __grid_constant__ CUtensorMap mapH, const GemmParams prm) {
    extern __shared__ __align__(1024) uint8_t smem_raw[];
#define F1_MAP 0
    const int pair = blockIdx.x >> 1;
    const int tile_n = F1_MAP == 0 ? (pair & 7) : F1_MAP == 1 ? (blockIdx.x >> 4) : (blockIdx.x & 7);
    const int tile_m = F1_MAP == 0 ? (pair >> 3) * 2 + (blockIdx.x & 1) : F1_MAP == 1 ? (blockIdx.x & 15) : (blockIdx.x >> 3);
    gemm_body<224, 512 / F1_BK, FFN1_STAGES, EPI_FFN1, F1_MC>(&mapA, &mapW4, &mapW3, &mapA, &mapH, prm, tile_m, tile_n, smem_raw);
}

#define ATT_NPOLY 11
constexpr int NPOLY = ATT_NPOLY;
__host__ __device__ constexpr bool is_mufu(int i) { return ((i + 1) * (16 - NPOLY)) / 16 != (i * (16 - NPOLY)) / 16; }

__device__ __forceinline__ float ex2(float x) { float r; asm("ex2.approx.ftz.f32 %0, %1;" : "=f"(r) : "f"(x)); return r; }
__device__ __forceinline__ uint32_t exp_pair_mufu(float a, float b) { return pack_bf16(ex2(a), ex2(b)); }
__device__ __forceinline__ uint32_t exp_pair_fma(float a, float b, uint32_t c3f) {
    constexpr float MAGIC = 98430.4140625f;
    const float ta = a + MAGIC, tb = b + (MAGIC - 143.5f);
    uint32_t y, m, r;
    asm("mad.lo.u32 %0, %1, 65536, %2;" : "=r"(y) : "r"(__float_as_uint(tb)), "r"(__float_as_uint(ta)));
    asm("lop3.b32 %0, %1, 0x007F007F, %2, 0xEA;" : "=r"(m) : "r"(y), "r"(c3f));
    const uint32_t e = y & 0xFF80FF80u;
    asm("fma.rn.bf16x2 %0, %1, %2, %3;" : "=r"(r) : "r"(y), "r"(m), "r"(e));
    return r;
}

constexpr int KCH = 256, NCH = S_ / KCH;
constexpr int K_BYTES = S_ * 32, V_BYTES = (S_ / 16) * 768;
constexpr int QO_BYTES = 128 * 128;
constexpr int ATT_SMEM = K_BYTES + V_BYTES + QO_BYTES;

__global__ void __launch_bounds__(512, 1) attn_kernel(const __grid_constant__ CUtensorMap mapQ, const __grid_constant__ CUtensorMap mapO,
                                                       const __nv_bfloat16* __restrict__ wo, const __nv_bfloat16* __restrict__ w1,
                                                       const __nv_bfloat16* __restrict__ w2, int tk) {
    extern __shared__ __align__(1024) uint8_t smem[];
    __shared__ uint64_t bars[NCH + 1];
    __shared__ int s_slow;
    const int tid = threadIdx.x, wg = tid >> 7, warp = (tid >> 5) & 3, lane = tid & 31;
    const uint32_t sK = smem_u32(smem), sV = sK + K_BYTES, sQ = sV + V_BYTES;
    if (blockIdx.x >= 128) {
        pdl_launch();
        pdl_wait();
        side_job(blockIdx.x - 128, (float*)smem, wo, w1, w2);
        return;
    }
    CK(tk, 9);
    if (tid == 0) TL(tk, 0);
    if (tid < 32) {
        if (tid <= NCH) mbar_init(smem_u32(&bars[tid]), 1);
        else if (tid == 29) s_slow = 0;
        else if (tid == 30) prefetch_tmap(&mapO);
        else if (tid == 31) prefetch_tmap(&mapQ);
        fence_mbar_init();
    }
    __syncthreads();
    pdl_launch();
    CK(tk, 10);
    pdl_wait();
    CK(tk, 11);
    if (tid == 0) TL(tk, 1);
    const int wu = __shfl_sync(0xffffffffu, tid >> 5, 0);
    auto fetch_chunk = [&](int w) {
        if (elect_one()) {
            const uint32_t bar = smem_u32(&bars[w]);
            mbar_expect_tx(bar, KCH * 32 + (KCH / 16) * 768);
            bulk_load(sK + w * KCH * 32, g_kimg + w * KCH * 32, KCH * 32, bar);
            bulk_load(sV + w * (KCH / 16) * 768, g_vimg + w * (KCH / 16) * 768, (KCH / 16) * 768, bar);
        }
    };
    const int tb = blockIdx.x >> 3, hg = blockIdx.x & 7;
    if (wu == 1 && elect_one()) {
        mbar_expect_tx(smem_u32(&bars[NCH]), QO_BYTES);
        tma2d(sQ, &mapQ, hg * 64, tb * 128, smem_u32(&bars[NCH]));
    }
    if (wu == 0) fetch_chunk(0);
    const int g = lane >> 2;
    float kvm = g_kvmax[lane];
    const int lrow = warp * 16 + (lane & 7) + ((lane >> 3) & 1) * 8;
    const uint32_t qoff = lrow * 128 + (((2 * wg + (lane >> 4)) ^ (lrow & 7)) << 4);
    uint32_t qa[2][4];
    mbar_wait(smem_u32(&bars[NCH]), 0);
    ldsm_x4(qa[0][0], qa[0][1], qa[0][2], qa[0][3], sQ + qoff);
    ldsm_x4(qa[1][0], qa[1][1], qa[1][2], qa[1][3], sQ + 8192 + qoff);
    CK(tk, 12);
    {
        float qn = 0.f;
#pragma unroll
        for (int m = 0; m < 2; m++) {
            float n0 = bf_lo(qa[m][0]) * bf_lo(qa[m][0]) + bf_hi(qa[m][0]) * bf_hi(qa[m][0]) + bf_lo(qa[m][2]) * bf_lo(qa[m][2]) + bf_hi(qa[m][2]) * bf_hi(qa[m][2]);
            float n1 = bf_lo(qa[m][1]) * bf_lo(qa[m][1]) + bf_hi(qa[m][1]) * bf_hi(qa[m][1]) + bf_lo(qa[m][3]) * bf_lo(qa[m][3]) + bf_hi(qa[m][3]) * bf_hi(qa[m][3]);
            n0 += __shfl_xor_sync(0xffffffffu, n0, 1); n0 += __shfl_xor_sync(0xffffffffu, n0, 2);
            n1 += __shfl_xor_sync(0xffffffffu, n1, 1); n1 += __shfl_xor_sync(0xffffffffu, n1, 2);
            if (!(n0 == n0) || !(n1 == n1)) n0 = INFINITY;
            qn = fmaxf(qn, fmaxf(n0, n1));
        }
        CK(tk, 13);
#pragma unroll
        for (int o = 1; o < 16; o <<= 1) kvm = fmaxf(kvm, __shfl_xor_sync(0xffffffffu, kvm, o));
        const float km = __shfl_sync(0xffffffffu, kvm, 0), vm = __shfl_sync(0xffffffffu, kvm, 16);
        const bool ok = (qn * km <= 10000.f) && (vm <= 16384.f);
        if (!ok) s_slow = 1;
    }
    CK(tk, 14);
    float oacc[2][12];
#pragma unroll
    for (int m = 0; m < 2; m++)
#pragma unroll
        for (int i = 0; i < 12; i++) oacc[m][i] = 0.f;
    __syncthreads();
    const bool slow = s_slow != 0;
    if (wu >= 1 && wu < NCH) fetch_chunk(wu);
    CK(tk, 15);

    const uint64_t dK0 = mkdesc(sK, 128, 256, 0);
    const uint64_t dV0 = mkdesc(sV, 128, 256, 0);
    uint32_t c3f;
    asm volatile("mov.b32 %0, 0x3F003F00;" : "=r"(c3f));
    if (!slow) {
        uint64_t dK = dK0, dV = dV0;
        float s[32];
        fence_regs(oacc[0]); fence_regs(oacc[1]);
        mbar_wait(smem_u32(&bars[0]), 0);
        wg_fence();
        wgmma_rs_n64_z(s, qa[0][0], qa[0][1], qa[0][2], qa[0][3], dK);
        wg_commit();
#pragma unroll 1
        for (int ch = 0; ch < NCH; ch++) {
#pragma unroll
            for (int tt = 0; tt < KCH / 64; tt++) {
#pragma unroll
                for (int m = 0; m < 2; m++) {
                    wg_wait<0>();
                    fence_regs(s);
                    uint32_t p[16];
#pragma unroll
                    for (int i = 0; i < 16; i++) p[i] = is_mufu(i) ? exp_pair_mufu(s[2 * i], s[2 * i + 1]) : exp_pair_fma(s[2 * i], s[2 * i + 1], c3f);
                    if (m == 1 && tt == KCH / 64 - 1) mbar_wait(smem_u32(&bars[ch + 1 < NCH ? ch + 1 : ch]), 0);
                    wg_fence();
#pragma unroll
                    for (int kk = 0; kk < 4; kk++)
                        wgmma_rs_n24_tb(oacc[m], p[4 * kk], p[4 * kk + 1], p[4 * kk + 2], p[4 * kk + 3], dV + (uint64_t)((tt * 4 + kk) * (768 / 16)));
                    wgmma_rs_n64_z(s, qa[1 - m][0], qa[1 - m][1], qa[1 - m][2], qa[1 - m][3], dK + (uint64_t)((tt + m) * (64 * 32 / 16)));
                    wg_commit();
                }
            }
            dK += KCH * 32 / 16;
            dV += (KCH / 16) * (768 / 16);
        }
        wg_wait<0>();
        fence_regs(s);
    } else {
        float mx[2][2] = {{-INFINITY, -INFINITY}, {-INFINITY, -INFINITY}};
#pragma unroll 1
        for (int t = 0; t < S_ / 64; t++) {
            if ((t & 3) == 0) mbar_wait(smem_u32(&bars[t >> 2]), 0);
            const uint64_t dK = dK0 + (uint64_t)(t * 64 * 32 / 16);
            const uint64_t dV = dV0 + (uint64_t)(t * 4 * 768 / 16);
#pragma unroll
            for (int m = 0; m < 2; m++) {
                float s[32];
                wg_fence();
                wgmma_rs_n64_z(s, qa[m][0], qa[m][1], qa[m][2], qa[m][3], dK);
                wg_commit();
                wg_wait<0>();
                fence_regs(s);
                fence_regs(oacc[m]);
                float r0 = mx[m][0], r1 = mx[m][1];
#pragma unroll
                for (int j = 0; j < 8; j++) {
                    r0 = fmaxf(r0, fmaxf(s[4 * j], s[4 * j + 1]));
                    r1 = fmaxf(r1, fmaxf(s[4 * j + 2], s[4 * j + 3]));
                }
                r0 = fmaxf(r0, __shfl_xor_sync(0xffffffffu, r0, 1)); r0 = fmaxf(r0, __shfl_xor_sync(0xffffffffu, r0, 2));
                r1 = fmaxf(r1, __shfl_xor_sync(0xffffffffu, r1, 1)); r1 = fmaxf(r1, __shfl_xor_sync(0xffffffffu, r1, 2));
                const float al0 = ex2(mx[m][0] - r0), al1 = ex2(mx[m][1] - r1);
                mx[m][0] = r0; mx[m][1] = r1;
#pragma unroll
                for (int j = 0; j < 3; j++) {
                    oacc[m][4 * j] *= al0; oacc[m][4 * j + 1] *= al0;
                    oacc[m][4 * j + 2] *= al1; oacc[m][4 * j + 3] *= al1;
                }
                uint32_t p[16];
#pragma unroll
                for (int j = 0; j < 8; j++) {
                    p[2 * j] = pack_bf16(ex2(s[4 * j] - r0), ex2(s[4 * j + 1] - r0));
                    p[2 * j + 1] = pack_bf16(ex2(s[4 * j + 2] - r1), ex2(s[4 * j + 3] - r1));
                }
                fence_regs(oacc[m]);
                wg_fence();
#pragma unroll
                for (int kk = 0; kk < 4; kk++)
                    wgmma_rs_n24_tb(oacc[m], p[4 * kk], p[4 * kk + 1], p[4 * kk + 2], p[4 * kk + 3], dV + (uint64_t)(kk * 768 / 16));
                wg_commit();
                wg_wait<0>();
            }
        }
    }
    fence_regs(oacc[0]); fence_regs(oacc[1]);
    if (tid == 0) TL(tk, 2);
#pragma unroll
    for (int m = 0; m < 2; m++) {
        const float l0 = __shfl_sync(0xffffffffu, oacc[m][8], lane & ~3);
        const float l1 = __shfl_sync(0xffffffffu, oacc[m][10], lane & ~3);
        const float r0 = __fdividef(1.0f, l0), r1 = __fdividef(1.0f, l1);
        stsm_x4(sQ + m * 8192 + qoff, pack_bf16(oacc[m][0] * r0, oacc[m][1] * r0), pack_bf16(oacc[m][2] * r1, oacc[m][3] * r1),
                pack_bf16(oacc[m][4] * r0, oacc[m][5] * r0), pack_bf16(oacc[m][6] * r1, oacc[m][7] * r1));
    }
    fence_async_smem();
    __syncthreads();
    if (wu == 0 && elect_one()) {
        tma2d_store(&mapO, sQ, hg * 64, tb * 128);
        bulk_commit();
        bulk_wait_read();
    }
    if (tid == 0) TL(tk, 3);
}

typedef CUresult (*EncodeFn)(CUtensorMap*, CUtensorMapDataType, cuuint32_t, void*, const cuuint64_t*, const cuuint64_t*, const cuuint32_t*,
                             const cuuint32_t*, CUtensorMapInterleave, CUtensorMapSwizzle, CUtensorMapL2promotion, CUtensorMapFloatOOBfill);

EncodeFn get_encode() {
    static EncodeFn fn = nullptr;
    if (!fn) {
        void* p = nullptr;
        cudaDriverEntryPointQueryResult qr;
        cudaGetDriverEntryPoint("cuTensorMapEncodeTiled", &p, cudaEnableDefault, &qr);
        fn = (EncodeFn)p;
    }
    return fn;
}
CUtensorMap map2d(const void* ptr, uint64_t cols, uint64_t rows, uint32_t bc, uint32_t br, CUtensorMapSwizzle sw) {
    CUtensorMap m;
    cuuint64_t gd[2] = {cols, rows}, gs[1] = {cols * 2};
    cuuint32_t bx[2] = {bc, br}, es[2] = {1, 1};
    get_encode()(&m, CU_TENSOR_MAP_DATA_TYPE_BFLOAT16, 2, (void*)ptr, gd, gs, bx, es, CU_TENSOR_MAP_INTERLEAVE_NONE, sw,
                 L2PROMO, CU_TENSOR_MAP_FLOAT_OOB_FILL_NONE);
    return m;
}
CUtensorMap map3d32(const void* ptr, uint64_t cols, uint64_t rows, uint32_t br, uint32_t nb) {
    CUtensorMap m;
    cuuint64_t gd[3] = {32, rows, cols / 32}, gs[2] = {cols * 2, 64};
    cuuint32_t bx[3] = {32, br, nb}, es[3] = {1, 1, 1};
    get_encode()(&m, CU_TENSOR_MAP_DATA_TYPE_BFLOAT16, 3, (void*)ptr, gd, gs, bx, es, CU_TENSOR_MAP_INTERLEAVE_NONE, CU_TENSOR_MAP_SWIZZLE_64B,
                 L2PROMO, CU_TENSOR_MAP_FLOAT_OOB_FILL_NONE);
    return m;
}

template <typename... KArgs, typename... Args>
void launch(void (*kern)(KArgs...), int grid, int block, int smem, int cluster, bool pdl, Args... args) {
    cudaLaunchConfig_t cfg = {};
    cfg.gridDim = dim3(grid);
    cfg.blockDim = dim3(block);
    cfg.dynamicSmemBytes = smem;
    cfg.stream = cudaStreamPerThread;
    cudaLaunchAttribute at[2];
    int n = 0;
    if (cluster > 1) { at[n].id = cudaLaunchAttributeClusterDimension; at[n].val.clusterDim.x = cluster; at[n].val.clusterDim.y = 1; at[n].val.clusterDim.z = 1; n++; }
    if (pdl) { at[n].id = cudaLaunchAttributeProgrammaticStreamSerialization; at[n].val.programmaticStreamSerializationAllowed = 1; n++; }
    cfg.attrs = at;
    cfg.numAttrs = n;
    cudaLaunchKernelEx(&cfg, kern, KArgs(args)...);
}

template <typename T> void* sym(const T& s) { void* p = nullptr; cudaGetSymbolAddress(&p, s); return p; }

}

extern "C" void kernel_launch(void* const* d_in, const int* in_sizes, int n_in, void* d_out, int out_size) {
    const __nv_bfloat16* x = (const __nv_bfloat16*)d_in[0];
    const __nv_bfloat16* wq = (const __nv_bfloat16*)d_in[1];
    const __nv_bfloat16* wk = (const __nv_bfloat16*)d_in[2];
    const __nv_bfloat16* wv = (const __nv_bfloat16*)d_in[3];
    const __nv_bfloat16* wo = (const __nv_bfloat16*)d_in[4];
    const __nv_bfloat16* w1 = (const __nv_bfloat16*)d_in[6];
    const __nv_bfloat16* w2 = (const __nv_bfloat16*)d_in[7];

    constexpr int SM_QKV = GemmSmem<QKV_STAGES, EPI_QKV>::TOTAL, SM_QKV0 = GemmSmem<QKV_STAGES, EPI_QKV>::TOTAL_SELF;
    static_assert(SM_QKV0 <= 232448, "shared memory");
    constexpr int SM_WO = GemmSmem<WO_STAGES, EPI_RES>::TOTAL, SM_FFN2 = GemmSmem<FFN2_STAGES, EPI_RES>::TOTAL;
    static_assert(SM_WO > 116736 && SM_FFN2 > 116736, "one CTA per SM");
    constexpr int SM_FFN1 = GemmSmem<FFN1_STAGES, EPI_FFN1>::TOTAL;
    cudaFuncSetAttribute(qkv_kernel<false>, cudaFuncAttributeMaxDynamicSharedMemorySize, SM_QKV);
    cudaFuncSetAttribute(qkv_kernel<true>, cudaFuncAttributeMaxDynamicSharedMemorySize, SM_QKV0);
    cudaFuncSetAttribute(res_gemm_kernel<8, WO_STAGES>, cudaFuncAttributeMaxDynamicSharedMemorySize, SM_WO);
    cudaFuncSetAttribute(ffn1_kernel, cudaFuncAttributeMaxDynamicSharedMemorySize, SM_FFN1);
    cudaFuncSetAttribute(res_gemm_kernel<28, FFN2_STAGES>, cudaFuncAttributeMaxDynamicSharedMemorySize, SM_FFN2);
    cudaFuncSetAttribute(attn_kernel, cudaFuncAttributeMaxDynamicSharedMemorySize, ATT_SMEM);
    cudaFuncSetAttribute(qkv_kernel<false>, cudaFuncAttributePreferredSharedMemoryCarveout, 100);
    cudaFuncSetAttribute(qkv_kernel<true>, cudaFuncAttributePreferredSharedMemoryCarveout, 100);
    cudaFuncSetAttribute(res_gemm_kernel<8, WO_STAGES>, cudaFuncAttributePreferredSharedMemoryCarveout, 100);
    cudaFuncSetAttribute(ffn1_kernel, cudaFuncAttributePreferredSharedMemoryCarveout, 100);
    cudaFuncSetAttribute(res_gemm_kernel<28, FFN2_STAGES>, cudaFuncAttributePreferredSharedMemoryCarveout, 100);
    cudaFuncSetAttribute(attn_kernel, cudaFuncAttributePreferredSharedMemoryCarveout, 100);

    void *q = sym(g_q), *o = sym(g_o), *x1 = sym(g_x1), *x2 = sym(g_x2), *x3 = sym(g_x3), *h = sym(g_h);
    float2* stats = (float2*)sym(g_stats);
    const void* xs[5] = {x, x1, x2, x3, d_out};

    const CUtensorMapSwizzle SW128 = CU_TENSOR_MAP_SWIZZLE_128B, SW64 = CU_TENSOR_MAP_SWIZZLE_64B;
    const CUtensorMap mWq = map3d32(wq, D_, D_, 64, 2);
    const CUtensorMap mWo = map2d(wo, D_, D_, 64, 64, SW128);
    const CUtensorMap mW1a = map3d32(w1, F_, D_, F1_BK, 4), mW1b = map3d32(w1, F_, D_, F1_BK, 3);
    const CUtensorMap mW2 = map2d(w2, D_, F_, 64, 64, SW128);
    const CUtensorMap mQ = map2d(q, D_, S_, 64, 64, SW128);
    const CUtensorMap mQa = map2d(q, D_, S_, 64, 128, SW128), mOs = map2d(o, D_, S_, 64, 128, SW128);
    const CUtensorMap mHst = map2d(h, F_, S_, 32, 16, SW64);
    CUtensorMap mXa[4], mXf[4], mXr[4], mXs[5];
    for (int i = 0; i < 4; i++) {
        mXa[i] = map2d(xs[i], D_, S_, 64, QKV_MC ? 64 : 128, SW128);
        mXf[i] = F1_BK == 64 ? map2d(xs[i], D_, S_, 64, 128, SW128) : map2d(xs[i], D_, S_, 32, 128, SW64);
        mXr[i] = map2d(xs[i], D_, S_, 64, 128, SW128);
    }
    for (int i = 0; i < 5; i++) mXs[i] = map2d(xs[i], D_, S_, 64, 64, SW128);
    const CUtensorMap mOa = map2d(o, D_, S_, 64, WO_MC ? 64 : 128, SW128);
    const CUtensorMap mHa = map2d(h, F_, S_, 64, F2_MC ? 64 : 128, SW128);

    for (int layer = 0; layer < 2; layer++) {
        const int xi = layer * 2;
        GemmParams p;
        p.wkv = wk; p.wv = wv;
        p.stats_in = stats + (size_t)xi * 8 * S_; p.stats_out = nullptr; p.tk = 1 + 5 * layer;
        if (layer == 0) launch(qkv_kernel<true>, 128, 640, SM_QKV0, QKV_MC ? 2 : 1, false, mXa[xi], mWq, mQ, p);
        else launch(qkv_kernel<false>, 128, 288, SM_QKV, QKV_MC ? 2 : 1, true, mXa[xi], mWq, mQ, p);
        launch(attn_kernel, layer == 0 ? 128 + SIDE_CTAS : 128, 512, ATT_SMEM, 1, true, mQa, mOs, wo, w1, w2, 2 + 5 * layer);
        p.stats_in = nullptr; p.stats_out = stats + (size_t)(xi + 1) * 8 * S_; p.tk = 3 + 5 * layer;
        launch(res_gemm_kernel<8, WO_STAGES>, 128, 288, SM_WO, WO_MC ? 2 : 1, true, mOa, mWo, mXr[xi], mXs[xi + 1], p);
        p.stats_in = stats + (size_t)(xi + 1) * 8 * S_; p.stats_out = nullptr; p.tk = 4 + 5 * layer;
        launch(ffn1_kernel, 128, F1_INLINE ? 256 : 288, SM_FFN1, F1_MC ? 2 : 1, true, mXf[xi + 1], mW1a, mW1b, mHst, p);
        p.stats_in = nullptr; p.stats_out = layer == 0 ? stats + (size_t)2 * 8 * S_ : nullptr; p.tk = 5 + 5 * layer;
        launch(res_gemm_kernel<28, FFN2_STAGES>, 128, 288, SM_FFN2, F2_MC ? 2 : 1, true, mHa, mW2, mXr[xi + 1], mXs[xi + 2], p);
    }
}
```

```cpp
#include <cuda_runtime.h>
#include <cuda_bf16.h>
#include <cuda.h>
#include <stdint.h>

#define F1_INLINE 0
#define QKV_MC 0
#define WO_MC 0
#define F2_MC 0
#define F1_MC 2
#define SELF_WAIT 0
#define ATT_VAR 1
#define SIDE_WAIT 1
#define L2PROMO CU_TENSOR_MAP_L2_PROMOTION_L2_128B
#define PREB 1
#define RES_WAIT0 0

namespace {

constexpr int S_ = 2048, D_ = 512, H_ = 32, F_ = 1792;

__device__ __align__(1024) __nv_bfloat16 g_q[S_ * D_];
__device__ __align__(1024) __nv_bfloat16 g_o[S_ * D_];
__device__ __align__(1024) __nv_bfloat16 g_x1[S_ * D_];
__device__ __align__(1024) __nv_bfloat16 g_x2[S_ * D_];
__device__ __align__(1024) __nv_bfloat16 g_x3[S_ * D_];
__device__ __align__(1024) __nv_bfloat16 g_h[S_ * F_];
__device__ __align__(1024) uint8_t g_kimg[S_ * 32];
__device__ __align__(1024) uint8_t g_vimg[(S_ / 16) * 768];
__device__ __align__(1024) float2 g_stats[4][8 * S_];
__device__ __align__(16) float g_cs_q[D_];
__device__ __align__(16) float g_cs_kv[32];
__device__ __align__(16) float g_cs_1[F_];
__device__ __align__(16) float g_kvmax[32];

#define TL(k, slot)
#define CK(k, i)
#define CP(k, i)

__device__ __forceinline__ uint32_t smem_u32(const void* p) { return (uint32_t)__cvta_generic_to_shared(p); }
__device__ __forceinline__ void mbar_init(uint32_t bar, uint32_t cnt) {
    asm volatile("mbarrier.init.shared::cta.b64 [%0], %1;" ::"r"(bar), "r"(cnt));
}
__device__ __forceinline__ void mbar_expect_tx(uint32_t bar, uint32_t bytes) {
    asm volatile("mbarrier.arrive.expect_tx.shared::cta.b64 _, [%0], %1;" ::"r"(bar), "r"(bytes) : "memory");
}
__device__ __forceinline__ void mbar_arrive(uint32_t bar) {
    asm volatile("mbarrier.arrive.shared::cta.b64 _, [%0];" ::"r"(bar) : "memory");
}
__device__ __forceinline__ void mbar_arrive_remote(uint32_t bar, uint32_t cta) {
    asm volatile("{\n.reg .b32 ra;\nmapa.shared::cluster.u32 ra, %0, %1;\nmbarrier.arrive.shared::cluster.b64 _, [ra];\n}" ::"r"(bar), "r"(cta) : "memory");
}
__device__ __forceinline__ void mbar_wait(uint32_t bar, uint32_t parity) {
    asm volatile("{\n.reg .pred p;\nWAIT_%=:\nmbarrier.try_wait.parity.shared::cta.b64 p, [%0], %1;\n@p bra DONE_%=;\nbra WAIT_%=;\nDONE_%=:\n}" ::"r"(bar), "r"(parity) : "memory");
}
__device__ __forceinline__ void bulk_load(uint32_t dst, const void* src, uint32_t bytes, uint32_t bar) {
    asm volatile("cp.async.bulk.shared::cluster.global.mbarrier::complete_tx::bytes [%0], [%1], %2, [%3];" ::"r"(dst), "l"(src), "r"(bytes), "r"(bar) : "memory");
}
__device__ __forceinline__ void tma2d(uint32_t dst, const CUtensorMap* m, int c0, int c1, uint32_t bar) {
    asm volatile("cp.async.bulk.tensor.2d.shared::cluster.global.mbarrier::complete_tx::bytes [%0], [%1, {%3, %4}], [%2];" ::"r"(dst), "l"(m), "r"(bar), "r"(c0), "r"(c1) : "memory");
}
__device__ __forceinline__ void tma2d_mc(uint32_t dst, const CUtensorMap* m, int c0, int c1, uint32_t bar, uint16_t mask) {
    asm volatile("cp.async.bulk.tensor.2d.shared::cluster.global.mbarrier::complete_tx::bytes.multicast::cluster [%0], [%1, {%3, %4}], [%2], %5;" ::"r"(dst), "l"(m), "r"(bar), "r"(c0), "r"(c1), "h"(mask) : "memory");
}
__device__ __forceinline__ void tma3d(uint32_t dst, const CUtensorMap* m, int c0, int c1, int c2, uint32_t bar) {
    asm volatile("cp.async.bulk.tensor.3d.shared::cluster.global.mbarrier::complete_tx::bytes [%0], [%1, {%3, %4, %5}], [%2];" ::"r"(dst), "l"(m), "r"(bar), "r"(c0), "r"(c1), "r"(c2) : "memory");
}
__device__ __forceinline__ void tma3d_mc(uint32_t dst, const CUtensorMap* m, int c0, int c1, int c2, uint32_t bar, uint16_t mask) {
    asm volatile("cp.async.bulk.tensor.3d.shared::cluster.global.mbarrier::complete_tx::bytes.multicast::cluster [%0], [%1, {%3, %4, %5}], [%2], %6;" ::"r"(dst), "l"(m), "r"(bar), "r"(c0), "r"(c1), "r"(c2), "h"(mask) : "memory");
}
__device__ __forceinline__ void tma2d_store(const CUtensorMap* m, uint32_t src, int c0, int c1) {
    asm volatile("cp.async.bulk.tensor.2d.global.shared::cta.bulk_group [%0, {%2, %3}], [%1];" ::"l"(m), "r"(src), "r"(c0), "r"(c1) : "memory");
}
__device__ __forceinline__ void tma3d_store(const CUtensorMap* m, uint32_t src, int c0, int c1, int c2) {
    asm volatile("cp.async.bulk.tensor.3d.global.shared::cta.bulk_group [%0, {%2, %3, %4}], [%1];" ::"l"(m), "r"(src), "r"(c0), "r"(c1), "r"(c2) : "memory");
}
__device__ __forceinline__ void bulk_commit() { asm volatile("cp.async.bulk.commit_group;" ::: "memory"); }
__device__ __forceinline__ void bulk_wait_read() { asm volatile("cp.async.bulk.wait_group.read 0;" ::: "memory"); }
__device__ __forceinline__ void prefetch_tmap(const CUtensorMap* m) { asm volatile("prefetch.tensormap [%0];" ::"l"(m) : "memory"); }
__device__ __forceinline__ void fence_async_smem() { asm volatile("fence.proxy.async.shared::cta;" ::: "memory"); }
__device__ __forceinline__ void fence_mbar_init() { asm volatile("fence.mbarrier_init.release.cluster;" ::: "memory"); }
__device__ __forceinline__ void cluster_sync() { asm volatile("barrier.cluster.arrive.release.aligned;\nbarrier.cluster.wait.acquire.aligned;" ::: "memory"); }
__device__ __forceinline__ uint32_t cluster_rank() { uint32_t r; asm volatile("mov.u32 %0, %%cluster_ctarank;" : "=r"(r)); return r; }
__device__ __forceinline__ void pdl_wait() { asm volatile("griddepcontrol.wait;" ::: "memory"); }
__device__ __forceinline__ void pdl_launch() { asm volatile("griddepcontrol.launch_dependents;" ::: "memory"); }
__device__ __forceinline__ bool elect_one() {
    uint32_t p;
    asm volatile("{\n.reg .pred p;\nelect.sync _|p, 0xffffffff;\nselp.b32 %0, 1, 0, p;\n}" : "=r"(p));
    return p != 0;
}
__device__ __forceinline__ void named_bar(int id, int n) { asm volatile("bar.sync %0, %1;" ::"r"(id), "r"(n) : "memory"); }

__device__ __forceinline__ void wg_fence() { asm volatile("wgmma.fence.sync.aligned;" ::: "memory"); }
__device__ __forceinline__ void wg_commit() { asm volatile("wgmma.commit_group.sync.aligned;" ::: "memory"); }
template <int N> __device__ __forceinline__ void wg_wait() { asm volatile("wgmma.wait_group.sync.aligned %0;" ::"n"(N) : "memory"); }
template <int N> __device__ __forceinline__ void fence_regs(float (&d)[N]) {
#pragma unroll
    for (int i = 0; i < N; i++) asm volatile("" : "+f"(d[i])::"memory");
}
__device__ __forceinline__ uint64_t mkdesc(uint32_t addr, uint32_t lbo, uint32_t sbo, uint32_t swz) {
    uint64_t d = 0;
    d |= (uint64_t)((addr & 0x3FFFF) >> 4);
    d |= (uint64_t)((lbo & 0x3FFFF) >> 4) << 16;
    d |= (uint64_t)((sbo & 0x3FFFF) >> 4) << 32;
    d |= (uint64_t)swz << 62;
    return d;
}
__device__ __forceinline__ void ldsm_x4(uint32_t& r0, uint32_t& r1, uint32_t& r2, uint32_t& r3, uint32_t addr) {
    asm volatile("ldmatrix.sync.aligned.m8n8.x4.shared.b16 {%0,%1,%2,%3}, [%4];" : "=r"(r0), "=r"(r1), "=r"(r2), "=r"(r3) : "r"(addr) : "memory");
}
__device__ __forceinline__ void stsm_x4(uint32_t addr, uint32_t r0, uint32_t r1, uint32_t r2, uint32_t r3) {
    asm volatile("stmatrix.sync.aligned.m8n8.x4.shared.b16 [%0], {%1,%2,%3,%4};" ::"r"(addr), "r"(r0), "r"(r1), "r"(r2), "r"(r3) : "memory");
}
__device__ __forceinline__ void ldsm_x4_t(uint32_t& r0, uint32_t& r1, uint32_t& r2, uint32_t& r3, uint32_t addr) {
    asm volatile("ldmatrix.sync.aligned.m8n8.x4.trans.shared.b16 {%0,%1,%2,%3}, [%4];" : "=r"(r0), "=r"(r1), "=r"(r2), "=r"(r3) : "r"(addr) : "memory");
}
__device__ __forceinline__ void hmma(float (&d)[4], uint32_t a0, uint32_t a1, uint32_t a2, uint32_t a3, uint32_t b0, uint32_t b1) {
    asm volatile("mma.sync.aligned.m16n8k16.row.col.f32.bf16.bf16.f32 {%0,%1,%2,%3}, {%4,%5,%6,%7}, {%8,%9}, {%0,%1,%2,%3};"
                 : "+f"(d[0]), "+f"(d[1]), "+f"(d[2]), "+f"(d[3]) : "r"(a0), "r"(a1), "r"(a2), "r"(a3), "r"(b0), "r"(b1));
}
__device__ __forceinline__ uint32_t pack_bf16(float lo, float hi) {
    uint32_t r;
    asm("cvt.rn.bf16x2.f32 %0, %1, %2;" : "=r"(r) : "f"(hi), "f"(lo));
    return r;
}
__device__ __forceinline__ float bf_lo(uint32_t v) { return __uint_as_float(v << 16); }
__device__ __forceinline__ float bf_hi(uint32_t v) { return __uint_as_float(v & 0xFFFF0000u); }

#define WG_REGS_4(o) "+f"(d[o]), "+f"(d[o + 1]), "+f"(d[o + 2]), "+f"(d[o + 3])
#define WG_REGS_8(o) WG_REGS_4(o), WG_REGS_4(o + 4)
#define WG_REGS_16(o) WG_REGS_8(o), WG_REGS_8(o + 8)
#define WG_REGS_32(o) WG_REGS_16(o), WG_REGS_16(o + 16)

__device__ __forceinline__ void wgmma_ss_n80_tb(float (&d)[40], uint64_t dA, uint64_t dB, int sc) {
    asm volatile("{\n.reg .pred p;\nsetp.ne.b32 p, %42, 0;\n"
                 "wgmma.mma_async.sync.aligned.m64n80k16.f32.bf16.bf16 "
                 "{%0,%1,%2,%3,%4,%5,%6,%7,%8,%9,%10,%11,%12,%13,%14,%15,%16,%17,%18,%19,%20,%21,%22,%23,%24,%25,%26,%27,%28,%29,%30,%31,"
                 "%32,%33,%34,%35,%36,%37,%38,%39}, %40, %41, p, 1, 1, 0, 1;\n}\n"
                 : WG_REGS_32(0), WG_REGS_8(32) : "l"(dA), "l"(dB), "r"(sc));
}
__device__ __forceinline__ void wgmma_ss_n64_tb(float (&d)[32], uint64_t dA, uint64_t dB, int sc) {
    asm volatile("{\n.reg .pred p;\nsetp.ne.b32 p, %34, 0;\n"
                 "wgmma.mma_async.sync.aligned.m64n64k16.f32.bf16.bf16 "
                 "{%0,%1,%2,%3,%4,%5,%6,%7,%8,%9,%10,%11,%12,%13,%14,%15,%16,%17,%18,%19,%20,%21,%22,%23,%24,%25,%26,%27,%28,%29,%30,%31}, "
                 "%32, %33, p, 1, 1, 0, 1;\n}\n"
                 : WG_REGS_32(0) : "l"(dA), "l"(dB), "r"(sc));
}
__device__ __forceinline__ void wgmma_ss_n224_tb(float (&d)[112], uint64_t dA, uint64_t dB, int sc) {
    asm volatile("{\n.reg .pred p;\nsetp.ne.b32 p, %114, 0;\n"
                 "wgmma.mma_async.sync.aligned.m64n224k16.f32.bf16.bf16 "
                 "{%0,%1,%2,%3,%4,%5,%6,%7,%8,%9,%10,%11,%12,%13,%14,%15,%16,%17,%18,%19,%20,%21,%22,%23,%24,%25,%26,%27,%28,%29,%30,%31,"
                 "%32,%33,%34,%35,%36,%37,%38,%39,%40,%41,%42,%43,%44,%45,%46,%47,%48,%49,%50,%51,%52,%53,%54,%55,%56,%57,%58,%59,%60,%61,%62,%63,"
                 "%64,%65,%66,%67,%68,%69,%70,%71,%72,%73,%74,%75,%76,%77,%78,%79,%80,%81,%82,%83,%84,%85,%86,%87,%88,%89,%90,%91,%92,%93,%94,%95,"
                 "%96,%97,%98,%99,%100,%101,%102,%103,%104,%105,%106,%107,%108,%109,%110,%111}, "
                 "%112, %113, p, 1, 1, 0, 1;\n}\n"
                 : WG_REGS_32(0), WG_REGS_32(32), WG_REGS_32(64), WG_REGS_16(96) : "l"(dA), "l"(dB), "r"(sc));
}
template <int BN> __device__ __forceinline__ void wgmma_ss_tb(float (&d)[BN / 2], uint64_t dA, uint64_t dB, int sc) {
    if constexpr (BN == 64) wgmma_ss_n64_tb(d, dA, dB, sc);
    else if constexpr (BN == 80) wgmma_ss_n80_tb(d, dA, dB, sc);
    else wgmma_ss_n224_tb(d, dA, dB, sc);
}
__device__ __forceinline__ void wgmma_rs_n64_tb(float (&d)[32], uint32_t a, uint64_t dB, int sc) {
    asm volatile("{\n.reg .pred p;\nsetp.ne.b32 p, %34, 0;\n"
                 "wgmma.mma_async.sync.aligned.m64n64k16.f32.bf16.bf16 "
                 "{%0,%1,%2,%3,%4,%5,%6,%7,%8,%9,%10,%11,%12,%13,%14,%15,%16,%17,%18,%19,%20,%21,%22,%23,%24,%25,%26,%27,%28,%29,%30,%31}, "
                 "{%32,%32,%32,%32}, %33, p, 1, 1, 1;\n}\n"
                 : WG_REGS_32(0) : "r"(a), "l"(dB), "r"(sc));
}
__device__ __forceinline__ void wgmma_rs_n80_tb(float (&d)[40], uint32_t a, uint64_t dB, int sc) {
    asm volatile("{\n.reg .pred p;\nsetp.ne.b32 p, %42, 0;\n"
                 "wgmma.mma_async.sync.aligned.m64n80k16.f32.bf16.bf16 "
                 "{%0,%1,%2,%3,%4,%5,%6,%7,%8,%9,%10,%11,%12,%13,%14,%15,%16,%17,%18,%19,%20,%21,%22,%23,%24,%25,%26,%27,%28,%29,%30,%31,"
                 "%32,%33,%34,%35,%36,%37,%38,%39}, {%40,%40,%40,%40}, %41, p, 1, 1, 1;\n}\n"
                 : WG_REGS_32(0), WG_REGS_8(32) : "r"(a), "l"(dB), "r"(sc));
}
template <int BN> __device__ __forceinline__ void wgmma_rs_ones(float (&d)[BN / 2], uint64_t dB, int sc) {
    if constexpr (BN == 80) wgmma_rs_n80_tb(d, 0x3F803F80u, dB, sc);
    else if constexpr (BN == 64) wgmma_rs_n64_tb(d, 0x3F803F80u, dB, sc);
}
__device__ __forceinline__ void wgmma_rs_n64_z(float (&d)[32], uint32_t a0, uint32_t a1, uint32_t a2, uint32_t a3, uint64_t dB) {
    asm volatile("{\n.reg .pred p;\nsetp.ne.b32 p, 0, 0;\n"
                 "wgmma.mma_async.sync.aligned.m64n64k16.f32.bf16.bf16 "
                 "{%0,%1,%2,%3,%4,%5,%6,%7,%8,%9,%10,%11,%12,%13,%14,%15,%16,%17,%18,%19,%20,%21,%22,%23,%24,%25,%26,%27,%28,%29,%30,%31}, "
                 "{%32,%33,%34,%35}, %36, p, 1, 1, 0;\n}\n"
                 : "=f"(d[0]), "=f"(d[1]), "=f"(d[2]), "=f"(d[3]), "=f"(d[4]), "=f"(d[5]), "=f"(d[6]), "=f"(d[7]),
                   "=f"(d[8]), "=f"(d[9]), "=f"(d[10]), "=f"(d[11]), "=f"(d[12]), "=f"(d[13]), "=f"(d[14]), "=f"(d[15]),
                   "=f"(d[16]), "=f"(d[17]), "=f"(d[18]), "=f"(d[19]), "=f"(d[20]), "=f"(d[21]), "=f"(d[22]), "=f"(d[23]),
                   "=f"(d[24]), "=f"(d[25]), "=f"(d[26]), "=f"(d[27]), "=f"(d[28]), "=f"(d[29]), "=f"(d[30]), "=f"(d[31])
                 : "r"(a0), "r"(a1), "r"(a2), "r"(a3), "l"(dB));
}
__device__ __forceinline__ void wgmma_rs_n24_tb(float (&d)[12], uint32_t a0, uint32_t a1, uint32_t a2, uint32_t a3, uint64_t dB) {
    asm volatile("{\n.reg .pred p;\nsetp.eq.b32 p, 0, 0;\n"
                 "wgmma.mma_async.sync.aligned.m64n24k16.f32.bf16.bf16 "
                 "{%0,%1,%2,%3,%4,%5,%6,%7,%8,%9,%10,%11}, {%12,%13,%14,%15}, %16, p, 1, 1, 1;\n}\n"
                 : WG_REGS_8(0), WG_REGS_4(8) : "r"(a0), "r"(a1), "r"(a2), "r"(a3), "l"(dB));
}

constexpr int SIDE_CTAS = 4;
__device__ __forceinline__ void side_job(int cta, float* red  , const __nv_bfloat16* __restrict__ wo,
                                         const __nv_bfloat16* __restrict__ w1, const __nv_bfloat16* __restrict__ w2) {
    const int tid = threadIdx.x, warp = tid >> 5, lane = tid & 31;
    for (int line = cta * 512 + tid; line < 18432; line += SIDE_CTAS * 512) {
        const char* p = line < 4096 ? (const char*)wo + (size_t)line * 128 : (const char*)w2 + (size_t)(line - 4096) * 128;
        asm volatile("prefetch.global.L2 [%0];" ::"l"(p));
    }
    const int rg = lane >> 3, c8 = lane & 7;
    for (int slab = cta; slab < F_ / 64; slab += SIDE_CTAS) {
        const __nv_bfloat16* base = w1 + slab * 64 + c8 * 8;
        uint4 v[8];
#pragma unroll
        for (int i = 0; i < 8; i++) v[i] = __ldg((const uint4*)(base + (size_t)(warp * 32 + rg + 4 * i) * F_));
        float acc[8];
#pragma unroll
        for (int i = 0; i < 8; i++) acc[i] = 0.f;
#pragma unroll
        for (int i = 0; i < 8; i++) {
            acc[0] += bf_lo(v[i].x); acc[1] += bf_hi(v[i].x); acc[2] += bf_lo(v[i].y); acc[3] += bf_hi(v[i].y);
            acc[4] += bf_lo(v[i].z); acc[5] += bf_hi(v[i].z); acc[6] += bf_lo(v[i].w); acc[7] += bf_hi(v[i].w);
        }
#pragma unroll
        for (int i = 0; i < 8; i++) {
            acc[i] += __shfl_xor_sync(0xffffffffu, acc[i], 8);
            acc[i] += __shfl_xor_sync(0xffffffffu, acc[i], 16);
        }
        if (rg == 0) {
#pragma unroll
            for (int i = 0; i < 8; i++) red[warp * 64 + c8 * 8 + i] = acc[i];
        }
        __syncthreads();
        if (tid < 64) {
            float s = 0.f;
#pragma unroll
            for (int i = 0; i < 16; i++) s += red[i * 64 + tid];
            g_cs_1[slab * 64 + tid] = s;
        }
        __syncthreads();
    }
}

enum { EPI_QKV = 0, EPI_RES = 1, EPI_FFN1 = 2 };

struct GemmParams {
    const float2* stats_in;
    float2* stats_out;
    const __nv_bfloat16* wkv;
    const __nv_bfloat16* wv;
    int tk;
};

template <int BK_, int NBLK> struct Geo {
    static constexpr int BK = BK_, A_BYTES = 128 * BK * 2, A_SWZ = BK == 64 ? 1 : 2, A_SBO = BK * 16;
    static constexpr int BLK = BK * 64;
    static constexpr int B_BYTES = NBLK * BLK, B_SWZ = 2, B_LBO = BLK, B_SBO = 512, B_KSTEP = 1024;
};
template <> struct Geo<64, 0> {
    static constexpr int BK = 64, A_BYTES = 128 * 128, A_SWZ = 1, A_SBO = 1024, BLK = 8192;
    static constexpr int B_BYTES = 64 * 128, B_SWZ = 1, B_LBO = 8192, B_SBO = 1024, B_KSTEP = 2048;
};
#define F1_BK 32
template <int EPI> struct EpiGeo;
template <> struct EpiGeo<EPI_QKV> { using G = Geo<64, 3>; };
template <> struct EpiGeo<EPI_RES> { using G = Geo<64, 0>; };
template <> struct EpiGeo<EPI_FFN1> { using G = Geo<F1_BK, 7>; };

template <int STAGES, int EPI> struct GemmSmem {
    using G = typename EpiGeo<EPI>::G;
    static constexpr int STAGE = G::A_BYTES + G::B_BYTES;
    static constexpr int AUX_OFF = STAGES * STAGE;
    static constexpr int TOTAL = AUX_OFF + 1152;
    static constexpr int TOTAL_SELF = AUX_OFF + 704 + 1024 + 1280;
};

struct RowStatRaw { float2 a0, a1, b0, b1; };
__device__ __forceinline__ RowStatRaw load_row_stats(const float2* __restrict__ st, int row0, int c) {
    RowStatRaw r;
    r.a0 = st[(2 * c) * S_ + row0]; r.a1 = st[(2 * c + 1) * S_ + row0];
    r.b0 = st[(2 * c) * S_ + row0 + 8]; r.b1 = st[(2 * c + 1) * S_ + row0 + 8];
    return r;
}
__device__ __forceinline__ void finish_row_stats(const RowStatRaw& r, float& mean0, float& rstd0, float& mean1, float& rstd1) {
    float sa = r.a0.x + r.a1.x, sb = r.b0.x + r.b1.x;
    sa += __shfl_xor_sync(0xffffffffu, sa, 1); sa += __shfl_xor_sync(0xffffffffu, sa, 2);
    sb += __shfl_xor_sync(0xffffffffu, sb, 1); sb += __shfl_xor_sync(0xffffffffu, sb, 2);
    mean0 = sa * 0.125f; mean1 = sb * 0.125f;
    float ma = r.a0.y + r.a1.y + 64.f * ((r.a0.x - mean0) * (r.a0.x - mean0) + (r.a1.x - mean0) * (r.a1.x - mean0));
    float mb = r.b0.y + r.b1.y + 64.f * ((r.b0.x - mean1) * (r.b0.x - mean1) + (r.b1.x - mean1) * (r.b1.x - mean1));
    ma += __shfl_xor_sync(0xffffffffu, ma, 1); ma += __shfl_xor_sync(0xffffffffu, ma, 2);
    mb += __shfl_xor_sync(0xffffffffu, mb, 1); mb += __shfl_xor_sync(0xffffffffu, mb, 2);
    rstd0 = 1.0f / sqrtf(ma * (1.f / 512.f) + 1e-5f);
    rstd1 = 1.0f / sqrtf(mb * (1.f / 512.f) + 1e-5f);
}

template <int BN, int KB, int STAGES, int EPI, int MC, bool SELF = false>
__device__ __forceinline__ void gemm_body(const CUtensorMap* mapA, const CUtensorMap* mapB, const CUtensorMap* mapB2, const CUtensorMap* mapR,
                                          const CUtensorMap* mapC, const GemmParams& prm, int tile_m, int tile_n, uint8_t* smem_raw) {
    using SM = GemmSmem<STAGES, EPI>;
    using G = typename SM::G;
    constexpr bool XKV = BN == 80;
    constexpr int TN = EPI == EPI_QKV ? 64 : BN;
    CP(prm.tk, 0);
    pdl_launch();
    const uint32_t sbase = smem_u32(smem_raw);
    if (sbase & 1023) __trap();
    uint8_t* sgen = smem_raw;
    const uint32_t bar_full = sbase + SM::AUX_OFF, bar_empty = bar_full + 8 * STAGES;
    float* s_cs = (float*)(sgen + SM::AUX_OFF + 256);
    float* s_row = (float*)(sgen + SM::AUX_OFF + 704);
    float* s_red = (float*)(sgen + SM::AUX_OFF + 640);
    const int tid = threadIdx.x, lane = tid & 31;
    const int warp = __shfl_sync(0xffffffffu, tid >> 5, 0);
    const uint32_t rank = MC ? cluster_rank() : 0;
    if (tid == 0) TL(prm.tk, 0);

    constexpr bool INLINE_PROD = EPI == EPI_FFN1 && F1_INLINE;
    constexpr int PWARP = INLINE_PROD ? 0 : 8;
    if (warp == PWARP && elect_one()) {
#pragma unroll
        for (int s = 0; s < STAGES; s++) { mbar_init(bar_full + 8 * s, 1); mbar_init(bar_empty + 8 * s, MC ? 4 : 2); }
        fence_mbar_init();
    }
    if (warp == 1 && elect_one()) { prefetch_tmap(mapB); prefetch_tmap(mapA); prefetch_tmap(mapC); }
    CP(prm.tk, 1);
    __syncthreads();
    CP(prm.tk, 2);
    if (MC) asm volatile("barrier.cluster.arrive.relaxed.aligned;" ::: "memory");
    auto cluster_wait = [&]() { if (MC) asm volatile("barrier.cluster.wait.acquire.aligned;" ::: "memory"); };

    const int m0 = tile_m * 128, n0 = tile_n * TN;
    constexpr uint32_t STAGE_TX = G::A_BYTES + (EPI == EPI_QKV ? 2 * G::BLK : G::B_BYTES);
    auto loadB = [&](int kb, int s) {
        const uint32_t dst = sbase + s * SM::STAGE + G::A_BYTES, bar = bar_full + 8 * s;
        if constexpr (EPI == EPI_RES) {
            tma2d(dst, mapB, n0, kb * 64, bar);
        } else if constexpr (EPI == EPI_QKV) {
            tma3d(dst, mapB, 0, kb * G::BK, tile_n * 2, bar);
        } else {
            if constexpr (MC == 2) {
                if (rank == 0) tma3d_mc(dst, mapB, 0, kb * G::BK, tile_n * 7, bar, 3);
                else tma3d_mc(dst + 4 * G::BLK, mapB2, 0, kb * G::BK, tile_n * 7 + 4, bar, 3);
            } else {
                tma3d(dst, mapB, 0, kb * G::BK, tile_n * 7, bar);
                tma3d(dst + 4 * G::BLK, mapB2, 0, kb * G::BK, tile_n * 7 + 4, bar);
            }
        }
    };
    auto loadA = [&](int kb, int s) {
        const uint32_t dst = sbase + s * SM::STAGE, bar = bar_full + 8 * s;
        if constexpr (MC == 1) tma2d_mc(dst + rank * (G::A_BYTES / 2), mapA, kb * G::BK, m0 + rank * 64, bar, 3);
        else tma2d(dst, mapA, kb * G::BK, m0, bar);
    };
    constexpr int PRE = STAGES < KB ? STAGES : KB;
#define F1_LAG 2
    constexpr int LAG = F1_LAG;
    constexpr int PRE_B = PRE < PREB ? PRE : PREB;
    auto prologue_loads = [&]() {
        if (elect_one()) {
#pragma unroll
            for (int kb = 0; kb < PRE; kb++) mbar_expect_tx(bar_full + 8 * kb, STAGE_TX);
        }
        CP(prm.tk, 3);
        cluster_wait();
        CP(prm.tk, 4);
        if (elect_one()) {
#pragma unroll
            for (int kb = 0; kb < PRE_B; kb++) loadB(kb, kb);
        }
        CP(prm.tk, 5);
        if (!SELF) pdl_wait();
        CP(prm.tk, 6);
        if (elect_one()) {
#pragma unroll
            for (int kb = 0; kb < PRE; kb++) {
                loadA(kb, kb);
                if (kb + PRE_B < PRE) loadB(kb + PRE_B, kb + PRE_B);
            }
            if constexpr (EPI == EPI_RES && KB < STAGES) {
                mbar_expect_tx(bar_full + 8 * KB, 16384);
                tma2d(sbase + KB * SM::STAGE, mapR, n0, m0, bar_full + 8 * KB);
            }
        }
    };
    if (SELF && warp >= 8) {
        if (warp == 8) prologue_loads();
        static_assert(!SELF || (STAGES >= KB && EPI == EPI_QKV), "SELF needs every k block resident");
        if ((warp >> 2) == 3) {
            float csum[BN / 2];
            const uint64_t dB0 = mkdesc(sbase + G::A_BYTES, G::B_LBO, G::B_SBO, G::B_SWZ);
            if constexpr (XKV) named_bar(6, 384);
#pragma unroll 1
            for (int kb = 0; kb < KB; kb++) {
                mbar_wait(bar_full + 8 * kb, 0);
                const uint64_t dB = dB0 + (uint64_t)(kb * (SM::STAGE >> 4));
                wg_fence();
#pragma unroll
                for (int k = 0; k < G::BK / 16; k++) {
                    if constexpr (SELF) wgmma_rs_ones<BN>(csum, dB + (uint64_t)(k * (G::B_KSTEP >> 4)), (kb | k) != 0);
                }
                wg_commit();
            }
            wg_wait<0>();
            fence_regs(csum);
            if (warp == 12 && lane < 4) {
#pragma unroll
                for (int j = 0; j < BN / 8; j++) {
                    const float2 v = make_float2(csum[4 * j], csum[4 * j + 1]);
                    *(float2*)(s_cs + 8 * j + 2 * lane) = v;
                    if (tile_m == 0) {
                        if (j < 8) *(float2*)(g_cs_q + n0 + 8 * j + 2 * lane) = v;
                        else *(float2*)(g_cs_kv + tile_n * 16 + 8 * (j - 8) + 2 * lane) = v;
                    }
                }
            }
        } else {
            const int t = (warp < 12 ? warp - 8 : warp - 12) * 32 + lane;
            float ss[4] = {0.f, 0.f, 0.f, 0.f}, sq[4] = {0.f, 0.f, 0.f, 0.f};
#pragma unroll 1
            for (int kb = 0; kb < KB; kb++) {
                mbar_wait(bar_full + 8 * kb, 0);
                const uint32_t arow = sbase + kb * SM::STAGE + (t >> 1) * 128;
                uint32_t w[4][4];
#pragma unroll
                for (int j = 0; j < 4; j++)
                    asm volatile("ld.shared.v4.u32 {%0,%1,%2,%3}, [%4];" : "=r"(w[j][0]), "=r"(w[j][1]), "=r"(w[j][2]), "=r"(w[j][3])
                                 : "r"(arow + (((2 * j + (t & 1) + 2 * ((t >> 1) & 3)) & 7) << 4)));
#pragma unroll
                for (int j = 0; j < 4; j++)
#pragma unroll
                    for (int i = 0; i < 4; i++) {
                        const float lo = bf_lo(w[j][i]), hi = bf_hi(w[j][i]);
                        ss[i] += lo + hi;
                        sq[i] = fmaf(lo, lo, fmaf(hi, hi, sq[i]));
                    }
            }
            float tsum = (ss[0] + ss[1]) + (ss[2] + ss[3]), tsq = (sq[0] + sq[1]) + (sq[2] + sq[3]);
            tsum += __shfl_xor_sync(0xffffffffu, tsum, 1);
            tsq += __shfl_xor_sync(0xffffffffu, tsq, 1);
            if ((t & 1) == 0) {
                const float md = tsum * (1.f / 512.f);
                const float var = fmaxf(tsq * (1.f / 512.f) - md * md, 0.f);
                *(float2*)(s_row + t) = make_float2(md, 1.0f / sqrtf(var + 1e-5f));
            }
        }
        named_bar(4, 640);
    } else if (!INLINE_PROD && warp == 8) {
        prologue_loads();
        int s = PRE % STAGES, ph = (PRE / STAGES) & 1;
#pragma unroll 1
        for (int kb = PRE; kb < KB; kb++) {
            mbar_wait(bar_empty + 8 * s, ph ^ 1);
            if (elect_one()) {
                mbar_expect_tx(bar_full + 8 * s, STAGE_TX);
                loadB(kb, s);
                loadA(kb, s);
            }
            if (++s == STAGES) { s = 0; ph ^= 1; }
        }
        if constexpr (EPI == EPI_RES && KB >= STAGES) {
            mbar_wait(bar_empty + 8 * s, ph ^ 1);
            if (elect_one()) {
                mbar_expect_tx(bar_full + 8 * s, 16384);
                tma2d(sbase + s * SM::STAGE, mapR, n0, m0, bar_full + 8 * s);
            }
        }
    } else {
        if (INLINE_PROD && warp == 0) prologue_loads(); else cluster_wait();
        const int wg = warp >> 2, g = lane >> 2, c = lane & 3;
        const int rloc = wg * 64 + (warp & 3) * 16 + g;
        const int row0 = m0 + rloc;
        float mean0 = 0.f, rstd0 = 1.f, mean1 = 0.f, rstd1 = 1.f;
        if constexpr (XKV) {
            static_assert(!XKV || STAGES >= KB, "the K / V weight block must stay resident");
            const __nv_bfloat16* wsrc = tile_n == 0 ? prm.wkv : prm.wv;
            uint4 v[4];
#pragma unroll
            for (int i = 0; i < 4; i++) v[i] = __ldg((const uint4*)wsrc + tid + 256 * i);
#pragma unroll
            for (int i = 0; i < 4; i++) {
                const int idx = tid + 256 * i, k = idx >> 1, kr = k & 63;
                const uint32_t dst = sbase + (k >> 6) * SM::STAGE + G::A_BYTES + 2 * G::BLK + kr * 64 + (((idx & 1) ^ ((kr >> 1) & 3)) << 4);
                asm volatile("st.shared.v4.u32 [%0], {%1,%2,%3,%4};" ::"r"(dst), "r"(v[i].x), "r"(v[i].y), "r"(v[i].z), "r"(v[i].w) : "memory");
            }
            fence_async_smem();
            if constexpr (SELF) named_bar(6, 384); else named_bar(6, 256);
        }
        RowStatRaw raw;
        float csv = 0.f;
        float2 cskv[2] = {make_float2(0.f, 0.f), make_float2(0.f, 0.f)};
        auto ln_inputs = [&]() {
            pdl_wait();
            if constexpr (EPI != EPI_RES) {
                raw = load_row_stats(prm.stats_in, row0, c);
                const float* cs = EPI == EPI_FFN1 ? g_cs_1 + n0 : g_cs_q + n0;
                if (tid < TN) csv = cs[tid];
                if constexpr (XKV) {
                    cskv[0] = *(const float2*)(g_cs_kv + tile_n * 16 + 2 * c);
                    cskv[1] = *(const float2*)(g_cs_kv + tile_n * 16 + 8 + 2 * c);
                }
            }
        };
        if (!SELF) ln_inputs();
        float acc[BN / 2];
        const uint64_t dA0 = mkdesc(sbase + wg * (G::A_BYTES / 2), 16, G::A_SBO, G::A_SWZ);
        const uint64_t dB0 = mkdesc(sbase + G::A_BYTES, G::B_LBO, G::B_SBO, G::B_SWZ);
        int s = 0, ph = 0;
#pragma unroll 1
        for (int kb = 0; kb < KB; kb++) {
            mbar_wait(bar_full + 8 * s, ph);
            const uint64_t dA = dA0 + (uint64_t)(s * (SM::STAGE >> 4)), dB = dB0 + (uint64_t)(s * (SM::STAGE >> 4));
            wg_fence();
#pragma unroll
            for (int k = 0; k < G::BK / 16; k++) wgmma_ss_tb<BN>(acc, dA + (uint64_t)(k * 2), dB + (uint64_t)(k * (G::B_KSTEP >> 4)), (kb | k) != 0);
            wg_commit();
            if constexpr (EPI == EPI_RES && RES_WAIT0) {
                wg_wait<0>();
                if ((warp & 3) == 0 && elect_one()) {
                    if (MC) { mbar_arrive_remote(bar_empty + 8 * s, 0); mbar_arrive_remote(bar_empty + 8 * s, 1); }
                    else mbar_arrive(bar_empty + 8 * s);
                }
            } else if (kb > 0) {
                wg_wait<1>();
                const int sp = s == 0 ? STAGES - 1 : s - 1;
                if ((warp & 3) == 0 && elect_one()) {
                    if (MC) { mbar_arrive_remote(bar_empty + 8 * sp, 0); mbar_arrive_remote(bar_empty + 8 * sp, 1); }
                    else mbar_arrive(bar_empty + 8 * sp);
                }
                if (INLINE_PROD && warp == 0 && kb >= LAG && kb - LAG + STAGES < KB) {
                    const int sq = LAG == 1 ? sp : (sp == 0 ? STAGES - 1 : sp - 1);
                    mbar_wait(bar_empty + 8 * sq, ((kb - LAG) / STAGES) & 1);
                    if (elect_one()) {
                        mbar_expect_tx(bar_full + 8 * sq, STAGE_TX);
                        loadB(kb - LAG + STAGES, sq);
                        loadA(kb - LAG + STAGES, sq);
                    }
                }
            }
            if (++s == STAGES) { s = 0; ph ^= 1; }
        }
        if constexpr (SELF) {
            named_bar(4, 640);
            const float2 r0 = *(const float2*)(s_row + 2 * rloc), r1 = *(const float2*)(s_row + 2 * rloc + 16);
            mean0 = r0.x; rstd0 = r0.y; mean1 = r1.x; rstd1 = r1.y;
        } else if constexpr (EPI != EPI_RES) {
            finish_row_stats(raw, mean0, rstd0, mean1, rstd1);
            if (tid < TN) s_cs[tid] = csv;
        }
        wg_wait<0>();
        fence_regs(acc);
        if (tid == 0) TL(prm.tk, 2);
        if constexpr (EPI != EPI_RES) named_bar(1, 256);

        if constexpr (EPI != EPI_FFN1) {
            const uint32_t stile = sbase + (EPI == EPI_RES ? s * SM::STAGE : 0);
            const int mrow = wg * 64 + (warp & 3) * 16 + (lane & 7) + ((lane >> 3) & 1) * 8;
            const uint32_t rbase = stile + mrow * 128;
            if constexpr (EPI == EPI_RES) {
                mbar_wait(bar_full + 8 * s, ph);
                float s0 = 0.f, s1 = 0.f;
#pragma unroll
                for (int jj = 0; jj < 4; jj++) {
                    uint32_t r0, r1, r2, r3;
                    const uint32_t addr = rbase + (((2 * jj + (lane >> 4)) ^ (mrow & 7)) << 4);
                    ldsm_x4(r0, r1, r2, r3, addr);
                    const uint32_t u0 = pack_bf16(acc[8 * jj] + bf_lo(r0), acc[8 * jj + 1] + bf_hi(r0));
                    const uint32_t u1 = pack_bf16(acc[8 * jj + 2] + bf_lo(r1), acc[8 * jj + 3] + bf_hi(r1));
                    const uint32_t u2 = pack_bf16(acc[8 * jj + 4] + bf_lo(r2), acc[8 * jj + 5] + bf_hi(r2));
                    const uint32_t u3 = pack_bf16(acc[8 * jj + 6] + bf_lo(r3), acc[8 * jj + 7] + bf_hi(r3));
                    stsm_x4(addr, u0, u1, u2, u3);
                    acc[8 * jj] = bf_lo(u0); acc[8 * jj + 1] = bf_hi(u0); acc[8 * jj + 4] = bf_lo(u2); acc[8 * jj + 5] = bf_hi(u2);
                    acc[8 * jj + 2] = bf_lo(u1); acc[8 * jj + 3] = bf_hi(u1); acc[8 * jj + 6] = bf_lo(u3); acc[8 * jj + 7] = bf_hi(u3);
                    s0 += (acc[8 * jj] + acc[8 * jj + 1]) + (acc[8 * jj + 4] + acc[8 * jj + 5]);
                    s1 += (acc[8 * jj + 2] + acc[8 * jj + 3]) + (acc[8 * jj + 6] + acc[8 * jj + 7]);
                }
                fence_async_smem();
                named_bar(2 + wg, 128);
                if ((warp & 3) == 0 && elect_one()) { tma2d_store(mapC, stile + wg * 8192, n0, m0 + wg * 64); bulk_commit(); }
                if (prm.stats_out) {
                    s0 += __shfl_xor_sync(0xffffffffu, s0, 1); s0 += __shfl_xor_sync(0xffffffffu, s0, 2);
                    s1 += __shfl_xor_sync(0xffffffffu, s1, 1); s1 += __shfl_xor_sync(0xffffffffu, s1, 2);
                    const float mu0 = s0 * (1.f / 64.f), mu1 = s1 * (1.f / 64.f);
                    float q0 = 0.f, q1 = 0.f;
#pragma unroll
                    for (int j = 0; j < 8; j++) {
                        float d;
                        d = acc[4 * j] - mu0; q0 += d * d; d = acc[4 * j + 1] - mu0; q0 += d * d;
                        d = acc[4 * j + 2] - mu1; q1 += d * d; d = acc[4 * j + 3] - mu1; q1 += d * d;
                    }
                    q0 += __shfl_xor_sync(0xffffffffu, q0, 1); q0 += __shfl_xor_sync(0xffffffffu, q0, 2);
                    q1 += __shfl_xor_sync(0xffffffffu, q1, 1); q1 += __shfl_xor_sync(0xffffffffu, q1, 2);
                    if (c == 0) {
                        prm.stats_out[tile_n * S_ + row0] = make_float2(mu0, q0);
                        prm.stats_out[tile_n * S_ + row0 + 8] = make_float2(mu1, q1);
                    }
                }
            } else {
                const float sc = 0.25f * 1.4426950408889634f;
                const float a0 = rstd0 * sc, a1 = rstd1 * sc, rm0 = a0 * mean0, rm1 = a1 * mean1;
#pragma unroll
                for (int jj = 0; jj < 4; jj++) {
                    const float2 ca = *(const float2*)(s_cs + 16 * jj + 2 * c), cb = *(const float2*)(s_cs + 16 * jj + 8 + 2 * c);
                    const uint32_t u0 = pack_bf16(acc[8 * jj] * a0 - rm0 * ca.x, acc[8 * jj + 1] * a0 - rm0 * ca.y);
                    const uint32_t u1 = pack_bf16(acc[8 * jj + 2] * a1 - rm1 * ca.x, acc[8 * jj + 3] * a1 - rm1 * ca.y);
                    const uint32_t u2 = pack_bf16(acc[8 * jj + 4] * a0 - rm0 * cb.x, acc[8 * jj + 5] * a0 - rm0 * cb.y);
                    const uint32_t u3 = pack_bf16(acc[8 * jj + 6] * a1 - rm1 * cb.x, acc[8 * jj + 7] * a1 - rm1 * cb.y);
                    stsm_x4(rbase + (((2 * jj + (lane >> 4)) ^ (mrow & 7)) << 4), u0, u1, u2, u3);
                }
                fence_async_smem();
                named_bar(2 + wg, 128);
                if ((warp & 3) == 0 && elect_one()) { tma2d_store(mapC, stile + wg * 8192, n0, m0 + wg * 64); bulk_commit(); }
            }
            if constexpr (XKV) {
                {
                    const float* acx = &acc[32];
                    const float rm0 = rstd0 * mean0, rm1 = rstd1 * mean1;
                    float n0s = 0.f, n1s = 0.f, vmax = 0.f;
#pragma unroll
                    for (int j = 0; j < 2; j++) {
                        const float2 cs2 = SELF ? *(const float2*)(s_cs + 64 + 8 * j + 2 * c) : cskv[j];
                        const uint32_t u0 = pack_bf16(acx[4 * j] * rstd0 - rm0 * cs2.x, acx[4 * j + 1] * rstd0 - rm0 * cs2.y);
                        const uint32_t u1 = pack_bf16(acx[4 * j + 2] * rstd1 - rm1 * cs2.x, acx[4 * j + 3] * rstd1 - rm1 * cs2.y);
                        n0s += bf_lo(u0) * bf_lo(u0) + bf_hi(u0) * bf_hi(u0);
                        n1s += bf_lo(u1) * bf_lo(u1) + bf_hi(u1) * bf_hi(u1);
                        vmax = fmaxf(vmax, fmaxf(fmaxf(fabsf(bf_lo(u0)), fabsf(bf_hi(u0))), fmaxf(fabsf(bf_lo(u1)), fabsf(bf_hi(u1)))));
                        if (tile_n == 0) {
                            *(uint32_t*)(g_kimg + (row0 >> 3) * 256 + j * 128 + g * 16 + c * 4) = u0;
                            *(uint32_t*)(g_kimg + ((row0 + 8) >> 3) * 256 + j * 128 + g * 16 + c * 4) = u1;
                        } else {
                            uint8_t* vb = g_vimg + (row0 >> 4) * 768 + j * 256 + g * 16 + c * 4;
                            *(uint32_t*)(vb) = u0;
                            *(uint32_t*)(vb + 128) = u1;
                        }
                    }
                    if (tile_n == 1) {
                        uint8_t* vb = g_vimg + (row0 >> 4) * 768 + 512 + g * 16 + c * 4;
                        const uint32_t one = c == 0 ? 0x00003F80u : 0u;
                        *(uint32_t*)(vb) = one;
                        *(uint32_t*)(vb + 128) = one;
                    }
                    n0s += __shfl_xor_sync(0xffffffffu, n0s, 1); n0s += __shfl_xor_sync(0xffffffffu, n0s, 2);
                    n1s += __shfl_xor_sync(0xffffffffu, n1s, 1); n1s += __shfl_xor_sync(0xffffffffu, n1s, 2);
                    float km = tile_n == 0 ? fmaxf(n0s, n1s) : vmax;
                    if (!(n0s + n1s < INFINITY)) km = INFINITY;
#pragma unroll
                    for (int o = 1; o < 32; o <<= 1) km = fmaxf(km, __shfl_xor_sync(0xffffffffu, km, o));
                    if (lane == 0) s_red[warp] = km;
                    named_bar(1, 256);
                    if (tid == 0) {
                        float a = 0.f;
                        for (int i = 0; i < 8; i++) a = fmaxf(a, s_red[i]);
                        g_kvmax[tile_n * 16 + tile_m] = a;
                    }
                }
            }
            if ((warp & 3) == 0) bulk_wait_read();
        } else {
            const uint32_t stile = sbase + wg * (7 * 4096);
            const int mrow = (warp & 3) * 16 + (lane & 7) + ((lane >> 3) & 1) * 8;
            const float a0 = 0.5f * rstd0, a1 = 0.5f * rstd1, rm0 = a0 * mean0, rm1 = a1 * mean1;
#pragma unroll
            for (int jj = 0; jj < 14; jj++) {
                const float2 ca = *(const float2*)(s_cs + 16 * jj + 2 * c), cb = *(const float2*)(s_cs + 16 * jj + 8 + 2 * c);
                float y[8] = {acc[8 * jj] * a0 - rm0 * ca.x,     acc[8 * jj + 1] * a0 - rm0 * ca.y,
                              acc[8 * jj + 2] * a1 - rm1 * ca.x, acc[8 * jj + 3] * a1 - rm1 * ca.y,
                              acc[8 * jj + 4] * a0 - rm0 * cb.x, acc[8 * jj + 5] * a0 - rm0 * cb.y,
                              acc[8 * jj + 6] * a1 - rm1 * cb.x, acc[8 * jj + 7] * a1 - rm1 * cb.y};
#pragma unroll
                for (int i = 0; i < 8; i++) {
                    float t;
                    asm("tanh.approx.f32 %0, %1;" : "=f"(t) : "f"(y[i]));
                    y[i] = fmaf(y[i], t, y[i]);
                }
                const int chunk = (2 * jj + (lane >> 4)) & 3, blk = jj >> 1;
                stsm_x4(stile + blk * 4096 + mrow * 64 + ((chunk ^ ((mrow >> 1) & 3)) << 4),
                        pack_bf16(y[0], y[1]), pack_bf16(y[2], y[3]), pack_bf16(y[4], y[5]), pack_bf16(y[6], y[7]));
                if (jj & 1) {
                    fence_async_smem();
                    __syncwarp();
                    if (elect_one()) {
                        tma2d_store(mapC, stile + blk * 4096 + (warp & 3) * 1024, n0 + blk * 32, m0 + wg * 64 + (warp & 3) * 16);
                        bulk_commit();
                    }
                }
            }
            bulk_wait_read();
        }
    }
    if (tid == 0) TL(prm.tk, 3);
    if (MC) cluster_sync();
}

#define WO_ST 9
#define F2_ST 6
#define F1_ST (F1_BK == 64 ? 5 : 9)
#define QKV_ST 8
constexpr int QKV_STAGES = QKV_ST, WO_STAGES = WO_ST, FFN2_STAGES = F2_ST, FFN1_STAGES = F1_ST;
template <bool SELF>
__global__ void __launch_bounds__(SELF ? 640 : 288) qkv_kernel(const __grid_constant__ CUtensorMap mapA, const __grid_constant__ CUtensorMap mapWq,
                                                  const __grid_constant__ CUtensorMap mapQ, const GemmParams prm) {
    extern __shared__ __align__(1024) uint8_t smem_raw[];
    const int tn = blockIdx.x & 7;
    if (tn < 2) gemm_body<80, 8, QKV_STAGES, EPI_QKV, QKV_MC, SELF>(&mapA, &mapWq, &mapWq, &mapA, &mapQ, prm, blockIdx.x >> 3, tn, smem_raw);
    else gemm_body<64, 8, QKV_STAGES, EPI_QKV, QKV_MC, SELF>(&mapA, &mapWq, &mapWq, &mapA, &mapQ, prm, blockIdx.x >> 3, tn, smem_raw);
}
template <int KB, int STAGES>
__global__ void __launch_bounds__(288) res_gemm_kernel(const __grid_constant__ CUtensorMap mapA, const __grid_constant__ CUtensorMap mapW,
                                                       const __grid_constant__ CUtensorMap mapR, const __grid_constant__ CUtensorMap mapC, const GemmParams prm) {
    extern __shared__ __align__(1024) uint8_t smem_raw[];
#define RES_MAP 0
    gemm_body<64, KB, STAGES, EPI_RES, (KB == 8 ? WO_MC : F2_MC)>(&mapA, &mapW, &mapW, &mapR, &mapC, prm, RES_MAP ? blockIdx.x & 15 : blockIdx.x >> 3,
                                                                  RES_MAP ? blockIdx.x >> 4 : blockIdx.x & 7, smem_raw);
}
__global__ void __launch_bounds__(F1_INLINE ? 256 : 288) ffn1_kernel(const __grid_constant__ CUtensorMap mapA, const __grid_constant__ CUtensorMap mapW4,
                                                   const __grid_constant__ CUtensorMap mapW3, const __grid_constant__ CUtensorMap mapH, const GemmParams prm) {
    extern __shared__ __align__(1024) uint8_t smem_raw[];
#define F1_MAP 0
    const int pair = blockIdx.x >> 1;
    const int tile_n = F1_MAP == 0 ? (pair & 7) : F1_MAP == 1 ? (blockIdx.x >> 4) : (blockIdx.x & 7);
    const int tile_m = F1_MAP == 0 ? (pair >> 3) * 2 + (blockIdx.x & 1) : F1_MAP == 1 ? (blockIdx.x & 15) : (blockIdx.x >> 3);
    gemm_body<224, 512 / F1_BK, FFN1_STAGES, EPI_FFN1, F1_MC>(&mapA, &mapW4, &mapW3, &mapA, &mapH, prm, tile_m, tile_n, smem_raw);
}

#define ATT_NPOLY 11
constexpr int NPOLY = ATT_NPOLY;
__host__ __device__ constexpr bool is_mufu(int i) { return ((i + 1) * (16 - NPOLY)) / 16 != (i * (16 - NPOLY)) / 16; }

__device__ __forceinline__ float ex2(float x) { float r; asm("ex2.approx.ftz.f32 %0, %1;" : "=f"(r) : "f"(x)); return r; }
__device__ __forceinline__ uint32_t exp_pair_mufu(float a, float b) { return pack_bf16(ex2(a), ex2(b)); }
__device__ __forceinline__ uint32_t exp_pair_fma(float a, float b, uint32_t c3f) {
    constexpr float MAGIC = 98430.4140625f;
    const float ta = a + MAGIC, tb = b + (MAGIC - 143.5f);
    uint32_t y, m, r;
    asm("mad.lo.u32 %0, %1, 65536, %2;" : "=r"(y) : "r"(__float_as_uint(tb)), "r"(__float_as_uint(ta)));
    asm("lop3.b32 %0, %1, 0x007F007F, %2, 0xEA;" : "=r"(m) : "r"(y), "r"(c3f));
    const uint32_t e = y & 0xFF80FF80u;
    asm("fma.rn.bf16x2 %0, %1, %2, %3;" : "=r"(r) : "r"(y), "r"(m), "r"(e));
    return r;
}

constexpr int KCH = 256, NCH = S_ / KCH;
constexpr int K_BYTES = S_ * 32, V_BYTES = (S_ / 16) * 768;
constexpr int QO_BYTES = 128 * 128;
constexpr int ATT_SMEM = K_BYTES + V_BYTES + QO_BYTES;

__global__ void __launch_bounds__(512, 1) attn_kernel(const __grid_constant__ CUtensorMap mapQ, const __grid_constant__ CUtensorMap mapO,
                                                       const __nv_bfloat16* __restrict__ wo, const __nv_bfloat16* __restrict__ w1,
                                                       const __nv_bfloat16* __restrict__ w2, int tk) {
    extern __shared__ __align__(1024) uint8_t smem[];
    __shared__ uint64_t bars[NCH + 1];
    __shared__ int s_slow;
    const int tid = threadIdx.x, wg = tid >> 7, warp = (tid >> 5) & 3, lane = tid & 31;
    const uint32_t sK = smem_u32(smem), sV = sK + K_BYTES, sQ = sV + V_BYTES;
    if (blockIdx.x >= 128) {
        pdl_launch();
        pdl_wait();
        side_job(blockIdx.x - 128, (float*)smem, wo, w1, w2);
        return;
    }
    CK(tk, 9);
    if (tid == 0) TL(tk, 0);
    if (tid == 0) {
#pragma unroll
        for (int i = 0; i <= NCH; i++) mbar_init(smem_u32(&bars[i]), 1);
        s_slow = 0;
        fence_mbar_init();
    }
    if (tid == 32) { prefetch_tmap(&mapQ); prefetch_tmap(&mapO); }
    __syncthreads();
    pdl_launch();
    CK(tk, 10);
    pdl_wait();
    CK(tk, 11);
    if (tid == 0) TL(tk, 1);
    const int wu = __shfl_sync(0xffffffffu, tid >> 5, 0);
    auto fetch_chunk = [&](int w) {
        if (elect_one()) {
            const uint32_t bar = smem_u32(&bars[w]);
            mbar_expect_tx(bar, KCH * 32 + (KCH / 16) * 768);
            bulk_load(sK + w * KCH * 32, g_kimg + w * KCH * 32, KCH * 32, bar);
            bulk_load(sV + w * (KCH / 16) * 768, g_vimg + w * (KCH / 16) * 768, (KCH / 16) * 768, bar);
        }
    };
    const int tb = blockIdx.x >> 3, hg = blockIdx.x & 7;
    if (wu == 1 && elect_one()) {
        mbar_expect_tx(smem_u32(&bars[NCH]), QO_BYTES);
        tma2d(sQ, &mapQ, hg * 64, tb * 128, smem_u32(&bars[NCH]));
    }
    if (wu == 0) fetch_chunk(0);
    const int g = lane >> 2;
    float kvm = g_kvmax[lane];
    const int lrow = warp * 16 + (lane & 7) + ((lane >> 3) & 1) * 8;
    const uint32_t qoff = lrow * 128 + (((2 * wg + (lane >> 4)) ^ (lrow & 7)) << 4);
    uint32_t qa[2][4];
    mbar_wait(smem_u32(&bars[NCH]), 0);
    ldsm_x4(qa[0][0], qa[0][1], qa[0][2], qa[0][3], sQ + qoff);
    ldsm_x4(qa[1][0], qa[1][1], qa[1][2], qa[1][3], sQ + 8192 + qoff);
    CK(tk, 12);
    {
        float qn = 0.f;
#pragma unroll
        for (int m = 0; m < 2; m++) {
            float n0 = bf_lo(qa[m][0]) * bf_lo(qa[m][0]) + bf_hi(qa[m][0]) * bf_hi(qa[m][0]) + bf_lo(qa[m][2]) * bf_lo(qa[m][2]) + bf_hi(qa[m][2]) * bf_hi(qa[m][2]);
            float n1 = bf_lo(qa[m][1]) * bf_lo(qa[m][1]) + bf_hi(qa[m][1]) * bf_hi(qa[m][1]) + bf_lo(qa[m][3]) * bf_lo(qa[m][3]) + bf_hi(qa[m][3]) * bf_hi(qa[m][3]);
            n0 += __shfl_xor_sync(0xffffffffu, n0, 1); n0 += __shfl_xor_sync(0xffffffffu, n0, 2);
            n1 += __shfl_xor_sync(0xffffffffu, n1, 1); n1 += __shfl_xor_sync(0xffffffffu, n1, 2);
            if (!(n0 == n0) || !(n1 == n1)) n0 = INFINITY;
            qn = fmaxf(qn, fmaxf(n0, n1));
        }
        CK(tk, 13);
#pragma unroll
        for (int o = 1; o < 16; o <<= 1) kvm = fmaxf(kvm, __shfl_xor_sync(0xffffffffu, kvm, o));
        const float km = __shfl_sync(0xffffffffu, kvm, 0), vm = __shfl_sync(0xffffffffu, kvm, 16);
        const bool ok = (qn * km <= 10000.f) && (vm <= 16384.f);
        if (!ok) s_slow = 1;
    }
    CK(tk, 14);
    float oacc[2][12];
#pragma unroll
    for (int m = 0; m < 2; m++)
#pragma unroll
        for (int i = 0; i < 12; i++) oacc[m][i] = 0.f;
    __syncthreads();
    const bool slow = s_slow != 0;
    if (wu >= 1 && wu < NCH) fetch_chunk(wu);
    CK(tk, 15);

    const uint64_t dK0 = mkdesc(sK, 128, 256, 0);
    const uint64_t dV0 = mkdesc(sV, 128, 256, 0);
    uint32_t c3f;
    asm volatile("mov.b32 %0, 0x3F003F00;" : "=r"(c3f));
    if (!slow) {
        uint64_t dK = dK0, dV = dV0;
        float s[32];
        fence_regs(oacc[0]); fence_regs(oacc[1]);
        mbar_wait(smem_u32(&bars[0]), 0);
        wg_fence();
        wgmma_rs_n64_z(s, qa[0][0], qa[0][1], qa[0][2], qa[0][3], dK);
        wg_commit();
#pragma unroll 1
        for (int ch = 0; ch < NCH; ch++) {
#pragma unroll
            for (int tt = 0; tt < KCH / 64; tt++) {
#pragma unroll
                for (int m = 0; m < 2; m++) {
                    wg_wait<0>();
                    fence_regs(s);
                    uint32_t p[16];
#pragma unroll
                    for (int i = 0; i < 16; i++) p[i] = is_mufu(i) ? exp_pair_mufu(s[2 * i], s[2 * i + 1]) : exp_pair_fma(s[2 * i], s[2 * i + 1], c3f);
                    if (m == 1 && tt == KCH / 64 - 1) mbar_wait(smem_u32(&bars[ch + 1 < NCH ? ch + 1 : ch]), 0);
                    wg_fence();
#pragma unroll
                    for (int kk = 0; kk < 4; kk++)
                        wgmma_rs_n24_tb(oacc[m], p[4 * kk], p[4 * kk + 1], p[4 * kk + 2], p[4 * kk + 3], dV + (uint64_t)((tt * 4 + kk) * (768 / 16)));
                    wgmma_rs_n64_z(s, qa[1 - m][0], qa[1 - m][1], qa[1 - m][2], qa[1 - m][3], dK + (uint64_t)((tt + m) * (64 * 32 / 16)));
                    wg_commit();
                }
            }
            dK += KCH * 32 / 16;
            dV += (KCH / 16) * (768 / 16);
        }
        wg_wait<0>();
        fence_regs(s);
    } else {
        float mx[2][2] = {{-INFINITY, -INFINITY}, {-INFINITY, -INFINITY}};
#pragma unroll 1
        for (int t = 0; t < S_ / 64; t++) {
            if ((t & 3) == 0) mbar_wait(smem_u32(&bars[t >> 2]), 0);
            const uint64_t dK = dK0 + (uint64_t)(t * 64 * 32 / 16);
            const uint64_t dV = dV0 + (uint64_t)(t * 4 * 768 / 16);
#pragma unroll
            for (int m = 0; m < 2; m++) {
                float s[32];
                wg_fence();
                wgmma_rs_n64_z(s, qa[m][0], qa[m][1], qa[m][2], qa[m][3], dK);
                wg_commit();
                wg_wait<0>();
                fence_regs(s);
                fence_regs(oacc[m]);
                float r0 = mx[m][0], r1 = mx[m][1];
#pragma unroll
                for (int j = 0; j < 8; j++) {
                    r0 = fmaxf(r0, fmaxf(s[4 * j], s[4 * j + 1]));
                    r1 = fmaxf(r1, fmaxf(s[4 * j + 2], s[4 * j + 3]));
                }
                r0 = fmaxf(r0, __shfl_xor_sync(0xffffffffu, r0, 1)); r0 = fmaxf(r0, __shfl_xor_sync(0xffffffffu, r0, 2));
                r1 = fmaxf(r1, __shfl_xor_sync(0xffffffffu, r1, 1)); r1 = fmaxf(r1, __shfl_xor_sync(0xffffffffu, r1, 2));
                const float al0 = ex2(mx[m][0] - r0), al1 = ex2(mx[m][1] - r1);
                mx[m][0] = r0; mx[m][1] = r1;
#pragma unroll
                for (int j = 0; j < 3; j++) {
                    oacc[m][4 * j] *= al0; oacc[m][4 * j + 1] *= al0;
                    oacc[m][4 * j + 2] *= al1; oacc[m][4 * j + 3] *= al1;
                }
                uint32_t p[16];
#pragma unroll
                for (int j = 0; j < 8; j++) {
                    p[2 * j] = pack_bf16(ex2(s[4 * j] - r0), ex2(s[4 * j + 1] - r0));
                    p[2 * j + 1] = pack_bf16(ex2(s[4 * j + 2] - r1), ex2(s[4 * j + 3] - r1));
                }
                fence_regs(oacc[m]);
                wg_fence();
#pragma unroll
                for (int kk = 0; kk < 4; kk++)
                    wgmma_rs_n24_tb(oacc[m], p[4 * kk], p[4 * kk + 1], p[4 * kk + 2], p[4 * kk + 3], dV + (uint64_t)(kk * 768 / 16));
                wg_commit();
                wg_wait<0>();
            }
        }
    }
    fence_regs(oacc[0]); fence_regs(oacc[1]);
    if (tid == 0) TL(tk, 2);
#pragma unroll
    for (int m = 0; m < 2; m++) {
        const float l0 = __shfl_sync(0xffffffffu, oacc[m][8], lane & ~3);
        const float l1 = __shfl_sync(0xffffffffu, oacc[m][10], lane & ~3);
        const float r0 = __fdividef(1.0f, l0), r1 = __fdividef(1.0f, l1);
        stsm_x4(sQ + m * 8192 + qoff, pack_bf16(oacc[m][0] * r0, oacc[m][1] * r0), pack_bf16(oacc[m][2] * r1, oacc[m][3] * r1),
                pack_bf16(oacc[m][4] * r0, oacc[m][5] * r0), pack_bf16(oacc[m][6] * r1, oacc[m][7] * r1));
    }
    fence_async_smem();
    __syncthreads();
    if (wu == 0 && elect_one()) {
        tma2d_store(&mapO, sQ, hg * 64, tb * 128);
        bulk_commit();
        bulk_wait_read();
    }
    if (tid == 0) TL(tk, 3);
}

typedef CUresult (*EncodeFn)(CUtensorMap*, CUtensorMapDataType, cuuint32_t, void*, const cuuint64_t*, const cuuint64_t*, const cuuint32_t*,
                             const cuuint32_t*, CUtensorMapInterleave, CUtensorMapSwizzle, CUtensorMapL2promotion, CUtensorMapFloatOOBfill);

EncodeFn get_encode() {
    static EncodeFn fn = nullptr;
    if (!fn) {
        void* p = nullptr;
        cudaDriverEntryPointQueryResult qr;
        cudaGetDriverEntryPoint("cuTensorMapEncodeTiled", &p, cudaEnableDefault, &qr);
        fn = (EncodeFn)p;
    }
    return fn;
}
CUtensorMap map2d(const void* ptr, uint64_t cols, uint64_t rows, uint32_t bc, uint32_t br, CUtensorMapSwizzle sw) {
    CUtensorMap m;
    cuuint64_t gd[2] = {cols, rows}, gs[1] = {cols * 2};
    cuuint32_t bx[2] = {bc, br}, es[2] = {1, 1};
    get_encode()(&m, CU_TENSOR_MAP_DATA_TYPE_BFLOAT16, 2, (void*)ptr, gd, gs, bx, es, CU_TENSOR_MAP_INTERLEAVE_NONE, sw,
                 L2PROMO, CU_TENSOR_MAP_FLOAT_OOB_FILL_NONE);
    return m;
}
CUtensorMap map3d32(const void* ptr, uint64_t cols, uint64_t rows, uint32_t br, uint32_t nb) {
    CUtensorMap m;
    cuuint64_t gd[3] = {32, rows, cols / 32}, gs[2] = {cols * 2, 64};
    cuuint32_t bx[3] = {32, br, nb}, es[3] = {1, 1, 1};
    get_encode()(&m, CU_TENSOR_MAP_DATA_TYPE_BFLOAT16, 3, (void*)ptr, gd, gs, bx, es, CU_TENSOR_MAP_INTERLEAVE_NONE, CU_TENSOR_MAP_SWIZZLE_64B,
                 L2PROMO, CU_TENSOR_MAP_FLOAT_OOB_FILL_NONE);
    return m;
}

template <typename... KArgs, typename... Args>
void launch(void (*kern)(KArgs...), int grid, int block, int smem, int cluster, bool pdl, Args... args) {
    cudaLaunchConfig_t cfg = {};
    cfg.gridDim = dim3(grid);
    cfg.blockDim = dim3(block);
    cfg.dynamicSmemBytes = smem;
    cfg.stream = cudaStreamPerThread;
    cudaLaunchAttribute at[2];
    int n = 0;
    if (cluster > 1) { at[n].id = cudaLaunchAttributeClusterDimension; at[n].val.clusterDim.x = cluster; at[n].val.clusterDim.y = 1; at[n].val.clusterDim.z = 1; n++; }
    if (pdl) { at[n].id = cudaLaunchAttributeProgrammaticStreamSerialization; at[n].val.programmaticStreamSerializationAllowed = 1; n++; }
    cfg.attrs = at;
    cfg.numAttrs = n;
    cudaLaunchKernelEx(&cfg, kern, KArgs(args)...);
}

template <typename T> void* sym(const T& s) { void* p = nullptr; cudaGetSymbolAddress(&p, s); return p; }

}

extern "C" void kernel_launch(void* const* d_in, const int* in_sizes, int n_in, void* d_out, int out_size) {
    const __nv_bfloat16* x = (const __nv_bfloat16*)d_in[0];
    const __nv_bfloat16* wq = (const __nv_bfloat16*)d_in[1];
    const __nv_bfloat16* wk = (const __nv_bfloat16*)d_in[2];
    const __nv_bfloat16* wv = (const __nv_bfloat16*)d_in[3];
    const __nv_bfloat16* wo = (const __nv_bfloat16*)d_in[4];
    const __nv_bfloat16* w1 = (const __nv_bfloat16*)d_in[6];
    const __nv_bfloat16* w2 = (const __nv_bfloat16*)d_in[7];

    constexpr int SM_QKV = GemmSmem<QKV_STAGES, EPI_QKV>::TOTAL, SM_QKV0 = GemmSmem<QKV_STAGES, EPI_QKV>::TOTAL_SELF;
    static_assert(SM_QKV0 <= 232448, "shared memory");
    constexpr int SM_WO = GemmSmem<WO_STAGES, EPI_RES>::TOTAL, SM_FFN2 = GemmSmem<FFN2_STAGES, EPI_RES>::TOTAL;
    static_assert(SM_WO > 116736 && SM_FFN2 > 116736, "one CTA per SM");
    constexpr int SM_FFN1 = GemmSmem<FFN1_STAGES, EPI_FFN1>::TOTAL;
    cudaFuncSetAttribute(qkv_kernel<false>, cudaFuncAttributeMaxDynamicSharedMemorySize, SM_QKV);
    cudaFuncSetAttribute(qkv_kernel<true>, cudaFuncAttributeMaxDynamicSharedMemorySize, SM_QKV0);
    cudaFuncSetAttribute(res_gemm_kernel<8, WO_STAGES>, cudaFuncAttributeMaxDynamicSharedMemorySize, SM_WO);
    cudaFuncSetAttribute(ffn1_kernel, cudaFuncAttributeMaxDynamicSharedMemorySize, SM_FFN1);
    cudaFuncSetAttribute(res_gemm_kernel<28, FFN2_STAGES>, cudaFuncAttributeMaxDynamicSharedMemorySize, SM_FFN2);
    cudaFuncSetAttribute(attn_kernel, cudaFuncAttributeMaxDynamicSharedMemorySize, ATT_SMEM);
    cudaFuncSetAttribute(qkv_kernel<false>, cudaFuncAttributePreferredSharedMemoryCarveout, 100);
    cudaFuncSetAttribute(qkv_kernel<true>, cudaFuncAttributePreferredSharedMemoryCarveout, 100);
    cudaFuncSetAttribute(res_gemm_kernel<8, WO_STAGES>, cudaFuncAttributePreferredSharedMemoryCarveout, 100);
    cudaFuncSetAttribute(ffn1_kernel, cudaFuncAttributePreferredSharedMemoryCarveout, 100);
    cudaFuncSetAttribute(res_gemm_kernel<28, FFN2_STAGES>, cudaFuncAttributePreferredSharedMemoryCarveout, 100);
    cudaFuncSetAttribute(attn_kernel, cudaFuncAttributePreferredSharedMemoryCarveout, 100);

    void *q = sym(g_q), *o = sym(g_o), *x1 = sym(g_x1), *x2 = sym(g_x2), *x3 = sym(g_x3), *h = sym(g_h);
    float2* stats = (float2*)sym(g_stats);
    const void* xs[5] = {x, x1, x2, x3, d_out};

    const CUtensorMapSwizzle SW128 = CU_TENSOR_MAP_SWIZZLE_128B, SW64 = CU_TENSOR_MAP_SWIZZLE_64B;
    const CUtensorMap mWq = map3d32(wq, D_, D_, 64, 2);
    const CUtensorMap mWo = map2d(wo, D_, D_, 64, 64, SW128);
    const CUtensorMap mW1a = map3d32(w1, F_, D_, F1_BK, 4), mW1b = map3d32(w1, F_, D_, F1_BK, 3);
    const CUtensorMap mW2 = map2d(w2, D_, F_, 64, 64, SW128);
    const CUtensorMap mQ = map2d(q, D_, S_, 64, 64, SW128);
    const CUtensorMap mQa = map2d(q, D_, S_, 64, 128, SW128), mOs = map2d(o, D_, S_, 64, 128, SW128);
    const CUtensorMap mHst = map2d(h, F_, S_, 32, 16, SW64);
    CUtensorMap mXa[4], mXf[4], mXr[4], mXs[5];
    for (int i = 0; i < 4; i++) {
        mXa[i] = map2d(xs[i], D_, S_, 64, QKV_MC ? 64 : 128, SW128);
        mXf[i] = F1_BK == 64 ? map2d(xs[i], D_, S_, 64, 128, SW128) : map2d(xs[i], D_, S_, 32, 128, SW64);
        mXr[i] = map2d(xs[i], D_, S_, 64, 128, SW128);
    }
    for (int i = 0; i < 5; i++) mXs[i] = map2d(xs[i], D_, S_, 64, 64, SW128);
    const CUtensorMap mOa = map2d(o, D_, S_, 64, WO_MC ? 64 : 128, SW128);
    const CUtensorMap mHa = map2d(h, F_, S_, 64, F2_MC ? 64 : 128, SW128);

    for (int layer = 0; layer < 2; layer++) {
        const int xi = layer * 2;
        GemmParams p;
        p.wkv = wk; p.wv = wv;
        p.stats_in = stats + (size_t)xi * 8 * S_; p.stats_out = nullptr; p.tk = 1 + 5 * layer;
        if (layer == 0) launch(qkv_kernel<true>, 128, 640, SM_QKV0, QKV_MC ? 2 : 1, false, mXa[xi], mWq, mQ, p);
        else launch(qkv_kernel<false>, 128, 288, SM_QKV, QKV_MC ? 2 : 1, true, mXa[xi], mWq, mQ, p);
        launch(attn_kernel, layer == 0 ? 128 + SIDE_CTAS : 128, 512, ATT_SMEM, 1, true, mQa, mOs, wo, w1, w2, 2 + 5 * layer);
        p.stats_in = nullptr; p.stats_out = stats + (size_t)(xi + 1) * 8 * S_; p.tk = 3 + 5 * layer;
        launch(res_gemm_kernel<8, WO_STAGES>, 128, 288, SM_WO, WO_MC ? 2 : 1, true, mOa, mWo, mXr[xi], mXs[xi + 1], p);
        p.stats_in = stats + (size_t)(xi + 1) * 8 * S_; p.stats_out = nullptr; p.tk = 4 + 5 * layer;
        launch(ffn1_kernel, 128, F1_INLINE ? 256 : 288, SM_FFN1, F1_MC ? 2 : 1, true, mXf[xi + 1], mW1a, mW1b, mHst, p);
        p.stats_in = nullptr; p.stats_out = layer == 0 ? stats + (size_t)2 * 8 * S_ : nullptr; p.tk = 5 + 5 * layer;
        launch(res_gemm_kernel<28, FFN2_STAGES>, 128, 288, SM_FFN2, F2_MC ? 2 : 1, true, mHa, mW2, mXr[xi + 1], mXs[xi + 2], p);
    }
}
```

```cpp
#include <cuda_runtime.h>
#include <cuda_bf16.h>
#include <cuda.h>
#include <stdint.h>

namespace {

constexpr int S_ = 2048, D_ = 512, F_ = 1792;

__device__ __align__(1024) __nv_bfloat16 g_q[S_ * D_];
__device__ __align__(1024) __nv_bfloat16 g_o[S_ * D_];
__device__ __align__(1024) __nv_bfloat16 g_x1[S_ * D_];
__device__ __align__(1024) __nv_bfloat16 g_x2[S_ * D_];
__device__ __align__(1024) __nv_bfloat16 g_x3[S_ * D_];
__device__ __align__(1024) __nv_bfloat16 g_h[S_ * F_];
__device__ __align__(1024) uint8_t g_kimg[S_ * 32];
__device__ __align__(1024) uint8_t g_vimg[(S_ / 16) * 768];
__device__ __align__(1024) float2 g_stats[4][8 * S_];
__device__ __align__(16) float g_cs_q[D_];
__device__ __align__(16) float g_cs_kv[32];
__device__ __align__(16) float g_cs_1[F_];
__device__ __align__(16) float g_kvmax[32];

#define TL(k, slot)
#define CK(k, i)
#define CP(k, i)

__device__ __forceinline__ uint32_t smem_u32(const void* p) { return (uint32_t)__cvta_generic_to_shared(p); }
__device__ __forceinline__ void mbar_init(uint32_t bar, uint32_t cnt) {
    asm volatile("mbarrier.init.shared::cta.b64 [%0], %1;" ::"r"(bar), "r"(cnt));
}
__device__ __forceinline__ void mbar_expect_tx(uint32_t bar, uint32_t bytes) {
    asm volatile("mbarrier.arrive.expect_tx.shared::cta.b64 _, [%0], %1;" ::"r"(bar), "r"(bytes) : "memory");
}
__device__ __forceinline__ void mbar_arrive(uint32_t bar) {
    asm volatile("mbarrier.arrive.shared::cta.b64 _, [%0];" ::"r"(bar) : "memory");
}
__device__ __forceinline__ void mbar_arrive_remote(uint32_t bar, uint32_t cta) {
    asm volatile("{\n.reg .b32 ra;\nmapa.shared::cluster.u32 ra, %0, %1;\nmbarrier.arrive.shared::cluster.b64 _, [ra];\n}" ::"r"(bar), "r"(cta) : "memory");
}
__device__ __forceinline__ void mbar_wait(uint32_t bar, uint32_t parity) {
    asm volatile("{\n.reg .pred p;\nWAIT_%=:\nmbarrier.try_wait.parity.shared::cta.b64 p, [%0], %1;\n@p bra DONE_%=;\nbra WAIT_%=;\nDONE_%=:\n}" ::"r"(bar), "r"(parity) : "memory");
}
__device__ __forceinline__ void bulk_load(uint32_t dst, const void* src, uint32_t bytes, uint32_t bar) {
    asm volatile("cp.async.bulk.shared::cluster.global.mbarrier::complete_tx::bytes [%0], [%1], %2, [%3];" ::"r"(dst), "l"(src), "r"(bytes), "r"(bar) : "memory");
}
__device__ __forceinline__ void tma2d(uint32_t dst, const CUtensorMap* m, int c0, int c1, uint32_t bar) {
    asm volatile("cp.async.bulk.tensor.2d.shared::cluster.global.mbarrier::complete_tx::bytes [%0], [%1, {%3, %4}], [%2];" ::"r"(dst), "l"(m), "r"(bar), "r"(c0), "r"(c1) : "memory");
}
__device__ __forceinline__ void tma3d(uint32_t dst, const CUtensorMap* m, int c0, int c1, int c2, uint32_t bar) {
    asm volatile("cp.async.bulk.tensor.3d.shared::cluster.global.mbarrier::complete_tx::bytes [%0], [%1, {%3, %4, %5}], [%2];" ::"r"(dst), "l"(m), "r"(bar), "r"(c0), "r"(c1), "r"(c2) : "memory");
}
__device__ __forceinline__ void tma3d_mc(uint32_t dst, const CUtensorMap* m, int c0, int c1, int c2, uint32_t bar, uint16_t mask) {
    asm volatile("cp.async.bulk.tensor.3d.shared::cluster.global.mbarrier::complete_tx::bytes.multicast::cluster [%0], [%1, {%3, %4, %5}], [%2], %6;" ::"r"(dst), "l"(m), "r"(bar), "r"(c0), "r"(c1), "r"(c2), "h"(mask) : "memory");
}
__device__ __forceinline__ void tma2d_store(const CUtensorMap* m, uint32_t src, int c0, int c1) {
    asm volatile("cp.async.bulk.tensor.2d.global.shared::cta.bulk_group [%0, {%2, %3}], [%1];" ::"l"(m), "r"(src), "r"(c0), "r"(c1) : "memory");
}
__device__ __forceinline__ void bulk_commit() { asm volatile("cp.async.bulk.commit_group;" ::: "memory"); }
__device__ __forceinline__ void bulk_wait_read() { asm volatile("cp.async.bulk.wait_group.read 0;" ::: "memory"); }
__device__ __forceinline__ void prefetch_tmap(const CUtensorMap* m) { asm volatile("prefetch.tensormap [%0];" ::"l"(m) : "memory"); }
__device__ __forceinline__ void fence_async_smem() { asm volatile("fence.proxy.async.shared::cta;" ::: "memory"); }
__device__ __forceinline__ void fence_mbar_init() { asm volatile("fence.mbarrier_init.release.cluster;" ::: "memory"); }
__device__ __forceinline__ void cluster_sync() { asm volatile("barrier.cluster.arrive.release.aligned;\nbarrier.cluster.wait.acquire.aligned;" ::: "memory"); }
__device__ __forceinline__ uint32_t cluster_rank() { uint32_t r; asm volatile("mov.u32 %0, %%cluster_ctarank;" : "=r"(r)); return r; }
__device__ __forceinline__ void pdl_wait() { asm volatile("griddepcontrol.wait;" ::: "memory"); }
__device__ __forceinline__ void pdl_launch() { asm volatile("griddepcontrol.launch_dependents;" ::: "memory"); }
__device__ __forceinline__ bool elect_one() {
    uint32_t p;
    asm volatile("{\n.reg .pred p;\nelect.sync _|p, 0xffffffff;\nselp.b32 %0, 1, 0, p;\n}" : "=r"(p));
    return p != 0;
}
__device__ __forceinline__ void named_bar(int id, int n) { asm volatile("bar.sync %0, %1;" ::"r"(id), "r"(n) : "memory"); }

__device__ __forceinline__ void wg_fence() { asm volatile("wgmma.fence.sync.aligned;" ::: "memory"); }
__device__ __forceinline__ void wg_commit() { asm volatile("wgmma.commit_group.sync.aligned;" ::: "memory"); }
template <int N> __device__ __forceinline__ void wg_wait() { asm volatile("wgmma.wait_group.sync.aligned %0;" ::"n"(N) : "memory"); }
template <int N> __device__ __forceinline__ void fence_regs(float (&d)[N]) {
#pragma unroll
    for (int i = 0; i < N; i++) asm volatile("" : "+f"(d[i])::"memory");
}
__device__ __forceinline__ uint64_t mkdesc(uint32_t addr, uint32_t lbo, uint32_t sbo, uint32_t swz) {
    uint64_t d = 0;
    d |= (uint64_t)((addr & 0x3FFFF) >> 4);
    d |= (uint64_t)((lbo & 0x3FFFF) >> 4) << 16;
    d |= (uint64_t)((sbo & 0x3FFFF) >> 4) << 32;
    d |= (uint64_t)swz << 62;
    return d;
}
__device__ __forceinline__ void ldsm_x4(uint32_t& r0, uint32_t& r1, uint32_t& r2, uint32_t& r3, uint32_t addr) {
    asm volatile("ldmatrix.sync.aligned.m8n8.x4.shared.b16 {%0,%1,%2,%3}, [%4];" : "=r"(r0), "=r"(r1), "=r"(r2), "=r"(r3) : "r"(addr) : "memory");
}
__device__ __forceinline__ void stsm_x4(uint32_t addr, uint32_t r0, uint32_t r1, uint32_t r2, uint32_t r3) {
    asm volatile("stmatrix.sync.aligned.m8n8.x4.shared.b16 [%0], {%1,%2,%3,%4};" ::"r"(addr), "r"(r0), "r"(r1), "r"(r2), "r"(r3) : "memory");
}
__device__ __forceinline__ uint32_t pack_bf16(float lo, float hi) {
    uint32_t r;
    asm("cvt.rn.bf16x2.f32 %0, %1, %2;" : "=r"(r) : "f"(hi), "f"(lo));
    return r;
}
__device__ __forceinline__ float bf_lo(uint32_t v) { return __uint_as_float(v << 16); }
__device__ __forceinline__ float bf_hi(uint32_t v) { return __uint_as_float(v & 0xFFFF0000u); }

#define WG_REGS_4(o) "+f"(d[o]), "+f"(d[o + 1]), "+f"(d[o + 2]), "+f"(d[o + 3])
#define WG_REGS_8(o) WG_REGS_4(o), WG_REGS_4(o + 4)
#define WG_REGS_16(o) WG_REGS_8(o), WG_REGS_8(o + 8)
#define WG_REGS_32(o) WG_REGS_16(o), WG_REGS_16(o + 16)

__device__ __forceinline__ void wgmma_ss_n80_tb(float (&d)[40], uint64_t dA, uint64_t dB, int sc) {
    asm volatile("{\n.reg .pred p;\nsetp.ne.b32 p, %42, 0;\n"
                 "wgmma.mma_async.sync.aligned.m64n80k16.f32.bf16.bf16 "
                 "{%0,%1,%2,%3,%4,%5,%6,%7,%8,%9,%10,%11,%12,%13,%14,%15,%16,%17,%18,%19,%20,%21,%22,%23,%24,%25,%26,%27,%28,%29,%30,%31,"
                 "%32,%33,%34,%35,%36,%37,%38,%39}, %40, %41, p, 1, 1, 0, 1;\n}\n"
                 : WG_REGS_32(0), WG_REGS_8(32) : "l"(dA), "l"(dB), "r"(sc));
}
__device__ __forceinline__ void wgmma_ss_n64_tb(float (&d)[32], uint64_t dA, uint64_t dB, int sc) {
    asm volatile("{\n.reg .pred p;\nsetp.ne.b32 p, %34, 0;\n"
                 "wgmma.mma_async.sync.aligned.m64n64k16.f32.bf16.bf16 "
                 "{%0,%1,%2,%3,%4,%5,%6,%7,%8,%9,%10,%11,%12,%13,%14,%15,%16,%17,%18,%19,%20,%21,%22,%23,%24,%25,%26,%27,%28,%29,%30,%31}, "
                 "%32, %33, p, 1, 1, 0, 1;\n}\n"
                 : WG_REGS_32(0) : "l"(dA), "l"(dB), "r"(sc));
}
__device__ __forceinline__ void wgmma_ss_n224_tb(float (&d)[112], uint64_t dA, uint64_t dB, int sc) {
    asm volatile("{\n.reg .pred p;\nsetp.ne.b32 p, %114, 0;\n"
                 "wgmma.mma_async.sync.aligned.m64n224k16.f32.bf16.bf16 "
                 "{%0,%1,%2,%3,%4,%5,%6,%7,%8,%9,%10,%11,%12,%13,%14,%15,%16,%17,%18,%19,%20,%21,%22,%23,%24,%25,%26,%27,%28,%29,%30,%31,"
                 "%32,%33,%34,%35,%36,%37,%38,%39,%40,%41,%42,%43,%44,%45,%46,%47,%48,%49,%50,%51,%52,%53,%54,%55,%56,%57,%58,%59,%60,%61,%62,%63,"
                 "%64,%65,%66,%67,%68,%69,%70,%71,%72,%73,%74,%75,%76,%77,%78,%79,%80,%81,%82,%83,%84,%85,%86,%87,%88,%89,%90,%91,%92,%93,%94,%95,"
                 "%96,%97,%98,%99,%100,%101,%102,%103,%104,%105,%106,%107,%108,%109,%110,%111}, "
                 "%112, %113, p, 1, 1, 0, 1;\n}\n"
                 : WG_REGS_32(0), WG_REGS_32(32), WG_REGS_32(64), WG_REGS_16(96) : "l"(dA), "l"(dB), "r"(sc));
}
template <int BN> __device__ __forceinline__ void wgmma_ss_tb(float (&d)[BN / 2], uint64_t dA, uint64_t dB, int sc) {
    if constexpr (BN == 64) wgmma_ss_n64_tb(d, dA, dB, sc);
    else if constexpr (BN == 80) wgmma_ss_n80_tb(d, dA, dB, sc);
    else wgmma_ss_n224_tb(d, dA, dB, sc);
}
__device__ __forceinline__ void wgmma_rs_n64_tb(float (&d)[32], uint32_t a, uint64_t dB, int sc) {
    asm volatile("{\n.reg .pred p;\nsetp.ne.b32 p, %34, 0;\n"
                 "wgmma.mma_async.sync.aligned.m64n64k16.f32.bf16.bf16 "
                 "{%0,%1,%2,%3,%4,%5,%6,%7,%8,%9,%10,%11,%12,%13,%14,%15,%16,%17,%18,%19,%20,%21,%22,%23,%24,%25,%26,%27,%28,%29,%30,%31}, "
                 "{%32,%32,%32,%32}, %33, p, 1, 1, 1;\n}\n"
                 : WG_REGS_32(0) : "r"(a), "l"(dB), "r"(sc));
}
__device__ __forceinline__ void wgmma_rs_n80_tb(float (&d)[40], uint32_t a, uint64_t dB, int sc) {
    asm volatile("{\n.reg .pred p;\nsetp.ne.b32 p, %42, 0;\n"
                 "wgmma.mma_async.sync.aligned.m64n80k16.f32.bf16.bf16 "
                 "{%0,%1,%2,%3,%4,%5,%6,%7,%8,%9,%10,%11,%12,%13,%14,%15,%16,%17,%18,%19,%20,%21,%22,%23,%24,%25,%26,%27,%28,%29,%30,%31,"
                 "%32,%33,%34,%35,%36,%37,%38,%39}, {%40,%40,%40,%40}, %41, p, 1, 1, 1;\n}\n"
                 : WG_REGS_32(0), WG_REGS_8(32) : "r"(a), "l"(dB), "r"(sc));
}
template <int BN> __device__ __forceinline__ void wgmma_rs_ones(float (&d)[BN / 2], uint64_t dB, int sc) {
    if constexpr (BN == 80) wgmma_rs_n80_tb(d, 0x3F803F80u, dB, sc);
    else if constexpr (BN == 64) wgmma_rs_n64_tb(d, 0x3F803F80u, dB, sc);
}
__device__ __forceinline__ void wgmma_rs_n64_z(float (&d)[32], uint32_t a0, uint32_t a1, uint32_t a2, uint32_t a3, uint64_t dB) {
    asm volatile("{\n.reg .pred p;\nsetp.ne.b32 p, 0, 0;\n"
                 "wgmma.mma_async.sync.aligned.m64n64k16.f32.bf16.bf16 "
                 "{%0,%1,%2,%3,%4,%5,%6,%7,%8,%9,%10,%11,%12,%13,%14,%15,%16,%17,%18,%19,%20,%21,%22,%23,%24,%25,%26,%27,%28,%29,%30,%31}, "
                 "{%32,%33,%34,%35}, %36, p, 1, 1, 0;\n}\n"
                 : "=f"(d[0]), "=f"(d[1]), "=f"(d[2]), "=f"(d[3]), "=f"(d[4]), "=f"(d[5]), "=f"(d[6]), "=f"(d[7]),
                   "=f"(d[8]), "=f"(d[9]), "=f"(d[10]), "=f"(d[11]), "=f"(d[12]), "=f"(d[13]), "=f"(d[14]), "=f"(d[15]),
                   "=f"(d[16]), "=f"(d[17]), "=f"(d[18]), "=f"(d[19]), "=f"(d[20]), "=f"(d[21]), "=f"(d[22]), "=f"(d[23]),
                   "=f"(d[24]), "=f"(d[25]), "=f"(d[26]), "=f"(d[27]), "=f"(d[28]), "=f"(d[29]), "=f"(d[30]), "=f"(d[31])
                 : "r"(a0), "r"(a1), "r"(a2), "r"(a3), "l"(dB));
}
__device__ __forceinline__ void wgmma_rs_n24_tb(float (&d)[12], uint32_t a0, uint32_t a1, uint32_t a2, uint32_t a3, uint64_t dB) {
    asm volatile("{\n.reg .pred p;\nsetp.eq.b32 p, 0, 0;\n"
                 "wgmma.mma_async.sync.aligned.m64n24k16.f32.bf16.bf16 "
                 "{%0,%1,%2,%3,%4,%5,%6,%7,%8,%9,%10,%11}, {%12,%13,%14,%15}, %16, p, 1, 1, 1;\n}\n"
                 : WG_REGS_8(0), WG_REGS_4(8) : "r"(a0), "r"(a1), "r"(a2), "r"(a3), "l"(dB));
}

constexpr int SIDE_CTAS = 4;
__device__ __forceinline__ void side_job(int cta, float* red  , const __nv_bfloat16* __restrict__ wo,
                                         const __nv_bfloat16* __restrict__ w1, const __nv_bfloat16* __restrict__ w2) {
    const int tid = threadIdx.x, warp = tid >> 5, lane = tid & 31;
    for (int line = cta * 512 + tid; line < 18432; line += SIDE_CTAS * 512) {
        const char* p = line < 4096 ? (const char*)wo + (size_t)line * 128 : (const char*)w2 + (size_t)(line - 4096) * 128;
        asm volatile("prefetch.global.L2 [%0];" ::"l"(p));
    }
    const int rg = lane >> 3, c8 = lane & 7;
    for (int slab = cta; slab < F_ / 64; slab += SIDE_CTAS) {
        const __nv_bfloat16* base = w1 + slab * 64 + c8 * 8;
        uint4 v[8];
#pragma unroll
        for (int i = 0; i < 8; i++) v[i] = __ldg((const uint4*)(base + (size_t)(warp * 32 + rg + 4 * i) * F_));
        float acc[8];
#pragma unroll
        for (int i = 0; i < 8; i++) acc[i] = 0.f;
#pragma unroll
        for (int i = 0; i < 8; i++) {
            acc[0] += bf_lo(v[i].x); acc[1] += bf_hi(v[i].x); acc[2] += bf_lo(v[i].y); acc[3] += bf_hi(v[i].y);
            acc[4] += bf_lo(v[i].z); acc[5] += bf_hi(v[i].z); acc[6] += bf_lo(v[i].w); acc[7] += bf_hi(v[i].w);
        }
#pragma unroll
        for (int i = 0; i < 8; i++) {
            acc[i] += __shfl_xor_sync(0xffffffffu, acc[i], 8);
            acc[i] += __shfl_xor_sync(0xffffffffu, acc[i], 16);
        }
        if (rg == 0) {
#pragma unroll
            for (int i = 0; i < 8; i++) red[warp * 64 + c8 * 8 + i] = acc[i];
        }
        __syncthreads();
        if (tid < 64) {
            float s = 0.f;
#pragma unroll
            for (int i = 0; i < 16; i++) s += red[i * 64 + tid];
            g_cs_1[slab * 64 + tid] = s;
        }
        __syncthreads();
    }
}

enum { EPI_QKV = 0, EPI_RES = 1, EPI_FFN1 = 2 };

struct GemmParams {
    const float2* stats_in;
    float2* stats_out;
    const __nv_bfloat16* wkv;
    const __nv_bfloat16* wv;
    int tk;
};

template <int BK_, int NBLK> struct Geo {
    static constexpr int BK = BK_, A_BYTES = 128 * BK * 2, A_SWZ = BK == 64 ? 1 : 2, A_SBO = BK * 16;
    static constexpr int BLK = BK * 64;
    static constexpr int B_BYTES = NBLK * BLK, B_SWZ = 2, B_LBO = BLK, B_SBO = 512, B_KSTEP = 1024;
};
template <> struct Geo<64, 0> {
    static constexpr int BK = 64, A_BYTES = 128 * 128, A_SWZ = 1, A_SBO = 1024, BLK = 8192;
    static constexpr int B_BYTES = 64 * 128, B_SWZ = 1, B_LBO = 8192, B_SBO = 1024, B_KSTEP = 2048;
};
#define F1_BK 32
template <int EPI> struct EpiGeo;
template <> struct EpiGeo<EPI_QKV> { using G = Geo<64, 3>; };
template <> struct EpiGeo<EPI_RES> { using G = Geo<64, 0>; };
template <> struct EpiGeo<EPI_FFN1> { using G = Geo<F1_BK, 7>; };

template <int STAGES, int EPI> struct GemmSmem {
    using G = typename EpiGeo<EPI>::G;
    static constexpr int STAGE = G::A_BYTES + G::B_BYTES;
    static constexpr int AUX_OFF = STAGES * STAGE;
    static constexpr int TOTAL = AUX_OFF + 1152;
    static constexpr int TOTAL_SELF = AUX_OFF + 704 + 1024;
};

struct RowStatRaw { float2 a0, a1, b0, b1; };
__device__ __forceinline__ RowStatRaw load_row_stats(const float2* __restrict__ st, int row0, int c) {
    RowStatRaw r;
    r.a0 = st[(2 * c) * S_ + row0]; r.a1 = st[(2 * c + 1) * S_ + row0];
    r.b0 = st[(2 * c) * S_ + row0 + 8]; r.b1 = st[(2 * c + 1) * S_ + row0 + 8];
    return r;
}
__device__ __forceinline__ void finish_row_stats(const RowStatRaw& r, float& mean0, float& rstd0, float& mean1, float& rstd1) {
    float sa = r.a0.x + r.a1.x, sb = r.b0.x + r.b1.x;
    sa += __shfl_xor_sync(0xffffffffu, sa, 1); sa += __shfl_xor_sync(0xffffffffu, sa, 2);
    sb += __shfl_xor_sync(0xffffffffu, sb, 1); sb += __shfl_xor_sync(0xffffffffu, sb, 2);
    mean0 = sa * 0.125f; mean1 = sb * 0.125f;
    float ma = r.a0.y + r.a1.y + 64.f * ((r.a0.x - mean0) * (r.a0.x - mean0) + (r.a1.x - mean0) * (r.a1.x - mean0));
    float mb = r.b0.y + r.b1.y + 64.f * ((r.b0.x - mean1) * (r.b0.x - mean1) + (r.b1.x - mean1) * (r.b1.x - mean1));
    ma += __shfl_xor_sync(0xffffffffu, ma, 1); ma += __shfl_xor_sync(0xffffffffu, ma, 2);
    mb += __shfl_xor_sync(0xffffffffu, mb, 1); mb += __shfl_xor_sync(0xffffffffu, mb, 2);
    rstd0 = 1.0f / sqrtf(ma * (1.f / 512.f) + 1e-5f);
    rstd1 = 1.0f / sqrtf(mb * (1.f / 512.f) + 1e-5f);
}

template <int BN, int KB, int STAGES, int EPI, bool MC, bool SELF = false>
__device__ __forceinline__ void gemm_body(const CUtensorMap* mapA, const CUtensorMap* mapB, const CUtensorMap* mapB2, const CUtensorMap* mapR,
                                          const CUtensorMap* mapC, const GemmParams& prm, int tile_m, int tile_n, uint8_t* smem_raw) {
    using SM = GemmSmem<STAGES, EPI>;
    using G = typename SM::G;
    constexpr bool XKV = BN == 80;
    constexpr int TN = EPI == EPI_QKV ? 64 : BN;
    CP(prm.tk, 0);
    pdl_launch();
    const uint32_t sbase = smem_u32(smem_raw);
    if (sbase & 1023) __trap();
    uint8_t* sgen = smem_raw;
    const uint32_t bar_full = sbase + SM::AUX_OFF, bar_empty = bar_full + 8 * STAGES;
    float* s_cs = (float*)(sgen + SM::AUX_OFF + 256);
    float* s_row = (float*)(sgen + SM::AUX_OFF + 704);
    float* s_red = (float*)(sgen + SM::AUX_OFF + 640);
    const int tid = threadIdx.x, lane = tid & 31;
    const int warp = __shfl_sync(0xffffffffu, tid >> 5, 0);
    const uint32_t rank = MC ? cluster_rank() : 0;
    if (tid == 0) TL(prm.tk, 0);

    if (warp == 8 && elect_one()) {
#pragma unroll
        for (int s = 0; s < STAGES; s++) { mbar_init(bar_full + 8 * s, 1); mbar_init(bar_empty + 8 * s, MC ? 4 : 2); }
        fence_mbar_init();
    }
    if (warp == 1 && elect_one()) { prefetch_tmap(mapB); prefetch_tmap(mapA); prefetch_tmap(mapC); }
    CP(prm.tk, 1);
    __syncthreads();
    CP(prm.tk, 2);
    if (MC) asm volatile("barrier.cluster.arrive.relaxed.aligned;" ::: "memory");
    auto cluster_wait = [&]() { if (MC) asm volatile("barrier.cluster.wait.acquire.aligned;" ::: "memory"); };

    const int m0 = tile_m * 128, n0 = tile_n * TN;
    constexpr uint32_t STAGE_TX = G::A_BYTES + (EPI == EPI_QKV ? 2 * G::BLK : G::B_BYTES);
    auto loadB = [&](int kb, int s) {
        const uint32_t dst = sbase + s * SM::STAGE + G::A_BYTES, bar = bar_full + 8 * s;
        if constexpr (EPI == EPI_RES) {
            tma2d(dst, mapB, n0, kb * 64, bar);
        } else if constexpr (EPI == EPI_QKV) {
            tma3d(dst, mapB, 0, kb * G::BK, tile_n * 2, bar);
        } else {
            if constexpr (MC) {
                if (rank == 0) tma3d_mc(dst, mapB, 0, kb * G::BK, tile_n * 7, bar, 3);
                else tma3d_mc(dst + 4 * G::BLK, mapB2, 0, kb * G::BK, tile_n * 7 + 4, bar, 3);
            } else {
                tma3d(dst, mapB, 0, kb * G::BK, tile_n * 7, bar);
                tma3d(dst + 4 * G::BLK, mapB2, 0, kb * G::BK, tile_n * 7 + 4, bar);
            }
        }
    };
    auto loadA = [&](int kb, int s) {
        const uint32_t dst = sbase + s * SM::STAGE, bar = bar_full + 8 * s;
        tma2d(dst, mapA, kb * G::BK, m0, bar);
    };
    constexpr int PRE = STAGES < KB ? STAGES : KB;
    constexpr int PRE_B = 1;
    auto prologue_loads = [&]() {
        if (elect_one()) {
#pragma unroll
            for (int kb = 0; kb < PRE; kb++) mbar_expect_tx(bar_full + 8 * kb, STAGE_TX);
        }
        CP(prm.tk, 3);
        cluster_wait();
        CP(prm.tk, 4);
        if (elect_one()) {
#pragma unroll
            for (int kb = 0; kb < PRE_B; kb++) loadB(kb, kb);
        }
        CP(prm.tk, 5);
        if (!SELF) pdl_wait();
        CP(prm.tk, 6);
        if (elect_one()) {
#pragma unroll
            for (int kb = 0; kb < PRE; kb++) {
                loadA(kb, kb);
                if (kb + PRE_B < PRE) loadB(kb + PRE_B, kb + PRE_B);
            }
            if constexpr (EPI == EPI_RES && KB < STAGES) {
                mbar_expect_tx(bar_full + 8 * KB, 16384);
                tma2d(sbase + KB * SM::STAGE, mapR, n0, m0, bar_full + 8 * KB);
            }
        }
    };
    if (SELF && warp >= 8) {
        if (warp == 8) prologue_loads();
        static_assert(!SELF || (STAGES >= KB && EPI == EPI_QKV), "SELF needs every k block resident");
        if ((warp >> 2) == 3) {
            float csum[BN / 2];
            const uint64_t dB0 = mkdesc(sbase + G::A_BYTES, G::B_LBO, G::B_SBO, G::B_SWZ);
            if constexpr (XKV) named_bar(6, 384);
#pragma unroll 1
            for (int kb = 0; kb < KB; kb++) {
                mbar_wait(bar_full + 8 * kb, 0);
                const uint64_t dB = dB0 + (uint64_t)(kb * (SM::STAGE >> 4));
                wg_fence();
#pragma unroll
                for (int k = 0; k < G::BK / 16; k++) {
                    if constexpr (SELF) wgmma_rs_ones<BN>(csum, dB + (uint64_t)(k * (G::B_KSTEP >> 4)), (kb | k) != 0);
                }
                wg_commit();
            }
            wg_wait<0>();
            fence_regs(csum);
            if (warp == 12 && lane < 4) {
#pragma unroll
                for (int j = 0; j < BN / 8; j++) {
                    const float2 v = make_float2(csum[4 * j], csum[4 * j + 1]);
                    *(float2*)(s_cs + 8 * j + 2 * lane) = v;
                    if (tile_m == 0) {
                        if (j < 8) *(float2*)(g_cs_q + n0 + 8 * j + 2 * lane) = v;
                        else *(float2*)(g_cs_kv + tile_n * 16 + 8 * (j - 8) + 2 * lane) = v;
                    }
                }
            }
        } else {
            const int t = (warp < 12 ? warp - 8 : warp - 12) * 32 + lane;
            float ss[4] = {0.f, 0.f, 0.f, 0.f}, sq[4] = {0.f, 0.f, 0.f, 0.f};
#pragma unroll 1
            for (int kb = 0; kb < KB; kb++) {
                mbar_wait(bar_full + 8 * kb, 0);
                const uint32_t arow = sbase + kb * SM::STAGE + (t >> 1) * 128;
                uint32_t w[4][4];
#pragma unroll
                for (int j = 0; j < 4; j++)
                    asm volatile("ld.shared.v4.u32 {%0,%1,%2,%3}, [%4];" : "=r"(w[j][0]), "=r"(w[j][1]), "=r"(w[j][2]), "=r"(w[j][3])
                                 : "r"(arow + (((2 * j + (t & 1) + 2 * ((t >> 1) & 3)) & 7) << 4)));
#pragma unroll
                for (int j = 0; j < 4; j++)
#pragma unroll
                    for (int i = 0; i < 4; i++) {
                        const float lo = bf_lo(w[j][i]), hi = bf_hi(w[j][i]);
                        ss[i] += lo + hi;
                        sq[i] = fmaf(lo, lo, fmaf(hi, hi, sq[i]));
                    }
            }
            float tsum = (ss[0] + ss[1]) + (ss[2] + ss[3]), tsq = (sq[0] + sq[1]) + (sq[2] + sq[3]);
            tsum += __shfl_xor_sync(0xffffffffu, tsum, 1);
            tsq += __shfl_xor_sync(0xffffffffu, tsq, 1);
            if ((t & 1) == 0) {
                const float md = tsum * (1.f / 512.f);
                const float var = fmaxf(tsq * (1.f / 512.f) - md * md, 0.f);
                *(float2*)(s_row + t) = make_float2(md, 1.0f / sqrtf(var + 1e-5f));
            }
        }
        named_bar(4, 640);
    } else if (warp == 8) {
        prologue_loads();
        int s = PRE % STAGES, ph = (PRE / STAGES) & 1;
#pragma unroll 1
        for (int kb = PRE; kb < KB; kb++) {
            mbar_wait(bar_empty + 8 * s, ph ^ 1);
            if (elect_one()) {
                mbar_expect_tx(bar_full + 8 * s, STAGE_TX);
                loadB(kb, s);
                loadA(kb, s);
            }
            if (++s == STAGES) { s = 0; ph ^= 1; }
        }
        if constexpr (EPI == EPI_RES && KB >= STAGES) {
            mbar_wait(bar_empty + 8 * s, ph ^ 1);
            if (elect_one()) {
                mbar_expect_tx(bar_full + 8 * s, 16384);
                tma2d(sbase + s * SM::STAGE, mapR, n0, m0, bar_full + 8 * s);
            }
        }
    } else {
        cluster_wait();
        const int wg = warp >> 2, g = lane >> 2, c = lane & 3;
        const int rloc = wg * 64 + (warp & 3) * 16 + g;
        const int row0 = m0 + rloc;
        float mean0 = 0.f, rstd0 = 1.f, mean1 = 0.f, rstd1 = 1.f;
        if constexpr (XKV) {
            static_assert(!XKV || STAGES >= KB, "the K / V weight block must stay resident");
            const __nv_bfloat16* wsrc = tile_n == 0 ? prm.wkv : prm.wv;
            uint4 v[4];
#pragma unroll
            for (int i = 0; i < 4; i++) v[i] = __ldg((const uint4*)wsrc + tid + 256 * i);
#pragma unroll
            for (int i = 0; i < 4; i++) {
                const int idx = tid + 256 * i, k = idx >> 1, kr = k & 63;
                const uint32_t dst = sbase + (k >> 6) * SM::STAGE + G::A_BYTES + 2 * G::BLK + kr * 64 + (((idx & 1) ^ ((kr >> 1) & 3)) << 4);
                asm volatile("st.shared.v4.u32 [%0], {%1,%2,%3,%4};" ::"r"(dst), "r"(v[i].x), "r"(v[i].y), "r"(v[i].z), "r"(v[i].w) : "memory");
            }
            fence_async_smem();
            if constexpr (SELF) named_bar(6, 384); else named_bar(6, 256);
        }
        RowStatRaw raw;
        float csv = 0.f;
        float2 cskv[2] = {make_float2(0.f, 0.f), make_float2(0.f, 0.f)};
        auto ln_inputs = [&]() {
            pdl_wait();
            if constexpr (EPI != EPI_RES) {
                raw = load_row_stats(prm.stats_in, row0, c);
                const float* cs = EPI == EPI_FFN1 ? g_cs_1 + n0 : g_cs_q + n0;
                if (tid < TN) csv = cs[tid];
                if constexpr (XKV) {
                    cskv[0] = *(const float2*)(g_cs_kv + tile_n * 16 + 2 * c);
                    cskv[1] = *(const float2*)(g_cs_kv + tile_n * 16 + 8 + 2 * c);
                }
            }
        };
        if (!SELF) ln_inputs();
        float acc[BN / 2];
        const uint64_t dA0 = mkdesc(sbase + wg * (G::A_BYTES / 2), 16, G::A_SBO, G::A_SWZ);
        const uint64_t dB0 = mkdesc(sbase + G::A_BYTES, G::B_LBO, G::B_SBO, G::B_SWZ);
        int s = 0, ph = 0;
#pragma unroll 1
        for (int kb = 0; kb < KB; kb++) {
            mbar_wait(bar_full + 8 * s, ph);
            const uint64_t dA = dA0 + (uint64_t)(s * (SM::STAGE >> 4)), dB = dB0 + (uint64_t)(s * (SM::STAGE >> 4));
            wg_fence();
#pragma unroll
            for (int k = 0; k < G::BK / 16; k++) wgmma_ss_tb<BN>(acc, dA + (uint64_t)(k * 2), dB + (uint64_t)(k * (G::B_KSTEP >> 4)), (kb | k) != 0);
            wg_commit();
            if (kb > 0) {
                wg_wait<1>();
                const int sp = s == 0 ? STAGES - 1 : s - 1;
                if ((warp & 3) == 0 && elect_one()) {
                    if (MC) { mbar_arrive_remote(bar_empty + 8 * sp, 0); mbar_arrive_remote(bar_empty + 8 * sp, 1); }
                    else mbar_arrive(bar_empty + 8 * sp);
                }
            }
            if (++s == STAGES) { s = 0; ph ^= 1; }
        }
        if constexpr (SELF) {
            named_bar(4, 640);
            const float2 r0 = *(const float2*)(s_row + 2 * rloc), r1 = *(const float2*)(s_row + 2 * rloc + 16);
            mean0 = r0.x; rstd0 = r0.y; mean1 = r1.x; rstd1 = r1.y;
        } else if constexpr (EPI != EPI_RES) {
            finish_row_stats(raw, mean0, rstd0, mean1, rstd1);
            if (tid < TN) s_cs[tid] = csv;
        }
        wg_wait<0>();
        fence_regs(acc);
        if (tid == 0) TL(prm.tk, 2);
        if constexpr (EPI != EPI_RES) named_bar(1, 256);

        if constexpr (EPI != EPI_FFN1) {
            const uint32_t stile = sbase + (EPI == EPI_RES ? s * SM::STAGE : 0);
            const int mrow = wg * 64 + (warp & 3) * 16 + (lane & 7) + ((lane >> 3) & 1) * 8;
            const uint32_t rbase = stile + mrow * 128;
            if constexpr (EPI == EPI_RES) {
                mbar_wait(bar_full + 8 * s, ph);
                float s0 = 0.f, s1 = 0.f;
#pragma unroll
                for (int jj = 0; jj < 4; jj++) {
                    uint32_t r0, r1, r2, r3;
                    const uint32_t addr = rbase + (((2 * jj + (lane >> 4)) ^ (mrow & 7)) << 4);
                    ldsm_x4(r0, r1, r2, r3, addr);
                    const uint32_t u0 = pack_bf16(acc[8 * jj] + bf_lo(r0), acc[8 * jj + 1] + bf_hi(r0));
                    const uint32_t u1 = pack_bf16(acc[8 * jj + 2] + bf_lo(r1), acc[8 * jj + 3] + bf_hi(r1));
                    const uint32_t u2 = pack_bf16(acc[8 * jj + 4] + bf_lo(r2), acc[8 * jj + 5] + bf_hi(r2));
                    const uint32_t u3 = pack_bf16(acc[8 * jj + 6] + bf_lo(r3), acc[8 * jj + 7] + bf_hi(r3));
                    stsm_x4(addr, u0, u1, u2, u3);
                    acc[8 * jj] = bf_lo(u0); acc[8 * jj + 1] = bf_hi(u0); acc[8 * jj + 4] = bf_lo(u2); acc[8 * jj + 5] = bf_hi(u2);
                    acc[8 * jj + 2] = bf_lo(u1); acc[8 * jj + 3] = bf_hi(u1); acc[8 * jj + 6] = bf_lo(u3); acc[8 * jj + 7] = bf_hi(u3);
                    s0 += (acc[8 * jj] + acc[8 * jj + 1]) + (acc[8 * jj + 4] + acc[8 * jj + 5]);
                    s1 += (acc[8 * jj + 2] + acc[8 * jj + 3]) + (acc[8 * jj + 6] + acc[8 * jj + 7]);
                }
                fence_async_smem();
                named_bar(2 + wg, 128);
                if ((warp & 3) == 0 && elect_one()) { tma2d_store(mapC, stile + wg * 8192, n0, m0 + wg * 64); bulk_commit(); }
                if (prm.stats_out) {
                    s0 += __shfl_xor_sync(0xffffffffu, s0, 1); s0 += __shfl_xor_sync(0xffffffffu, s0, 2);
                    s1 += __shfl_xor_sync(0xffffffffu, s1, 1); s1 += __shfl_xor_sync(0xffffffffu, s1, 2);
                    const float mu0 = s0 * (1.f / 64.f), mu1 = s1 * (1.f / 64.f);
                    float q0 = 0.f, q1 = 0.f;
#pragma unroll
                    for (int j = 0; j < 8; j++) {
                        float d;
                        d = acc[4 * j] - mu0; q0 += d * d; d = acc[4 * j + 1] - mu0; q0 += d * d;
                        d = acc[4 * j + 2] - mu1; q1 += d * d; d = acc[4 * j + 3] - mu1; q1 += d * d;
                    }
                    q0 += __shfl_xor_sync(0xffffffffu, q0, 1); q0 += __shfl_xor_sync(0xffffffffu, q0, 2);
                    q1 += __shfl_xor_sync(0xffffffffu, q1, 1); q1 += __shfl_xor_sync(0xffffffffu, q1, 2);
                    if (c == 0) {
                        prm.stats_out[tile_n * S_ + row0] = make_float2(mu0, q0);
                        prm.stats_out[tile_n * S_ + row0 + 8] = make_float2(mu1, q1);
                    }
                }
            } else {
                const float sc = 0.25f * 1.4426950408889634f;
                const float a0 = rstd0 * sc, a1 = rstd1 * sc, rm0 = a0 * mean0, rm1 = a1 * mean1;
#pragma unroll
                for (int jj = 0; jj < 4; jj++) {
                    const float2 ca = *(const float2*)(s_cs + 16 * jj + 2 * c), cb = *(const float2*)(s_cs + 16 * jj + 8 + 2 * c);
                    const uint32_t u0 = pack_bf16(acc[8 * jj] * a0 - rm0 * ca.x, acc[8 * jj + 1] * a0 - rm0 * ca.y);
                    const uint32_t u1 = pack_bf16(acc[8 * jj + 2] * a1 - rm1 * ca.x, acc[8 * jj + 3] * a1 - rm1 * ca.y);
                    const uint32_t u2 = pack_bf16(acc[8 * jj + 4] * a0 - rm0 * cb.x, acc[8 * jj + 5] * a0 - rm0 * cb.y);
                    const uint32_t u3 = pack_bf16(acc[8 * jj + 6] * a1 - rm1 * cb.x, acc[8 * jj + 7] * a1 - rm1 * cb.y);
                    stsm_x4(rbase + (((2 * jj + (lane >> 4)) ^ (mrow & 7)) << 4), u0, u1, u2, u3);
                }
                fence_async_smem();
                named_bar(2 + wg, 128);
                if ((warp & 3) == 0 && elect_one()) { tma2d_store(mapC, stile + wg * 8192, n0, m0 + wg * 64); bulk_commit(); }
            }
            if constexpr (XKV) {
                {
                    const float* acx = &acc[32];
                    const float rm0 = rstd0 * mean0, rm1 = rstd1 * mean1;
                    float n0s = 0.f, n1s = 0.f, vmax = 0.f;
#pragma unroll
                    for (int j = 0; j < 2; j++) {
                        const float2 cs2 = SELF ? *(const float2*)(s_cs + 64 + 8 * j + 2 * c) : cskv[j];
                        const uint32_t u0 = pack_bf16(acx[4 * j] * rstd0 - rm0 * cs2.x, acx[4 * j + 1] * rstd0 - rm0 * cs2.y);
                        const uint32_t u1 = pack_bf16(acx[4 * j + 2] * rstd1 - rm1 * cs2.x, acx[4 * j + 3] * rstd1 - rm1 * cs2.y);
                        n0s += bf_lo(u0) * bf_lo(u0) + bf_hi(u0) * bf_hi(u0);
                        n1s += bf_lo(u1) * bf_lo(u1) + bf_hi(u1) * bf_hi(u1);
                        vmax = fmaxf(vmax, fmaxf(fmaxf(fabsf(bf_lo(u0)), fabsf(bf_hi(u0))), fmaxf(fabsf(bf_lo(u1)), fabsf(bf_hi(u1)))));
                        if (tile_n == 0) {
                            *(uint32_t*)(g_kimg + (row0 >> 3) * 256 + j * 128 + g * 16 + c * 4) = u0;
                            *(uint32_t*)(g_kimg + ((row0 + 8) >> 3) * 256 + j * 128 + g * 16 + c * 4) = u1;
                        } else {
                            uint8_t* vb = g_vimg + (row0 >> 4) * 768 + j * 256 + g * 16 + c * 4;
                            *(uint32_t*)(vb) = u0;
                            *(uint32_t*)(vb + 128) = u1;
                        }
                    }
                    if (tile_n == 1) {
                        uint8_t* vb = g_vimg + (row0 >> 4) * 768 + 512 + g * 16 + c * 4;
                        const uint32_t one = c == 0 ? 0x00003F80u : 0u;
                        *(uint32_t*)(vb) = one;
                        *(uint32_t*)(vb + 128) = one;
                    }
                    n0s += __shfl_xor_sync(0xffffffffu, n0s, 1); n0s += __shfl_xor_sync(0xffffffffu, n0s, 2);
                    n1s += __shfl_xor_sync(0xffffffffu, n1s, 1); n1s += __shfl_xor_sync(0xffffffffu, n1s, 2);
                    float km = tile_n == 0 ? fmaxf(n0s, n1s) : vmax;
                    if (!(n0s + n1s < INFINITY)) km = INFINITY;
#pragma unroll
                    for (int o = 1; o < 32; o <<= 1) km = fmaxf(km, __shfl_xor_sync(0xffffffffu, km, o));
                    if (lane == 0) s_red[warp] = km;
                    named_bar(1, 256);
                    if (tid == 0) {
                        float a = 0.f;
                        for (int i = 0; i < 8; i++) a = fmaxf(a, s_red[i]);
                        g_kvmax[tile_n * 16 + tile_m] = a;
                    }
                }
            }
            if ((warp & 3) == 0) bulk_wait_read();
        } else {
            const uint32_t stile = sbase + wg * (7 * 4096);
            const int mrow = (warp & 3) * 16 + (lane & 7) + ((lane >> 3) & 1) * 8;
            const float a0 = 0.5f * rstd0, a1 = 0.5f * rstd1, rm0 = a0 * mean0, rm1 = a1 * mean1;
#pragma unroll
            for (int jj = 0; jj < 14; jj++) {
                const float2 ca = *(const float2*)(s_cs + 16 * jj + 2 * c), cb = *(const float2*)(s_cs + 16 * jj + 8 + 2 * c);
                float y[8] = {acc[8 * jj] * a0 - rm0 * ca.x,     acc[8 * jj + 1] * a0 - rm0 * ca.y,
                              acc[8 * jj + 2] * a1 - rm1 * ca.x, acc[8 * jj + 3] * a1 - rm1 * ca.y,
                              acc[8 * jj + 4] * a0 - rm0 * cb.x, acc[8 * jj + 5] * a0 - rm0 * cb.y,
                              acc[8 * jj + 6] * a1 - rm1 * cb.x, acc[8 * jj + 7] * a1 - rm1 * cb.y};
#pragma unroll
                for (int i = 0; i < 8; i++) {
                    float t;
                    asm("tanh.approx.f32 %0, %1;" : "=f"(t) : "f"(y[i]));
                    y[i] = fmaf(y[i], t, y[i]);
                }
                const int chunk = (2 * jj + (lane >> 4)) & 3, blk = jj >> 1;
                stsm_x4(stile + blk * 4096 + mrow * 64 + ((chunk ^ ((mrow >> 1) & 3)) << 4),
                        pack_bf16(y[0], y[1]), pack_bf16(y[2], y[3]), pack_bf16(y[4], y[5]), pack_bf16(y[6], y[7]));
                if (jj & 1) {
                    fence_async_smem();
                    __syncwarp();
                    if (elect_one()) {
                        tma2d_store(mapC, stile + blk * 4096 + (warp & 3) * 1024, n0 + blk * 32, m0 + wg * 64 + (warp & 3) * 16);
                        bulk_commit();
                    }
                }
            }
            bulk_wait_read();
        }
    }
    if (tid == 0) TL(prm.tk, 3);
    if (MC) cluster_sync();
}

#define WO_ST 9
#define F2_ST 6
#define F1_ST (F1_BK == 64 ? 5 : 9)
#define QKV_ST 8
constexpr int QKV_STAGES = QKV_ST, WO_STAGES = WO_ST, FFN2_STAGES = F2_ST, FFN1_STAGES = F1_ST;
template <bool SELF>
__global__ void __launch_bounds__(SELF ? 640 : 288) qkv_kernel(const __grid_constant__ CUtensorMap mapA, const __grid_constant__ CUtensorMap mapWq,
                                                  const __grid_constant__ CUtensorMap mapQ, const GemmParams prm) {
    extern __shared__ __align__(1024) uint8_t smem_raw[];
    const int tn = blockIdx.x & 7;
    if (tn < 2) gemm_body<80, 8, QKV_STAGES, EPI_QKV, false, SELF>(&mapA, &mapWq, &mapWq, &mapA, &mapQ, prm, blockIdx.x >> 3, tn, smem_raw);
    else gemm_body<64, 8, QKV_STAGES, EPI_QKV, false, SELF>(&mapA, &mapWq, &mapWq, &mapA, &mapQ, prm, blockIdx.x >> 3, tn, smem_raw);
}
template <int KB, int STAGES>
__global__ void __launch_bounds__(288) res_gemm_kernel(const __grid_constant__ CUtensorMap mapA, const __grid_constant__ CUtensorMap mapW,
                                                       const __grid_constant__ CUtensorMap mapR, const __grid_constant__ CUtensorMap mapC, const GemmParams prm) {
    extern __shared__ __align__(1024) uint8_t smem_raw[];
    gemm_body<64, KB, STAGES, EPI_RES, false>(&mapA, &mapW, &mapW, &mapR, &mapC, prm, blockIdx.x >> 3, blockIdx.x & 7, smem_raw);
}
__global__ void __launch_bounds__(288) ffn1_kernel(const __grid_constant__ CUtensorMap mapA, const __grid_constant__ CUtensorMap mapW4,
                                                   const __grid_constant__ CUtensorMap mapW3, const __grid_constant__ CUtensorMap mapH, const GemmParams prm) {
    extern __shared__ __align__(1024) uint8_t smem_raw[];
    const int pair = blockIdx.x >> 1, tile_n = pair & 7, tile_m = (pair >> 3) * 2 + (blockIdx.x & 1);
    gemm_body<224, 512 / F1_BK, FFN1_STAGES, EPI_FFN1, true>(&mapA, &mapW4, &mapW3, &mapA, &mapH, prm, tile_m, tile_n, smem_raw);
}

#define ATT_NPOLY 11
constexpr int NPOLY = ATT_NPOLY;
__host__ __device__ constexpr bool is_mufu(int i) { return ((i + 1) * (16 - NPOLY)) / 16 != (i * (16 - NPOLY)) / 16; }

__device__ __forceinline__ float ex2(float x) { float r; asm("ex2.approx.ftz.f32 %0, %1;" : "=f"(r) : "f"(x)); return r; }
__device__ __forceinline__ uint32_t exp_pair_mufu(float a, float b) { return pack_bf16(ex2(a), ex2(b)); }
__device__ __forceinline__ uint32_t exp_pair_fma(float a, float b, uint32_t c3f) {
    constexpr float MAGIC = 98430.4140625f;
    const float ta = a + MAGIC, tb = b + (MAGIC - 143.5f);
    uint32_t y, m, r;
    asm("mad.lo.u32 %0, %1, 65536, %2;" : "=r"(y) : "r"(__float_as_uint(tb)), "r"(__float_as_uint(ta)));
    asm("lop3.b32 %0, %1, 0x007F007F, %2, 0xEA;" : "=r"(m) : "r"(y), "r"(c3f));
    const uint32_t e = y & 0xFF80FF80u;
    asm("fma.rn.bf16x2 %0, %1, %2, %3;" : "=r"(r) : "r"(y), "r"(m), "r"(e));
    return r;
}

constexpr int KCH = 256, NCH = S_ / KCH;
constexpr int K_BYTES = S_ * 32, V_BYTES = (S_ / 16) * 768;
constexpr int QO_BYTES = 128 * 128;
constexpr int ATT_SMEM = K_BYTES + V_BYTES + QO_BYTES;

__global__ void __launch_bounds__(512, 1) attn_kernel(const __grid_constant__ CUtensorMap mapQ, const __grid_constant__ CUtensorMap mapO,
                                                       const __nv_bfloat16* __restrict__ wo, const __nv_bfloat16* __restrict__ w1,
                                                       const __nv_bfloat16* __restrict__ w2, int tk) {
    extern __shared__ __align__(1024) uint8_t smem[];
    __shared__ uint64_t bars[NCH + 1];
    __shared__ int s_slow;
    const int tid = threadIdx.x, wg = tid >> 7, warp = (tid >> 5) & 3, lane = tid & 31;
    const uint32_t sK = smem_u32(smem), sV = sK + K_BYTES, sQ = sV + V_BYTES;
    if (blockIdx.x >= 128) {
        pdl_launch();
        pdl_wait();
        side_job(blockIdx.x - 128, (float*)smem, wo, w1, w2);
        return;
    }
    CK(tk, 9);
    if (tid == 0) TL(tk, 0);
    if (tid == 0) {
#pragma unroll
        for (int i = 0; i <= NCH; i++) mbar_init(smem_u32(&bars[i]), 1);
        s_slow = 0;
        fence_mbar_init();
    }
    if (tid == 32) { prefetch_tmap(&mapQ); prefetch_tmap(&mapO); }
    __syncthreads();
    pdl_launch();
    CK(tk, 10);
    pdl_wait();
    CK(tk, 11);
    if (tid == 0) TL(tk, 1);
    const int wu = __shfl_sync(0xffffffffu, tid >> 5, 0);
    auto fetch_chunk = [&](int w) {
        if (elect_one()) {
            const uint32_t bar = smem_u32(&bars[w]);
            mbar_expect_tx(bar, KCH * 32 + (KCH / 16) * 768);
            bulk_load(sK + w * KCH * 32, g_kimg + w * KCH * 32, KCH * 32, bar);
            bulk_load(sV + w * (KCH / 16) * 768, g_vimg + w * (KCH / 16) * 768, (KCH / 16) * 768, bar);
        }
    };
    const int tb = blockIdx.x >> 3, hg = blockIdx.x & 7;
    if (wu == 1 && elect_one()) {
        mbar_expect_tx(smem_u32(&bars[NCH]), QO_BYTES);
        tma2d(sQ, &mapQ, hg * 64, tb * 128, smem_u32(&bars[NCH]));
    }
    if (wu == 0) fetch_chunk(0);
    float kvm = g_kvmax[lane];
    const int lrow = warp * 16 + (lane & 7) + ((lane >> 3) & 1) * 8;
    const uint32_t qoff = lrow * 128 + (((2 * wg + (lane >> 4)) ^ (lrow & 7)) << 4);
    uint32_t qa[2][4];
    mbar_wait(smem_u32(&bars[NCH]), 0);
    ldsm_x4(qa[0][0], qa[0][1], qa[0][2], qa[0][3], sQ + qoff);
    ldsm_x4(qa[1][0], qa[1][1], qa[1][2], qa[1][3], sQ + 8192 + qoff);
    CK(tk, 12);
    {
        float qn = 0.f;
#pragma unroll
        for (int m = 0; m < 2; m++) {
            float n0 = bf_lo(qa[m][0]) * bf_lo(qa[m][0]) + bf_hi(qa[m][0]) * bf_hi(qa[m][0]) + bf_lo(qa[m][2]) * bf_lo(qa[m][2]) + bf_hi(qa[m][2]) * bf_hi(qa[m][2]);
            float n1 = bf_lo(qa[m][1]) * bf_lo(qa[m][1]) + bf_hi(qa[m][1]) * bf_hi(qa[m][1]) + bf_lo(qa[m][3]) * bf_lo(qa[m][3]) + bf_hi(qa[m][3]) * bf_hi(qa[m][3]);
            n0 += __shfl_xor_sync(0xffffffffu, n0, 1); n0 += __shfl_xor_sync(0xffffffffu, n0, 2);
            n1 += __shfl_xor_sync(0xffffffffu, n1, 1); n1 += __shfl_xor_sync(0xffffffffu, n1, 2);
            if (!(n0 == n0) || !(n1 == n1)) n0 = INFINITY;
            qn = fmaxf(qn, fmaxf(n0, n1));
        }
        CK(tk, 13);
#pragma unroll
        for (int o = 1; o < 16; o <<= 1) kvm = fmaxf(kvm, __shfl_xor_sync(0xffffffffu, kvm, o));
        const float km = __shfl_sync(0xffffffffu, kvm, 0), vm = __shfl_sync(0xffffffffu, kvm, 16);
        const bool ok = (qn * km <= 10000.f) && (vm <= 16384.f);
        if (!ok) s_slow = 1;
    }
    CK(tk, 14);
    float oacc[2][12];
#pragma unroll
    for (int m = 0; m < 2; m++)
#pragma unroll
        for (int i = 0; i < 12; i++) oacc[m][i] = 0.f;
    __syncthreads();
    const bool slow = s_slow != 0;
    if (wu >= 1 && wu < NCH) fetch_chunk(wu);
    CK(tk, 15);

    const uint64_t dK0 = mkdesc(sK, 128, 256, 0);
    const uint64_t dV0 = mkdesc(sV, 128, 256, 0);
    uint32_t c3f;
    asm volatile("mov.b32 %0, 0x3F003F00;" : "=r"(c3f));
    if (!slow) {
        uint64_t dK = dK0, dV = dV0;
        float s[32];
        fence_regs(oacc[0]); fence_regs(oacc[1]);
        mbar_wait(smem_u32(&bars[0]), 0);
        wg_fence();
        wgmma_rs_n64_z(s, qa[0][0], qa[0][1], qa[0][2], qa[0][3], dK);
        wg_commit();
#pragma unroll 1
        for (int ch = 0; ch < NCH; ch++) {
#pragma unroll
            for (int tt = 0; tt < KCH / 64; tt++) {
#pragma unroll
                for (int m = 0; m < 2; m++) {
                    wg_wait<0>();
                    fence_regs(s);
                    uint32_t p[16];
#pragma unroll
                    for (int i = 0; i < 16; i++) p[i] = is_mufu(i) ? exp_pair_mufu(s[2 * i], s[2 * i + 1]) : exp_pair_fma(s[2 * i], s[2 * i + 1], c3f);
                    if (m == 1 && tt == KCH / 64 - 1) mbar_wait(smem_u32(&bars[ch + 1 < NCH ? ch + 1 : ch]), 0);
                    wg_fence();
#pragma unroll
                    for (int kk = 0; kk < 4; kk++)
                        wgmma_rs_n24_tb(oacc[m], p[4 * kk], p[4 * kk + 1], p[4 * kk + 2], p[4 * kk + 3], dV + (uint64_t)((tt * 4 + kk) * (768 / 16)));
                    wgmma_rs_n64_z(s, qa[1 - m][0], qa[1 - m][1], qa[1 - m][2], qa[1 - m][3], dK + (uint64_t)((tt + m) * (64 * 32 / 16)));
                    wg_commit();
                }
            }
            dK += KCH * 32 / 16;
            dV += (KCH / 16) * (768 / 16);
        }
        wg_wait<0>();
        fence_regs(s);
    } else {
        float mx[2][2] = {{-INFINITY, -INFINITY}, {-INFINITY, -INFINITY}};
#pragma unroll 1
        for (int t = 0; t < S_ / 64; t++) {
            if ((t & 3) == 0) mbar_wait(smem_u32(&bars[t >> 2]), 0);
            const uint64_t dK = dK0 + (uint64_t)(t * 64 * 32 / 16);
            const uint64_t dV = dV0 + (uint64_t)(t * 4 * 768 / 16);
#pragma unroll
            for (int m = 0; m < 2; m++) {
                float s[32];
                wg_fence();
                wgmma_rs_n64_z(s, qa[m][0], qa[m][1], qa[m][2], qa[m][3], dK);
                wg_commit();
                wg_wait<0>();
                fence_regs(s);
                fence_regs(oacc[m]);
                float r0 = mx[m][0], r1 = mx[m][1];
#pragma unroll
                for (int j = 0; j < 8; j++) {
                    r0 = fmaxf(r0, fmaxf(s[4 * j], s[4 * j + 1]));
                    r1 = fmaxf(r1, fmaxf(s[4 * j + 2], s[4 * j + 3]));
                }
                r0 = fmaxf(r0, __shfl_xor_sync(0xffffffffu, r0, 1)); r0 = fmaxf(r0, __shfl_xor_sync(0xffffffffu, r0, 2));
                r1 = fmaxf(r1, __shfl_xor_sync(0xffffffffu, r1, 1)); r1 = fmaxf(r1, __shfl_xor_sync(0xffffffffu, r1, 2));
                const float al0 = ex2(mx[m][0] - r0), al1 = ex2(mx[m][1] - r1);
                mx[m][0] = r0; mx[m][1] = r1;
#pragma unroll
                for (int j = 0; j < 3; j++) {
                    oacc[m][4 * j] *= al0; oacc[m][4 * j + 1] *= al0;
                    oacc[m][4 * j + 2] *= al1; oacc[m][4 * j + 3] *= al1;
                }
                uint32_t p[16];
#pragma unroll
                for (int j = 0; j < 8; j++) {
                    p[2 * j] = pack_bf16(ex2(s[4 * j] - r0), ex2(s[4 * j + 1] - r0));
                    p[2 * j + 1] = pack_bf16(ex2(s[4 * j + 2] - r1), ex2(s[4 * j + 3] - r1));
                }
                fence_regs(oacc[m]);
                wg_fence();
#pragma unroll
                for (int kk = 0; kk < 4; kk++)
                    wgmma_rs_n24_tb(oacc[m], p[4 * kk], p[4 * kk + 1], p[4 * kk + 2], p[4 * kk + 3], dV + (uint64_t)(kk * 768 / 16));
                wg_commit();
                wg_wait<0>();
            }
        }
    }
    fence_regs(oacc[0]); fence_regs(oacc[1]);
    if (tid == 0) TL(tk, 2);
#pragma unroll
    for (int m = 0; m < 2; m++) {
        const float l0 = __shfl_sync(0xffffffffu, oacc[m][8], lane & ~3);
        const float l1 = __shfl_sync(0xffffffffu, oacc[m][10], lane & ~3);
        const float r0 = __fdividef(1.0f, l0), r1 = __fdividef(1.0f, l1);
        stsm_x4(sQ + m * 8192 + qoff, pack_bf16(oacc[m][0] * r0, oacc[m][1] * r0), pack_bf16(oacc[m][2] * r1, oacc[m][3] * r1),
                pack_bf16(oacc[m][4] * r0, oacc[m][5] * r0), pack_bf16(oacc[m][6] * r1, oacc[m][7] * r1));
    }
    fence_async_smem();
    __syncthreads();
    if (wu == 0 && elect_one()) {
        tma2d_store(&mapO, sQ, hg * 64, tb * 128);
        bulk_commit();
        bulk_wait_read();
    }
    if (tid == 0) TL(tk, 3);
}

typedef CUresult (*EncodeFn)(CUtensorMap*, CUtensorMapDataType, cuuint32_t, void*, const cuuint64_t*, const cuuint64_t*, const cuuint32_t*,
                             const cuuint32_t*, CUtensorMapInterleave, CUtensorMapSwizzle, CUtensorMapL2promotion, CUtensorMapFloatOOBfill);

EncodeFn get_encode() {
    static EncodeFn fn = nullptr;
    if (!fn) {
        void* p = nullptr;
        cudaDriverEntryPointQueryResult qr;
        cudaGetDriverEntryPoint("cuTensorMapEncodeTiled", &p, cudaEnableDefault, &qr);
        fn = (EncodeFn)p;
    }
    return fn;
}
CUtensorMap map2d(const void* ptr, uint64_t cols, uint64_t rows, uint32_t bc, uint32_t br, CUtensorMapSwizzle sw) {
    CUtensorMap m;
    cuuint64_t gd[2] = {cols, rows}, gs[1] = {cols * 2};
    cuuint32_t bx[2] = {bc, br}, es[2] = {1, 1};
    get_encode()(&m, CU_TENSOR_MAP_DATA_TYPE_BFLOAT16, 2, (void*)ptr, gd, gs, bx, es, CU_TENSOR_MAP_INTERLEAVE_NONE, sw,
                 CU_TENSOR_MAP_L2_PROMOTION_L2_128B, CU_TENSOR_MAP_FLOAT_OOB_FILL_NONE);
    return m;
}
CUtensorMap map3d32(const void* ptr, uint64_t cols, uint64_t rows, uint32_t br, uint32_t nb) {
    CUtensorMap m;
    cuuint64_t gd[3] = {32, rows, cols / 32}, gs[2] = {cols * 2, 64};
    cuuint32_t bx[3] = {32, br, nb}, es[3] = {1, 1, 1};
    get_encode()(&m, CU_TENSOR_MAP_DATA_TYPE_BFLOAT16, 3, (void*)ptr, gd, gs, bx, es, CU_TENSOR_MAP_INTERLEAVE_NONE, CU_TENSOR_MAP_SWIZZLE_64B,
                 CU_TENSOR_MAP_L2_PROMOTION_L2_128B, CU_TENSOR_MAP_FLOAT_OOB_FILL_NONE);
    return m;
}

template <typename... KArgs, typename... Args>
void launch(void (*kern)(KArgs...), int grid, int block, int smem, int cluster, bool pdl, Args... args) {
    cudaLaunchConfig_t cfg = {};
    cfg.gridDim = dim3(grid);
    cfg.blockDim = dim3(block);
    cfg.dynamicSmemBytes = smem;
    cfg.stream = cudaStreamPerThread;
    cudaLaunchAttribute at[2];
    int n = 0;
    if (cluster > 1) { at[n].id = cudaLaunchAttributeClusterDimension; at[n].val.clusterDim.x = cluster; at[n].val.clusterDim.y = 1; at[n].val.clusterDim.z = 1; n++; }
    if (pdl) { at[n].id = cudaLaunchAttributeProgrammaticStreamSerialization; at[n].val.programmaticStreamSerializationAllowed = 1; n++; }
    cfg.attrs = at;
    cfg.numAttrs = n;
    cudaLaunchKernelEx(&cfg, kern, KArgs(args)...);
}

template <typename T> void* sym(const T& s) { void* p = nullptr; cudaGetSymbolAddress(&p, s); return p; }

}

extern "C" void kernel_launch(void* const* d_in, const int* in_sizes, int n_in, void* d_out, int out_size) {
    const __nv_bfloat16* x = (const __nv_bfloat16*)d_in[0];
    const __nv_bfloat16* wq = (const __nv_bfloat16*)d_in[1];
    const __nv_bfloat16* wk = (const __nv_bfloat16*)d_in[2];
    const __nv_bfloat16* wv = (const __nv_bfloat16*)d_in[3];
    const __nv_bfloat16* wo = (const __nv_bfloat16*)d_in[4];
    const __nv_bfloat16* w1 = (const __nv_bfloat16*)d_in[6];
    const __nv_bfloat16* w2 = (const __nv_bfloat16*)d_in[7];

    constexpr int SM_QKV = GemmSmem<QKV_STAGES, EPI_QKV>::TOTAL, SM_QKV0 = GemmSmem<QKV_STAGES, EPI_QKV>::TOTAL_SELF;
    static_assert(SM_QKV0 <= 232448, "shared memory");
    constexpr int SM_WO = GemmSmem<WO_STAGES, EPI_RES>::TOTAL, SM_FFN2 = GemmSmem<FFN2_STAGES, EPI_RES>::TOTAL;
    static_assert(SM_WO > 116736 && SM_FFN2 > 116736, "one CTA per SM");
    constexpr int SM_FFN1 = GemmSmem<FFN1_STAGES, EPI_FFN1>::TOTAL;
    cudaFuncSetAttribute(qkv_kernel<false>, cudaFuncAttributeMaxDynamicSharedMemorySize, SM_QKV);
    cudaFuncSetAttribute(qkv_kernel<true>, cudaFuncAttributeMaxDynamicSharedMemorySize, SM_QKV0);
    cudaFuncSetAttribute(res_gemm_kernel<8, WO_STAGES>, cudaFuncAttributeMaxDynamicSharedMemorySize, SM_WO);
    cudaFuncSetAttribute(ffn1_kernel, cudaFuncAttributeMaxDynamicSharedMemorySize, SM_FFN1);
    cudaFuncSetAttribute(res_gemm_kernel<28, FFN2_STAGES>, cudaFuncAttributeMaxDynamicSharedMemorySize, SM_FFN2);
    cudaFuncSetAttribute(attn_kernel, cudaFuncAttributeMaxDynamicSharedMemorySize, ATT_SMEM);
    cudaFuncSetAttribute(qkv_kernel<false>, cudaFuncAttributePreferredSharedMemoryCarveout, 100);
    cudaFuncSetAttribute(qkv_kernel<true>, cudaFuncAttributePreferredSharedMemoryCarveout, 100);
    cudaFuncSetAttribute(res_gemm_kernel<8, WO_STAGES>, cudaFuncAttributePreferredSharedMemoryCarveout, 100);
    cudaFuncSetAttribute(ffn1_kernel, cudaFuncAttributePreferredSharedMemoryCarveout, 100);
    cudaFuncSetAttribute(res_gemm_kernel<28, FFN2_STAGES>, cudaFuncAttributePreferredSharedMemoryCarveout, 100);
    cudaFuncSetAttribute(attn_kernel, cudaFuncAttributePreferredSharedMemoryCarveout, 100);

    void *q = sym(g_q), *o = sym(g_o), *x1 = sym(g_x1), *x2 = sym(g_x2), *x3 = sym(g_x3), *h = sym(g_h);
    float2* stats = (float2*)sym(g_stats);
    const void* xs[5] = {x, x1, x2, x3, d_out};

    const CUtensorMapSwizzle SW128 = CU_TENSOR_MAP_SWIZZLE_128B, SW64 = CU_TENSOR_MAP_SWIZZLE_64B;
    const CUtensorMap mWq = map3d32(wq, D_, D_, 64, 2);
    const CUtensorMap mWo = map2d(wo, D_, D_, 64, 64, SW128);
    const CUtensorMap mW1a = map3d32(w1, F_, D_, F1_BK, 4), mW1b = map3d32(w1, F_, D_, F1_BK, 3);
    const CUtensorMap mW2 = map2d(w2, D_, F_, 64, 64, SW128);
    const CUtensorMap mQ = map2d(q, D_, S_, 64, 64, SW128);
    const CUtensorMap mQa = map2d(q, D_, S_, 64, 128, SW128), mOs = map2d(o, D_, S_, 64, 128, SW128);
    const CUtensorMap mHst = map2d(h, F_, S_, 32, 16, SW64);
    CUtensorMap mXa[4], mXf[4], mXr[4], mXs[5];
    for (int i = 0; i < 4; i++) {
        mXa[i] = map2d(xs[i], D_, S_, 64, 128, SW128);
        mXf[i] = F1_BK == 64 ? map2d(xs[i], D_, S_, 64, 128, SW128) : map2d(xs[i], D_, S_, 32, 128, SW64);
        mXr[i] = map2d(xs[i], D_, S_, 64, 128, SW128);
    }
    for (int i = 0; i < 5; i++) mXs[i] = map2d(xs[i], D_, S_, 64, 64, SW128);
    const CUtensorMap mOa = map2d(o, D_, S_, 64, 128, SW128);
    const CUtensorMap mHa = map2d(h, F_, S_, 64, 128, SW128);

    for (int layer = 0; layer < 2; layer++) {
        const int xi = layer * 2;
        GemmParams p;
        p.wkv = wk; p.wv = wv;
        p.stats_in = stats + (size_t)xi * 8 * S_; p.stats_out = nullptr; p.tk = 1 + 5 * layer;
        if (layer == 0) launch(qkv_kernel<true>, 128, 640, SM_QKV0, 1, false, mXa[xi], mWq, mQ, p);
        else launch(qkv_kernel<false>, 128, 288, SM_QKV, 1, true, mXa[xi], mWq, mQ, p);
        launch(attn_kernel, layer == 0 ? 128 + SIDE_CTAS : 128, 512, ATT_SMEM, 1, true, mQa, mOs, wo, w1, w2, 2 + 5 * layer);
        p.stats_in = nullptr; p.stats_out = stats + (size_t)(xi + 1) * 8 * S_; p.tk = 3 + 5 * layer;
        launch(res_gemm_kernel<8, WO_STAGES>, 128, 288, SM_WO, 1, true, mOa, mWo, mXr[xi], mXs[xi + 1], p);
        p.stats_in = stats + (size_t)(xi + 1) * 8 * S_; p.stats_out = nullptr; p.tk = 4 + 5 * layer;
        launch(ffn1_kernel, 128, 288, SM_FFN1, 2, true, mXf[xi + 1], mW1a, mW1b, mHst, p);
        p.stats_in = nullptr; p.stats_out = layer == 0 ? stats + (size_t)2 * 8 * S_ : nullptr; p.tk = 5 + 5 * layer;
        launch(res_gemm_kernel<28, FFN2_STAGES>, 128, 288, SM_FFN2, 1, true, mHa, mW2, mXr[xi + 1], mXs[xi + 2], p);
    }
}
```

```cpp
#include <cuda_runtime.h>
#include <cuda_bf16.h>
#include <cuda.h>
#include <stdint.h>

namespace {

constexpr int S_ = 2048, D_ = 512, F_ = 1792;

__device__ __align__(1024) __nv_bfloat16 g_q[S_ * D_];
__device__ __align__(1024) __nv_bfloat16 g_o[S_ * D_];
__device__ __align__(1024) __nv_bfloat16 g_x1[S_ * D_];
__device__ __align__(1024) __nv_bfloat16 g_x2[S_ * D_];
__device__ __align__(1024) __nv_bfloat16 g_x3[S_ * D_];
__device__ __align__(1024) __nv_bfloat16 g_h[S_ * F_];
__device__ __align__(1024) uint8_t g_kimg[S_ * 32];
__device__ __align__(1024) uint8_t g_vimg[(S_ / 16) * 768];
__device__ __align__(1024) float2 g_stats[4][8 * S_];
__device__ __align__(16) float g_cs_q[D_];
__device__ __align__(16) float g_cs_kv[32];
__device__ __align__(16) float g_cs_1[F_];
__device__ __align__(16) float g_kvmax[32];

#define TL(k, slot)
#define CK(k, i)
#define CP(k, i)

__device__ __forceinline__ uint32_t smem_u32(const void* p) { return (uint32_t)__cvta_generic_to_shared(p); }
__device__ __forceinline__ void mbar_init(uint32_t bar, uint32_t cnt) {
    asm volatile("mbarrier.init.shared::cta.b64 [%0], %1;" ::"r"(bar), "r"(cnt));
}
__device__ __forceinline__ void mbar_expect_tx(uint32_t bar, uint32_t bytes) {
    asm volatile("mbarrier.arrive.expect_tx.shared::cta.b64 _, [%0], %1;" ::"r"(bar), "r"(bytes) : "memory");
}
__device__ __forceinline__ void mbar_arrive(uint32_t bar) {
    asm volatile("mbarrier.arrive.shared::cta.b64 _, [%0];" ::"r"(bar) : "memory");
}
__device__ __forceinline__ void mbar_wait(uint32_t bar, uint32_t parity) {
    asm volatile("{\n.reg .pred p;\nWAIT_%=:\nmbarrier.try_wait.parity.shared::cta.b64 p, [%0], %1;\n@p bra DONE_%=;\nbra WAIT_%=;\nDONE_%=:\n}" ::"r"(bar), "r"(parity) : "memory");
}
__device__ __forceinline__ void bulk_load(uint32_t dst, const void* src, uint32_t bytes, uint32_t bar) {
    asm volatile("cp.async.bulk.shared::cluster.global.mbarrier::complete_tx::bytes [%0], [%1], %2, [%3];" ::"r"(dst), "l"(src), "r"(bytes), "r"(bar) : "memory");
}
__device__ __forceinline__ void tma2d(uint32_t dst, const CUtensorMap* m, int c0, int c1, uint32_t bar) {
    asm volatile("cp.async.bulk.tensor.2d.shared::cluster.global.mbarrier::complete_tx::bytes [%0], [%1, {%3, %4}], [%2];" ::"r"(dst), "l"(m), "r"(bar), "r"(c0), "r"(c1) : "memory");
}
__device__ __forceinline__ void tma3d(uint32_t dst, const CUtensorMap* m, int c0, int c1, int c2, uint32_t bar) {
    asm volatile("cp.async.bulk.tensor.3d.shared::cluster.global.mbarrier::complete_tx::bytes [%0], [%1, {%3, %4, %5}], [%2];" ::"r"(dst), "l"(m), "r"(bar), "r"(c0), "r"(c1), "r"(c2) : "memory");
}
__device__ __forceinline__ void tma2d_store(const CUtensorMap* m, uint32_t src, int c0, int c1) {
    asm volatile("cp.async.bulk.tensor.2d.global.shared::cta.bulk_group [%0, {%2, %3}], [%1];" ::"l"(m), "r"(src), "r"(c0), "r"(c1) : "memory");
}
__device__ __forceinline__ void bulk_commit() { asm volatile("cp.async.bulk.commit_group;" ::: "memory"); }
__device__ __forceinline__ void bulk_wait_read() { asm volatile("cp.async.bulk.wait_group.read 0;" ::: "memory"); }
__device__ __forceinline__ void prefetch_tmap(const CUtensorMap* m) { asm volatile("prefetch.tensormap [%0];" ::"l"(m) : "memory"); }
__device__ __forceinline__ void fence_async_smem() { asm volatile("fence.proxy.async.shared::cta;" ::: "memory"); }
__device__ __forceinline__ void fence_mbar_init() { asm volatile("fence.mbarrier_init.release.cluster;" ::: "memory"); }
__device__ __forceinline__ void pdl_wait() { asm volatile("griddepcontrol.wait;" ::: "memory"); }
__device__ __forceinline__ void pdl_launch() { asm volatile("griddepcontrol.launch_dependents;" ::: "memory"); }
__device__ __forceinline__ bool elect_one() {
    uint32_t p;
    asm volatile("{\n.reg .pred p;\nelect.sync _|p, 0xffffffff;\nselp.b32 %0, 1, 0, p;\n}" : "=r"(p));
    return p != 0;
}
__device__ __forceinline__ void named_bar(int id, int n) { asm volatile("bar.sync %0, %1;" ::"r"(id), "r"(n) : "memory"); }

__device__ __forceinline__ void wg_fence() { asm volatile("wgmma.fence.sync.aligned;" ::: "memory"); }
__device__ __forceinline__ void wg_commit() { asm volatile("wgmma.commit_group.sync.aligned;" ::: "memory"); }
template <int N> __device__ __forceinline__ void wg_wait() { asm volatile("wgmma.wait_group.sync.aligned %0;" ::"n"(N) : "memory"); }
template <int N> __device__ __forceinline__ void fence_regs(float (&d)[N]) {
#pragma unroll
    for (int i = 0; i < N; i++) asm volatile("" : "+f"(d[i])::"memory");
}
__device__ __forceinline__ uint64_t mkdesc(uint32_t addr, uint32_t lbo, uint32_t sbo, uint32_t swz) {
    uint64_t d = 0;
    d |= (uint64_t)((addr & 0x3FFFF) >> 4);
    d |= (uint64_t)((lbo & 0x3FFFF) >> 4) << 16;
    d |= (uint64_t)((sbo & 0x3FFFF) >> 4) << 32;
    d |= (uint64_t)swz << 62;
    return d;
}
__device__ __forceinline__ void ldsm_x4(uint32_t& r0, uint32_t& r1, uint32_t& r2, uint32_t& r3, uint32_t addr) {
    asm volatile("ldmatrix.sync.aligned.m8n8.x4.shared.b16 {%0,%1,%2,%3}, [%4];" : "=r"(r0), "=r"(r1), "=r"(r2), "=r"(r3) : "r"(addr) : "memory");
}
__device__ __forceinline__ void stsm_x4(uint32_t addr, uint32_t r0, uint32_t r1, uint32_t r2, uint32_t r3) {
    asm volatile("stmatrix.sync.aligned.m8n8.x4.shared.b16 [%0], {%1,%2,%3,%4};" ::"r"(addr), "r"(r0), "r"(r1), "r"(r2), "r"(r3) : "memory");
}
__device__ __forceinline__ uint32_t pack_bf16(float lo, float hi) {
    uint32_t r;
    asm("cvt.rn.bf16x2.f32 %0, %1, %2;" : "=r"(r) : "f"(hi), "f"(lo));
    return r;
}
__device__ __forceinline__ float bf_lo(uint32_t v) { return __uint_as_float(v << 16); }
__device__ __forceinline__ float bf_hi(uint32_t v) { return __uint_as_float(v & 0xFFFF0000u); }

#define WG_REGS_4(o) "+f"(d[o]), "+f"(d[o + 1]), "+f"(d[o + 2]), "+f"(d[o + 3])
#define WG_REGS_8(o) WG_REGS_4(o), WG_REGS_4(o + 4)
#define WG_REGS_16(o) WG_REGS_8(o), WG_REGS_8(o + 8)
#define WG_REGS_32(o) WG_REGS_16(o), WG_REGS_16(o + 16)

__device__ __forceinline__ void wgmma_ss_n80_tb(float (&d)[40], uint64_t dA, uint64_t dB, int sc) {
    asm volatile("{\n.reg .pred p;\nsetp.ne.b32 p, %42, 0;\n"
                 "wgmma.mma_async.sync.aligned.m64n80k16.f32.bf16.bf16 "
                 "{%0,%1,%2,%3,%4,%5,%6,%7,%8,%9,%10,%11,%12,%13,%14,%15,%16,%17,%18,%19,%20,%21,%22,%23,%24,%25,%26,%27,%28,%29,%30,%31,"
                 "%32,%33,%34,%35,%36,%37,%38,%39}, %40, %41, p, 1, 1, 0, 1;\n}\n"
                 : WG_REGS_32(0), WG_REGS_8(32) : "l"(dA), "l"(dB), "r"(sc));
}
__device__ __forceinline__ void wgmma_ss_n64_tb(float (&d)[32], uint64_t dA, uint64_t dB, int sc) {
    asm volatile("{\n.reg .pred p;\nsetp.ne.b32 p, %34, 0;\n"
                 "wgmma.mma_async.sync.aligned.m64n64k16.f32.bf16.bf16 "
                 "{%0,%1,%2,%3,%4,%5,%6,%7,%8,%9,%10,%11,%12,%13,%14,%15,%16,%17,%18,%19,%20,%21,%22,%23,%24,%25,%26,%27,%28,%29,%30,%31}, "
                 "%32, %33, p, 1, 1, 0, 1;\n}\n"
                 : WG_REGS_32(0) : "l"(dA), "l"(dB), "r"(sc));
}
__device__ __forceinline__ void wgmma_ss_n224_tb(float (&d)[112], uint64_t dA, uint64_t dB, int sc) {
    asm volatile("{\n.reg .pred p;\nsetp.ne.b32 p, %114, 0;\n"
                 "wgmma.mma_async.sync.aligned.m64n224k16.f32.bf16.bf16 "
                 "{%0,%1,%2,%3,%4,%5,%6,%7,%8,%9,%10,%11,%12,%13,%14,%15,%16,%17,%18,%19,%20,%21,%22,%23,%24,%25,%26,%27,%28,%29,%30,%31,"
                 "%32,%33,%34,%35,%36,%37,%38,%39,%40,%41,%42,%43,%44,%45,%46,%47,%48,%49,%50,%51,%52,%53,%54,%55,%56,%57,%58,%59,%60,%61,%62,%63,"
                 "%64,%65,%66,%67,%68,%69,%70,%71,%72,%73,%74,%75,%76,%77,%78,%79,%80,%81,%82,%83,%84,%85,%86,%87,%88,%89,%90,%91,%92,%93,%94,%95,"
                 "%96,%97,%98,%99,%100,%101,%102,%103,%104,%105,%106,%107,%108,%109,%110,%111}, "
                 "%112, %113, p, 1, 1, 0, 1;\n}\n"
                 : WG_REGS_32(0), WG_REGS_32(32), WG_REGS_32(64), WG_REGS_16(96) : "l"(dA), "l"(dB), "r"(sc));
}
template <int BN> __device__ __forceinline__ void wgmma_ss_tb(float (&d)[BN / 2], uint64_t dA, uint64_t dB, int sc) {
    if constexpr (BN == 64) wgmma_ss_n64_tb(d, dA, dB, sc);
    else if constexpr (BN == 80) wgmma_ss_n80_tb(d, dA, dB, sc);
    else wgmma_ss_n224_tb(d, dA, dB, sc);
}
__device__ __forceinline__ void wgmma_rs_n64_tb(float (&d)[32], uint32_t a, uint64_t dB, int sc) {
    asm volatile("{\n.reg .pred p;\nsetp.ne.b32 p, %34, 0;\n"
                 "wgmma.mma_async.sync.aligned.m64n64k16.f32.bf16.bf16 "
                 "{%0,%1,%2,%3,%4,%5,%6,%7,%8,%9,%10,%11,%12,%13,%14,%15,%16,%17,%18,%19,%20,%21,%22,%23,%24,%25,%26,%27,%28,%29,%30,%31}, "
                 "{%32,%32,%32,%32}, %33, p, 1, 1, 1;\n}\n"
                 : WG_REGS_32(0) : "r"(a), "l"(dB), "r"(sc));
}
__device__ __forceinline__ void wgmma_rs_n80_tb(float (&d)[40], uint32_t a, uint64_t dB, int sc) {
    asm volatile("{\n.reg .pred p;\nsetp.ne.b32 p, %42, 0;\n"
                 "wgmma.mma_async.sync.aligned.m64n80k16.f32.bf16.bf16 "
                 "{%0,%1,%2,%3,%4,%5,%6,%7,%8,%9,%10,%11,%12,%13,%14,%15,%16,%17,%18,%19,%20,%21,%22,%23,%24,%25,%26,%27,%28,%29,%30,%31,"
                 "%32,%33,%34,%35,%36,%37,%38,%39}, {%40,%40,%40,%40}, %41, p, 1, 1, 1;\n}\n"
                 : WG_REGS_32(0), WG_REGS_8(32) : "r"(a), "l"(dB), "r"(sc));
}
template <int BN> __device__ __forceinline__ void wgmma_rs_ones(float (&d)[BN / 2], uint64_t dB, int sc) {
    if constexpr (BN == 80) wgmma_rs_n80_tb(d, 0x3F803F80u, dB, sc);
    else if constexpr (BN == 64) wgmma_rs_n64_tb(d, 0x3F803F80u, dB, sc);
}
__device__ __forceinline__ void wgmma_rs_n64_z(float (&d)[32], uint32_t a0, uint32_t a1, uint32_t a2, uint32_t a3, uint64_t dB) {
    asm volatile("{\n.reg .pred p;\nsetp.ne.b32 p, 0, 0;\n"
                 "wgmma.mma_async.sync.aligned.m64n64k16.f32.bf16.bf16 "
                 "{%0,%1,%2,%3,%4,%5,%6,%7,%8,%9,%10,%11,%12,%13,%14,%15,%16,%17,%18,%19,%20,%21,%22,%23,%24,%25,%26,%27,%28,%29,%30,%31}, "
                 "{%32,%33,%34,%35}, %36, p, 1, 1, 0;\n}\n"
                 : "=f"(d[0]), "=f"(d[1]), "=f"(d[2]), "=f"(d[3]), "=f"(d[4]), "=f"(d[5]), "=f"(d[6]), "=f"(d[7]),
                   "=f"(d[8]), "=f"(d[9]), "=f"(d[10]), "=f"(d[11]), "=f"(d[12]), "=f"(d[13]), "=f"(d[14]), "=f"(d[15]),
                   "=f"(d[16]), "=f"(d[17]), "=f"(d[18]), "=f"(d[19]), "=f"(d[20]), "=f"(d[21]), "=f"(d[22]), "=f"(d[23]),
                   "=f"(d[24]), "=f"(d[25]), "=f"(d[26]), "=f"(d[27]), "=f"(d[28]), "=f"(d[29]), "=f"(d[30]), "=f"(d[31])
                 : "r"(a0), "r"(a1), "r"(a2), "r"(a3), "l"(dB));
}
__device__ __forceinline__ void wgmma_rs_n24_tb(float (&d)[12], uint32_t a0, uint32_t a1, uint32_t a2, uint32_t a3, uint64_t dB) {
    asm volatile("{\n.reg .pred p;\nsetp.eq.b32 p, 0, 0;\n"
                 "wgmma.mma_async.sync.aligned.m64n24k16.f32.bf16.bf16 "
                 "{%0,%1,%2,%3,%4,%5,%6,%7,%8,%9,%10,%11}, {%12,%13,%14,%15}, %16, p, 1, 1, 1;\n}\n"
                 : WG_REGS_8(0), WG_REGS_4(8) : "r"(a0), "r"(a1), "r"(a2), "r"(a3), "l"(dB));
}

constexpr int SIDE_CTAS = 4;
__device__ __forceinline__ void side_job(int cta, float* red  , const __nv_bfloat16* __restrict__ wo,
                                         const __nv_bfloat16* __restrict__ w1, const __nv_bfloat16* __restrict__ w2) {
    const int tid = threadIdx.x, warp = tid >> 5, lane = tid & 31;
    for (int line = cta * 512 + tid; line < 18432; line += SIDE_CTAS * 512) {
        const char* p = line < 4096 ? (const char*)wo + (size_t)line * 128 : (const char*)w2 + (size_t)(line - 4096) * 128;
        asm volatile("prefetch.global.L2 [%0];" ::"l"(p));
    }
    const int rg = lane >> 3, c8 = lane & 7;
    for (int slab = cta; slab < F_ / 64; slab += SIDE_CTAS) {
        const __nv_bfloat16* base = w1 + slab * 64 + c8 * 8;
        uint4 v[8];
#pragma unroll
        for (int i = 0; i < 8; i++) v[i] = __ldg((const uint4*)(base + (size_t)(warp * 32 + rg + 4 * i) * F_));
        float acc[8];
#pragma unroll
        for (int i = 0; i < 8; i++) acc[i] = 0.f;
#pragma unroll
        for (int i = 0; i < 8; i++) {
            acc[0] += bf_lo(v[i].x); acc[1] += bf_hi(v[i].x); acc[2] += bf_lo(v[i].y); acc[3] += bf_hi(v[i].y);
            acc[4] += bf_lo(v[i].z); acc[5] += bf_hi(v[i].z); acc[6] += bf_lo(v[i].w); acc[7] += bf_hi(v[i].w);
        }
#pragma unroll
        for (int i = 0; i < 8; i++) {
            acc[i] += __shfl_xor_sync(0xffffffffu, acc[i], 8);
            acc[i] += __shfl_xor_sync(0xffffffffu, acc[i], 16);
        }
        if (rg == 0) {
#pragma unroll
            for (int i = 0; i < 8; i++) red[warp * 64 + c8 * 8 + i] = acc[i];
        }
        __syncthreads();
        if (tid < 64) {
            float s = 0.f;
#pragma unroll
            for (int i = 0; i < 16; i++) s += red[i * 64 + tid];
            g_cs_1[slab * 64 + tid] = s;
        }
        __syncthreads();
    }
}

enum { EPI_QKV = 0, EPI_RES = 1, EPI_FFN1 = 2 };

struct GemmParams {
    const float2* stats_in;
    float2* stats_out;
    const __nv_bfloat16* wkv;
    const __nv_bfloat16* wv;
    int tk;
};

template <int BK_, int NBLK> struct Geo {
    static constexpr int BK = BK_, A_BYTES = 128 * BK * 2, A_SWZ = BK == 64 ? 1 : 2, A_SBO = BK * 16;
    static constexpr int BLK = BK * 64;
    static constexpr int B_BYTES = NBLK * BLK, B_SWZ = 2, B_LBO = BLK, B_SBO = 512, B_KSTEP = 1024;
};
template <> struct Geo<64, 0> {
    static constexpr int BK = 64, A_BYTES = 128 * 128, A_SWZ = 1, A_SBO = 1024, BLK = 8192;
    static constexpr int B_BYTES = 64 * 128, B_SWZ = 1, B_LBO = 8192, B_SBO = 1024, B_KSTEP = 2048;
};
template <int EPI> struct EpiGeo;
template <> struct EpiGeo<EPI_QKV> { using G = Geo<64, 3>; };
template <> struct EpiGeo<EPI_RES> { using G = Geo<64, 0>; };
template <> struct EpiGeo<EPI_FFN1> { using G = Geo<64, 7>; };

template <int STAGES, int EPI> struct GemmSmem {
    using G = typename EpiGeo<EPI>::G;
    static constexpr int STAGE = G::A_BYTES + G::B_BYTES;
    static constexpr int AUX_OFF = STAGES * STAGE;
    static constexpr int TOTAL = AUX_OFF + 1152;
    static constexpr int TOTAL_SELF = AUX_OFF + 704 + 1024;
};

struct RowStatRaw { float2 a0, a1, b0, b1; };
__device__ __forceinline__ RowStatRaw load_row_stats(const float2* __restrict__ st, int row0, int c) {
    RowStatRaw r;
    r.a0 = st[(2 * c) * S_ + row0]; r.a1 = st[(2 * c + 1) * S_ + row0];
    r.b0 = st[(2 * c) * S_ + row0 + 8]; r.b1 = st[(2 * c + 1) * S_ + row0 + 8];
    return r;
}
__device__ __forceinline__ void finish_row_stats(const RowStatRaw& r, float& mean0, float& rstd0, float& mean1, float& rstd1) {
    float sa = r.a0.x + r.a1.x, sb = r.b0.x + r.b1.x;
    sa += __shfl_xor_sync(0xffffffffu, sa, 1); sa += __shfl_xor_sync(0xffffffffu, sa, 2);
    sb += __shfl_xor_sync(0xffffffffu, sb, 1); sb += __shfl_xor_sync(0xffffffffu, sb, 2);
    mean0 = sa * 0.125f; mean1 = sb * 0.125f;
    float ma = r.a0.y + r.a1.y + 64.f * ((r.a0.x - mean0) * (r.a0.x - mean0) + (r.a1.x - mean0) * (r.a1.x - mean0));
    float mb = r.b0.y + r.b1.y + 64.f * ((r.b0.x - mean1) * (r.b0.x - mean1) + (r.b1.x - mean1) * (r.b1.x - mean1));
    ma += __shfl_xor_sync(0xffffffffu, ma, 1); ma += __shfl_xor_sync(0xffffffffu, ma, 2);
    mb += __shfl_xor_sync(0xffffffffu, mb, 1); mb += __shfl_xor_sync(0xffffffffu, mb, 2);
    rstd0 = 1.0f / sqrtf(ma * (1.f / 512.f) + 1e-5f);
    rstd1 = 1.0f / sqrtf(mb * (1.f / 512.f) + 1e-5f);
}

template <int BN, int KB, int STAGES, int EPI, bool SELF = false>
__device__ __forceinline__ void gemm_body(const CUtensorMap* mapA, const CUtensorMap* mapB, const CUtensorMap* mapR,
                                          const CUtensorMap* mapC, const GemmParams& prm, int tile_m, int tile_n, uint8_t* smem_raw) {
    using SM = GemmSmem<STAGES, EPI>;
    using G = typename SM::G;
    constexpr bool XKV = BN == 80;
    constexpr int TN = EPI == EPI_QKV ? 64 : BN;
    CP(prm.tk, 0);
    pdl_launch();
    const uint32_t sbase = smem_u32(smem_raw);
    if (sbase & 1023) __trap();
    uint8_t* sgen = smem_raw;
    const uint32_t bar_full = sbase + SM::AUX_OFF, bar_empty = bar_full + 8 * STAGES;
    float* s_cs = (float*)(sgen + SM::AUX_OFF + 256);
    float* s_row = (float*)(sgen + SM::AUX_OFF + 704);
    float* s_red = (float*)(sgen + SM::AUX_OFF + 640);
    const int tid = threadIdx.x, lane = tid & 31;
    const int warp = __shfl_sync(0xffffffffu, tid >> 5, 0);
    if (tid == 0) TL(prm.tk, 0);

    if (warp == 8 && elect_one()) {
#pragma unroll
        for (int s = 0; s < STAGES; s++) { mbar_init(bar_full + 8 * s, 1); mbar_init(bar_empty + 8 * s, 2); }
        fence_mbar_init();
    }
    if (warp == 1 && elect_one()) { prefetch_tmap(mapB); prefetch_tmap(mapA); prefetch_tmap(mapC); }
    CP(prm.tk, 1);
    __syncthreads();
    CP(prm.tk, 2);

    const int m0 = tile_m * 128, n0 = tile_n * TN;
    constexpr uint32_t STAGE_TX = G::A_BYTES + (EPI == EPI_QKV ? 2 * G::BLK : G::B_BYTES);
    auto loadB = [&](int kb, int s) {
        const uint32_t dst = sbase + s * SM::STAGE + G::A_BYTES, bar = bar_full + 8 * s;
        if constexpr (EPI == EPI_RES) {
            tma2d(dst, mapB, n0, kb * 64, bar);
        } else if constexpr (EPI == EPI_QKV) {
            tma3d(dst, mapB, 0, kb * G::BK, tile_n * 2, bar);
        } else {
            tma3d(dst, mapB, 0, kb * G::BK, tile_n * 7, bar);
        }
    };
    auto loadA = [&](int kb, int s) {
        const uint32_t dst = sbase + s * SM::STAGE, bar = bar_full + 8 * s;
        tma2d(dst, mapA, kb * G::BK, m0, bar);
    };
    constexpr int PRE = STAGES < KB ? STAGES : KB;
    constexpr int PRE_B = 1;
    auto prologue_loads = [&]() {
        if (elect_one()) {
#pragma unroll
            for (int kb = 0; kb < PRE; kb++) mbar_expect_tx(bar_full + 8 * kb, STAGE_TX);
        }
        if (elect_one()) {
#pragma unroll
            for (int kb = 0; kb < PRE_B; kb++) loadB(kb, kb);
        }
        CP(prm.tk, 5);
        if (!SELF) pdl_wait();
        CP(prm.tk, 6);
        if (elect_one()) {
#pragma unroll
            for (int kb = 0; kb < PRE; kb++) {
                loadA(kb, kb);
                if (kb + PRE_B < PRE) loadB(kb + PRE_B, kb + PRE_B);
            }
            if constexpr (EPI == EPI_RES && KB < STAGES) {
                mbar_expect_tx(bar_full + 8 * KB, 16384);
                tma2d(sbase + KB * SM::STAGE, mapR, n0, m0, bar_full + 8 * KB);
            }
        }
    };
    if (SELF && warp >= 8) {
        if (warp == 8) prologue_loads();
        static_assert(!SELF || (STAGES >= KB && EPI == EPI_QKV), "SELF needs every k block resident");
        if ((warp >> 2) == 3) {
            float csum[BN / 2];
            const uint64_t dB0 = mkdesc(sbase + G::A_BYTES, G::B_LBO, G::B_SBO, G::B_SWZ);
            if constexpr (XKV) named_bar(6, 384);
#pragma unroll 1
            for (int kb = 0; kb < KB; kb++) {
                mbar_wait(bar_full + 8 * kb, 0);
                const uint64_t dB = dB0 + (uint64_t)(kb * (SM::STAGE >> 4));
                wg_fence();
#pragma unroll
                for (int k = 0; k < G::BK / 16; k++) {
                    if constexpr (SELF) wgmma_rs_ones<BN>(csum, dB + (uint64_t)(k * (G::B_KSTEP >> 4)), (kb | k) != 0);
                }
                wg_commit();
            }
            wg_wait<0>();
            fence_regs(csum);
            if (warp == 12 && lane < 4) {
#pragma unroll
                for (int j = 0; j < BN / 8; j++) {
                    const float2 v = make_float2(csum[4 * j], csum[4 * j + 1]);
                    *(float2*)(s_cs + 8 * j + 2 * lane) = v;
                    if (tile_m == 0) {
                        if (j < 8) *(float2*)(g_cs_q + n0 + 8 * j + 2 * lane) = v;
                        else *(float2*)(g_cs_kv + tile_n * 16 + 8 * (j - 8) + 2 * lane) = v;
                    }
                }
            }
        } else {
            const int t = (warp < 12 ? warp - 8 : warp - 12) * 32 + lane;
            float ss[4] = {0.f, 0.f, 0.f, 0.f}, sq[4] = {0.f, 0.f, 0.f, 0.f};
#pragma unroll 1
            for (int kb = 0; kb < KB; kb++) {
                mbar_wait(bar_full + 8 * kb, 0);
                const uint32_t arow = sbase + kb * SM::STAGE + (t >> 1) * 128;
                uint32_t w[4][4];
#pragma unroll
                for (int j = 0; j < 4; j++)
                    asm volatile("ld.shared.v4.u32 {%0,%1,%2,%3}, [%4];" : "=r"(w[j][0]), "=r"(w[j][1]), "=r"(w[j][2]), "=r"(w[j][3])
                                 : "r"(arow + (((2 * j + (t & 1) + 2 * ((t >> 1) & 3)) & 7) << 4)));
#pragma unroll
                for (int j = 0; j < 4; j++)
#pragma unroll
                    for (int i = 0; i < 4; i++) {
                        const float lo = bf_lo(w[j][i]), hi = bf_hi(w[j][i]);
                        ss[i] += lo + hi;
                        sq[i] = fmaf(lo, lo, fmaf(hi, hi, sq[i]));
                    }
            }
            float tsum = (ss[0] + ss[1]) + (ss[2] + ss[3]), tsq = (sq[0] + sq[1]) + (sq[2] + sq[3]);
            tsum += __shfl_xor_sync(0xffffffffu, tsum, 1);
            tsq += __shfl_xor_sync(0xffffffffu, tsq, 1);
            if ((t & 1) == 0) {
                const float md = tsum * (1.f / 512.f);
                const float var = fmaxf(tsq * (1.f / 512.f) - md * md, 0.f);
                *(float2*)(s_row + t) = make_float2(md, 1.0f / sqrtf(var + 1e-5f));
            }
        }
        named_bar(4, 640);
    } else if (warp == 8) {
        prologue_loads();
        int s = PRE % STAGES, ph = (PRE / STAGES) & 1;
#pragma unroll 1
        for (int kb = PRE; kb < KB; kb++) {
            mbar_wait(bar_empty + 8 * s, ph ^ 1);
            if (elect_one()) {
                mbar_expect_tx(bar_full + 8 * s, STAGE_TX);
                loadB(kb, s);
                loadA(kb, s);
            }
            if (++s == STAGES) { s = 0; ph ^= 1; }
        }
        if constexpr (EPI == EPI_RES && KB >= STAGES) {
            mbar_wait(bar_empty + 8 * s, ph ^ 1);
            if (elect_one()) {
                mbar_expect_tx(bar_full + 8 * s, 16384);
                tma2d(sbase + s * SM::STAGE, mapR, n0, m0, bar_full + 8 * s);
            }
        }
    } else {
        const int wg = warp >> 2, g = lane >> 2, c = lane & 3;
        const int rloc = wg * 64 + (warp & 3) * 16 + g;
        const int row0 = m0 + rloc;
        float mean0 = 0.f, rstd0 = 1.f, mean1 = 0.f, rstd1 = 1.f;
        if constexpr (XKV) {
            static_assert(!XKV || STAGES >= KB, "the K / V weight block must stay resident");
            const __nv_bfloat16* wsrc = tile_n == 0 ? prm.wkv : prm.wv;
            uint4 v[4];
#pragma unroll
            for (int i = 0; i < 4; i++) v[i] = __ldg((const uint4*)wsrc + tid + 256 * i);
#pragma unroll
            for (int i = 0; i < 4; i++) {
                const int idx = tid + 256 * i, k = idx >> 1, kr = k & 63;
                const uint32_t dst = sbase + (k >> 6) * SM::STAGE + G::A_BYTES + 2 * G::BLK + kr * 64 + (((idx & 1) ^ ((kr >> 1) & 3)) << 4);
                asm volatile("st.shared.v4.u32 [%0], {%1,%2,%3,%4};" ::"r"(dst), "r"(v[i].x), "r"(v[i].y), "r"(v[i].z), "r"(v[i].w) : "memory");
            }
            fence_async_smem();
            if constexpr (SELF) named_bar(6, 384); else named_bar(6, 256);
        }
        RowStatRaw raw;
        float csv = 0.f;
        float2 cskv[2] = {make_float2(0.f, 0.f), make_float2(0.f, 0.f)};
        auto ln_inputs = [&]() {
            pdl_wait();
            if constexpr (EPI != EPI_RES) {
                raw = load_row_stats(prm.stats_in, row0, c);
                const float* cs = EPI == EPI_FFN1 ? g_cs_1 + n0 : g_cs_q + n0;
                if (tid < TN) csv = cs[tid];
                if constexpr (XKV) {
                    cskv[0] = *(const float2*)(g_cs_kv + tile_n * 16 + 2 * c);
                    cskv[1] = *(const float2*)(g_cs_kv + tile_n * 16 + 8 + 2 * c);
                }
            }
        };
        if (!SELF) ln_inputs();
        float acc[BN / 2];
        const uint64_t dA0 = mkdesc(sbase + wg * (G::A_BYTES / 2), 16, G::A_SBO, G::A_SWZ);
        const uint64_t dB0 = mkdesc(sbase + G::A_BYTES, G::B_LBO, G::B_SBO, G::B_SWZ);
        int s = 0, ph = 0;
#pragma unroll 1
        for (int kb = 0; kb < KB; kb++) {
            mbar_wait(bar_full + 8 * s, ph);
            const uint64_t dA = dA0 + (uint64_t)(s * (SM::STAGE >> 4)), dB = dB0 + (uint64_t)(s * (SM::STAGE >> 4));
            wg_fence();
#pragma unroll
            for (int k = 0; k < G::BK / 16; k++) wgmma_ss_tb<BN>(acc, dA + (uint64_t)(k * 2), dB + (uint64_t)(k * (G::B_KSTEP >> 4)), (kb | k) != 0);
            wg_commit();
            if (kb > 0) {
                wg_wait<1>();
                const int sp = s == 0 ? STAGES - 1 : s - 1;
                if ((warp & 3) == 0 && elect_one()) mbar_arrive(bar_empty + 8 * sp);
            }
            if (++s == STAGES) { s = 0; ph ^= 1; }
        }
        if constexpr (SELF) {
            named_bar(4, 640);
            const float2 r0 = *(const float2*)(s_row + 2 * rloc), r1 = *(const float2*)(s_row + 2 * rloc + 16);
            mean0 = r0.x; rstd0 = r0.y; mean1 = r1.x; rstd1 = r1.y;
        } else if constexpr (EPI != EPI_RES) {
            finish_row_stats(raw, mean0, rstd0, mean1, rstd1);
            if (tid < TN) s_cs[tid] = csv;
        }
        wg_wait<0>();
        fence_regs(acc);
        if (tid == 0) TL(prm.tk, 2);
        if constexpr (EPI != EPI_RES) named_bar(1, 256);

        if constexpr (EPI != EPI_FFN1) {
            const uint32_t stile = sbase + (EPI == EPI_RES ? s * SM::STAGE : 0);
            const int mrow = wg * 64 + (warp & 3) * 16 + (lane & 7) + ((lane >> 3) & 1) * 8;
            const uint32_t rbase = stile + mrow * 128;
            if constexpr (EPI == EPI_RES) {
                mbar_wait(bar_full + 8 * s, ph);
                float s0 = 0.f, s1 = 0.f;
#pragma unroll
                for (int jj = 0; jj < 4; jj++) {
                    uint32_t r0, r1, r2, r3;
                    const uint32_t addr = rbase + (((2 * jj + (lane >> 4)) ^ (mrow & 7)) << 4);
                    ldsm_x4(r0, r1, r2, r3, addr);
                    const uint32_t u0 = pack_bf16(acc[8 * jj] + bf_lo(r0), acc[8 * jj + 1] + bf_hi(r0));
                    const uint32_t u1 = pack_bf16(acc[8 * jj + 2] + bf_lo(r1), acc[8 * jj + 3] + bf_hi(r1));
                    const uint32_t u2 = pack_bf16(acc[8 * jj + 4] + bf_lo(r2), acc[8 * jj + 5] + bf_hi(r2));
                    const uint32_t u3 = pack_bf16(acc[8 * jj + 6] + bf_lo(r3), acc[8 * jj + 7] + bf_hi(r3));
                    stsm_x4(addr, u0, u1, u2, u3);
                    acc[8 * jj] = bf_lo(u0); acc[8 * jj + 1] = bf_hi(u0); acc[8 * jj + 4] = bf_lo(u2); acc[8 * jj + 5] = bf_hi(u2);
                    acc[8 * jj + 2] = bf_lo(u1); acc[8 * jj + 3] = bf_hi(u1); acc[8 * jj + 6] = bf_lo(u3); acc[8 * jj + 7] = bf_hi(u3);
                    s0 += (acc[8 * jj] + acc[8 * jj + 1]) + (acc[8 * jj + 4] + acc[8 * jj + 5]);
                    s1 += (acc[8 * jj + 2] + acc[8 * jj + 3]) + (acc[8 * jj + 6] + acc[8 * jj + 7]);
                }
                fence_async_smem();
                named_bar(2 + wg, 128);
                if ((warp & 3) == 0 && elect_one()) { tma2d_store(mapC, stile + wg * 8192, n0, m0 + wg * 64); bulk_commit(); }
                if (prm.stats_out) {
                    s0 += __shfl_xor_sync(0xffffffffu, s0, 1); s0 += __shfl_xor_sync(0xffffffffu, s0, 2);
                    s1 += __shfl_xor_sync(0xffffffffu, s1, 1); s1 += __shfl_xor_sync(0xffffffffu, s1, 2);
                    const float mu0 = s0 * (1.f / 64.f), mu1 = s1 * (1.f / 64.f);
                    float q0 = 0.f, q1 = 0.f;
#pragma unroll
                    for (int j = 0; j < 8; j++) {
                        float d;
                        d = acc[4 * j] - mu0; q0 += d * d; d = acc[4 * j + 1] - mu0; q0 += d * d;
                        d = acc[4 * j + 2] - mu1; q1 += d * d; d = acc[4 * j + 3] - mu1; q1 += d * d;
                    }
                    q0 += __shfl_xor_sync(0xffffffffu, q0, 1); q0 += __shfl_xor_sync(0xffffffffu, q0, 2);
                    q1 += __shfl_xor_sync(0xffffffffu, q1, 1); q1 += __shfl_xor_sync(0xffffffffu, q1, 2);
                    if (c == 0) {
                        prm.stats_out[tile_n * S_ + row0] = make_float2(mu0, q0);
                        prm.stats_out[tile_n * S_ + row0 + 8] = make_float2(mu1, q1);
                    }
                }
            } else {
                const float sc = 0.25f * 1.4426950408889634f;
                const float a0 = rstd0 * sc, a1 = rstd1 * sc, rm0 = a0 * mean0, rm1 = a1 * mean1;
#pragma unroll
                for (int jj = 0; jj < 4; jj++) {
                    const float2 ca = *(const float2*)(s_cs + 16 * jj + 2 * c), cb = *(const float2*)(s_cs + 16 * jj + 8 + 2 * c);
                    const uint32_t u0 = pack_bf16(acc[8 * jj] * a0 - rm0 * ca.x, acc[8 * jj + 1] * a0 - rm0 * ca.y);
                    const uint32_t u1 = pack_bf16(acc[8 * jj + 2] * a1 - rm1 * ca.x, acc[8 * jj + 3] * a1 - rm1 * ca.y);
                    const uint32_t u2 = pack_bf16(acc[8 * jj + 4] * a0 - rm0 * cb.x, acc[8 * jj + 5] * a0 - rm0 * cb.y);
                    const uint32_t u3 = pack_bf16(acc[8 * jj + 6] * a1 - rm1 * cb.x, acc[8 * jj + 7] * a1 - rm1 * cb.y);
                    stsm_x4(rbase + (((2 * jj + (lane >> 4)) ^ (mrow & 7)) << 4), u0, u1, u2, u3);
                }
                fence_async_smem();
                named_bar(2 + wg, 128);
                if ((warp & 3) == 0 && elect_one()) { tma2d_store(mapC, stile + wg * 8192, n0, m0 + wg * 64); bulk_commit(); }
            }
            if constexpr (XKV) {
                {
                    const float* acx = &acc[32];
                    const float rm0 = rstd0 * mean0, rm1 = rstd1 * mean1;
                    float n0s = 0.f, n1s = 0.f, vmax = 0.f;
#pragma unroll
                    for (int j = 0; j < 2; j++) {
                        const float2 cs2 = SELF ? *(const float2*)(s_cs + 64 + 8 * j + 2 * c) : cskv[j];
                        const uint32_t u0 = pack_bf16(acx[4 * j] * rstd0 - rm0 * cs2.x, acx[4 * j + 1] * rstd0 - rm0 * cs2.y);
                        const uint32_t u1 = pack_bf16(acx[4 * j + 2] * rstd1 - rm1 * cs2.x, acx[4 * j + 3] * rstd1 - rm1 * cs2.y);
                        n0s += bf_lo(u0) * bf_lo(u0) + bf_hi(u0) * bf_hi(u0);
                        n1s += bf_lo(u1) * bf_lo(u1) + bf_hi(u1) * bf_hi(u1);
                        vmax = fmaxf(vmax, fmaxf(fmaxf(fabsf(bf_lo(u0)), fabsf(bf_hi(u0))), fmaxf(fabsf(bf_lo(u1)), fabsf(bf_hi(u1)))));
                        if (tile_n == 0) {
                            *(uint32_t*)(g_kimg + (row0 >> 3) * 256 + j * 128 + g * 16 + c * 4) = u0;
                            *(uint32_t*)(g_kimg + ((row0 + 8) >> 3) * 256 + j * 128 + g * 16 + c * 4) = u1;
                        } else {
                            uint8_t* vb = g_vimg + (row0 >> 4) * 768 + j * 256 + g * 16 + c * 4;
                            *(uint32_t*)(vb) = u0;
                            *(uint32_t*)(vb + 128) = u1;
                        }
                    }
                    if (tile_n == 1) {
                        uint8_t* vb = g_vimg + (row0 >> 4) * 768 + 512 + g * 16 + c * 4;
                        const uint32_t one = c == 0 ? 0x00003F80u : 0u;
                        *(uint32_t*)(vb) = one;
                        *(uint32_t*)(vb + 128) = one;
                    }
                    n0s += __shfl_xor_sync(0xffffffffu, n0s, 1); n0s += __shfl_xor_sync(0xffffffffu, n0s, 2);
                    n1s += __shfl_xor_sync(0xffffffffu, n1s, 1); n1s += __shfl_xor_sync(0xffffffffu, n1s, 2);
                    float km = tile_n == 0 ? fmaxf(n0s, n1s) : vmax;
                    if (!(n0s + n1s < INFINITY)) km = INFINITY;
#pragma unroll
                    for (int o = 1; o < 32; o <<= 1) km = fmaxf(km, __shfl_xor_sync(0xffffffffu, km, o));
                    if (lane == 0) s_red[warp] = km;
                    named_bar(1, 256);
                    if (tid == 0) {
                        float a = 0.f;
                        for (int i = 0; i < 8; i++) a = fmaxf(a, s_red[i]);
                        g_kvmax[tile_n * 16 + tile_m] = a;
                    }
                }
            }
            if ((warp & 3) == 0) bulk_wait_read();
        } else {
            const uint32_t stile = sbase + wg * (7 * 4096);
            const int mrow = (warp & 3) * 16 + (lane & 7) + ((lane >> 3) & 1) * 8;
            const float a0 = 0.5f * rstd0, a1 = 0.5f * rstd1, rm0 = a0 * mean0, rm1 = a1 * mean1;
#pragma unroll
            for (int jj = 0; jj < 14; jj++) {
                const float2 ca = *(const float2*)(s_cs + 16 * jj + 2 * c), cb = *(const float2*)(s_cs + 16 * jj + 8 + 2 * c);
                float y[8] = {acc[8 * jj] * a0 - rm0 * ca.x,     acc[8 * jj + 1] * a0 - rm0 * ca.y,
                              acc[8 * jj + 2] * a1 - rm1 * ca.x, acc[8 * jj + 3] * a1 - rm1 * ca.y,
                              acc[8 * jj + 4] * a0 - rm0 * cb.x, acc[8 * jj + 5] * a0 - rm0 * cb.y,
                              acc[8 * jj + 6] * a1 - rm1 * cb.x, acc[8 * jj + 7] * a1 - rm1 * cb.y};
#pragma unroll
                for (int i = 0; i < 8; i++) {
                    float t;
                    asm("tanh.approx.f32 %0, %1;" : "=f"(t) : "f"(y[i]));
                    y[i] = fmaf(y[i], t, y[i]);
                }
                const int chunk = (2 * jj + (lane >> 4)) & 3, blk = jj >> 1;
                stsm_x4(stile + blk * 4096 + mrow * 64 + ((chunk ^ ((mrow >> 1) & 3)) << 4),
                        pack_bf16(y[0], y[1]), pack_bf16(y[2], y[3]), pack_bf16(y[4], y[5]), pack_bf16(y[6], y[7]));
                if (jj & 1) {
                    fence_async_smem();
                    __syncwarp();
                    if (elect_one()) {
                        tma2d_store(mapC, stile + blk * 4096 + (warp & 3) * 1024, n0 + blk * 32, m0 + wg * 64 + (warp & 3) * 16);
                        bulk_commit();
                    }
                }
            }
            bulk_wait_read();
        }
    }
    if (tid == 0) TL(prm.tk, 3);
}

#define WO_ST 9
#define F2_ST 6
#define F1_ST 5
#define QKV_ST 8
constexpr int QKV_STAGES = QKV_ST, WO_STAGES = WO_ST, FFN2_STAGES = F2_ST, FFN1_STAGES = F1_ST;
template <bool SELF>
__global__ void __launch_bounds__(SELF ? 640 : 288) qkv_kernel(const __grid_constant__ CUtensorMap mapA, const __grid_constant__ CUtensorMap mapWq,
                                                  const __grid_constant__ CUtensorMap mapQ, const GemmParams prm) {
    extern __shared__ __align__(1024) uint8_t smem_raw[];
    const int tn = blockIdx.x & 7;
    if (tn < 2) gemm_body<80, 8, QKV_STAGES, EPI_QKV, SELF>(&mapA, &mapWq, &mapA, &mapQ, prm, blockIdx.x >> 3, tn, smem_raw);
    else gemm_body<64, 8, QKV_STAGES, EPI_QKV, SELF>(&mapA, &mapWq, &mapA, &mapQ, prm, blockIdx.x >> 3, tn, smem_raw);
}
template <int KB, int STAGES>
__global__ void __launch_bounds__(288) res_gemm_kernel(const __grid_constant__ CUtensorMap mapA, const __grid_constant__ CUtensorMap mapW,
                                                       const __grid_constant__ CUtensorMap mapR, const __grid_constant__ CUtensorMap mapC, const GemmParams prm) {
    extern __shared__ __align__(1024) uint8_t smem_raw[];
    gemm_body<64, KB, STAGES, EPI_RES>(&mapA, &mapW, &mapR, &mapC, prm, blockIdx.x >> 3, blockIdx.x & 7, smem_raw);
}
__global__ void __launch_bounds__(288) ffn1_kernel(const __grid_constant__ CUtensorMap mapA, const __grid_constant__ CUtensorMap mapW,
                                                   const __grid_constant__ CUtensorMap mapH, const GemmParams prm) {
    extern __shared__ __align__(1024) uint8_t smem_raw[];
    gemm_body<224, 8, FFN1_STAGES, EPI_FFN1>(&mapA, &mapW, &mapA, &mapH, prm, blockIdx.x >> 3, blockIdx.x & 7, smem_raw);
}

#define ATT_NPOLY 11
constexpr int NPOLY = ATT_NPOLY;
__host__ __device__ constexpr bool is_mufu(int i) { return ((i + 1) * (16 - NPOLY)) / 16 != (i * (16 - NPOLY)) / 16; }

__device__ __forceinline__ float ex2(float x) { float r; asm("ex2.approx.ftz.f32 %0, %1;" : "=f"(r) : "f"(x)); return r; }
__device__ __forceinline__ uint32_t exp_pair_mufu(float a, float b) { return pack_bf16(ex2(a), ex2(b)); }
__device__ __forceinline__ uint32_t exp_pair_fma(float a, float b, uint32_t c3f) {
    constexpr float MAGIC = 98430.4140625f;
    const float ta = a + MAGIC, tb = b + (MAGIC - 143.5f);
    uint32_t y, m, r;
    asm("mad.lo.u32 %0, %1, 65536, %2;" : "=r"(y) : "r"(__float_as_uint(tb)), "r"(__float_as_uint(ta)));
    asm("lop3.b32 %0, %1, 0x007F007F, %2, 0xEA;" : "=r"(m) : "r"(y), "r"(c3f));
    const uint32_t e = y & 0xFF80FF80u;
    asm("fma.rn.bf16x2 %0, %1, %2, %3;" : "=r"(r) : "r"(y), "r"(m), "r"(e));
    return r;
}

constexpr int KCH = 256, NCH = S_ / KCH;
constexpr int K_BYTES = S_ * 32, V_BYTES = (S_ / 16) * 768;
constexpr int QO_BYTES = 128 * 128;
constexpr int ATT_SMEM = K_BYTES + V_BYTES + QO_BYTES;

__global__ void __launch_bounds__(512, 1) attn_kernel(const __grid_constant__ CUtensorMap mapQ, const __grid_constant__ CUtensorMap mapO,
                                                       const __nv_bfloat16* __restrict__ wo, const __nv_bfloat16* __restrict__ w1,
                                                       const __nv_bfloat16* __restrict__ w2, int tk) {
    extern __shared__ __align__(1024) uint8_t smem[];
    __shared__ uint64_t bars[NCH + 1];
    __shared__ int s_slow;
    const int tid = threadIdx.x, wg = tid >> 7, warp = (tid >> 5) & 3, lane = tid & 31;
    const uint32_t sK = smem_u32(smem), sV = sK + K_BYTES, sQ = sV + V_BYTES;
    if (blockIdx.x >= 128) {
        pdl_launch();
        pdl_wait();
        side_job(blockIdx.x - 128, (float*)smem, wo, w1, w2);
        return;
    }
    CK(tk, 9);
    if (tid == 0) TL(tk, 0);
    if (tid == 0) {
#pragma unroll
        for (int i = 0; i <= NCH; i++) mbar_init(smem_u32(&bars[i]), 1);
        s_slow = 0;
        fence_mbar_init();
    }
    if (tid == 32) { prefetch_tmap(&mapQ); prefetch_tmap(&mapO); }
    __syncthreads();
    pdl_launch();
    CK(tk, 10);
    pdl_wait();
    CK(tk, 11);
    if (tid == 0) TL(tk, 1);
    const int wu = __shfl_sync(0xffffffffu, tid >> 5, 0);
    auto fetch_chunk = [&](int w) {
        if (elect_one()) {
            const uint32_t bar = smem_u32(&bars[w]);
            mbar_expect_tx(bar, KCH * 32 + (KCH / 16) * 768);
            bulk_load(sK + w * KCH * 32, g_kimg + w * KCH * 32, KCH * 32, bar);
            bulk_load(sV + w * (KCH / 16) * 768, g_vimg + w * (KCH / 16) * 768, (KCH / 16) * 768, bar);
        }
    };
    const int tb = blockIdx.x >> 3, hg = blockIdx.x & 7;
    if (wu == 1 && elect_one()) {
        mbar_expect_tx(smem_u32(&bars[NCH]), QO_BYTES);
        tma2d(sQ, &mapQ, hg * 64, tb * 128, smem_u32(&bars[NCH]));
    }
    if (wu == 0) fetch_chunk(0);
    float kvm = g_kvmax[lane];
    const int lrow = warp * 16 + (lane & 7) + ((lane >> 3) & 1) * 8;
    const uint32_t qoff = lrow * 128 + (((2 * wg + (lane >> 4)) ^ (lrow & 7)) << 4);
    uint32_t qa[2][4];
    mbar_wait(smem_u32(&bars[NCH]), 0);
    ldsm_x4(qa[0][0], qa[0][1], qa[0][2], qa[0][3], sQ + qoff);
    ldsm_x4(qa[1][0], qa[1][1], qa[1][2], qa[1][3], sQ + 8192 + qoff);
    CK(tk, 12);
    {
        float qn = 0.f;
#pragma unroll
        for (int m = 0; m < 2; m++) {
            float n0 = bf_lo(qa[m][0]) * bf_lo(qa[m][0]) + bf_hi(qa[m][0]) * bf_hi(qa[m][0]) + bf_lo(qa[m][2]) * bf_lo(qa[m][2]) + bf_hi(qa[m][2]) * bf_hi(qa[m][2]);
            float n1 = bf_lo(qa[m][1]) * bf_lo(qa[m][1]) + bf_hi(qa[m][1]) * bf_hi(qa[m][1]) + bf_lo(qa[m][3]) * bf_lo(qa[m][3]) + bf_hi(qa[m][3]) * bf_hi(qa[m][3]);
            n0 += __shfl_xor_sync(0xffffffffu, n0, 1); n0 += __shfl_xor_sync(0xffffffffu, n0, 2);
            n1 += __shfl_xor_sync(0xffffffffu, n1, 1); n1 += __shfl_xor_sync(0xffffffffu, n1, 2);
            if (!(n0 == n0) || !(n1 == n1)) n0 = INFINITY;
            qn = fmaxf(qn, fmaxf(n0, n1));
        }
        CK(tk, 13);
#pragma unroll
        for (int o = 1; o < 16; o <<= 1) kvm = fmaxf(kvm, __shfl_xor_sync(0xffffffffu, kvm, o));
        const float km = __shfl_sync(0xffffffffu, kvm, 0), vm = __shfl_sync(0xffffffffu, kvm, 16);
        const bool ok = (qn * km <= 10000.f) && (vm <= 16384.f);
        if (!ok) s_slow = 1;
    }
    CK(tk, 14);
    float oacc[2][12];
#pragma unroll
    for (int m = 0; m < 2; m++)
#pragma unroll
        for (int i = 0; i < 12; i++) oacc[m][i] = 0.f;
    __syncthreads();
    const bool slow = s_slow != 0;
    if (wu >= 1 && wu < NCH) fetch_chunk(wu);
    CK(tk, 15);

    const uint64_t dK0 = mkdesc(sK, 128, 256, 0);
    const uint64_t dV0 = mkdesc(sV, 128, 256, 0);
    uint32_t c3f;
    asm volatile("mov.b32 %0, 0x3F003F00;" : "=r"(c3f));
    if (!slow) {
        uint64_t dK = dK0, dV = dV0;
        float s[32];
        fence_regs(oacc[0]); fence_regs(oacc[1]);
        mbar_wait(smem_u32(&bars[0]), 0);
        wg_fence();
        wgmma_rs_n64_z(s, qa[0][0], qa[0][1], qa[0][2], qa[0][3], dK);
        wg_commit();
#pragma unroll 1
        for (int ch = 0; ch < NCH; ch++) {
#pragma unroll
            for (int tt = 0; tt < KCH / 64; tt++) {
#pragma unroll
                for (int m = 0; m < 2; m++) {
                    wg_wait<0>();
                    fence_regs(s);
                    uint32_t p[16];
#pragma unroll
                    for (int i = 0; i < 16; i++) p[i] = is_mufu(i) ? exp_pair_mufu(s[2 * i], s[2 * i + 1]) : exp_pair_fma(s[2 * i], s[2 * i + 1], c3f);
                    if (m == 1 && tt == KCH / 64 - 1) mbar_wait(smem_u32(&bars[ch + 1 < NCH ? ch + 1 : ch]), 0);
                    wg_fence();
#pragma unroll
                    for (int kk = 0; kk < 4; kk++)
                        wgmma_rs_n24_tb(oacc[m], p[4 * kk], p[4 * kk + 1], p[4 * kk + 2], p[4 * kk + 3], dV + (uint64_t)((tt * 4 + kk) * (768 / 16)));
                    wgmma_rs_n64_z(s, qa[1 - m][0], qa[1 - m][1], qa[1 - m][2], qa[1 - m][3], dK + (uint64_t)((tt + m) * (64 * 32 / 16)));
                    wg_commit();
                }
            }
            dK += KCH * 32 / 16;
            dV += (KCH / 16) * (768 / 16);
        }
        wg_wait<0>();
        fence_regs(s);
    } else {
        float mx[2][2] = {{-INFINITY, -INFINITY}, {-INFINITY, -INFINITY}};
#pragma unroll 1
        for (int t = 0; t < S_ / 64; t++) {
            if ((t & 3) == 0) mbar_wait(smem_u32(&bars[t >> 2]), 0);
            const uint64_t dK = dK0 + (uint64_t)(t * 64 * 32 / 16);
            const uint64_t dV = dV0 + (uint64_t)(t * 4 * 768 / 16);
#pragma unroll
            for (int m = 0; m < 2; m++) {
                float s[32];
                wg_fence();
                wgmma_rs_n64_z(s, qa[m][0], qa[m][1], qa[m][2], qa[m][3], dK);
                wg_commit();
                wg_wait<0>();
                fence_regs(s);
                fence_regs(oacc[m]);
                float r0 = mx[m][0], r1 = mx[m][1];
#pragma unroll
                for (int j = 0; j < 8; j++) {
                    r0 = fmaxf(r0, fmaxf(s[4 * j], s[4 * j + 1]));
                    r1 = fmaxf(r1, fmaxf(s[4 * j + 2], s[4 * j + 3]));
                }
                r0 = fmaxf(r0, __shfl_xor_sync(0xffffffffu, r0, 1)); r0 = fmaxf(r0, __shfl_xor_sync(0xffffffffu, r0, 2));
                r1 = fmaxf(r1, __shfl_xor_sync(0xffffffffu, r1, 1)); r1 = fmaxf(r1, __shfl_xor_sync(0xffffffffu, r1, 2));
                const float al0 = ex2(mx[m][0] - r0), al1 = ex2(mx[m][1] - r1);
                mx[m][0] = r0; mx[m][1] = r1;
#pragma unroll
                for (int j = 0; j < 3; j++) {
                    oacc[m][4 * j] *= al0; oacc[m][4 * j + 1] *= al0;
                    oacc[m][4 * j + 2] *= al1; oacc[m][4 * j + 3] *= al1;
                }
                uint32_t p[16];
#pragma unroll
                for (int j = 0; j < 8; j++) {
                    p[2 * j] = pack_bf16(ex2(s[4 * j] - r0), ex2(s[4 * j + 1] - r0));
                    p[2 * j + 1] = pack_bf16(ex2(s[4 * j + 2] - r1), ex2(s[4 * j + 3] - r1));
                }
                fence_regs(oacc[m]);
                wg_fence();
#pragma unroll
                for (int kk = 0; kk < 4; kk++)
                    wgmma_rs_n24_tb(oacc[m], p[4 * kk], p[4 * kk + 1], p[4 * kk + 2], p[4 * kk + 3], dV + (uint64_t)(kk * 768 / 16));
                wg_commit();
                wg_wait<0>();
            }
        }
    }
    fence_regs(oacc[0]); fence_regs(oacc[1]);
    if (tid == 0) TL(tk, 2);
#pragma unroll
    for (int m = 0; m < 2; m++) {
        const float l0 = __shfl_sync(0xffffffffu, oacc[m][8], lane & ~3);
        const float l1 = __shfl_sync(0xffffffffu, oacc[m][10], lane & ~3);
        const float r0 = __fdividef(1.0f, l0), r1 = __fdividef(1.0f, l1);
        stsm_x4(sQ + m * 8192 + qoff, pack_bf16(oacc[m][0] * r0, oacc[m][1] * r0), pack_bf16(oacc[m][2] * r1, oacc[m][3] * r1),
                pack_bf16(oacc[m][4] * r0, oacc[m][5] * r0), pack_bf16(oacc[m][6] * r1, oacc[m][7] * r1));
    }
    fence_async_smem();
    __syncthreads();
    if (wu == 0 && elect_one()) {
        tma2d_store(&mapO, sQ, hg * 64, tb * 128);
        bulk_commit();
        bulk_wait_read();
    }
    if (tid == 0) TL(tk, 3);
}

typedef CUresult (*EncodeFn)(CUtensorMap*, CUtensorMapDataType, cuuint32_t, void*, const cuuint64_t*, const cuuint64_t*, const cuuint32_t*,
                             const cuuint32_t*, CUtensorMapInterleave, CUtensorMapSwizzle, CUtensorMapL2promotion, CUtensorMapFloatOOBfill);

EncodeFn get_encode() {
    static EncodeFn fn = nullptr;
    if (!fn) {
        void* p = nullptr;
        cudaDriverEntryPointQueryResult qr;
        cudaGetDriverEntryPoint("cuTensorMapEncodeTiled", &p, cudaEnableDefault, &qr);
        fn = (EncodeFn)p;
    }
    return fn;
}
CUtensorMap map2d(const void* ptr, uint64_t cols, uint64_t rows, uint32_t bc, uint32_t br, CUtensorMapSwizzle sw) {
    CUtensorMap m;
    cuuint64_t gd[2] = {cols, rows}, gs[1] = {cols * 2};
    cuuint32_t bx[2] = {bc, br}, es[2] = {1, 1};
    get_encode()(&m, CU_TENSOR_MAP_DATA_TYPE_BFLOAT16, 2, (void*)ptr, gd, gs, bx, es, CU_TENSOR_MAP_INTERLEAVE_NONE, sw,
                 CU_TENSOR_MAP_L2_PROMOTION_L2_128B, CU_TENSOR_MAP_FLOAT_OOB_FILL_NONE);
    return m;
}
CUtensorMap map3d32(const void* ptr, uint64_t cols, uint64_t rows, uint32_t br, uint32_t nb) {
    CUtensorMap m;
    cuuint64_t gd[3] = {32, rows, cols / 32}, gs[2] = {cols * 2, 64};
    cuuint32_t bx[3] = {32, br, nb}, es[3] = {1, 1, 1};
    get_encode()(&m, CU_TENSOR_MAP_DATA_TYPE_BFLOAT16, 3, (void*)ptr, gd, gs, bx, es, CU_TENSOR_MAP_INTERLEAVE_NONE, CU_TENSOR_MAP_SWIZZLE_64B,
                 CU_TENSOR_MAP_L2_PROMOTION_L2_128B, CU_TENSOR_MAP_FLOAT_OOB_FILL_NONE);
    return m;
}

template <typename... KArgs, typename... Args>
void launch(void (*kern)(KArgs...), int grid, int block, int smem, int cluster, bool pdl, Args... args) {
    cudaLaunchConfig_t cfg = {};
    cfg.gridDim = dim3(grid);
    cfg.blockDim = dim3(block);
    cfg.dynamicSmemBytes = smem;
    cfg.stream = cudaStreamPerThread;
    cudaLaunchAttribute at[2];
    int n = 0;
    if (cluster > 1) { at[n].id = cudaLaunchAttributeClusterDimension; at[n].val.clusterDim.x = cluster; at[n].val.clusterDim.y = 1; at[n].val.clusterDim.z = 1; n++; }
    if (pdl) { at[n].id = cudaLaunchAttributeProgrammaticStreamSerialization; at[n].val.programmaticStreamSerializationAllowed = 1; n++; }
    cfg.attrs = at;
    cfg.numAttrs = n;
    cudaLaunchKernelEx(&cfg, kern, KArgs(args)...);
}

template <typename T> void* sym(const T& s) { void* p = nullptr; cudaGetSymbolAddress(&p, s); return p; }

}

extern "C" void kernel_launch(void* const* d_in, const int* in_sizes, int n_in, void* d_out, int out_size) {
    const __nv_bfloat16* x = (const __nv_bfloat16*)d_in[0];
    const __nv_bfloat16* wq = (const __nv_bfloat16*)d_in[1];
    const __nv_bfloat16* wk = (const __nv_bfloat16*)d_in[2];
    const __nv_bfloat16* wv = (const __nv_bfloat16*)d_in[3];
    const __nv_bfloat16* wo = (const __nv_bfloat16*)d_in[4];
    const __nv_bfloat16* w1 = (const __nv_bfloat16*)d_in[6];
    const __nv_bfloat16* w2 = (const __nv_bfloat16*)d_in[7];

    constexpr int SM_QKV = GemmSmem<QKV_STAGES, EPI_QKV>::TOTAL, SM_QKV0 = GemmSmem<QKV_STAGES, EPI_QKV>::TOTAL_SELF;
    static_assert(SM_QKV0 <= 232448, "shared memory");
    constexpr int SM_WO = GemmSmem<WO_STAGES, EPI_RES>::TOTAL, SM_FFN2 = GemmSmem<FFN2_STAGES, EPI_RES>::TOTAL;
    static_assert(SM_WO > 116736 && SM_FFN2 > 116736, "one CTA per SM");
    constexpr int SM_FFN1 = GemmSmem<FFN1_STAGES, EPI_FFN1>::TOTAL;
    cudaFuncSetAttribute(qkv_kernel<false>, cudaFuncAttributeMaxDynamicSharedMemorySize, SM_QKV);
    cudaFuncSetAttribute(qkv_kernel<true>, cudaFuncAttributeMaxDynamicSharedMemorySize, SM_QKV0);
    cudaFuncSetAttribute(res_gemm_kernel<8, WO_STAGES>, cudaFuncAttributeMaxDynamicSharedMemorySize, SM_WO);
    cudaFuncSetAttribute(ffn1_kernel, cudaFuncAttributeMaxDynamicSharedMemorySize, SM_FFN1);
    cudaFuncSetAttribute(res_gemm_kernel<28, FFN2_STAGES>, cudaFuncAttributeMaxDynamicSharedMemorySize, SM_FFN2);
    cudaFuncSetAttribute(attn_kernel, cudaFuncAttributeMaxDynamicSharedMemorySize, ATT_SMEM);
    cudaFuncSetAttribute(qkv_kernel<false>, cudaFuncAttributePreferredSharedMemoryCarveout, 100);
    cudaFuncSetAttribute(qkv_kernel<true>, cudaFuncAttributePreferredSharedMemoryCarveout, 100);
    cudaFuncSetAttribute(res_gemm_kernel<8, WO_STAGES>, cudaFuncAttributePreferredSharedMemoryCarveout, 100);
    cudaFuncSetAttribute(ffn1_kernel, cudaFuncAttributePreferredSharedMemoryCarveout, 100);
    cudaFuncSetAttribute(res_gemm_kernel<28, FFN2_STAGES>, cudaFuncAttributePreferredSharedMemoryCarveout, 100);
    cudaFuncSetAttribute(attn_kernel, cudaFuncAttributePreferredSharedMemoryCarveout, 100);

    void *q = sym(g_q), *o = sym(g_o), *x1 = sym(g_x1), *x2 = sym(g_x2), *x3 = sym(g_x3), *h = sym(g_h);
    float2* stats = (float2*)sym(g_stats);
    const void* xs[5] = {x, x1, x2, x3, d_out};

    const CUtensorMapSwizzle SW128 = CU_TENSOR_MAP_SWIZZLE_128B, SW64 = CU_TENSOR_MAP_SWIZZLE_64B;
    const CUtensorMap mWq = map3d32(wq, D_, D_, 64, 2);
    const CUtensorMap mWo = map2d(wo, D_, D_, 64, 64, SW128);
    const CUtensorMap mW1 = map3d32(w1, F_, D_, 64, 7);
    const CUtensorMap mW2 = map2d(w2, D_, F_, 64, 64, SW128);
    const CUtensorMap mQ = map2d(q, D_, S_, 64, 64, SW128);
    const CUtensorMap mQa = map2d(q, D_, S_, 64, 128, SW128), mOs = map2d(o, D_, S_, 64, 128, SW128);
    const CUtensorMap mHst = map2d(h, F_, S_, 32, 16, SW64);
    CUtensorMap mXa[4], mXs[5];
    for (int i = 0; i < 4; i++) {
        mXa[i] = map2d(xs[i], D_, S_, 64, 128, SW128);
    }
    for (int i = 0; i < 5; i++) mXs[i] = map2d(xs[i], D_, S_, 64, 64, SW128);
    const CUtensorMap mOa = map2d(o, D_, S_, 64, 128, SW128);
    const CUtensorMap mHa = map2d(h, F_, S_, 64, 128, SW128);

    for (int layer = 0; layer < 2; layer++) {
        const int xi = layer * 2;
        GemmParams p;
        p.wkv = wk; p.wv = wv;
        p.stats_in = stats + (size_t)xi * 8 * S_; p.stats_out = nullptr; p.tk = 1 + 5 * layer;
        if (layer == 0) launch(qkv_kernel<true>, 128, 640, SM_QKV0, 1, false, mXa[xi], mWq, mQ, p);
        else launch(qkv_kernel<false>, 128, 288, SM_QKV, 2, true, mXa[xi], mWq, mQ, p);
        launch(attn_kernel, layer == 0 ? 128 + SIDE_CTAS : 128, 512, ATT_SMEM, 1, true, mQa, mOs, wo, w1, w2, 2 + 5 * layer);
        p.stats_in = nullptr; p.stats_out = stats + (size_t)(xi + 1) * 8 * S_; p.tk = 3 + 5 * layer;
        launch(res_gemm_kernel<8, WO_STAGES>, 128, 288, SM_WO, 2, true, mOa, mWo, mXa[xi], mXs[xi + 1], p);
        p.stats_in = stats + (size_t)(xi + 1) * 8 * S_; p.stats_out = nullptr; p.tk = 4 + 5 * layer;
        launch(ffn1_kernel, 128, 288, SM_FFN1, 1, true, mXa[xi + 1], mW1, mHst, p);
        p.stats_in = nullptr; p.stats_out = layer == 0 ? stats + (size_t)2 * 8 * S_ : nullptr; p.tk = 5 + 5 * layer;
        launch(res_gemm_kernel<28, FFN2_STAGES>, 128, 288, SM_FFN2, 2, true, mHa, mW2, mXa[xi + 1], mXs[xi + 2], p);
    }
}
```

```cpp
#include <cuda_runtime.h>
#include <cuda_bf16.h>
#include <cuda.h>
#include <stdint.h>

#define F2_SK 1
#define F2SK_ST 6
#define F2SK_CL 2

namespace {

constexpr int S_ = 2048, D_ = 512, F_ = 1792;

__device__ __align__(1024) __nv_bfloat16 g_q[S_ * D_];
__device__ __align__(1024) __nv_bfloat16 g_o[S_ * D_];
__device__ __align__(1024) __nv_bfloat16 g_x1[S_ * D_];
__device__ __align__(1024) __nv_bfloat16 g_x2[S_ * D_];
__device__ __align__(1024) __nv_bfloat16 g_x3[S_ * D_];
__device__ __align__(1024) __nv_bfloat16 g_h[S_ * F_];
__device__ __align__(1024) uint8_t g_kimg[S_ * 32];
__device__ __align__(1024) uint8_t g_vimg[(S_ / 16) * 768];
__device__ __align__(1024) float2 g_stats[4][8 * S_];
__device__ __align__(16) float g_cs_q[D_];
__device__ __align__(16) float g_cs_kv[32];
__device__ __align__(16) float g_cs_1[F_];
__device__ __align__(16) float g_kvmax[32];

#define TL(k, slot)
#define CK(k, i)
#define CP(k, i)

__device__ __forceinline__ uint32_t smem_u32(const void* p) { return (uint32_t)__cvta_generic_to_shared(p); }
__device__ __forceinline__ void mbar_init(uint32_t bar, uint32_t cnt) {
    asm volatile("mbarrier.init.shared::cta.b64 [%0], %1;" ::"r"(bar), "r"(cnt));
}
__device__ __forceinline__ void mbar_expect_tx(uint32_t bar, uint32_t bytes) {
    asm volatile("mbarrier.arrive.expect_tx.shared::cta.b64 _, [%0], %1;" ::"r"(bar), "r"(bytes) : "memory");
}
__device__ __forceinline__ void mbar_arrive(uint32_t bar) {
    asm volatile("mbarrier.arrive.shared::cta.b64 _, [%0];" ::"r"(bar) : "memory");
}
__device__ __forceinline__ void mbar_wait(uint32_t bar, uint32_t parity) {
    asm volatile("{\n.reg .pred p;\nWAIT_%=:\nmbarrier.try_wait.parity.shared::cta.b64 p, [%0], %1;\n@p bra DONE_%=;\nbra WAIT_%=;\nDONE_%=:\n}" ::"r"(bar), "r"(parity) : "memory");
}
__device__ __forceinline__ void bulk_load(uint32_t dst, const void* src, uint32_t bytes, uint32_t bar) {
    asm volatile("cp.async.bulk.shared::cluster.global.mbarrier::complete_tx::bytes [%0], [%1], %2, [%3];" ::"r"(dst), "l"(src), "r"(bytes), "r"(bar) : "memory");
}
__device__ __forceinline__ void tma2d(uint32_t dst, const CUtensorMap* m, int c0, int c1, uint32_t bar) {
    asm volatile("cp.async.bulk.tensor.2d.shared::cluster.global.mbarrier::complete_tx::bytes [%0], [%1, {%3, %4}], [%2];" ::"r"(dst), "l"(m), "r"(bar), "r"(c0), "r"(c1) : "memory");
}
__device__ __forceinline__ void tma3d(uint32_t dst, const CUtensorMap* m, int c0, int c1, int c2, uint32_t bar) {
    asm volatile("cp.async.bulk.tensor.3d.shared::cluster.global.mbarrier::complete_tx::bytes [%0], [%1, {%3, %4, %5}], [%2];" ::"r"(dst), "l"(m), "r"(bar), "r"(c0), "r"(c1), "r"(c2) : "memory");
}
__device__ __forceinline__ void tma2d_store(const CUtensorMap* m, uint32_t src, int c0, int c1) {
    asm volatile("cp.async.bulk.tensor.2d.global.shared::cta.bulk_group [%0, {%2, %3}], [%1];" ::"l"(m), "r"(src), "r"(c0), "r"(c1) : "memory");
}
__device__ __forceinline__ void bulk_commit() { asm volatile("cp.async.bulk.commit_group;" ::: "memory"); }
__device__ __forceinline__ void bulk_wait_read() { asm volatile("cp.async.bulk.wait_group.read 0;" ::: "memory"); }
__device__ __forceinline__ void prefetch_tmap(const CUtensorMap* m) { asm volatile("prefetch.tensormap [%0];" ::"l"(m) : "memory"); }
__device__ __forceinline__ void fence_async_smem() { asm volatile("fence.proxy.async.shared::cta;" ::: "memory"); }
__device__ __forceinline__ void fence_mbar_init() { asm volatile("fence.mbarrier_init.release.cluster;" ::: "memory"); }
__device__ __forceinline__ void pdl_wait() { asm volatile("griddepcontrol.wait;" ::: "memory"); }
__device__ __forceinline__ void pdl_launch() { asm volatile("griddepcontrol.launch_dependents;" ::: "memory"); }
__device__ __forceinline__ bool elect_one() {
    uint32_t p;
    asm volatile("{\n.reg .pred p;\nelect.sync _|p, 0xffffffff;\nselp.b32 %0, 1, 0, p;\n}" : "=r"(p));
    return p != 0;
}
__device__ __forceinline__ void named_bar(int id, int n) { asm volatile("bar.sync %0, %1;" ::"r"(id), "r"(n) : "memory"); }

__device__ __forceinline__ void wg_fence() { asm volatile("wgmma.fence.sync.aligned;" ::: "memory"); }
__device__ __forceinline__ void wg_commit() { asm volatile("wgmma.commit_group.sync.aligned;" ::: "memory"); }
template <int N> __device__ __forceinline__ void wg_wait() { asm volatile("wgmma.wait_group.sync.aligned %0;" ::"n"(N) : "memory"); }
template <int N> __device__ __forceinline__ void fence_regs(float (&d)[N]) {
#pragma unroll
    for (int i = 0; i < N; i++) asm volatile("" : "+f"(d[i])::"memory");
}
__device__ __forceinline__ uint64_t mkdesc(uint32_t addr, uint32_t lbo, uint32_t sbo, uint32_t swz) {
    uint64_t d = 0;
    d |= (uint64_t)((addr & 0x3FFFF) >> 4);
    d |= (uint64_t)((lbo & 0x3FFFF) >> 4) << 16;
    d |= (uint64_t)((sbo & 0x3FFFF) >> 4) << 32;
    d |= (uint64_t)swz << 62;
    return d;
}
__device__ __forceinline__ void ldsm_x4(uint32_t& r0, uint32_t& r1, uint32_t& r2, uint32_t& r3, uint32_t addr) {
    asm volatile("ldmatrix.sync.aligned.m8n8.x4.shared.b16 {%0,%1,%2,%3}, [%4];" : "=r"(r0), "=r"(r1), "=r"(r2), "=r"(r3) : "r"(addr) : "memory");
}
__device__ __forceinline__ void stsm_x4(uint32_t addr, uint32_t r0, uint32_t r1, uint32_t r2, uint32_t r3) {
    asm volatile("stmatrix.sync.aligned.m8n8.x4.shared.b16 [%0], {%1,%2,%3,%4};" ::"r"(addr), "r"(r0), "r"(r1), "r"(r2), "r"(r3) : "memory");
}
__device__ __forceinline__ uint32_t pack_bf16(float lo, float hi) {
    uint32_t r;
    asm("cvt.rn.bf16x2.f32 %0, %1, %2;" : "=r"(r) : "f"(hi), "f"(lo));
    return r;
}
__device__ __forceinline__ float bf_lo(uint32_t v) { return __uint_as_float(v << 16); }
__device__ __forceinline__ float bf_hi(uint32_t v) { return __uint_as_float(v & 0xFFFF0000u); }

#define WG_REGS_4(o) "+f"(d[o]), "+f"(d[o + 1]), "+f"(d[o + 2]), "+f"(d[o + 3])
#define WG_REGS_8(o) WG_REGS_4(o), WG_REGS_4(o + 4)
#define WG_REGS_16(o) WG_REGS_8(o), WG_REGS_8(o + 8)
#define WG_REGS_32(o) WG_REGS_16(o), WG_REGS_16(o + 16)

__device__ __forceinline__ void wgmma_ss_n80_tb(float (&d)[40], uint64_t dA, uint64_t dB, int sc) {
    asm volatile("{\n.reg .pred p;\nsetp.ne.b32 p, %42, 0;\n"
                 "wgmma.mma_async.sync.aligned.m64n80k16.f32.bf16.bf16 "
                 "{%0,%1,%2,%3,%4,%5,%6,%7,%8,%9,%10,%11,%12,%13,%14,%15,%16,%17,%18,%19,%20,%21,%22,%23,%24,%25,%26,%27,%28,%29,%30,%31,"
                 "%32,%33,%34,%35,%36,%37,%38,%39}, %40, %41, p, 1, 1, 0, 1;\n}\n"
                 : WG_REGS_32(0), WG_REGS_8(32) : "l"(dA), "l"(dB), "r"(sc));
}
__device__ __forceinline__ void wgmma_ss_n64_tb(float (&d)[32], uint64_t dA, uint64_t dB, int sc) {
    asm volatile("{\n.reg .pred p;\nsetp.ne.b32 p, %34, 0;\n"
                 "wgmma.mma_async.sync.aligned.m64n64k16.f32.bf16.bf16 "
                 "{%0,%1,%2,%3,%4,%5,%6,%7,%8,%9,%10,%11,%12,%13,%14,%15,%16,%17,%18,%19,%20,%21,%22,%23,%24,%25,%26,%27,%28,%29,%30,%31}, "
                 "%32, %33, p, 1, 1, 0, 1;\n}\n"
                 : WG_REGS_32(0) : "l"(dA), "l"(dB), "r"(sc));
}
__device__ __forceinline__ void wgmma_ss_n128_tb(float (&d)[64], uint64_t dA, uint64_t dB, int sc) {
    asm volatile("{\n.reg .pred p;\nsetp.ne.b32 p, %66, 0;\n"
                 "wgmma.mma_async.sync.aligned.m64n128k16.f32.bf16.bf16 "
                 "{%0,%1,%2,%3,%4,%5,%6,%7,%8,%9,%10,%11,%12,%13,%14,%15,%16,%17,%18,%19,%20,%21,%22,%23,%24,%25,%26,%27,%28,%29,%30,%31,"
                 "%32,%33,%34,%35,%36,%37,%38,%39,%40,%41,%42,%43,%44,%45,%46,%47,%48,%49,%50,%51,%52,%53,%54,%55,%56,%57,%58,%59,%60,%61,%62,%63}, "
                 "%64, %65, p, 1, 1, 0, 1;\n}\n"
                 : WG_REGS_32(0), WG_REGS_32(32) : "l"(dA), "l"(dB), "r"(sc));
}
__device__ __forceinline__ void wgmma_ss_n224_tb(float (&d)[112], uint64_t dA, uint64_t dB, int sc) {
    asm volatile("{\n.reg .pred p;\nsetp.ne.b32 p, %114, 0;\n"
                 "wgmma.mma_async.sync.aligned.m64n224k16.f32.bf16.bf16 "
                 "{%0,%1,%2,%3,%4,%5,%6,%7,%8,%9,%10,%11,%12,%13,%14,%15,%16,%17,%18,%19,%20,%21,%22,%23,%24,%25,%26,%27,%28,%29,%30,%31,"
                 "%32,%33,%34,%35,%36,%37,%38,%39,%40,%41,%42,%43,%44,%45,%46,%47,%48,%49,%50,%51,%52,%53,%54,%55,%56,%57,%58,%59,%60,%61,%62,%63,"
                 "%64,%65,%66,%67,%68,%69,%70,%71,%72,%73,%74,%75,%76,%77,%78,%79,%80,%81,%82,%83,%84,%85,%86,%87,%88,%89,%90,%91,%92,%93,%94,%95,"
                 "%96,%97,%98,%99,%100,%101,%102,%103,%104,%105,%106,%107,%108,%109,%110,%111}, "
                 "%112, %113, p, 1, 1, 0, 1;\n}\n"
                 : WG_REGS_32(0), WG_REGS_32(32), WG_REGS_32(64), WG_REGS_16(96) : "l"(dA), "l"(dB), "r"(sc));
}
template <int BN> __device__ __forceinline__ void wgmma_ss_tb(float (&d)[BN / 2], uint64_t dA, uint64_t dB, int sc) {
    if constexpr (BN == 64) wgmma_ss_n64_tb(d, dA, dB, sc);
    else if constexpr (BN == 80) wgmma_ss_n80_tb(d, dA, dB, sc);
    else wgmma_ss_n224_tb(d, dA, dB, sc);
}
__device__ __forceinline__ void wgmma_rs_n64_tb(float (&d)[32], uint32_t a, uint64_t dB, int sc) {
    asm volatile("{\n.reg .pred p;\nsetp.ne.b32 p, %34, 0;\n"
                 "wgmma.mma_async.sync.aligned.m64n64k16.f32.bf16.bf16 "
                 "{%0,%1,%2,%3,%4,%5,%6,%7,%8,%9,%10,%11,%12,%13,%14,%15,%16,%17,%18,%19,%20,%21,%22,%23,%24,%25,%26,%27,%28,%29,%30,%31}, "
                 "{%32,%32,%32,%32}, %33, p, 1, 1, 1;\n}\n"
                 : WG_REGS_32(0) : "r"(a), "l"(dB), "r"(sc));
}
__device__ __forceinline__ void wgmma_rs_n80_tb(float (&d)[40], uint32_t a, uint64_t dB, int sc) {
    asm volatile("{\n.reg .pred p;\nsetp.ne.b32 p, %42, 0;\n"
                 "wgmma.mma_async.sync.aligned.m64n80k16.f32.bf16.bf16 "
                 "{%0,%1,%2,%3,%4,%5,%6,%7,%8,%9,%10,%11,%12,%13,%14,%15,%16,%17,%18,%19,%20,%21,%22,%23,%24,%25,%26,%27,%28,%29,%30,%31,"
                 "%32,%33,%34,%35,%36,%37,%38,%39}, {%40,%40,%40,%40}, %41, p, 1, 1, 1;\n}\n"
                 : WG_REGS_32(0), WG_REGS_8(32) : "r"(a), "l"(dB), "r"(sc));
}
template <int BN> __device__ __forceinline__ void wgmma_rs_ones(float (&d)[BN / 2], uint64_t dB, int sc) {
    if constexpr (BN == 80) wgmma_rs_n80_tb(d, 0x3F803F80u, dB, sc);
    else if constexpr (BN == 64) wgmma_rs_n64_tb(d, 0x3F803F80u, dB, sc);
}
__device__ __forceinline__ void wgmma_rs_n64_z(float (&d)[32], uint32_t a0, uint32_t a1, uint32_t a2, uint32_t a3, uint64_t dB) {
    asm volatile("{\n.reg .pred p;\nsetp.ne.b32 p, 0, 0;\n"
                 "wgmma.mma_async.sync.aligned.m64n64k16.f32.bf16.bf16 "
                 "{%0,%1,%2,%3,%4,%5,%6,%7,%8,%9,%10,%11,%12,%13,%14,%15,%16,%17,%18,%19,%20,%21,%22,%23,%24,%25,%26,%27,%28,%29,%30,%31}, "
                 "{%32,%33,%34,%35}, %36, p, 1, 1, 0;\n}\n"
                 : "=f"(d[0]), "=f"(d[1]), "=f"(d[2]), "=f"(d[3]), "=f"(d[4]), "=f"(d[5]), "=f"(d[6]), "=f"(d[7]),
                   "=f"(d[8]), "=f"(d[9]), "=f"(d[10]), "=f"(d[11]), "=f"(d[12]), "=f"(d[13]), "=f"(d[14]), "=f"(d[15]),
                   "=f"(d[16]), "=f"(d[17]), "=f"(d[18]), "=f"(d[19]), "=f"(d[20]), "=f"(d[21]), "=f"(d[22]), "=f"(d[23]),
                   "=f"(d[24]), "=f"(d[25]), "=f"(d[26]), "=f"(d[27]), "=f"(d[28]), "=f"(d[29]), "=f"(d[30]), "=f"(d[31])
                 : "r"(a0), "r"(a1), "r"(a2), "r"(a3), "l"(dB));
}
__device__ __forceinline__ void wgmma_rs_n24_tb(float (&d)[12], uint32_t a0, uint32_t a1, uint32_t a2, uint32_t a3, uint64_t dB) {
    asm volatile("{\n.reg .pred p;\nsetp.eq.b32 p, 0, 0;\n"
                 "wgmma.mma_async.sync.aligned.m64n24k16.f32.bf16.bf16 "
                 "{%0,%1,%2,%3,%4,%5,%6,%7,%8,%9,%10,%11}, {%12,%13,%14,%15}, %16, p, 1, 1, 1;\n}\n"
                 : WG_REGS_8(0), WG_REGS_4(8) : "r"(a0), "r"(a1), "r"(a2), "r"(a3), "l"(dB));
}

constexpr int SIDE_CTAS = 4;
__device__ __forceinline__ void side_job(int cta, float* red  , const __nv_bfloat16* __restrict__ wo,
                                         const __nv_bfloat16* __restrict__ w1, const __nv_bfloat16* __restrict__ w2) {
    const int tid = threadIdx.x, warp = tid >> 5, lane = tid & 31;
    for (int line = cta * 512 + tid; line < 18432; line += SIDE_CTAS * 512) {
        const char* p = line < 4096 ? (const char*)wo + (size_t)line * 128 : (const char*)w2 + (size_t)(line - 4096) * 128;
        asm volatile("prefetch.global.L2 [%0];" ::"l"(p));
    }
    const int rg = lane >> 3, c8 = lane & 7;
    for (int slab = cta; slab < F_ / 64; slab += SIDE_CTAS) {
        const __nv_bfloat16* base = w1 + slab * 64 + c8 * 8;
        uint4 v[8];
#pragma unroll
        for (int i = 0; i < 8; i++) v[i] = __ldg((const uint4*)(base + (size_t)(warp * 32 + rg + 4 * i) * F_));
        float acc[8];
#pragma unroll
        for (int i = 0; i < 8; i++) acc[i] = 0.f;
#pragma unroll
        for (int i = 0; i < 8; i++) {
            acc[0] += bf_lo(v[i].x); acc[1] += bf_hi(v[i].x); acc[2] += bf_lo(v[i].y); acc[3] += bf_hi(v[i].y);
            acc[4] += bf_lo(v[i].z); acc[5] += bf_hi(v[i].z); acc[6] += bf_lo(v[i].w); acc[7] += bf_hi(v[i].w);
        }
#pragma unroll
        for (int i = 0; i < 8; i++) {
            acc[i] += __shfl_xor_sync(0xffffffffu, acc[i], 8);
            acc[i] += __shfl_xor_sync(0xffffffffu, acc[i], 16);
        }
        if (rg == 0) {
#pragma unroll
            for (int i = 0; i < 8; i++) red[warp * 64 + c8 * 8 + i] = acc[i];
        }
        __syncthreads();
        if (tid < 64) {
            float s = 0.f;
#pragma unroll
            for (int i = 0; i < 16; i++) s += red[i * 64 + tid];
            g_cs_1[slab * 64 + tid] = s;
        }
        __syncthreads();
    }
}

enum { EPI_QKV = 0, EPI_RES = 1, EPI_FFN1 = 2 };

struct GemmParams {
    const float2* stats_in;
    float2* stats_out;
    const __nv_bfloat16* wkv;
    const __nv_bfloat16* wv;
    int tk;
};

template <int BK_, int NBLK> struct Geo {
    static constexpr int BK = BK_, A_BYTES = 128 * BK * 2, A_SWZ = BK == 64 ? 1 : 2, A_SBO = BK * 16;
    static constexpr int BLK = BK * 64;
    static constexpr int B_BYTES = NBLK * BLK, B_SWZ = 2, B_LBO = BLK, B_SBO = 512, B_KSTEP = 1024;
};
template <> struct Geo<64, 0> {
    static constexpr int BK = 64, A_BYTES = 128 * 128, A_SWZ = 1, A_SBO = 1024, BLK = 8192;
    static constexpr int B_BYTES = 64 * 128, B_SWZ = 1, B_LBO = 8192, B_SBO = 1024, B_KSTEP = 2048;
};
template <int EPI> struct EpiGeo;
template <> struct EpiGeo<EPI_QKV> { using G = Geo<64, 3>; };
template <> struct EpiGeo<EPI_RES> { using G = Geo<64, 0>; };
template <> struct EpiGeo<EPI_FFN1> { using G = Geo<64, 7>; };

template <int STAGES, int EPI> struct GemmSmem {
    using G = typename EpiGeo<EPI>::G;
    static constexpr int STAGE = G::A_BYTES + G::B_BYTES;
    static constexpr int AUX_OFF = STAGES * STAGE;
    static constexpr int TOTAL = AUX_OFF + 1152;
    static constexpr int TOTAL_SELF = AUX_OFF + 704 + 1024;
};

struct RowStatRaw { float2 a0, a1, b0, b1; };
__device__ __forceinline__ RowStatRaw load_row_stats(const float2* __restrict__ st, int row0, int c) {
    RowStatRaw r;
    r.a0 = st[(2 * c) * S_ + row0]; r.a1 = st[(2 * c + 1) * S_ + row0];
    r.b0 = st[(2 * c) * S_ + row0 + 8]; r.b1 = st[(2 * c + 1) * S_ + row0 + 8];
    return r;
}
__device__ __forceinline__ void finish_row_stats(const RowStatRaw& r, float& mean0, float& rstd0, float& mean1, float& rstd1) {
    float sa = r.a0.x + r.a1.x, sb = r.b0.x + r.b1.x;
    sa += __shfl_xor_sync(0xffffffffu, sa, 1); sa += __shfl_xor_sync(0xffffffffu, sa, 2);
    sb += __shfl_xor_sync(0xffffffffu, sb, 1); sb += __shfl_xor_sync(0xffffffffu, sb, 2);
    mean0 = sa * 0.125f; mean1 = sb * 0.125f;
    float ma = r.a0.y + r.a1.y + 64.f * ((r.a0.x - mean0) * (r.a0.x - mean0) + (r.a1.x - mean0) * (r.a1.x - mean0));
    float mb = r.b0.y + r.b1.y + 64.f * ((r.b0.x - mean1) * (r.b0.x - mean1) + (r.b1.x - mean1) * (r.b1.x - mean1));
    ma += __shfl_xor_sync(0xffffffffu, ma, 1); ma += __shfl_xor_sync(0xffffffffu, ma, 2);
    mb += __shfl_xor_sync(0xffffffffu, mb, 1); mb += __shfl_xor_sync(0xffffffffu, mb, 2);
    rstd0 = 1.0f / sqrtf(ma * (1.f / 512.f) + 1e-5f);
    rstd1 = 1.0f / sqrtf(mb * (1.f / 512.f) + 1e-5f);
}

template <int BN, int KB, int STAGES, int EPI, bool SELF = false>
__device__ __forceinline__ void gemm_body(const CUtensorMap* mapA, const CUtensorMap* mapB, const CUtensorMap* mapR,
                                          const CUtensorMap* mapC, const GemmParams& prm, int tile_m, int tile_n, uint8_t* smem_raw) {
    using SM = GemmSmem<STAGES, EPI>;
    using G = typename SM::G;
    constexpr bool XKV = BN == 80;
    constexpr int TN = EPI == EPI_QKV ? 64 : BN;
    CP(prm.tk, 0);
    pdl_launch();
    const uint32_t sbase = smem_u32(smem_raw);
    if (sbase & 1023) __trap();
    uint8_t* sgen = smem_raw;
    const uint32_t bar_full = sbase + SM::AUX_OFF, bar_empty = bar_full + 8 * STAGES;
    float* s_cs = (float*)(sgen + SM::AUX_OFF + 256);
    float* s_row = (float*)(sgen + SM::AUX_OFF + 704);
    float* s_red = (float*)(sgen + SM::AUX_OFF + 640);
    const int tid = threadIdx.x, lane = tid & 31;
    const int warp = __shfl_sync(0xffffffffu, tid >> 5, 0);
    if (tid == 0) TL(prm.tk, 0);

    if (warp == 8 && elect_one()) {
#pragma unroll
        for (int s = 0; s < STAGES; s++) { mbar_init(bar_full + 8 * s, 1); mbar_init(bar_empty + 8 * s, 2); }
        fence_mbar_init();
    }
    if (warp == 1 && elect_one()) { prefetch_tmap(mapB); prefetch_tmap(mapA); prefetch_tmap(mapC); }
    CP(prm.tk, 1);
    __syncthreads();
    CP(prm.tk, 2);

    const int m0 = tile_m * 128, n0 = tile_n * TN;
    constexpr uint32_t STAGE_TX = G::A_BYTES + (EPI == EPI_QKV ? 2 * G::BLK : G::B_BYTES);
    auto loadB = [&](int kb, int s) {
        const uint32_t dst = sbase + s * SM::STAGE + G::A_BYTES, bar = bar_full + 8 * s;
        if constexpr (EPI == EPI_RES) {
            tma2d(dst, mapB, n0, kb * 64, bar);
        } else if constexpr (EPI == EPI_QKV) {
            tma3d(dst, mapB, 0, kb * G::BK, tile_n * 2, bar);
        } else {
            tma3d(dst, mapB, 0, kb * G::BK, tile_n * 7, bar);
        }
    };
    auto loadA = [&](int kb, int s) {
        const uint32_t dst = sbase + s * SM::STAGE, bar = bar_full + 8 * s;
        tma2d(dst, mapA, kb * G::BK, m0, bar);
    };
    constexpr int PRE = STAGES < KB ? STAGES : KB;
    constexpr int PRE_B = 1;
    auto prologue_loads = [&]() {
        if (elect_one()) {
#pragma unroll
            for (int kb = 0; kb < PRE; kb++) mbar_expect_tx(bar_full + 8 * kb, STAGE_TX);
        }
        if (elect_one()) {
#pragma unroll
            for (int kb = 0; kb < PRE_B; kb++) loadB(kb, kb);
        }
        CP(prm.tk, 5);
        if (!SELF) pdl_wait();
        CP(prm.tk, 6);
        if (elect_one()) {
#pragma unroll
            for (int kb = 0; kb < PRE; kb++) {
                loadA(kb, kb);
                if (kb + PRE_B < PRE) loadB(kb + PRE_B, kb + PRE_B);
            }
            if constexpr (EPI == EPI_RES && KB < STAGES) {
                mbar_expect_tx(bar_full + 8 * KB, 16384);
                tma2d(sbase + KB * SM::STAGE, mapR, n0, m0, bar_full + 8 * KB);
            }
        }
    };
    if (SELF && warp >= 8) {
        if (warp == 8) prologue_loads();
        static_assert(!SELF || (STAGES >= KB && EPI == EPI_QKV), "SELF needs every k block resident");
        if ((warp >> 2) == 3) {
            float csum[BN / 2];
            const uint64_t dB0 = mkdesc(sbase + G::A_BYTES, G::B_LBO, G::B_SBO, G::B_SWZ);
            if constexpr (XKV) named_bar(6, 384);
#pragma unroll 1
            for (int kb = 0; kb < KB; kb++) {
                mbar_wait(bar_full + 8 * kb, 0);
                const uint64_t dB = dB0 + (uint64_t)(kb * (SM::STAGE >> 4));
                wg_fence();
#pragma unroll
                for (int k = 0; k < G::BK / 16; k++) {
                    if constexpr (SELF) wgmma_rs_ones<BN>(csum, dB + (uint64_t)(k * (G::B_KSTEP >> 4)), (kb | k) != 0);
                }
                wg_commit();
            }
            wg_wait<0>();
            fence_regs(csum);
            if (warp == 12 && lane < 4) {
#pragma unroll
                for (int j = 0; j < BN / 8; j++) {
                    const float2 v = make_float2(csum[4 * j], csum[4 * j + 1]);
                    *(float2*)(s_cs + 8 * j + 2 * lane) = v;
                    if (tile_m == 0) {
                        if (j < 8) *(float2*)(g_cs_q + n0 + 8 * j + 2 * lane) = v;
                        else *(float2*)(g_cs_kv + tile_n * 16 + 8 * (j - 8) + 2 * lane) = v;
                    }
                }
            }
        } else {
            const int t = (warp < 12 ? warp - 8 : warp - 12) * 32 + lane;
            float ss[4] = {0.f, 0.f, 0.f, 0.f}, sq[4] = {0.f, 0.f, 0.f, 0.f};
#pragma unroll 1
            for (int kb = 0; kb < KB; kb++) {
                mbar_wait(bar_full + 8 * kb, 0);
                const uint32_t arow = sbase + kb * SM::STAGE + (t >> 1) * 128;
                uint32_t w[4][4];
#pragma unroll
                for (int j = 0; j < 4; j++)
                    asm volatile("ld.shared.v4.u32 {%0,%1,%2,%3}, [%4];" : "=r"(w[j][0]), "=r"(w[j][1]), "=r"(w[j][2]), "=r"(w[j][3])
                                 : "r"(arow + (((2 * j + (t & 1) + 2 * ((t >> 1) & 3)) & 7) << 4)));
#pragma unroll
                for (int j = 0; j < 4; j++)
#pragma unroll
                    for (int i = 0; i < 4; i++) {
                        const float lo = bf_lo(w[j][i]), hi = bf_hi(w[j][i]);
                        ss[i] += lo + hi;
                        sq[i] = fmaf(lo, lo, fmaf(hi, hi, sq[i]));
                    }
            }
            float tsum = (ss[0] + ss[1]) + (ss[2] + ss[3]), tsq = (sq[0] + sq[1]) + (sq[2] + sq[3]);
            tsum += __shfl_xor_sync(0xffffffffu, tsum, 1);
            tsq += __shfl_xor_sync(0xffffffffu, tsq, 1);
            if ((t & 1) == 0) {
                const float md = tsum * (1.f / 512.f);
                const float var = fmaxf(tsq * (1.f / 512.f) - md * md, 0.f);
                *(float2*)(s_row + t) = make_float2(md, 1.0f / sqrtf(var + 1e-5f));
            }
        }
        named_bar(4, 640);
    } else if (warp == 8) {
        prologue_loads();
        int s = PRE % STAGES, ph = (PRE / STAGES) & 1;
#pragma unroll 1
        for (int kb = PRE; kb < KB; kb++) {
            mbar_wait(bar_empty + 8 * s, ph ^ 1);
            if (elect_one()) {
                mbar_expect_tx(bar_full + 8 * s, STAGE_TX);
                loadB(kb, s);
                loadA(kb, s);
            }
            if (++s == STAGES) { s = 0; ph ^= 1; }
        }
        if constexpr (EPI == EPI_RES && KB >= STAGES) {
            mbar_wait(bar_empty + 8 * s, ph ^ 1);
            if (elect_one()) {
                mbar_expect_tx(bar_full + 8 * s, 16384);
                tma2d(sbase + s * SM::STAGE, mapR, n0, m0, bar_full + 8 * s);
            }
        }
    } else {
        const int wg = warp >> 2, g = lane >> 2, c = lane & 3;
        const int rloc = wg * 64 + (warp & 3) * 16 + g;
        const int row0 = m0 + rloc;
        float mean0 = 0.f, rstd0 = 1.f, mean1 = 0.f, rstd1 = 1.f;
        if constexpr (XKV) {
            static_assert(!XKV || STAGES >= KB, "the K / V weight block must stay resident");
            const __nv_bfloat16* wsrc = tile_n == 0 ? prm.wkv : prm.wv;
            uint4 v[4];
#pragma unroll
            for (int i = 0; i < 4; i++) v[i] = __ldg((const uint4*)wsrc + tid + 256 * i);
#pragma unroll
            for (int i = 0; i < 4; i++) {
                const int idx = tid + 256 * i, k = idx >> 1, kr = k & 63;
                const uint32_t dst = sbase + (k >> 6) * SM::STAGE + G::A_BYTES + 2 * G::BLK + kr * 64 + (((idx & 1) ^ ((kr >> 1) & 3)) << 4);
                asm volatile("st.shared.v4.u32 [%0], {%1,%2,%3,%4};" ::"r"(dst), "r"(v[i].x), "r"(v[i].y), "r"(v[i].z), "r"(v[i].w) : "memory");
            }
            fence_async_smem();
            if constexpr (SELF) named_bar(6, 384); else named_bar(6, 256);
        }
        RowStatRaw raw;
        float csv = 0.f;
        float2 cskv[2] = {make_float2(0.f, 0.f), make_float2(0.f, 0.f)};
        auto ln_inputs = [&]() {
            pdl_wait();
            if constexpr (EPI != EPI_RES) {
                raw = load_row_stats(prm.stats_in, row0, c);
                const float* cs = EPI == EPI_FFN1 ? g_cs_1 + n0 : g_cs_q + n0;
                if (tid < TN) csv = cs[tid];
                if constexpr (XKV) {
                    cskv[0] = *(const float2*)(g_cs_kv + tile_n * 16 + 2 * c);
                    cskv[1] = *(const float2*)(g_cs_kv + tile_n * 16 + 8 + 2 * c);
                }
            }
        };
        if (!SELF) ln_inputs();
        float acc[BN / 2];
        const uint64_t dA0 = mkdesc(sbase + wg * (G::A_BYTES / 2), 16, G::A_SBO, G::A_SWZ);
        const uint64_t dB0 = mkdesc(sbase + G::A_BYTES, G::B_LBO, G::B_SBO, G::B_SWZ);
        int s = 0, ph = 0;
#pragma unroll 1
        for (int kb = 0; kb < KB; kb++) {
            mbar_wait(bar_full + 8 * s, ph);
            const uint64_t dA = dA0 + (uint64_t)(s * (SM::STAGE >> 4)), dB = dB0 + (uint64_t)(s * (SM::STAGE >> 4));
            wg_fence();
#pragma unroll
            for (int k = 0; k < G::BK / 16; k++) wgmma_ss_tb<BN>(acc, dA + (uint64_t)(k * 2), dB + (uint64_t)(k * (G::B_KSTEP >> 4)), (kb | k) != 0);
            wg_commit();
            if (kb > 0) {
                wg_wait<1>();
                const int sp = s == 0 ? STAGES - 1 : s - 1;
                if ((warp & 3) == 0 && elect_one()) mbar_arrive(bar_empty + 8 * sp);
            }
            if (++s == STAGES) { s = 0; ph ^= 1; }
        }
        if constexpr (SELF) {
            named_bar(4, 640);
            const float2 r0 = *(const float2*)(s_row + 2 * rloc), r1 = *(const float2*)(s_row + 2 * rloc + 16);
            mean0 = r0.x; rstd0 = r0.y; mean1 = r1.x; rstd1 = r1.y;
        } else if constexpr (EPI != EPI_RES) {
            finish_row_stats(raw, mean0, rstd0, mean1, rstd1);
            if (tid < TN) s_cs[tid] = csv;
        }
        wg_wait<0>();
        fence_regs(acc);
        if (tid == 0) TL(prm.tk, 2);
        if constexpr (EPI != EPI_RES) named_bar(1, 256);

        if constexpr (EPI != EPI_FFN1) {
            const uint32_t stile = sbase + (EPI == EPI_RES ? s * SM::STAGE : 0);
            const int mrow = wg * 64 + (warp & 3) * 16 + (lane & 7) + ((lane >> 3) & 1) * 8;
            const uint32_t rbase = stile + mrow * 128;
            if constexpr (EPI == EPI_RES) {
                mbar_wait(bar_full + 8 * s, ph);
                float s0 = 0.f, s1 = 0.f;
#pragma unroll
                for (int jj = 0; jj < 4; jj++) {
                    uint32_t r0, r1, r2, r3;
                    const uint32_t addr = rbase + (((2 * jj + (lane >> 4)) ^ (mrow & 7)) << 4);
                    ldsm_x4(r0, r1, r2, r3, addr);
                    const uint32_t u0 = pack_bf16(acc[8 * jj] + bf_lo(r0), acc[8 * jj + 1] + bf_hi(r0));
                    const uint32_t u1 = pack_bf16(acc[8 * jj + 2] + bf_lo(r1), acc[8 * jj + 3] + bf_hi(r1));
                    const uint32_t u2 = pack_bf16(acc[8 * jj + 4] + bf_lo(r2), acc[8 * jj + 5] + bf_hi(r2));
                    const uint32_t u3 = pack_bf16(acc[8 * jj + 6] + bf_lo(r3), acc[8 * jj + 7] + bf_hi(r3));
                    stsm_x4(addr, u0, u1, u2, u3);
                    acc[8 * jj] = bf_lo(u0); acc[8 * jj + 1] = bf_hi(u0); acc[8 * jj + 4] = bf_lo(u2); acc[8 * jj + 5] = bf_hi(u2);
                    acc[8 * jj + 2] = bf_lo(u1); acc[8 * jj + 3] = bf_hi(u1); acc[8 * jj + 6] = bf_lo(u3); acc[8 * jj + 7] = bf_hi(u3);
                    s0 += (acc[8 * jj] + acc[8 * jj + 1]) + (acc[8 * jj + 4] + acc[8 * jj + 5]);
                    s1 += (acc[8 * jj + 2] + acc[8 * jj + 3]) + (acc[8 * jj + 6] + acc[8 * jj + 7]);
                }
                fence_async_smem();
                named_bar(2 + wg, 128);
                if ((warp & 3) == 0 && elect_one()) { tma2d_store(mapC, stile + wg * 8192, n0, m0 + wg * 64); bulk_commit(); }
                if (prm.stats_out) {
                    s0 += __shfl_xor_sync(0xffffffffu, s0, 1); s0 += __shfl_xor_sync(0xffffffffu, s0, 2);
                    s1 += __shfl_xor_sync(0xffffffffu, s1, 1); s1 += __shfl_xor_sync(0xffffffffu, s1, 2);
                    const float mu0 = s0 * (1.f / 64.f), mu1 = s1 * (1.f / 64.f);
                    float q0 = 0.f, q1 = 0.f;
#pragma unroll
                    for (int j = 0; j < 8; j++) {
                        float d;
                        d = acc[4 * j] - mu0; q0 += d * d; d = acc[4 * j + 1] - mu0; q0 += d * d;
                        d = acc[4 * j + 2] - mu1; q1 += d * d; d = acc[4 * j + 3] - mu1; q1 += d * d;
                    }
                    q0 += __shfl_xor_sync(0xffffffffu, q0, 1); q0 += __shfl_xor_sync(0xffffffffu, q0, 2);
                    q1 += __shfl_xor_sync(0xffffffffu, q1, 1); q1 += __shfl_xor_sync(0xffffffffu, q1, 2);
                    if (c == 0) {
                        prm.stats_out[tile_n * S_ + row0] = make_float2(mu0, q0);
                        prm.stats_out[tile_n * S_ + row0 + 8] = make_float2(mu1, q1);
                    }
                }
            } else {
                const float sc = 0.25f * 1.4426950408889634f;
                const float a0 = rstd0 * sc, a1 = rstd1 * sc, rm0 = a0 * mean0, rm1 = a1 * mean1;
#pragma unroll
                for (int jj = 0; jj < 4; jj++) {
                    const float2 ca = *(const float2*)(s_cs + 16 * jj + 2 * c), cb = *(const float2*)(s_cs + 16 * jj + 8 + 2 * c);
                    const uint32_t u0 = pack_bf16(acc[8 * jj] * a0 - rm0 * ca.x, acc[8 * jj + 1] * a0 - rm0 * ca.y);
                    const uint32_t u1 = pack_bf16(acc[8 * jj + 2] * a1 - rm1 * ca.x, acc[8 * jj + 3] * a1 - rm1 * ca.y);
                    const uint32_t u2 = pack_bf16(acc[8 * jj + 4] * a0 - rm0 * cb.x, acc[8 * jj + 5] * a0 - rm0 * cb.y);
                    const uint32_t u3 = pack_bf16(acc[8 * jj + 6] * a1 - rm1 * cb.x, acc[8 * jj + 7] * a1 - rm1 * cb.y);
                    stsm_x4(rbase + (((2 * jj + (lane >> 4)) ^ (mrow & 7)) << 4), u0, u1, u2, u3);
                }
                fence_async_smem();
                named_bar(2 + wg, 128);
                if ((warp & 3) == 0 && elect_one()) { tma2d_store(mapC, stile + wg * 8192, n0, m0 + wg * 64); bulk_commit(); }
            }
            if constexpr (XKV) {
                {
                    const float* acx = &acc[32];
                    const float rm0 = rstd0 * mean0, rm1 = rstd1 * mean1;
                    float n0s = 0.f, n1s = 0.f, vmax = 0.f;
#pragma unroll
                    for (int j = 0; j < 2; j++) {
                        const float2 cs2 = SELF ? *(const float2*)(s_cs + 64 + 8 * j + 2 * c) : cskv[j];
                        const uint32_t u0 = pack_bf16(acx[4 * j] * rstd0 - rm0 * cs2.x, acx[4 * j + 1] * rstd0 - rm0 * cs2.y);
                        const uint32_t u1 = pack_bf16(acx[4 * j + 2] * rstd1 - rm1 * cs2.x, acx[4 * j + 3] * rstd1 - rm1 * cs2.y);
                        n0s += bf_lo(u0) * bf_lo(u0) + bf_hi(u0) * bf_hi(u0);
                        n1s += bf_lo(u1) * bf_lo(u1) + bf_hi(u1) * bf_hi(u1);
                        vmax = fmaxf(vmax, fmaxf(fmaxf(fabsf(bf_lo(u0)), fabsf(bf_hi(u0))), fmaxf(fabsf(bf_lo(u1)), fabsf(bf_hi(u1)))));
                        if (tile_n == 0) {
                            *(uint32_t*)(g_kimg + (row0 >> 3) * 256 + j * 128 + g * 16 + c * 4) = u0;
                            *(uint32_t*)(g_kimg + ((row0 + 8) >> 3) * 256 + j * 128 + g * 16 + c * 4) = u1;
                        } else {
                            uint8_t* vb = g_vimg + (row0 >> 4) * 768 + j * 256 + g * 16 + c * 4;
                            *(uint32_t*)(vb) = u0;
                            *(uint32_t*)(vb + 128) = u1;
                        }
                    }
                    if (tile_n == 1) {
                        uint8_t* vb = g_vimg + (row0 >> 4) * 768 + 512 + g * 16 + c * 4;
                        const uint32_t one = c == 0 ? 0x00003F80u : 0u;
                        *(uint32_t*)(vb) = one;
                        *(uint32_t*)(vb + 128) = one;
                    }
                    n0s += __shfl_xor_sync(0xffffffffu, n0s, 1); n0s += __shfl_xor_sync(0xffffffffu, n0s, 2);
                    n1s += __shfl_xor_sync(0xffffffffu, n1s, 1); n1s += __shfl_xor_sync(0xffffffffu, n1s, 2);
                    float km = tile_n == 0 ? fmaxf(n0s, n1s) : vmax;
                    if (!(n0s + n1s < INFINITY)) km = INFINITY;
#pragma unroll
                    for (int o = 1; o < 32; o <<= 1) km = fmaxf(km, __shfl_xor_sync(0xffffffffu, km, o));
                    if (lane == 0) s_red[warp] = km;
                    named_bar(1, 256);
                    if (tid == 0) {
                        float a = 0.f;
                        for (int i = 0; i < 8; i++) a = fmaxf(a, s_red[i]);
                        g_kvmax[tile_n * 16 + tile_m] = a;
                    }
                }
            }
            if ((warp & 3) == 0) bulk_wait_read();
        } else {
            const uint32_t stile = sbase + wg * (7 * 4096);
            const int mrow = (warp & 3) * 16 + (lane & 7) + ((lane >> 3) & 1) * 8;
            const float a0 = 0.5f * rstd0, a1 = 0.5f * rstd1, rm0 = a0 * mean0, rm1 = a1 * mean1;
#pragma unroll
            for (int jj = 0; jj < 14; jj++) {
                const float2 ca = *(const float2*)(s_cs + 16 * jj + 2 * c), cb = *(const float2*)(s_cs + 16 * jj + 8 + 2 * c);
                float y[8] = {acc[8 * jj] * a0 - rm0 * ca.x,     acc[8 * jj + 1] * a0 - rm0 * ca.y,
                              acc[8 * jj + 2] * a1 - rm1 * ca.x, acc[8 * jj + 3] * a1 - rm1 * ca.y,
                              acc[8 * jj + 4] * a0 - rm0 * cb.x, acc[8 * jj + 5] * a0 - rm0 * cb.y,
                              acc[8 * jj + 6] * a1 - rm1 * cb.x, acc[8 * jj + 7] * a1 - rm1 * cb.y};
#pragma unroll
                for (int i = 0; i < 8; i++) {
                    float t;
                    asm("tanh.approx.f32 %0, %1;" : "=f"(t) : "f"(y[i]));
                    y[i] = fmaf(y[i], t, y[i]);
                }
                const int chunk = (2 * jj + (lane >> 4)) & 3, blk = jj >> 1;
                stsm_x4(stile + blk * 4096 + mrow * 64 + ((chunk ^ ((mrow >> 1) & 3)) << 4),
                        pack_bf16(y[0], y[1]), pack_bf16(y[2], y[3]), pack_bf16(y[4], y[5]), pack_bf16(y[6], y[7]));
                if (jj & 1) {
                    fence_async_smem();
                    __syncwarp();
                    if (elect_one()) {
                        tma2d_store(mapC, stile + blk * 4096 + (warp & 3) * 1024, n0 + blk * 32, m0 + wg * 64 + (warp & 3) * 16);
                        bulk_commit();
                    }
                }
            }
            bulk_wait_read();
        }
    }
    if (tid == 0) TL(prm.tk, 3);
}

#define WO_ST 9
#define F2_ST 6
#define F1_ST 4
#define QKV_ST 8
constexpr int QKV_STAGES = QKV_ST, WO_STAGES = WO_ST, FFN2_STAGES = F2_ST, FFN1_STAGES = F1_ST;
template <bool SELF>
__global__ void __launch_bounds__(SELF ? 640 : 288) qkv_kernel(const __grid_constant__ CUtensorMap mapA, const __grid_constant__ CUtensorMap mapWq,
                                                  const __grid_constant__ CUtensorMap mapQ, const GemmParams prm) {
    extern __shared__ __align__(1024) uint8_t smem_raw[];
    const int tn = blockIdx.x & 7;
    if (tn < 2) gemm_body<80, 8, QKV_STAGES, EPI_QKV, SELF>(&mapA, &mapWq, &mapA, &mapQ, prm, blockIdx.x >> 3, tn, smem_raw);
    else gemm_body<64, 8, QKV_STAGES, EPI_QKV, SELF>(&mapA, &mapWq, &mapA, &mapQ, prm, blockIdx.x >> 3, tn, smem_raw);
}
template <int KB, int STAGES>
__global__ void __launch_bounds__(288) res_gemm_kernel(const __grid_constant__ CUtensorMap mapA, const __grid_constant__ CUtensorMap mapW,
                                                       const __grid_constant__ CUtensorMap mapR, const __grid_constant__ CUtensorMap mapC, const GemmParams prm) {
    extern __shared__ __align__(1024) uint8_t smem_raw[];
    gemm_body<64, KB, STAGES, EPI_RES>(&mapA, &mapW, &mapR, &mapC, prm, blockIdx.x >> 3, blockIdx.x & 7, smem_raw);
}
__global__ void __launch_bounds__(288) ffn1_kernel(const __grid_constant__ CUtensorMap mapA, const __grid_constant__ CUtensorMap mapW,
                                                   const __grid_constant__ CUtensorMap mapH, const GemmParams prm) {
    extern __shared__ __align__(1024) uint8_t smem_raw[];
    gemm_body<224, 8, FFN1_STAGES, EPI_FFN1>(&mapA, &mapW, &mapA, &mapH, prm, blockIdx.x >> 3, blockIdx.x & 7, smem_raw);
}

template <int STAGES> struct SkSmem {
    static constexpr int A_BYTES = 64 * 128, B_BYTES = 2 * 64 * 128, STAGE = A_BYTES + B_BYTES;
    static constexpr int AUX_OFF = STAGES * STAGE, TOTAL = AUX_OFF + 256;
};
template <int KB, int STAGES>
__global__ void __launch_bounds__(288) ffn2_kernel(const __grid_constant__ CUtensorMap mapA, const __grid_constant__ CUtensorMap mapW,
                                                   const __grid_constant__ CUtensorMap mapR, const __grid_constant__ CUtensorMap mapC, const GemmParams prm) {
    extern __shared__ __align__(1024) uint8_t smem_raw[];
    using SM = SkSmem<STAGES>;
    static_assert(KB >= STAGES && STAGES >= 4, "ring layout");
    pdl_launch();
    const uint32_t sbase = smem_u32(smem_raw);
    if (sbase & 1023) __trap();
    const uint32_t bar_full = sbase + SM::AUX_OFF, bar_empty = bar_full + 8 * STAGES;
    const int tid = threadIdx.x, lane = tid & 31;
    const int warp = __shfl_sync(0xffffffffu, tid >> 5, 0);
    const int tile_n = (blockIdx.x >> 1) & 3, tile_m = (blockIdx.x >> 3) * 2 + (blockIdx.x & 1);
    const int m0 = tile_m * 64, n0 = tile_n * 128;
    if (tid == 0) TL(prm.tk, 0);
    if (warp == 8 && elect_one()) {
#pragma unroll
        for (int s = 0; s < STAGES; s++) { mbar_init(bar_full + 8 * s, 1); mbar_init(bar_empty + 8 * s, 2); }
        fence_mbar_init();
    }
    if (warp == 1 && elect_one()) { prefetch_tmap(&mapW); prefetch_tmap(&mapA); prefetch_tmap(&mapR); prefetch_tmap(&mapC); }
    __syncthreads();
    if (warp == 8) {
        auto loadB = [&](int kb, int s) { tma3d(sbase + s * SM::STAGE + SM::A_BYTES, &mapW, 0, kb * 64, tile_n * 2, bar_full + 8 * s); };
        auto loadA = [&](int kb, int s) { tma2d(sbase + s * SM::STAGE, &mapA, kb * 64, m0, bar_full + 8 * s); };
        if (elect_one()) {
#pragma unroll
            for (int kb = 0; kb < STAGES; kb++) mbar_expect_tx(bar_full + 8 * kb, SM::STAGE);
            loadB(0, 0);
        }
        pdl_wait();
        if (elect_one()) {
#pragma unroll
            for (int kb = 0; kb < STAGES; kb++) {
                loadA(kb, kb);
                if (kb + 1 < STAGES) loadB(kb + 1, kb + 1);
            }
        }
        int s = 0, ph = 1;
#pragma unroll 1
        for (int kb = STAGES; kb < KB; kb++) {
            mbar_wait(bar_empty + 8 * s, ph ^ 1);
            if (elect_one()) {
                mbar_expect_tx(bar_full + 8 * s, SM::STAGE);
                loadA(kb, s);
                loadB(kb, s);
            }
            if (++s == STAGES) { s = 0; ph ^= 1; }
        }
        mbar_wait(bar_empty + 8 * s, ph ^ 1);
        if (elect_one()) {
            mbar_expect_tx(bar_full + 8 * s, 16384);
            tma3d(sbase + s * SM::STAGE, &mapR, 0, m0, tile_n * 2, bar_full + 8 * s);
        }
    } else {
        const int wg = warp >> 2, g = lane >> 2, c = lane & 3;
        float acc[64];
        const uint64_t dA0 = mkdesc(sbase + wg * 64, 16, 1024, 1);
        const uint64_t dB0 = mkdesc(sbase + SM::A_BYTES + wg * 4096, 8192, 1024, 1);
        int s = 0, ph = 0;
#pragma unroll 1
        for (int kb = 0; kb < KB; kb++) {
            mbar_wait(bar_full + 8 * s, ph);
            const uint64_t dA = dA0 + (uint64_t)(s * (SM::STAGE >> 4)), dB = dB0 + (uint64_t)(s * (SM::STAGE >> 4));
            wg_fence();
            wgmma_ss_n128_tb(acc, dA, dB, kb != 0);
            wgmma_ss_n128_tb(acc, dA + 2, dB + 128, 1);
            wg_commit();
            if (kb > 0) {
                wg_wait<1>();
                if ((warp & 3) == 0 && elect_one()) mbar_arrive(bar_empty + 8 * (s == 0 ? STAGES - 1 : s - 1));
            }
            if (++s == STAGES) { s = 0; ph ^= 1; }
        }
        const int s1 = s + 1 == STAGES ? 0 : s + 1, s2 = s1 + 1 == STAGES ? 0 : s1 + 1;
        mbar_wait(bar_empty + 8 * s1, ((KB + 1 - STAGES) / STAGES) & 1);
        mbar_wait(bar_empty + 8 * s2, ((KB + 2 - STAGES) / STAGES) & 1);
        pdl_wait();
        const uint32_t xw = sbase + (wg == 0 ? s1 : s2) * SM::STAGE + (tid & 127) * 16;
        const uint32_t xr = sbase + (wg == 0 ? s2 : s1) * SM::STAGE + (tid & 127) * 16;
        wg_wait<0>();
        fence_regs(acc);
        if (tid == 0) TL(prm.tk, 2);
        float v[32];
        if (wg == 0) {
#pragma unroll
            for (int i = 0; i < 8; i++)
                asm volatile("st.shared.v4.f32 [%0], {%1,%2,%3,%4};" ::"r"(xw + i * 2048), "f"(acc[32 + 4 * i]), "f"(acc[33 + 4 * i]), "f"(acc[34 + 4 * i]), "f"(acc[35 + 4 * i]) : "memory");
#pragma unroll
            for (int i = 0; i < 32; i++) v[i] = acc[i];
        } else {
#pragma unroll
            for (int i = 0; i < 8; i++)
                asm volatile("st.shared.v4.f32 [%0], {%1,%2,%3,%4};" ::"r"(xw + i * 2048), "f"(acc[4 * i]), "f"(acc[1 + 4 * i]), "f"(acc[2 + 4 * i]), "f"(acc[3 + 4 * i]) : "memory");
#pragma unroll
            for (int i = 0; i < 32; i++) v[i] = acc[32 + i];
        }
        const uint32_t stile = sbase + s * SM::STAGE + wg * 8192;
        const int mrow = (warp & 3) * 16 + (lane & 7) + ((lane >> 3) & 1) * 8;
        uint32_t rr[4][4];
        mbar_wait(bar_full + 8 * s, ph);
#pragma unroll
        for (int jj = 0; jj < 4; jj++)
            ldsm_x4(rr[jj][0], rr[jj][1], rr[jj][2], rr[jj][3], stile + mrow * 128 + (((2 * jj + (lane >> 4)) ^ (mrow & 7)) << 4));
        named_bar(1, 256);
#pragma unroll
        for (int i = 0; i < 8; i++) {
            float t0, t1, t2, t3;
            asm volatile("ld.shared.v4.f32 {%0,%1,%2,%3}, [%4];" : "=f"(t0), "=f"(t1), "=f"(t2), "=f"(t3) : "r"(xr + i * 2048) : "memory");
            v[4 * i] += t0; v[4 * i + 1] += t1; v[4 * i + 2] += t2; v[4 * i + 3] += t3;
        }
        float s0 = 0.f, s1v = 0.f;
#pragma unroll
        for (int jj = 0; jj < 4; jj++) {
            const uint32_t u0 = pack_bf16(v[8 * jj] + bf_lo(rr[jj][0]), v[8 * jj + 1] + bf_hi(rr[jj][0]));
            const uint32_t u1 = pack_bf16(v[8 * jj + 2] + bf_lo(rr[jj][1]), v[8 * jj + 3] + bf_hi(rr[jj][1]));
            const uint32_t u2 = pack_bf16(v[8 * jj + 4] + bf_lo(rr[jj][2]), v[8 * jj + 5] + bf_hi(rr[jj][2]));
            const uint32_t u3 = pack_bf16(v[8 * jj + 6] + bf_lo(rr[jj][3]), v[8 * jj + 7] + bf_hi(rr[jj][3]));
            stsm_x4(stile + mrow * 128 + (((2 * jj + (lane >> 4)) ^ (mrow & 7)) << 4), u0, u1, u2, u3);
            v[8 * jj] = bf_lo(u0); v[8 * jj + 1] = bf_hi(u0); v[8 * jj + 4] = bf_lo(u2); v[8 * jj + 5] = bf_hi(u2);
            v[8 * jj + 2] = bf_lo(u1); v[8 * jj + 3] = bf_hi(u1); v[8 * jj + 6] = bf_lo(u3); v[8 * jj + 7] = bf_hi(u3);
            s0 += (v[8 * jj] + v[8 * jj + 1]) + (v[8 * jj + 4] + v[8 * jj + 5]);
            s1v += (v[8 * jj + 2] + v[8 * jj + 3]) + (v[8 * jj + 6] + v[8 * jj + 7]);
        }
        fence_async_smem();
        named_bar(2 + wg, 128);
        if ((warp & 3) == 0 && elect_one()) { tma2d_store(&mapC, stile, n0 + wg * 64, m0); bulk_commit(); }
        if (prm.stats_out) {
            const int row0 = m0 + (warp & 3) * 16 + g;
            s0 += __shfl_xor_sync(0xffffffffu, s0, 1); s0 += __shfl_xor_sync(0xffffffffu, s0, 2);
            s1v += __shfl_xor_sync(0xffffffffu, s1v, 1); s1v += __shfl_xor_sync(0xffffffffu, s1v, 2);
            const float mu0 = s0 * (1.f / 64.f), mu1 = s1v * (1.f / 64.f);
            float q0 = 0.f, q1 = 0.f;
#pragma unroll
            for (int j = 0; j < 8; j++) {
                float d;
                d = v[4 * j] - mu0; q0 += d * d; d = v[4 * j + 1] - mu0; q0 += d * d;
                d = v[4 * j + 2] - mu1; q1 += d * d; d = v[4 * j + 3] - mu1; q1 += d * d;
            }
            q0 += __shfl_xor_sync(0xffffffffu, q0, 1); q0 += __shfl_xor_sync(0xffffffffu, q0, 2);
            q1 += __shfl_xor_sync(0xffffffffu, q1, 1); q1 += __shfl_xor_sync(0xffffffffu, q1, 2);
            if (c == 0) {
                prm.stats_out[(tile_n * 2 + wg) * S_ + row0] = make_float2(mu0, q0);
                prm.stats_out[(tile_n * 2 + wg) * S_ + row0 + 8] = make_float2(mu1, q1);
            }
        }
        if ((warp & 3) == 0) bulk_wait_read();
    }
    if (tid == 0) TL(prm.tk, 3);
}

#define ATT_NPOLY 11
constexpr int NPOLY = ATT_NPOLY;
__host__ __device__ constexpr bool is_mufu(int i) { return ((i + 1) * (16 - NPOLY)) / 16 != (i * (16 - NPOLY)) / 16; }

__device__ __forceinline__ float ex2(float x) { float r; asm("ex2.approx.ftz.f32 %0, %1;" : "=f"(r) : "f"(x)); return r; }
__device__ __forceinline__ uint32_t exp_pair_mufu(float a, float b) { return pack_bf16(ex2(a), ex2(b)); }
__device__ __forceinline__ uint32_t exp_pair_fma(float a, float b, uint32_t c3f) {
    constexpr float MAGIC = 98430.4140625f;
    const float ta = a + MAGIC, tb = b + (MAGIC - 143.5f);
    uint32_t y, m, r;
    asm("mad.lo.u32 %0, %1, 65536, %2;" : "=r"(y) : "r"(__float_as_uint(tb)), "r"(__float_as_uint(ta)));
    asm("lop3.b32 %0, %1, 0x007F007F, %2, 0xEA;" : "=r"(m) : "r"(y), "r"(c3f));
    const uint32_t e = y & 0xFF80FF80u;
    asm("fma.rn.bf16x2 %0, %1, %2, %3;" : "=r"(r) : "r"(y), "r"(m), "r"(e));
    return r;
}

constexpr int KCH = 256, NCH = S_ / KCH;
constexpr int K_BYTES = S_ * 32, V_BYTES = (S_ / 16) * 768;
constexpr int QO_BYTES = 128 * 128;
constexpr int ATT_SMEM = K_BYTES + V_BYTES + QO_BYTES;

__global__ void __launch_bounds__(512, 1) attn_kernel(const __grid_constant__ CUtensorMap mapQ, const __grid_constant__ CUtensorMap mapO,
                                                       const __nv_bfloat16* __restrict__ wo, const __nv_bfloat16* __restrict__ w1,
                                                       const __nv_bfloat16* __restrict__ w2, int tk) {
    extern __shared__ __align__(1024) uint8_t smem[];
    __shared__ uint64_t bars[NCH + 1];
    __shared__ int s_slow;
    const int tid = threadIdx.x, wg = tid >> 7, warp = (tid >> 5) & 3, lane = tid & 31;
    const uint32_t sK = smem_u32(smem), sV = sK + K_BYTES, sQ = sV + V_BYTES;
    if (blockIdx.x >= 128) {
        pdl_launch();
        pdl_wait();
        side_job(blockIdx.x - 128, (float*)smem, wo, w1, w2);
        return;
    }
    CK(tk, 9);
    if (tid == 0) TL(tk, 0);
    if (tid == 0) {
#pragma unroll
        for (int i = 0; i <= NCH; i++) mbar_init(smem_u32(&bars[i]), 1);
        s_slow = 0;
        fence_mbar_init();
    }
    if (tid == 32) { prefetch_tmap(&mapQ); prefetch_tmap(&mapO); }
    __syncthreads();
    pdl_launch();
    CK(tk, 10);
    pdl_wait();
    CK(tk, 11);
    if (tid == 0) TL(tk, 1);
    const int wu = __shfl_sync(0xffffffffu, tid >> 5, 0);
    auto fetch_chunk = [&](int w) {
        if (elect_one()) {
            const uint32_t bar = smem_u32(&bars[w]);
            mbar_expect_tx(bar, KCH * 32 + (KCH / 16) * 768);
            bulk_load(sK + w * KCH * 32, g_kimg + w * KCH * 32, KCH * 32, bar);
            bulk_load(sV + w * (KCH / 16) * 768, g_vimg + w * (KCH / 16) * 768, (KCH / 16) * 768, bar);
        }
    };
    const int tb = blockIdx.x >> 3, hg = blockIdx.x & 7;
    if (wu == 1 && elect_one()) {
        mbar_expect_tx(smem_u32(&bars[NCH]), QO_BYTES);
        tma2d(sQ, &mapQ, hg * 64, tb * 128, smem_u32(&bars[NCH]));
    }
    if (wu == 0) fetch_chunk(0);
    float kvm = g_kvmax[lane];
    const int lrow = warp * 16 + (lane & 7) + ((lane >> 3) & 1) * 8;
    const uint32_t qoff = lrow * 128 + (((2 * wg + (lane >> 4)) ^ (lrow & 7)) << 4);
    uint32_t qa[2][4];
    mbar_wait(smem_u32(&bars[NCH]), 0);
    ldsm_x4(qa[0][0], qa[0][1], qa[0][2], qa[0][3], sQ + qoff);
    ldsm_x4(qa[1][0], qa[1][1], qa[1][2], qa[1][3], sQ + 8192 + qoff);
    CK(tk, 12);
    {
        float qn = 0.f;
#pragma unroll
        for (int m = 0; m < 2; m++) {
            float n0 = bf_lo(qa[m][0]) * bf_lo(qa[m][0]) + bf_hi(qa[m][0]) * bf_hi(qa[m][0]) + bf_lo(qa[m][2]) * bf_lo(qa[m][2]) + bf_hi(qa[m][2]) * bf_hi(qa[m][2]);
            float n1 = bf_lo(qa[m][1]) * bf_lo(qa[m][1]) + bf_hi(qa[m][1]) * bf_hi(qa[m][1]) + bf_lo(qa[m][3]) * bf_lo(qa[m][3]) + bf_hi(qa[m][3]) * bf_hi(qa[m][3]);
            n0 += __shfl_xor_sync(0xffffffffu, n0, 1); n0 += __shfl_xor_sync(0xffffffffu, n0, 2);
            n1 += __shfl_xor_sync(0xffffffffu, n1, 1); n1 += __shfl_xor_sync(0xffffffffu, n1, 2);
            if (!(n0 == n0) || !(n1 == n1)) n0 = INFINITY;
            qn = fmaxf(qn, fmaxf(n0, n1));
        }
        CK(tk, 13);
#pragma unroll
        for (int o = 1; o < 16; o <<= 1) kvm = fmaxf(kvm, __shfl_xor_sync(0xffffffffu, kvm, o));
        const float km = __shfl_sync(0xffffffffu, kvm, 0), vm = __shfl_sync(0xffffffffu, kvm, 16);
        const bool ok = (qn * km <= 10000.f) && (vm <= 16384.f);
        if (!ok) s_slow = 1;
    }
    CK(tk, 14);
    float oacc[2][12];
#pragma unroll
    for (int m = 0; m < 2; m++)
#pragma unroll
        for (int i = 0; i < 12; i++) oacc[m][i] = 0.f;
    __syncthreads();
    const bool slow = s_slow != 0;
    if (wu >= 1 && wu < NCH) fetch_chunk(wu);
    CK(tk, 15);

    const uint64_t dK0 = mkdesc(sK, 128, 256, 0);
    const uint64_t dV0 = mkdesc(sV, 128, 256, 0);
    uint32_t c3f;
    asm volatile("mov.b32 %0, 0x3F003F00;" : "=r"(c3f));
    if (!slow) {
        uint64_t dK = dK0, dV = dV0;
        float s[32];
        fence_regs(oacc[0]); fence_regs(oacc[1]);
        mbar_wait(smem_u32(&bars[0]), 0);
        wg_fence();
        wgmma_rs_n64_z(s, qa[0][0], qa[0][1], qa[0][2], qa[0][3], dK);
        wg_commit();
#pragma unroll 1
        for (int ch = 0; ch < NCH; ch++) {
#pragma unroll
            for (int tt = 0; tt < KCH / 64; tt++) {
#pragma unroll
                for (int m = 0; m < 2; m++) {
                    wg_wait<0>();
                    fence_regs(s);
                    uint32_t p[16];
#pragma unroll
                    for (int i = 0; i < 16; i++) p[i] = is_mufu(i) ? exp_pair_mufu(s[2 * i], s[2 * i + 1]) : exp_pair_fma(s[2 * i], s[2 * i + 1], c3f);
                    if (m == 1 && tt == KCH / 64 - 1) mbar_wait(smem_u32(&bars[ch + 1 < NCH ? ch + 1 : ch]), 0);
                    wg_fence();
#pragma unroll
                    for (int kk = 0; kk < 4; kk++)
                        wgmma_rs_n24_tb(oacc[m], p[4 * kk], p[4 * kk + 1], p[4 * kk + 2], p[4 * kk + 3], dV + (uint64_t)((tt * 4 + kk) * (768 / 16)));
                    wgmma_rs_n64_z(s, qa[1 - m][0], qa[1 - m][1], qa[1 - m][2], qa[1 - m][3], dK + (uint64_t)((tt + m) * (64 * 32 / 16)));
                    wg_commit();
                }
            }
            dK += KCH * 32 / 16;
            dV += (KCH / 16) * (768 / 16);
        }
        wg_wait<0>();
        fence_regs(s);
    } else {
        float mx[2][2] = {{-INFINITY, -INFINITY}, {-INFINITY, -INFINITY}};
#pragma unroll 1
        for (int t = 0; t < S_ / 64; t++) {
            if ((t & 3) == 0) mbar_wait(smem_u32(&bars[t >> 2]), 0);
            const uint64_t dK = dK0 + (uint64_t)(t * 64 * 32 / 16);
            const uint64_t dV = dV0 + (uint64_t)(t * 4 * 768 / 16);
#pragma unroll
            for (int m = 0; m < 2; m++) {
                float s[32];
                wg_fence();
                wgmma_rs_n64_z(s, qa[m][0], qa[m][1], qa[m][2], qa[m][3], dK);
                wg_commit();
                wg_wait<0>();
                fence_regs(s);
                fence_regs(oacc[m]);
                float r0 = mx[m][0], r1 = mx[m][1];
#pragma unroll
                for (int j = 0; j < 8; j++) {
                    r0 = fmaxf(r0, fmaxf(s[4 * j], s[4 * j + 1]));
                    r1 = fmaxf(r1, fmaxf(s[4 * j + 2], s[4 * j + 3]));
                }
                r0 = fmaxf(r0, __shfl_xor_sync(0xffffffffu, r0, 1)); r0 = fmaxf(r0, __shfl_xor_sync(0xffffffffu, r0, 2));
                r1 = fmaxf(r1, __shfl_xor_sync(0xffffffffu, r1, 1)); r1 = fmaxf(r1, __shfl_xor_sync(0xffffffffu, r1, 2));
                const float al0 = ex2(mx[m][0] - r0), al1 = ex2(mx[m][1] - r1);
                mx[m][0] = r0; mx[m][1] = r1;
#pragma unroll
                for (int j = 0; j < 3; j++) {
                    oacc[m][4 * j] *= al0; oacc[m][4 * j + 1] *= al0;
                    oacc[m][4 * j + 2] *= al1; oacc[m][4 * j + 3] *= al1;
                }
                uint32_t p[16];
#pragma unroll
                for (int j = 0; j < 8; j++) {
                    p[2 * j] = pack_bf16(ex2(s[4 * j] - r0), ex2(s[4 * j + 1] - r0));
                    p[2 * j + 1] = pack_bf16(ex2(s[4 * j + 2] - r1), ex2(s[4 * j + 3] - r1));
                }
                fence_regs(oacc[m]);
                wg_fence();
#pragma unroll
                for (int kk = 0; kk < 4; kk++)
                    wgmma_rs_n24_tb(oacc[m], p[4 * kk], p[4 * kk + 1], p[4 * kk + 2], p[4 * kk + 3], dV + (uint64_t)(kk * 768 / 16));
                wg_commit();
                wg_wait<0>();
            }
        }
    }
    fence_regs(oacc[0]); fence_regs(oacc[1]);
    if (tid == 0) TL(tk, 2);
#pragma unroll
    for (int m = 0; m < 2; m++) {
        const float l0 = __shfl_sync(0xffffffffu, oacc[m][8], lane & ~3);
        const float l1 = __shfl_sync(0xffffffffu, oacc[m][10], lane & ~3);
        const float r0 = __fdividef(1.0f, l0), r1 = __fdividef(1.0f, l1);
        stsm_x4(sQ + m * 8192 + qoff, pack_bf16(oacc[m][0] * r0, oacc[m][1] * r0), pack_bf16(oacc[m][2] * r1, oacc[m][3] * r1),
                pack_bf16(oacc[m][4] * r0, oacc[m][5] * r0), pack_bf16(oacc[m][6] * r1, oacc[m][7] * r1));
    }
    fence_async_smem();
    __syncthreads();
    if (wu == 0 && elect_one()) {
        tma2d_store(&mapO, sQ, hg * 64, tb * 128);
        bulk_commit();
        bulk_wait_read();
    }
    if (tid == 0) TL(tk, 3);
}

typedef CUresult (*EncodeFn)(CUtensorMap*, CUtensorMapDataType, cuuint32_t, void*, const cuuint64_t*, const cuuint64_t*, const cuuint32_t*,
                             const cuuint32_t*, CUtensorMapInterleave, CUtensorMapSwizzle, CUtensorMapL2promotion, CUtensorMapFloatOOBfill);

EncodeFn get_encode() {
    static EncodeFn fn = nullptr;
    if (!fn) {
        void* p = nullptr;
        cudaDriverEntryPointQueryResult qr;
        cudaGetDriverEntryPoint("cuTensorMapEncodeTiled", &p, cudaEnableDefault, &qr);
        fn = (EncodeFn)p;
    }
    return fn;
}
CUtensorMap map2d(const void* ptr, uint64_t cols, uint64_t rows, uint32_t bc, uint32_t br, CUtensorMapSwizzle sw) {
    CUtensorMap m;
    cuuint64_t gd[2] = {cols, rows}, gs[1] = {cols * 2};
    cuuint32_t bx[2] = {bc, br}, es[2] = {1, 1};
    get_encode()(&m, CU_TENSOR_MAP_DATA_TYPE_BFLOAT16, 2, (void*)ptr, gd, gs, bx, es, CU_TENSOR_MAP_INTERLEAVE_NONE, sw,
                 CU_TENSOR_MAP_L2_PROMOTION_L2_128B, CU_TENSOR_MAP_FLOAT_OOB_FILL_NONE);
    return m;
}
CUtensorMap map3d64(const void* ptr, uint64_t cols, uint64_t rows, uint32_t br, uint32_t nb) {
    CUtensorMap m;
    cuuint64_t gd[3] = {64, rows, cols / 64}, gs[2] = {cols * 2, 128};
    cuuint32_t bx[3] = {64, br, nb}, es[3] = {1, 1, 1};
    get_encode()(&m, CU_TENSOR_MAP_DATA_TYPE_BFLOAT16, 3, (void*)ptr, gd, gs, bx, es, CU_TENSOR_MAP_INTERLEAVE_NONE, CU_TENSOR_MAP_SWIZZLE_128B,
                 CU_TENSOR_MAP_L2_PROMOTION_L2_128B, CU_TENSOR_MAP_FLOAT_OOB_FILL_NONE);
    return m;
}
CUtensorMap map3d32(const void* ptr, uint64_t cols, uint64_t rows, uint32_t br, uint32_t nb) {
    CUtensorMap m;
    cuuint64_t gd[3] = {32, rows, cols / 32}, gs[2] = {cols * 2, 64};
    cuuint32_t bx[3] = {32, br, nb}, es[3] = {1, 1, 1};
    get_encode()(&m, CU_TENSOR_MAP_DATA_TYPE_BFLOAT16, 3, (void*)ptr, gd, gs, bx, es, CU_TENSOR_MAP_INTERLEAVE_NONE, CU_TENSOR_MAP_SWIZZLE_64B,
                 CU_TENSOR_MAP_L2_PROMOTION_L2_128B, CU_TENSOR_MAP_FLOAT_OOB_FILL_NONE);
    return m;
}

template <typename... KArgs, typename... Args>
void launch(void (*kern)(KArgs...), int grid, int block, int smem, int cluster, bool pdl, Args... args) {
    cudaLaunchConfig_t cfg = {};
    cfg.gridDim = dim3(grid);
    cfg.blockDim = dim3(block);
    cfg.dynamicSmemBytes = smem;
    cfg.stream = cudaStreamPerThread;
    cudaLaunchAttribute at[2];
    int n = 0;
    if (cluster > 1) { at[n].id = cudaLaunchAttributeClusterDimension; at[n].val.clusterDim.x = cluster; at[n].val.clusterDim.y = 1; at[n].val.clusterDim.z = 1; n++; }
    if (pdl) { at[n].id = cudaLaunchAttributeProgrammaticStreamSerialization; at[n].val.programmaticStreamSerializationAllowed = 1; n++; }
    cfg.attrs = at;
    cfg.numAttrs = n;
    cudaLaunchKernelEx(&cfg, kern, KArgs(args)...);
}

template <typename T> void* sym(const T& s) { void* p = nullptr; cudaGetSymbolAddress(&p, s); return p; }

}

extern "C" void kernel_launch(void* const* d_in, const int* in_sizes, int n_in, void* d_out, int out_size) {
    const __nv_bfloat16* x = (const __nv_bfloat16*)d_in[0];
    const __nv_bfloat16* wq = (const __nv_bfloat16*)d_in[1];
    const __nv_bfloat16* wk = (const __nv_bfloat16*)d_in[2];
    const __nv_bfloat16* wv = (const __nv_bfloat16*)d_in[3];
    const __nv_bfloat16* wo = (const __nv_bfloat16*)d_in[4];
    const __nv_bfloat16* w1 = (const __nv_bfloat16*)d_in[6];
    const __nv_bfloat16* w2 = (const __nv_bfloat16*)d_in[7];

    constexpr int SM_QKV = GemmSmem<QKV_STAGES, EPI_QKV>::TOTAL, SM_QKV0 = GemmSmem<QKV_STAGES, EPI_QKV>::TOTAL_SELF;
    static_assert(SM_QKV0 <= 232448, "shared memory");
    constexpr int SM_WO = GemmSmem<WO_STAGES, EPI_RES>::TOTAL, SM_FFN2 = GemmSmem<FFN2_STAGES, EPI_RES>::TOTAL;
    static_assert(SM_WO > 116736 && SM_FFN2 > 116736, "one CTA per SM");
    constexpr int SM_FFN1 = GemmSmem<FFN1_STAGES, EPI_FFN1>::TOTAL;
    cudaFuncSetAttribute(qkv_kernel<false>, cudaFuncAttributeMaxDynamicSharedMemorySize, SM_QKV);
    cudaFuncSetAttribute(qkv_kernel<true>, cudaFuncAttributeMaxDynamicSharedMemorySize, SM_QKV0);
    cudaFuncSetAttribute(res_gemm_kernel<8, WO_STAGES>, cudaFuncAttributeMaxDynamicSharedMemorySize, SM_WO);
    cudaFuncSetAttribute(ffn1_kernel, cudaFuncAttributeMaxDynamicSharedMemorySize, SM_FFN1);
    cudaFuncSetAttribute(res_gemm_kernel<28, FFN2_STAGES>, cudaFuncAttributeMaxDynamicSharedMemorySize, SM_FFN2);
    cudaFuncSetAttribute(attn_kernel, cudaFuncAttributeMaxDynamicSharedMemorySize, ATT_SMEM);
    cudaFuncSetAttribute(ffn2_kernel<28, F2SK_ST>, cudaFuncAttributeMaxDynamicSharedMemorySize, SkSmem<F2SK_ST>::TOTAL);
    cudaFuncSetAttribute(ffn2_kernel<28, F2SK_ST>, cudaFuncAttributePreferredSharedMemoryCarveout, 100);
    cudaFuncSetAttribute(qkv_kernel<false>, cudaFuncAttributePreferredSharedMemoryCarveout, 100);
    cudaFuncSetAttribute(qkv_kernel<true>, cudaFuncAttributePreferredSharedMemoryCarveout, 100);
    cudaFuncSetAttribute(res_gemm_kernel<8, WO_STAGES>, cudaFuncAttributePreferredSharedMemoryCarveout, 100);
    cudaFuncSetAttribute(ffn1_kernel, cudaFuncAttributePreferredSharedMemoryCarveout, 100);
    cudaFuncSetAttribute(res_gemm_kernel<28, FFN2_STAGES>, cudaFuncAttributePreferredSharedMemoryCarveout, 100);
    cudaFuncSetAttribute(attn_kernel, cudaFuncAttributePreferredSharedMemoryCarveout, 100);

    void *q = sym(g_q), *o = sym(g_o), *x1 = sym(g_x1), *x2 = sym(g_x2), *x3 = sym(g_x3), *h = sym(g_h);
    float2* stats = (float2*)sym(g_stats);
    const void* xs[5] = {x, x1, x2, x3, d_out};

    const CUtensorMapSwizzle SW128 = CU_TENSOR_MAP_SWIZZLE_128B, SW64 = CU_TENSOR_MAP_SWIZZLE_64B;
    const CUtensorMap mWq = map3d32(wq, D_, D_, 64, 2);
    const CUtensorMap mWo = map2d(wo, D_, D_, 64, 64, SW128);
    const CUtensorMap mW1 = map3d32(w1, F_, D_, 64, 7);
    const CUtensorMap mW2 = map2d(w2, D_, F_, 64, 64, SW128);
    const CUtensorMap mQ = map2d(q, D_, S_, 64, 64, SW128);
    const CUtensorMap mQa = map2d(q, D_, S_, 64, 128, SW128), mOs = map2d(o, D_, S_, 64, 128, SW128);
    const CUtensorMap mHst = map2d(h, F_, S_, 32, 16, SW64);
    CUtensorMap mXa[4], mXs[5];
    for (int i = 0; i < 4; i++) {
        mXa[i] = map2d(xs[i], D_, S_, 64, 128, SW128);
    }
    for (int i = 0; i < 5; i++) mXs[i] = map2d(xs[i], D_, S_, 64, 64, SW128);
    const CUtensorMap mOa = map2d(o, D_, S_, 64, 128, SW128);
    const CUtensorMap mHa = map2d(h, F_, S_, 64, 128, SW128);

    for (int layer = 0; layer < 2; layer++) {
        const int xi = layer * 2;
        GemmParams p;
        p.wkv = wk; p.wv = wv;
        p.stats_in = stats + (size_t)xi * 8 * S_; p.stats_out = nullptr; p.tk = 1 + 5 * layer;
        if (layer == 0) launch(qkv_kernel<true>, 128, 640, SM_QKV0, 1, false, mXa[xi], mWq, mQ, p);
        else launch(qkv_kernel<false>, 128, 288, SM_QKV, 2, true, mXa[xi], mWq, mQ, p);
        launch(attn_kernel, layer == 0 ? 128 + SIDE_CTAS : 128, 512, ATT_SMEM, 1, true, mQa, mOs, wo, w1, w2, 2 + 5 * layer);
        p.stats_in = nullptr; p.stats_out = stats + (size_t)(xi + 1) * 8 * S_; p.tk = 3 + 5 * layer;
        launch(res_gemm_kernel<8, WO_STAGES>, 128, 288, SM_WO, 2, true, mOa, mWo, mXa[xi], mXs[xi + 1], p);
        p.stats_in = stats + (size_t)(xi + 1) * 8 * S_; p.stats_out = nullptr; p.tk = 4 + 5 * layer;
        launch(ffn1_kernel, 128, 288, SM_FFN1, 1, true, mXa[xi + 1], mW1, mHst, p);
        p.stats_in = nullptr; p.stats_out = layer == 0 ? stats + (size_t)2 * 8 * S_ : nullptr; p.tk = 5 + 5 * layer;
        launch(ffn2_kernel<28, F2SK_ST>, 128, 288, SkSmem<F2SK_ST>::TOTAL, F2SK_CL, true, map2d(h, F_, S_, 64, 64, SW128), map3d64(w2, D_, F_, 64, 2),
               map3d64(xs[xi + 1], D_, S_, 64, 2), mXs[xi + 2], p);
    }
}
```

```cpp
#include <cuda_runtime.h>
#include <cuda_bf16.h>
#include <cuda.h>
#include <stdint.h>

namespace {

constexpr int S_ = 2048, D_ = 512, F_ = 1792;

__device__ __align__(1024) __nv_bfloat16 g_q[S_ * D_];
__device__ __align__(1024) __nv_bfloat16 g_o[S_ * D_];
__device__ __align__(1024) __nv_bfloat16 g_x1[S_ * D_];
__device__ __align__(1024) __nv_bfloat16 g_x2[S_ * D_];
__device__ __align__(1024) __nv_bfloat16 g_x3[S_ * D_];
__device__ __align__(1024) __nv_bfloat16 g_h[S_ * F_];
__device__ __align__(1024) uint8_t g_kimg[S_ * 32];
__device__ __align__(1024) uint8_t g_vimg[(S_ / 16) * 768];
__device__ __align__(1024) float2 g_stats[4][8 * S_];
__device__ __align__(16) float g_cs_q[D_];
__device__ __align__(16) float g_cs_kv[32];
__device__ __align__(16) float g_cs_1[F_];
__device__ __align__(16) float g_kvmax[32];

__device__ __forceinline__ uint32_t smem_u32(const void* p) { return (uint32_t)__cvta_generic_to_shared(p); }
__device__ __forceinline__ void mbar_init(uint32_t bar, uint32_t cnt) {
    asm volatile("mbarrier.init.shared::cta.b64 [%0], %1;" ::"r"(bar), "r"(cnt));
}
__device__ __forceinline__ void mbar_expect_tx(uint32_t bar, uint32_t bytes) {
    asm volatile("mbarrier.arrive.expect_tx.shared::cta.b64 _, [%0], %1;" ::"r"(bar), "r"(bytes) : "memory");
}
__device__ __forceinline__ void mbar_arrive(uint32_t bar) {
    asm volatile("mbarrier.arrive.shared::cta.b64 _, [%0];" ::"r"(bar) : "memory");
}
__device__ __forceinline__ void mbar_wait(uint32_t bar, uint32_t parity) {
    asm volatile("{\n.reg .pred p;\nWAIT_%=:\nmbarrier.try_wait.parity.shared::cta.b64 p, [%0], %1;\n@p bra DONE_%=;\nbra WAIT_%=;\nDONE_%=:\n}" ::"r"(bar), "r"(parity) : "memory");
}
__device__ __forceinline__ void bulk_load(uint32_t dst, const void* src, uint32_t bytes, uint32_t bar) {
    asm volatile("cp.async.bulk.shared::cluster.global.mbarrier::complete_tx::bytes [%0], [%1], %2, [%3];" ::"r"(dst), "l"(src), "r"(bytes), "r"(bar) : "memory");
}
__device__ __forceinline__ void tma2d(uint32_t dst, const CUtensorMap* m, int c0, int c1, uint32_t bar) {
    asm volatile("cp.async.bulk.tensor.2d.shared::cluster.global.mbarrier::complete_tx::bytes [%0], [%1, {%3, %4}], [%2];" ::"r"(dst), "l"(m), "r"(bar), "r"(c0), "r"(c1) : "memory");
}
__device__ __forceinline__ void tma3d(uint32_t dst, const CUtensorMap* m, int c0, int c1, int c2, uint32_t bar) {
    asm volatile("cp.async.bulk.tensor.3d.shared::cluster.global.mbarrier::complete_tx::bytes [%0], [%1, {%3, %4, %5}], [%2];" ::"r"(dst), "l"(m), "r"(bar), "r"(c0), "r"(c1), "r"(c2) : "memory");
}
__device__ __forceinline__ void tma2d_store(const CUtensorMap* m, uint32_t src, int c0, int c1) {
    asm volatile("cp.async.bulk.tensor.2d.global.shared::cta.bulk_group [%0, {%2, %3}], [%1];" ::"l"(m), "r"(src), "r"(c0), "r"(c1) : "memory");
}
__device__ __forceinline__ void bulk_commit() { asm volatile("cp.async.bulk.commit_group;" ::: "memory"); }
__device__ __forceinline__ void bulk_wait_read() { asm volatile("cp.async.bulk.wait_group.read 0;" ::: "memory"); }
__device__ __forceinline__ void prefetch_tmap(const CUtensorMap* m) { asm volatile("prefetch.tensormap [%0];" ::"l"(m) : "memory"); }
__device__ __forceinline__ void fence_async_smem() { asm volatile("fence.proxy.async.shared::cta;" ::: "memory"); }
__device__ __forceinline__ void fence_mbar_init() { asm volatile("fence.mbarrier_init.release.cluster;" ::: "memory"); }
__device__ __forceinline__ void pdl_wait() { asm volatile("griddepcontrol.wait;" ::: "memory"); }
__device__ __forceinline__ void pdl_launch() { asm volatile("griddepcontrol.launch_dependents;" ::: "memory"); }
__device__ __forceinline__ bool elect_one() {
    uint32_t p;
    asm volatile("{\n.reg .pred p;\nelect.sync _|p, 0xffffffff;\nselp.b32 %0, 1, 0, p;\n}" : "=r"(p));
    return p != 0;
}
__device__ __forceinline__ void named_bar(int id, int n) { asm volatile("bar.sync %0, %1;" ::"r"(id), "r"(n) : "memory"); }

__device__ __forceinline__ void wg_fence() { asm volatile("wgmma.fence.sync.aligned;" ::: "memory"); }
__device__ __forceinline__ void wg_commit() { asm volatile("wgmma.commit_group.sync.aligned;" ::: "memory"); }
template <int N> __device__ __forceinline__ void wg_wait() { asm volatile("wgmma.wait_group.sync.aligned %0;" ::"n"(N) : "memory"); }
template <int N> __device__ __forceinline__ void fence_regs(float (&d)[N]) {
#pragma unroll
    for (int i = 0; i < N; i++) asm volatile("" : "+f"(d[i])::"memory");
}
__device__ __forceinline__ uint64_t mkdesc(uint32_t addr, uint32_t lbo, uint32_t sbo, uint32_t swz) {
    uint64_t d = 0;
    d |= (uint64_t)((addr & 0x3FFFF) >> 4);
    d |= (uint64_t)((lbo & 0x3FFFF) >> 4) << 16;
    d |= (uint64_t)((sbo & 0x3FFFF) >> 4) << 32;
    d |= (uint64_t)swz << 62;
    return d;
}
__device__ __forceinline__ void ldsm_x4(uint32_t& r0, uint32_t& r1, uint32_t& r2, uint32_t& r3, uint32_t addr) {
    asm volatile("ldmatrix.sync.aligned.m8n8.x4.shared.b16 {%0,%1,%2,%3}, [%4];" : "=r"(r0), "=r"(r1), "=r"(r2), "=r"(r3) : "r"(addr) : "memory");
}
__device__ __forceinline__ void stsm_x4(uint32_t addr, uint32_t r0, uint32_t r1, uint32_t r2, uint32_t r3) {
    asm volatile("stmatrix.sync.aligned.m8n8.x4.shared.b16 [%0], {%1,%2,%3,%4};" ::"r"(addr), "r"(r0), "r"(r1), "r"(r2), "r"(r3) : "memory");
}
__device__ __forceinline__ uint32_t pack_bf16(float lo, float hi) {
    uint32_t r;
    asm("cvt.rn.bf16x2.f32 %0, %1, %2;" : "=r"(r) : "f"(hi), "f"(lo));
    return r;
}
__device__ __forceinline__ float bf_lo(uint32_t v) { return __uint_as_float(v << 16); }
__device__ __forceinline__ float bf_hi(uint32_t v) { return __uint_as_float(v & 0xFFFF0000u); }

#define WG_REGS_4(o) "+f"(d[o]), "+f"(d[o + 1]), "+f"(d[o + 2]), "+f"(d[o + 3])
#define WG_REGS_8(o) WG_REGS_4(o), WG_REGS_4(o + 4)
#define WG_REGS_16(o) WG_REGS_8(o), WG_REGS_8(o + 8)
#define WG_REGS_32(o) WG_REGS_16(o), WG_REGS_16(o + 16)

__device__ __forceinline__ void wgmma_ss_n80_tb(float (&d)[40], uint64_t dA, uint64_t dB, int sc) {
    asm volatile("{\n.reg .pred p;\nsetp.ne.b32 p, %42, 0;\n"
                 "wgmma.mma_async.sync.aligned.m64n80k16.f32.bf16.bf16 "
                 "{%0,%1,%2,%3,%4,%5,%6,%7,%8,%9,%10,%11,%12,%13,%14,%15,%16,%17,%18,%19,%20,%21,%22,%23,%24,%25,%26,%27,%28,%29,%30,%31,"
                 "%32,%33,%34,%35,%36,%37,%38,%39}, %40, %41, p, 1, 1, 0, 1;\n}\n"
                 : WG_REGS_32(0), WG_REGS_8(32) : "l"(dA), "l"(dB), "r"(sc));
}
__device__ __forceinline__ void wgmma_ss_n64_tb(float (&d)[32], uint64_t dA, uint64_t dB, int sc) {
    asm volatile("{\n.reg .pred p;\nsetp.ne.b32 p, %34, 0;\n"
                 "wgmma.mma_async.sync.aligned.m64n64k16.f32.bf16.bf16 "
                 "{%0,%1,%2,%3,%4,%5,%6,%7,%8,%9,%10,%11,%12,%13,%14,%15,%16,%17,%18,%19,%20,%21,%22,%23,%24,%25,%26,%27,%28,%29,%30,%31}, "
                 "%32, %33, p, 1, 1, 0, 1;\n}\n"
                 : WG_REGS_32(0) : "l"(dA), "l"(dB), "r"(sc));
}
__device__ __forceinline__ void wgmma_ss_n224_tb(float (&d)[112], uint64_t dA, uint64_t dB, int sc) {
    asm volatile("{\n.reg .pred p;\nsetp.ne.b32 p, %114, 0;\n"
                 "wgmma.mma_async.sync.aligned.m64n224k16.f32.bf16.bf16 "
                 "{%0,%1,%2,%3,%4,%5,%6,%7,%8,%9,%10,%11,%12,%13,%14,%15,%16,%17,%18,%19,%20,%21,%22,%23,%24,%25,%26,%27,%28,%29,%30,%31,"
                 "%32,%33,%34,%35,%36,%37,%38,%39,%40,%41,%42,%43,%44,%45,%46,%47,%48,%49,%50,%51,%52,%53,%54,%55,%56,%57,%58,%59,%60,%61,%62,%63,"
                 "%64,%65,%66,%67,%68,%69,%70,%71,%72,%73,%74,%75,%76,%77,%78,%79,%80,%81,%82,%83,%84,%85,%86,%87,%88,%89,%90,%91,%92,%93,%94,%95,"
                 "%96,%97,%98,%99,%100,%101,%102,%103,%104,%105,%106,%107,%108,%109,%110,%111}, "
                 "%112, %113, p, 1, 1, 0, 1;\n}\n"
                 : WG_REGS_32(0), WG_REGS_32(32), WG_REGS_32(64), WG_REGS_16(96) : "l"(dA), "l"(dB), "r"(sc));
}
template <int BN> __device__ __forceinline__ void wgmma_ss_tb(float (&d)[BN / 2], uint64_t dA, uint64_t dB, int sc) {
    if constexpr (BN == 64) wgmma_ss_n64_tb(d, dA, dB, sc);
    else if constexpr (BN == 80) wgmma_ss_n80_tb(d, dA, dB, sc);
    else wgmma_ss_n224_tb(d, dA, dB, sc);
}
__device__ __forceinline__ void wgmma_rs_n64_tb(float (&d)[32], uint32_t a, uint64_t dB, int sc) {
    asm volatile("{\n.reg .pred p;\nsetp.ne.b32 p, %34, 0;\n"
                 "wgmma.mma_async.sync.aligned.m64n64k16.f32.bf16.bf16 "
                 "{%0,%1,%2,%3,%4,%5,%6,%7,%8,%9,%10,%11,%12,%13,%14,%15,%16,%17,%18,%19,%20,%21,%22,%23,%24,%25,%26,%27,%28,%29,%30,%31}, "
                 "{%32,%32,%32,%32}, %33, p, 1, 1, 1;\n}\n"
                 : WG_REGS_32(0) : "r"(a), "l"(dB), "r"(sc));
}
__device__ __forceinline__ void wgmma_rs_n80_tb(float (&d)[40], uint32_t a, uint64_t dB, int sc) {
    asm volatile("{\n.reg .pred p;\nsetp.ne.b32 p, %42, 0;\n"
                 "wgmma.mma_async.sync.aligned.m64n80k16.f32.bf16.bf16 "
                 "{%0,%1,%2,%3,%4,%5,%6,%7,%8,%9,%10,%11,%12,%13,%14,%15,%16,%17,%18,%19,%20,%21,%22,%23,%24,%25,%26,%27,%28,%29,%30,%31,"
                 "%32,%33,%34,%35,%36,%37,%38,%39}, {%40,%40,%40,%40}, %41, p, 1, 1, 1;\n}\n"
                 : WG_REGS_32(0), WG_REGS_8(32) : "r"(a), "l"(dB), "r"(sc));
}
template <int BN> __device__ __forceinline__ void wgmma_rs_ones(float (&d)[BN / 2], uint64_t dB, int sc) {
    if constexpr (BN == 80) wgmma_rs_n80_tb(d, 0x3F803F80u, dB, sc);
    else if constexpr (BN == 64) wgmma_rs_n64_tb(d, 0x3F803F80u, dB, sc);
}
__device__ __forceinline__ void wgmma_rs_n64_z(float (&d)[32], uint32_t a0, uint32_t a1, uint32_t a2, uint32_t a3, uint64_t dB) {
    asm volatile("{\n.reg .pred p;\nsetp.ne.b32 p, 0, 0;\n"
                 "wgmma.mma_async.sync.aligned.m64n64k16.f32.bf16.bf16 "
                 "{%0,%1,%2,%3,%4,%5,%6,%7,%8,%9,%10,%11,%12,%13,%14,%15,%16,%17,%18,%19,%20,%21,%22,%23,%24,%25,%26,%27,%28,%29,%30,%31}, "
                 "{%32,%33,%34,%35}, %36, p, 1, 1, 0;\n}\n"
                 : "=f"(d[0]), "=f"(d[1]), "=f"(d[2]), "=f"(d[3]), "=f"(d[4]), "=f"(d[5]), "=f"(d[6]), "=f"(d[7]),
                   "=f"(d[8]), "=f"(d[9]), "=f"(d[10]), "=f"(d[11]), "=f"(d[12]), "=f"(d[13]), "=f"(d[14]), "=f"(d[15]),
                   "=f"(d[16]), "=f"(d[17]), "=f"(d[18]), "=f"(d[19]), "=f"(d[20]), "=f"(d[21]), "=f"(d[22]), "=f"(d[23]),
                   "=f"(d[24]), "=f"(d[25]), "=f"(d[26]), "=f"(d[27]), "=f"(d[28]), "=f"(d[29]), "=f"(d[30]), "=f"(d[31])
                 : "r"(a0), "r"(a1), "r"(a2), "r"(a3), "l"(dB));
}
__device__ __forceinline__ void wgmma_rs_n24_tb(float (&d)[12], uint32_t a0, uint32_t a1, uint32_t a2, uint32_t a3, uint64_t dB) {
    asm volatile("{\n.reg .pred p;\nsetp.eq.b32 p, 0, 0;\n"
                 "wgmma.mma_async.sync.aligned.m64n24k16.f32.bf16.bf16 "
                 "{%0,%1,%2,%3,%4,%5,%6,%7,%8,%9,%10,%11}, {%12,%13,%14,%15}, %16, p, 1, 1, 1;\n}\n"
                 : WG_REGS_8(0), WG_REGS_4(8) : "r"(a0), "r"(a1), "r"(a2), "r"(a3), "l"(dB));
}

constexpr int SIDE_CTAS = 4;
__device__ __forceinline__ void side_job(int cta, float* red  , const __nv_bfloat16* __restrict__ wo,
                                         const __nv_bfloat16* __restrict__ w1, const __nv_bfloat16* __restrict__ w2) {
    const int tid = threadIdx.x, warp = tid >> 5, lane = tid & 31;
    for (int line = cta * 512 + tid; line < 18432; line += SIDE_CTAS * 512) {
        const char* p = line < 4096 ? (const char*)wo + (size_t)line * 128 : (const char*)w2 + (size_t)(line - 4096) * 128;
        asm volatile("prefetch.global.L2 [%0];" ::"l"(p));
    }
    const int rg = lane >> 3, c8 = lane & 7;
    for (int slab = cta; slab < F_ / 64; slab += SIDE_CTAS) {
        const __nv_bfloat16* base = w1 + slab * 64 + c8 * 8;
        uint4 v[8];
#pragma unroll
        for (int i = 0; i < 8; i++) v[i] = __ldg((const uint4*)(base + (size_t)(warp * 32 + rg + 4 * i) * F_));
        float acc[8];
#pragma unroll
        for (int i = 0; i < 8; i++) acc[i] = 0.f;
#pragma unroll
        for (int i = 0; i < 8; i++) {
            acc[0] += bf_lo(v[i].x); acc[1] += bf_hi(v[i].x); acc[2] += bf_lo(v[i].y); acc[3] += bf_hi(v[i].y);
            acc[4] += bf_lo(v[i].z); acc[5] += bf_hi(v[i].z); acc[6] += bf_lo(v[i].w); acc[7] += bf_hi(v[i].w);
        }
#pragma unroll
        for (int i = 0; i < 8; i++) {
            acc[i] += __shfl_xor_sync(0xffffffffu, acc[i], 8);
            acc[i] += __shfl_xor_sync(0xffffffffu, acc[i], 16);
        }
        if (rg == 0) {
#pragma unroll
            for (int i = 0; i < 8; i++) red[warp * 64 + c8 * 8 + i] = acc[i];
        }
        __syncthreads();
        if (tid < 64) {
            float s = 0.f;
#pragma unroll
            for (int i = 0; i < 16; i++) s += red[i * 64 + tid];
            g_cs_1[slab * 64 + tid] = s;
        }
        __syncthreads();
    }
}

enum { EPI_QKV = 0, EPI_RES = 1, EPI_FFN1 = 2 };

struct GemmParams {
    const float2* stats_in;
    float2* stats_out;
    const __nv_bfloat16* wkv;
    const __nv_bfloat16* wv;
};

template <int BK_, int NBLK> struct Geo {
    static constexpr int BK = BK_, A_BYTES = 128 * BK * 2, A_SWZ = BK == 64 ? 1 : 2, A_SBO = BK * 16;
    static constexpr int BLK = BK * 64;
    static constexpr int B_BYTES = NBLK * BLK, B_SWZ = 2, B_LBO = BLK, B_SBO = 512, B_KSTEP = 1024;
};
template <> struct Geo<64, 0> {
    static constexpr int BK = 64, A_BYTES = 128 * 128, A_SWZ = 1, A_SBO = 1024, BLK = 8192;
    static constexpr int B_BYTES = 64 * 128, B_SWZ = 1, B_LBO = 8192, B_SBO = 1024, B_KSTEP = 2048;
};
template <int EPI> struct EpiGeo;
template <> struct EpiGeo<EPI_QKV> { using G = Geo<64, 3>; };
template <> struct EpiGeo<EPI_RES> { using G = Geo<64, 0>; };
template <> struct EpiGeo<EPI_FFN1> { using G = Geo<64, 7>; };

template <int STAGES, int EPI> struct GemmSmem {
    using G = typename EpiGeo<EPI>::G;
    static constexpr int STAGE = G::A_BYTES + G::B_BYTES;
    static constexpr int AUX_OFF = STAGES * STAGE;
    static constexpr int TOTAL = AUX_OFF + 1152;
    static constexpr int TOTAL_SELF = AUX_OFF + 704 + 1024;
};

struct RowStatRaw { float2 a0, a1, b0, b1; };
__device__ __forceinline__ RowStatRaw load_row_stats(const float2* __restrict__ st, int row0, int c) {
    RowStatRaw r;
    r.a0 = st[(2 * c) * S_ + row0]; r.a1 = st[(2 * c + 1) * S_ + row0];
    r.b0 = st[(2 * c) * S_ + row0 + 8]; r.b1 = st[(2 * c + 1) * S_ + row0 + 8];
    return r;
}
__device__ __forceinline__ void finish_row_stats(const RowStatRaw& r, float& mean0, float& rstd0, float& mean1, float& rstd1) {
    float sa = r.a0.x + r.a1.x, sb = r.b0.x + r.b1.x;
    sa += __shfl_xor_sync(0xffffffffu, sa, 1); sa += __shfl_xor_sync(0xffffffffu, sa, 2);
    sb += __shfl_xor_sync(0xffffffffu, sb, 1); sb += __shfl_xor_sync(0xffffffffu, sb, 2);
    mean0 = sa * 0.125f; mean1 = sb * 0.125f;
    float ma = r.a0.y + r.a1.y + 64.f * ((r.a0.x - mean0) * (r.a0.x - mean0) + (r.a1.x - mean0) * (r.a1.x - mean0));
    float mb = r.b0.y + r.b1.y + 64.f * ((r.b0.x - mean1) * (r.b0.x - mean1) + (r.b1.x - mean1) * (r.b1.x - mean1));
    ma += __shfl_xor_sync(0xffffffffu, ma, 1); ma += __shfl_xor_sync(0xffffffffu, ma, 2);
    mb += __shfl_xor_sync(0xffffffffu, mb, 1); mb += __shfl_xor_sync(0xffffffffu, mb, 2);
    rstd0 = 1.0f / sqrtf(ma * (1.f / 512.f) + 1e-5f);
    rstd1 = 1.0f / sqrtf(mb * (1.f / 512.f) + 1e-5f);
}

template <int BN, int KB, int STAGES, int EPI, bool SELF = false>
__device__ __forceinline__ void gemm_body(const CUtensorMap* mapA, const CUtensorMap* mapB, const CUtensorMap* mapR,
                                          const CUtensorMap* mapC, const GemmParams& prm, int tile_m, int tile_n, uint8_t* smem_raw) {
    using SM = GemmSmem<STAGES, EPI>;
    using G = typename SM::G;
    constexpr bool XKV = BN == 80;
    constexpr int TN = EPI == EPI_QKV ? 64 : BN;
    pdl_launch();
    const uint32_t sbase = smem_u32(smem_raw);
    if (sbase & 1023) __trap();
    uint8_t* sgen = smem_raw;
    const uint32_t bar_full = sbase + SM::AUX_OFF, bar_empty = bar_full + 8 * STAGES;
    float* s_cs = (float*)(sgen + SM::AUX_OFF + 256);
    float* s_row = (float*)(sgen + SM::AUX_OFF + 704);
    float* s_red = (float*)(sgen + SM::AUX_OFF + 640);
    const int tid = threadIdx.x, lane = tid & 31;
    const int warp = __shfl_sync(0xffffffffu, tid >> 5, 0);

    if (warp == 8 && elect_one()) {
#pragma unroll
        for (int s = 0; s < STAGES; s++) { mbar_init(bar_full + 8 * s, 1); mbar_init(bar_empty + 8 * s, 2); }
        fence_mbar_init();
    }
    if (warp == 1 && elect_one()) { prefetch_tmap(mapB); prefetch_tmap(mapA); prefetch_tmap(mapC); }
    __syncthreads();

    const int m0 = tile_m * 128, n0 = tile_n * TN;
    constexpr uint32_t STAGE_TX = G::A_BYTES + (EPI == EPI_QKV ? 2 * G::BLK : G::B_BYTES);
    auto loadB = [&](int kb, int s) {
        const uint32_t dst = sbase + s * SM::STAGE + G::A_BYTES, bar = bar_full + 8 * s;
        if constexpr (EPI == EPI_RES) {
            tma2d(dst, mapB, n0, kb * 64, bar);
        } else if constexpr (EPI == EPI_QKV) {
            tma3d(dst, mapB, 0, kb * G::BK, tile_n * 2, bar);
        } else {
            tma3d(dst, mapB, 0, kb * G::BK, tile_n * 7, bar);
        }
    };
    auto loadA = [&](int kb, int s) {
        const uint32_t dst = sbase + s * SM::STAGE, bar = bar_full + 8 * s;
        tma2d(dst, mapA, kb * G::BK, m0, bar);
    };
    constexpr int PRE = STAGES < KB ? STAGES : KB;
    constexpr int PRE_B = 1;
    auto prologue_loads = [&]() {
        if (elect_one()) {
#pragma unroll
            for (int kb = 0; kb < PRE; kb++) mbar_expect_tx(bar_full + 8 * kb, STAGE_TX);
        }
        if (elect_one()) {
#pragma unroll
            for (int kb = 0; kb < PRE_B; kb++) loadB(kb, kb);
        }
        if (!SELF) pdl_wait();
        if (elect_one()) {
#pragma unroll
            for (int kb = 0; kb < PRE; kb++) {
                loadA(kb, kb);
                if (kb + PRE_B < PRE) loadB(kb + PRE_B, kb + PRE_B);
            }
            if constexpr (EPI == EPI_RES && KB < STAGES) {
                mbar_expect_tx(bar_full + 8 * KB, 16384);
                tma2d(sbase + KB * SM::STAGE, mapR, n0, m0, bar_full + 8 * KB);
            }
        }
    };
    if (SELF && warp >= 8) {
        if (warp == 8) prologue_loads();
        static_assert(!SELF || (STAGES >= KB && EPI == EPI_QKV), "SELF needs every k block resident");
        if ((warp >> 2) == 3) {
            float csum[BN / 2];
            const uint64_t dB0 = mkdesc(sbase + G::A_BYTES, G::B_LBO, G::B_SBO, G::B_SWZ);
            if constexpr (XKV) named_bar(6, 384);
#pragma unroll 1
            for (int kb = 0; kb < KB; kb++) {
                mbar_wait(bar_full + 8 * kb, 0);
                const uint64_t dB = dB0 + (uint64_t)(kb * (SM::STAGE >> 4));
                wg_fence();
#pragma unroll
                for (int k = 0; k < G::BK / 16; k++) {
                    if constexpr (SELF) wgmma_rs_ones<BN>(csum, dB + (uint64_t)(k * (G::B_KSTEP >> 4)), (kb | k) != 0);
                }
                wg_commit();
            }
            wg_wait<0>();
            fence_regs(csum);
            if (warp == 12 && lane < 4) {
#pragma unroll
                for (int j = 0; j < BN / 8; j++) {
                    const float2 v = make_float2(csum[4 * j], csum[4 * j + 1]);
                    *(float2*)(s_cs + 8 * j + 2 * lane) = v;
                    if (tile_m == 0) {
                        if (j < 8) *(float2*)(g_cs_q + n0 + 8 * j + 2 * lane) = v;
                        else *(float2*)(g_cs_kv + tile_n * 16 + 8 * (j - 8) + 2 * lane) = v;
                    }
                }
            }
        } else {
            const int t = (warp < 12 ? warp - 8 : warp - 12) * 32 + lane;
            float ss[4] = {0.f, 0.f, 0.f, 0.f}, sq[4] = {0.f, 0.f, 0.f, 0.f};
#pragma unroll 1
            for (int kb = 0; kb < KB; kb++) {
                mbar_wait(bar_full + 8 * kb, 0);
                const uint32_t arow = sbase + kb * SM::STAGE + (t >> 1) * 128;
                uint32_t w[4][4];
#pragma unroll
                for (int j = 0; j < 4; j++)
                    asm volatile("ld.shared.v4.u32 {%0,%1,%2,%3}, [%4];" : "=r"(w[j][0]), "=r"(w[j][1]), "=r"(w[j][2]), "=r"(w[j][3])
                                 : "r"(arow + (((2 * j + (t & 1) + 2 * ((t >> 1) & 3)) & 7) << 4)));
#pragma unroll
                for (int j = 0; j < 4; j++)
#pragma unroll
                    for (int i = 0; i < 4; i++) {
                        const float lo = bf_lo(w[j][i]), hi = bf_hi(w[j][i]);
                        ss[i] += lo + hi;
                        sq[i] = fmaf(lo, lo, fmaf(hi, hi, sq[i]));
                    }
            }
            float tsum = (ss[0] + ss[1]) + (ss[2] + ss[3]), tsq = (sq[0] + sq[1]) + (sq[2] + sq[3]);
            tsum += __shfl_xor_sync(0xffffffffu, tsum, 1);
            tsq += __shfl_xor_sync(0xffffffffu, tsq, 1);
            if ((t & 1) == 0) {
                const float md = tsum * (1.f / 512.f);
                const float var = fmaxf(tsq * (1.f / 512.f) - md * md, 0.f);
                *(float2*)(s_row + t) = make_float2(md, 1.0f / sqrtf(var + 1e-5f));
            }
        }
        named_bar(4, 640);
    } else if (warp == 8) {
        prologue_loads();
        int s = PRE % STAGES, ph = (PRE / STAGES) & 1;
#pragma unroll 1
        for (int kb = PRE; kb < KB; kb++) {
            mbar_wait(bar_empty + 8 * s, ph ^ 1);
            if (elect_one()) {
                mbar_expect_tx(bar_full + 8 * s, STAGE_TX);
                loadB(kb, s);
                loadA(kb, s);
            }
            if (++s == STAGES) { s = 0; ph ^= 1; }
        }
        if constexpr (EPI == EPI_RES && KB >= STAGES) {
            mbar_wait(bar_empty + 8 * s, ph ^ 1);
            if (elect_one()) {
                mbar_expect_tx(bar_full + 8 * s, 16384);
                tma2d(sbase + s * SM::STAGE, mapR, n0, m0, bar_full + 8 * s);
            }
        }
    } else {
        const int wg = warp >> 2, g = lane >> 2, c = lane & 3;
        const int rloc = wg * 64 + (warp & 3) * 16 + g;
        const int row0 = m0 + rloc;
        float mean0 = 0.f, rstd0 = 1.f, mean1 = 0.f, rstd1 = 1.f;
        if constexpr (XKV) {
            static_assert(!XKV || STAGES >= KB, "the K / V weight block must stay resident");
            const __nv_bfloat16* wsrc = tile_n == 0 ? prm.wkv : prm.wv;
            uint4 v[4];
#pragma unroll
            for (int i = 0; i < 4; i++) v[i] = __ldg((const uint4*)wsrc + tid + 256 * i);
#pragma unroll
            for (int i = 0; i < 4; i++) {
                const int idx = tid + 256 * i, k = idx >> 1, kr = k & 63;
                const uint32_t dst = sbase + (k >> 6) * SM::STAGE + G::A_BYTES + 2 * G::BLK + kr * 64 + (((idx & 1) ^ ((kr >> 1) & 3)) << 4);
                asm volatile("st.shared.v4.u32 [%0], {%1,%2,%3,%4};" ::"r"(dst), "r"(v[i].x), "r"(v[i].y), "r"(v[i].z), "r"(v[i].w) : "memory");
            }
            fence_async_smem();
            if constexpr (SELF) named_bar(6, 384); else named_bar(6, 256);
        }
        RowStatRaw raw;
        float csv = 0.f;
        float2 cskv[2] = {make_float2(0.f, 0.f), make_float2(0.f, 0.f)};
        auto ln_inputs = [&]() {
            pdl_wait();
            if constexpr (EPI != EPI_RES) {
                raw = load_row_stats(prm.stats_in, row0, c);
                const float* cs = EPI == EPI_FFN1 ? g_cs_1 + n0 : g_cs_q + n0;
                if (tid < TN) csv = cs[tid];
                if constexpr (XKV) {
                    cskv[0] = *(const float2*)(g_cs_kv + tile_n * 16 + 2 * c);
                    cskv[1] = *(const float2*)(g_cs_kv + tile_n * 16 + 8 + 2 * c);
                }
            }
        };
        if (!SELF) ln_inputs();
        float acc[BN / 2];
        const uint64_t dA0 = mkdesc(sbase + wg * (G::A_BYTES / 2), 16, G::A_SBO, G::A_SWZ);
        const uint64_t dB0 = mkdesc(sbase + G::A_BYTES, G::B_LBO, G::B_SBO, G::B_SWZ);
        int s = 0, ph = 0;
#pragma unroll 1
        for (int kb = 0; kb < KB; kb++) {
            mbar_wait(bar_full + 8 * s, ph);
            const uint64_t dA = dA0 + (uint64_t)(s * (SM::STAGE >> 4)), dB = dB0 + (uint64_t)(s * (SM::STAGE >> 4));
            wg_fence();
#pragma unroll
            for (int k = 0; k < G::BK / 16; k++) wgmma_ss_tb<BN>(acc, dA + (uint64_t)(k * 2), dB + (uint64_t)(k * (G::B_KSTEP >> 4)), (kb | k) != 0);
            wg_commit();
            if (kb > 0) {
                wg_wait<1>();
                const int sp = s == 0 ? STAGES - 1 : s - 1;
                if ((warp & 3) == 0 && elect_one()) mbar_arrive(bar_empty + 8 * sp);
            }
            if (++s == STAGES) { s = 0; ph ^= 1; }
        }
        if constexpr (SELF) {
            named_bar(4, 640);
            const float2 r0 = *(const float2*)(s_row + 2 * rloc), r1 = *(const float2*)(s_row + 2 * rloc + 16);
            mean0 = r0.x; rstd0 = r0.y; mean1 = r1.x; rstd1 = r1.y;
        } else if constexpr (EPI != EPI_RES) {
            finish_row_stats(raw, mean0, rstd0, mean1, rstd1);
            if (tid < TN) s_cs[tid] = csv;
        }
        wg_wait<0>();
        fence_regs(acc);
        if constexpr (EPI != EPI_RES) named_bar(1, 256);

        if constexpr (EPI != EPI_FFN1) {
            const uint32_t stile = sbase + (EPI == EPI_RES ? s * SM::STAGE : 0);
            const int mrow = wg * 64 + (warp & 3) * 16 + (lane & 7) + ((lane >> 3) & 1) * 8;
            const uint32_t rbase = stile + mrow * 128;
            if constexpr (EPI == EPI_RES) {
                mbar_wait(bar_full + 8 * s, ph);
                float s0 = 0.f, s1 = 0.f;
#pragma unroll
                for (int jj = 0; jj < 4; jj++) {
                    uint32_t r0, r1, r2, r3;
                    const uint32_t addr = rbase + (((2 * jj + (lane >> 4)) ^ (mrow & 7)) << 4);
                    ldsm_x4(r0, r1, r2, r3, addr);
                    const uint32_t u0 = pack_bf16(acc[8 * jj] + bf_lo(r0), acc[8 * jj + 1] + bf_hi(r0));
                    const uint32_t u1 = pack_bf16(acc[8 * jj + 2] + bf_lo(r1), acc[8 * jj + 3] + bf_hi(r1));
                    const uint32_t u2 = pack_bf16(acc[8 * jj + 4] + bf_lo(r2), acc[8 * jj + 5] + bf_hi(r2));
                    const uint32_t u3 = pack_bf16(acc[8 * jj + 6] + bf_lo(r3), acc[8 * jj + 7] + bf_hi(r3));
                    stsm_x4(addr, u0, u1, u2, u3);
                    acc[8 * jj] = bf_lo(u0); acc[8 * jj + 1] = bf_hi(u0); acc[8 * jj + 4] = bf_lo(u2); acc[8 * jj + 5] = bf_hi(u2);
                    acc[8 * jj + 2] = bf_lo(u1); acc[8 * jj + 3] = bf_hi(u1); acc[8 * jj + 6] = bf_lo(u3); acc[8 * jj + 7] = bf_hi(u3);
                    s0 += (acc[8 * jj] + acc[8 * jj + 1]) + (acc[8 * jj + 4] + acc[8 * jj + 5]);
                    s1 += (acc[8 * jj + 2] + acc[8 * jj + 3]) + (acc[8 * jj + 6] + acc[8 * jj + 7]);
                }
                fence_async_smem();
                named_bar(2 + wg, 128);
                if ((warp & 3) == 0 && elect_one()) { tma2d_store(mapC, stile + wg * 8192, n0, m0 + wg * 64); bulk_commit(); }
                if (prm.stats_out) {
                    s0 += __shfl_xor_sync(0xffffffffu, s0, 1); s0 += __shfl_xor_sync(0xffffffffu, s0, 2);
                    s1 += __shfl_xor_sync(0xffffffffu, s1, 1); s1 += __shfl_xor_sync(0xffffffffu, s1, 2);
                    const float mu0 = s0 * (1.f / 64.f), mu1 = s1 * (1.f / 64.f);
                    float q0 = 0.f, q1 = 0.f;
#pragma unroll
                    for (int j = 0; j < 8; j++) {
                        float d;
                        d = acc[4 * j] - mu0; q0 += d * d; d = acc[4 * j + 1] - mu0; q0 += d * d;
                        d = acc[4 * j + 2] - mu1; q1 += d * d; d = acc[4 * j + 3] - mu1; q1 += d * d;
                    }
                    q0 += __shfl_xor_sync(0xffffffffu, q0, 1); q0 += __shfl_xor_sync(0xffffffffu, q0, 2);
                    q1 += __shfl_xor_sync(0xffffffffu, q1, 1); q1 += __shfl_xor_sync(0xffffffffu, q1, 2);
                    if (c == 0) {
                        prm.stats_out[tile_n * S_ + row0] = make_float2(mu0, q0);
                        prm.stats_out[tile_n * S_ + row0 + 8] = make_float2(mu1, q1);
                    }
                }
            } else {
                const float sc = 0.25f * 1.4426950408889634f;
                const float a0 = rstd0 * sc, a1 = rstd1 * sc, rm0 = a0 * mean0, rm1 = a1 * mean1;
#pragma unroll
                for (int jj = 0; jj < 4; jj++) {
                    const float2 ca = *(const float2*)(s_cs + 16 * jj + 2 * c), cb = *(const float2*)(s_cs + 16 * jj + 8 + 2 * c);
                    const uint32_t u0 = pack_bf16(acc[8 * jj] * a0 - rm0 * ca.x, acc[8 * jj + 1] * a0 - rm0 * ca.y);
                    const uint32_t u1 = pack_bf16(acc[8 * jj + 2] * a1 - rm1 * ca.x, acc[8 * jj + 3] * a1 - rm1 * ca.y);
                    const uint32_t u2 = pack_bf16(acc[8 * jj + 4] * a0 - rm0 * cb.x, acc[8 * jj + 5] * a0 - rm0 * cb.y);
                    const uint32_t u3 = pack_bf16(acc[8 * jj + 6] * a1 - rm1 * cb.x, acc[8 * jj + 7] * a1 - rm1 * cb.y);
                    stsm_x4(rbase + (((2 * jj + (lane >> 4)) ^ (mrow & 7)) << 4), u0, u1, u2, u3);
                }
                fence_async_smem();
                named_bar(2 + wg, 128);
                if ((warp & 3) == 0 && elect_one()) { tma2d_store(mapC, stile + wg * 8192, n0, m0 + wg * 64); bulk_commit(); }
            }
            if constexpr (XKV) {
                {
                    const float* acx = &acc[32];
                    const float rm0 = rstd0 * mean0, rm1 = rstd1 * mean1;
                    float n0s = 0.f, n1s = 0.f, vmax = 0.f;
#pragma unroll
                    for (int j = 0; j < 2; j++) {
                        const float2 cs2 = SELF ? *(const float2*)(s_cs + 64 + 8 * j + 2 * c) : cskv[j];
                        const uint32_t u0 = pack_bf16(acx[4 * j] * rstd0 - rm0 * cs2.x, acx[4 * j + 1] * rstd0 - rm0 * cs2.y);
                        const uint32_t u1 = pack_bf16(acx[4 * j + 2] * rstd1 - rm1 * cs2.x, acx[4 * j + 3] * rstd1 - rm1 * cs2.y);
                        n0s += bf_lo(u0) * bf_lo(u0) + bf_hi(u0) * bf_hi(u0);
                        n1s += bf_lo(u1) * bf_lo(u1) + bf_hi(u1) * bf_hi(u1);
                        vmax = fmaxf(vmax, fmaxf(fmaxf(fabsf(bf_lo(u0)), fabsf(bf_hi(u0))), fmaxf(fabsf(bf_lo(u1)), fabsf(bf_hi(u1)))));
                        if (tile_n == 0) {
                            *(uint32_t*)(g_kimg + (row0 >> 3) * 256 + j * 128 + g * 16 + c * 4) = u0;
                            *(uint32_t*)(g_kimg + ((row0 + 8) >> 3) * 256 + j * 128 + g * 16 + c * 4) = u1;
                        } else {
                            uint8_t* vb = g_vimg + (row0 >> 4) * 768 + j * 256 + g * 16 + c * 4;
                            *(uint32_t*)(vb) = u0;
                            *(uint32_t*)(vb + 128) = u1;
                        }
                    }
                    if (tile_n == 1) {
                        uint8_t* vb = g_vimg + (row0 >> 4) * 768 + 512 + g * 16 + c * 4;
                        const uint32_t one = c == 0 ? 0x00003F80u : 0u;
                        *(uint32_t*)(vb) = one;
                        *(uint32_t*)(vb + 128) = one;
                    }
                    n0s += __shfl_xor_sync(0xffffffffu, n0s, 1); n0s += __shfl_xor_sync(0xffffffffu, n0s, 2);
                    n1s += __shfl_xor_sync(0xffffffffu, n1s, 1); n1s += __shfl_xor_sync(0xffffffffu, n1s, 2);
                    float km = tile_n == 0 ? fmaxf(n0s, n1s) : vmax;
                    if (!(n0s + n1s < INFINITY)) km = INFINITY;
#pragma unroll
                    for (int o = 1; o < 32; o <<= 1) km = fmaxf(km, __shfl_xor_sync(0xffffffffu, km, o));
                    if (lane == 0) s_red[warp] = km;
                    named_bar(1, 256);
                    if (tid == 0) {
                        float a = 0.f;
                        for (int i = 0; i < 8; i++) a = fmaxf(a, s_red[i]);
                        g_kvmax[tile_n * 16 + tile_m] = a;
                    }
                }
            }
            if ((warp & 3) == 0) bulk_wait_read();
        } else {
            const uint32_t stile = sbase + wg * (7 * 4096);
            const int mrow = (warp & 3) * 16 + (lane & 7) + ((lane >> 3) & 1) * 8;
            const float a0 = 0.5f * rstd0, a1 = 0.5f * rstd1, rm0 = a0 * mean0, rm1 = a1 * mean1;
#pragma unroll
            for (int jj = 0; jj < 14; jj++) {
                const float2 ca = *(const float2*)(s_cs + 16 * jj + 2 * c), cb = *(const float2*)(s_cs + 16 * jj + 8 + 2 * c);
                float y[8] = {acc[8 * jj] * a0 - rm0 * ca.x,     acc[8 * jj + 1] * a0 - rm0 * ca.y,
                              acc[8 * jj + 2] * a1 - rm1 * ca.x, acc[8 * jj + 3] * a1 - rm1 * ca.y,
                              acc[8 * jj + 4] * a0 - rm0 * cb.x, acc[8 * jj + 5] * a0 - rm0 * cb.y,
                              acc[8 * jj + 6] * a1 - rm1 * cb.x, acc[8 * jj + 7] * a1 - rm1 * cb.y};
#pragma unroll
                for (int i = 0; i < 8; i++) {
                    float t;
                    asm("tanh.approx.f32 %0, %1;" : "=f"(t) : "f"(y[i]));
                    y[i] = fmaf(y[i], t, y[i]);
                }
                const int chunk = (2 * jj + (lane >> 4)) & 3, blk = jj >> 1;
                stsm_x4(stile + blk * 4096 + mrow * 64 + ((chunk ^ ((mrow >> 1) & 3)) << 4),
                        pack_bf16(y[0], y[1]), pack_bf16(y[2], y[3]), pack_bf16(y[4], y[5]), pack_bf16(y[6], y[7]));
                if (jj & 1) {
                    fence_async_smem();
                    __syncwarp();
                    if (elect_one()) {
                        tma2d_store(mapC, stile + blk * 4096 + (warp & 3) * 1024, n0 + blk * 32, m0 + wg * 64 + (warp & 3) * 16);
                        bulk_commit();
                    }
                }
            }
            bulk_wait_read();
        }
    }
}

#define WO_ST 9
#define F2_ST 7
#define F1_ST 4
#define QKV_ST 8
constexpr int QKV_STAGES = QKV_ST, WO_STAGES = WO_ST, FFN2_STAGES = F2_ST, FFN1_STAGES = F1_ST;
template <bool SELF>
__global__ void __launch_bounds__(SELF ? 640 : 288) qkv_kernel(const __grid_constant__ CUtensorMap mapA, const __grid_constant__ CUtensorMap mapWq,
                                                  const __grid_constant__ CUtensorMap mapQ, const GemmParams prm) {
    extern __shared__ __align__(1024) uint8_t smem_raw[];
    const int tn = blockIdx.x & 7;
    if (tn < 2) gemm_body<80, 8, QKV_STAGES, EPI_QKV, SELF>(&mapA, &mapWq, &mapA, &mapQ, prm, blockIdx.x >> 3, tn, smem_raw);
    else gemm_body<64, 8, QKV_STAGES, EPI_QKV, SELF>(&mapA, &mapWq, &mapA, &mapQ, prm, blockIdx.x >> 3, tn, smem_raw);
}
template <int KB, int STAGES>
__global__ void __launch_bounds__(288) res_gemm_kernel(const __grid_constant__ CUtensorMap mapA, const __grid_constant__ CUtensorMap mapW,
                                                       const __grid_constant__ CUtensorMap mapR, const __grid_constant__ CUtensorMap mapC, const GemmParams prm) {
    extern __shared__ __align__(1024) uint8_t smem_raw[];
    gemm_body<64, KB, STAGES, EPI_RES>(&mapA, &mapW, &mapR, &mapC, prm, blockIdx.x >> 3, blockIdx.x & 7, smem_raw);
}
__global__ void __launch_bounds__(288) ffn1_kernel(const __grid_constant__ CUtensorMap mapA, const __grid_constant__ CUtensorMap mapW,
                                                   const __grid_constant__ CUtensorMap mapH, const GemmParams prm) {
    extern __shared__ __align__(1024) uint8_t smem_raw[];
    gemm_body<224, 8, FFN1_STAGES, EPI_FFN1>(&mapA, &mapW, &mapA, &mapH, prm, blockIdx.x >> 3, blockIdx.x & 7, smem_raw);
}

#define ATT_NPOLY 11
constexpr int NPOLY = ATT_NPOLY;
__host__ __device__ constexpr bool is_mufu(int i) { return (i * (16 - NPOLY)) % 16 < 16 - NPOLY; }

__device__ __forceinline__ float ex2(float x) { float r; asm("ex2.approx.ftz.f32 %0, %1;" : "=f"(r) : "f"(x)); return r; }
__device__ __forceinline__ uint32_t exp_pair_mufu(float a, float b) { return pack_bf16(ex2(a), ex2(b)); }
__device__ __forceinline__ uint32_t exp_pair_fma(float a, float b, uint32_t c3f) {
    constexpr float MAGIC = 98430.4140625f;
    const float ta = a + MAGIC, tb = b + (MAGIC - 143.5f);
    uint32_t y, m, r;
    asm("mad.lo.u32 %0, %1, 65536, %2;" : "=r"(y) : "r"(__float_as_uint(tb)), "r"(__float_as_uint(ta)));
    asm("lop3.b32 %0, %1, 0x007F007F, %2, 0xEA;" : "=r"(m) : "r"(y), "r"(c3f));
    const uint32_t e = y & 0xFF80FF80u;
    asm("fma.rn.bf16x2 %0, %1, %2, %3;" : "=r"(r) : "r"(y), "r"(m), "r"(e));
    return r;
}

constexpr int KCH = 256, NCH = S_ / KCH;
constexpr int K_BYTES = S_ * 32, V_BYTES = (S_ / 16) * 768;
constexpr int QO_BYTES = 128 * 128;
constexpr int ATT_SMEM = K_BYTES + V_BYTES + QO_BYTES;

__global__ void __launch_bounds__(512, 1) attn_kernel(const __grid_constant__ CUtensorMap mapQ, const __grid_constant__ CUtensorMap mapO,
                                                       const __nv_bfloat16* __restrict__ wo, const __nv_bfloat16* __restrict__ w1,
                                                       const __nv_bfloat16* __restrict__ w2) {
    extern __shared__ __align__(1024) uint8_t smem[];
    __shared__ uint64_t bars[NCH + 1];
    __shared__ int s_slow;
    const int tid = threadIdx.x, wg = tid >> 7, warp = (tid >> 5) & 3, lane = tid & 31;
    const uint32_t sK = smem_u32(smem), sV = sK + K_BYTES, sQ = sV + V_BYTES;
    if (blockIdx.x >= 128) {
        pdl_launch();
        pdl_wait();
        side_job(blockIdx.x - 128, (float*)smem, wo, w1, w2);
        return;
    }
    if (tid == 0) {
#pragma unroll
        for (int i = 0; i <= NCH; i++) mbar_init(smem_u32(&bars[i]), 1);
        s_slow = 0;
        fence_mbar_init();
    }
    if (tid == 32) { prefetch_tmap(&mapQ); prefetch_tmap(&mapO); }
    __syncthreads();
    pdl_launch();
    pdl_wait();
    const int wu = __shfl_sync(0xffffffffu, tid >> 5, 0);
    auto fetch_chunk = [&](int w) {
        if (elect_one()) {
            const uint32_t bar = smem_u32(&bars[w]);
            mbar_expect_tx(bar, KCH * 32 + (KCH / 16) * 768);
            bulk_load(sK + w * KCH * 32, g_kimg + w * KCH * 32, KCH * 32, bar);
            bulk_load(sV + w * (KCH / 16) * 768, g_vimg + w * (KCH / 16) * 768, (KCH / 16) * 768, bar);
        }
    };
    const int tb = blockIdx.x >> 3, hg = blockIdx.x & 7;
    if (wu == 1 && elect_one()) {
        mbar_expect_tx(smem_u32(&bars[NCH]), QO_BYTES);
        tma2d(sQ, &mapQ, hg * 64, tb * 128, smem_u32(&bars[NCH]));
    }
    if (wu == 0) fetch_chunk(0);
    float kvm = g_kvmax[lane];
    const int lrow = warp * 16 + (lane & 7) + ((lane >> 3) & 1) * 8;
    const uint32_t qoff = lrow * 128 + (((2 * wg + (lane >> 4)) ^ (lrow & 7)) << 4);
    uint32_t qa[2][4];
    mbar_wait(smem_u32(&bars[NCH]), 0);
    ldsm_x4(qa[0][0], qa[0][1], qa[0][2], qa[0][3], sQ + qoff);
    ldsm_x4(qa[1][0], qa[1][1], qa[1][2], qa[1][3], sQ + 8192 + qoff);
    {
        float qn = 0.f;
#pragma unroll
        for (int m = 0; m < 2; m++) {
            float n0 = bf_lo(qa[m][0]) * bf_lo(qa[m][0]) + bf_hi(qa[m][0]) * bf_hi(qa[m][0]) + bf_lo(qa[m][2]) * bf_lo(qa[m][2]) + bf_hi(qa[m][2]) * bf_hi(qa[m][2]);
            float n1 = bf_lo(qa[m][1]) * bf_lo(qa[m][1]) + bf_hi(qa[m][1]) * bf_hi(qa[m][1]) + bf_lo(qa[m][3]) * bf_lo(qa[m][3]) + bf_hi(qa[m][3]) * bf_hi(qa[m][3]);
            n0 += __shfl_xor_sync(0xffffffffu, n0, 1); n0 += __shfl_xor_sync(0xffffffffu, n0, 2);
            n1 += __shfl_xor_sync(0xffffffffu, n1, 1); n1 += __shfl_xor_sync(0xffffffffu, n1, 2);
            if (!(n0 == n0) || !(n1 == n1)) n0 = INFINITY;
            qn = fmaxf(qn, fmaxf(n0, n1));
        }
#pragma unroll
        for (int o = 1; o < 16; o <<= 1) kvm = fmaxf(kvm, __shfl_xor_sync(0xffffffffu, kvm, o));
        const float km = __shfl_sync(0xffffffffu, kvm, 0), vm = __shfl_sync(0xffffffffu, kvm, 16);
        const bool ok = (qn * km <= 10000.f) && (vm <= 16384.f);
        if (!ok) s_slow = 1;
    }
    float oacc[2][12];
#pragma unroll
    for (int m = 0; m < 2; m++)
#pragma unroll
        for (int i = 0; i < 12; i++) oacc[m][i] = 0.f;
    __syncthreads();
    const bool slow = s_slow != 0;
    if (wu >= 1 && wu < NCH) fetch_chunk(wu);

    const uint64_t dK0 = mkdesc(sK, 128, 256, 0);
    const uint64_t dV0 = mkdesc(sV, 128, 256, 0);
    uint32_t c3f;
    asm volatile("mov.b32 %0, 0x3F003F00;" : "=r"(c3f));
    if (!slow) {
        uint64_t dK = dK0, dV = dV0;
        float s[32];
        fence_regs(oacc[0]); fence_regs(oacc[1]);
        mbar_wait(smem_u32(&bars[0]), 0);
        wg_fence();
        wgmma_rs_n64_z(s, qa[0][0], qa[0][1], qa[0][2], qa[0][3], dK);
        wg_commit();
#pragma unroll 1
        for (int ch = 0; ch < NCH; ch++) {
#pragma unroll
            for (int tt = 0; tt < KCH / 64; tt++) {
#pragma unroll
                for (int m = 0; m < 2; m++) {
                    wg_wait<0>();
                    fence_regs(s);
                    uint32_t p[16];
#pragma unroll
                    for (int i = 0; i < 16; i++) p[i] = is_mufu(i) ? exp_pair_mufu(s[2 * i], s[2 * i + 1]) : exp_pair_fma(s[2 * i], s[2 * i + 1], c3f);
                    if (m == 1 && tt == KCH / 64 - 1) mbar_wait(smem_u32(&bars[ch + 1 < NCH ? ch + 1 : ch]), 0);
                    wg_fence();
#pragma unroll
                    for (int kk = 0; kk < 4; kk++)
                        wgmma_rs_n24_tb(oacc[m], p[4 * kk], p[4 * kk + 1], p[4 * kk + 2], p[4 * kk + 3], dV + (uint64_t)((tt * 4 + kk) * (768 / 16)));
                    wgmma_rs_n64_z(s, qa[1 - m][0], qa[1 - m][1], qa[1 - m][2], qa[1 - m][3], dK + (uint64_t)((tt + m) * (64 * 32 / 16)));
                    wg_commit();
                }
            }
            dK += KCH * 32 / 16;
            dV += (KCH / 16) * (768 / 16);
        }
        wg_wait<0>();
        fence_regs(s);
    } else {
        float mx[2][2] = {{-INFINITY, -INFINITY}, {-INFINITY, -INFINITY}};
#pragma unroll 1
        for (int t = 0; t < S_ / 64; t++) {
            if ((t & 3) == 0) mbar_wait(smem_u32(&bars[t >> 2]), 0);
            const uint64_t dK = dK0 + (uint64_t)(t * 64 * 32 / 16);
            const uint64_t dV = dV0 + (uint64_t)(t * 4 * 768 / 16);
#pragma unroll
            for (int m = 0; m < 2; m++) {
                float s[32];
                wg_fence();
                wgmma_rs_n64_z(s, qa[m][0], qa[m][1], qa[m][2], qa[m][3], dK);
                wg_commit();
                wg_wait<0>();
                fence_regs(s);
                fence_regs(oacc[m]);
                float r0 = mx[m][0], r1 = mx[m][1];
#pragma unroll
                for (int j = 0; j < 8; j++) {
                    r0 = fmaxf(r0, fmaxf(s[4 * j], s[4 * j + 1]));
                    r1 = fmaxf(r1, fmaxf(s[4 * j + 2], s[4 * j + 3]));
                }
                r0 = fmaxf(r0, __shfl_xor_sync(0xffffffffu, r0, 1)); r0 = fmaxf(r0, __shfl_xor_sync(0xffffffffu, r0, 2));
                r1 = fmaxf(r1, __shfl_xor_sync(0xffffffffu, r1, 1)); r1 = fmaxf(r1, __shfl_xor_sync(0xffffffffu, r1, 2));
                const float al0 = ex2(mx[m][0] - r0), al1 = ex2(mx[m][1] - r1);
                mx[m][0] = r0; mx[m][1] = r1;
#pragma unroll
                for (int j = 0; j < 3; j++) {
                    oacc[m][4 * j] *= al0; oacc[m][4 * j + 1] *= al0;
                    oacc[m][4 * j + 2] *= al1; oacc[m][4 * j + 3] *= al1;
                }
                uint32_t p[16];
#pragma unroll
                for (int j = 0; j < 8; j++) {
                    p[2 * j] = pack_bf16(ex2(s[4 * j] - r0), ex2(s[4 * j + 1] - r0));
                    p[2 * j + 1] = pack_bf16(ex2(s[4 * j + 2] - r1), ex2(s[4 * j + 3] - r1));
                }
                fence_regs(oacc[m]);
                wg_fence();
#pragma unroll
                for (int kk = 0; kk < 4; kk++)
                    wgmma_rs_n24_tb(oacc[m], p[4 * kk], p[4 * kk + 1], p[4 * kk + 2], p[4 * kk + 3], dV + (uint64_t)(kk * 768 / 16));
                wg_commit();
                wg_wait<0>();
            }
        }
    }
    fence_regs(oacc[0]); fence_regs(oacc[1]);
#pragma unroll
    for (int m = 0; m < 2; m++) {
        const float l0 = __shfl_sync(0xffffffffu, oacc[m][8], lane & ~3);
        const float l1 = __shfl_sync(0xffffffffu, oacc[m][10], lane & ~3);
        const float r0 = __fdividef(1.0f, l0), r1 = __fdividef(1.0f, l1);
        stsm_x4(sQ + m * 8192 + qoff, pack_bf16(oacc[m][0] * r0, oacc[m][1] * r0), pack_bf16(oacc[m][2] * r1, oacc[m][3] * r1),
                pack_bf16(oacc[m][4] * r0, oacc[m][5] * r0), pack_bf16(oacc[m][6] * r1, oacc[m][7] * r1));
    }
    fence_async_smem();
    __syncthreads();
    if (wu == 0 && elect_one()) {
        tma2d_store(&mapO, sQ, hg * 64, tb * 128);
        bulk_commit();
        bulk_wait_read();
    }
}

typedef CUresult (*EncodeFn)(CUtensorMap*, CUtensorMapDataType, cuuint32_t, void*, const cuuint64_t*, const cuuint64_t*, const cuuint32_t*,
                             const cuuint32_t*, CUtensorMapInterleave, CUtensorMapSwizzle, CUtensorMapL2promotion, CUtensorMapFloatOOBfill);

EncodeFn get_encode() {
    static EncodeFn fn = nullptr;
    if (!fn) {
        void* p = nullptr;
        cudaDriverEntryPointQueryResult qr;
        cudaGetDriverEntryPoint("cuTensorMapEncodeTiled", &p, cudaEnableDefault, &qr);
        fn = (EncodeFn)p;
    }
    return fn;
}
CUtensorMap map2d(const void* ptr, uint64_t cols, uint64_t rows, uint32_t bc, uint32_t br, CUtensorMapSwizzle sw) {
    CUtensorMap m;
    cuuint64_t gd[2] = {cols, rows}, gs[1] = {cols * 2};
    cuuint32_t bx[2] = {bc, br}, es[2] = {1, 1};
    get_encode()(&m, CU_TENSOR_MAP_DATA_TYPE_BFLOAT16, 2, (void*)ptr, gd, gs, bx, es, CU_TENSOR_MAP_INTERLEAVE_NONE, sw,
                 CU_TENSOR_MAP_L2_PROMOTION_L2_128B, CU_TENSOR_MAP_FLOAT_OOB_FILL_NONE);
    return m;
}
CUtensorMap map3d32(const void* ptr, uint64_t cols, uint64_t rows, uint32_t br, uint32_t nb) {
    CUtensorMap m;
    cuuint64_t gd[3] = {32, rows, cols / 32}, gs[2] = {cols * 2, 64};
    cuuint32_t bx[3] = {32, br, nb}, es[3] = {1, 1, 1};
    get_encode()(&m, CU_TENSOR_MAP_DATA_TYPE_BFLOAT16, 3, (void*)ptr, gd, gs, bx, es, CU_TENSOR_MAP_INTERLEAVE_NONE, CU_TENSOR_MAP_SWIZZLE_64B,
                 CU_TENSOR_MAP_L2_PROMOTION_L2_128B, CU_TENSOR_MAP_FLOAT_OOB_FILL_NONE);
    return m;
}

template <typename... KArgs, typename... Args>
void launch(void (*kern)(KArgs...), int grid, int block, int smem, int cluster, bool pdl, Args... args) {
    cudaLaunchConfig_t cfg = {};
    cfg.gridDim = dim3(grid);
    cfg.blockDim = dim3(block);
    cfg.dynamicSmemBytes = smem;
    cfg.stream = cudaStreamPerThread;
    cudaLaunchAttribute at[2];
    int n = 0;
    if (cluster > 1) { at[n].id = cudaLaunchAttributeClusterDimension; at[n].val.clusterDim.x = cluster; at[n].val.clusterDim.y = 1; at[n].val.clusterDim.z = 1; n++; }
    if (pdl) { at[n].id = cudaLaunchAttributeProgrammaticStreamSerialization; at[n].val.programmaticStreamSerializationAllowed = 1; n++; }
    cfg.attrs = at;
    cfg.numAttrs = n;
    cudaLaunchKernelEx(&cfg, kern, KArgs(args)...);
}

template <typename T> void* sym(const T& s) { void* p = nullptr; cudaGetSymbolAddress(&p, s); return p; }

}

extern "C" void kernel_launch(void* const* d_in, const int* in_sizes, int n_in, void* d_out, int out_size) {
    const __nv_bfloat16* x = (const __nv_bfloat16*)d_in[0];
    const __nv_bfloat16* wq = (const __nv_bfloat16*)d_in[1];
    const __nv_bfloat16* wk = (const __nv_bfloat16*)d_in[2];
    const __nv_bfloat16* wv = (const __nv_bfloat16*)d_in[3];
    const __nv_bfloat16* wo = (const __nv_bfloat16*)d_in[4];
    const __nv_bfloat16* w1 = (const __nv_bfloat16*)d_in[6];
    const __nv_bfloat16* w2 = (const __nv_bfloat16*)d_in[7];

    constexpr int SM_QKV = GemmSmem<QKV_STAGES, EPI_QKV>::TOTAL, SM_QKV0 = GemmSmem<QKV_STAGES, EPI_QKV>::TOTAL_SELF;
    static_assert(SM_QKV0 <= 232448, "shared memory");
    constexpr int SM_WO = GemmSmem<WO_STAGES, EPI_RES>::TOTAL, SM_FFN2 = GemmSmem<FFN2_STAGES, EPI_RES>::TOTAL;
    static_assert(SM_WO > 116736 && SM_FFN2 > 116736, "one CTA per SM");
    constexpr int SM_FFN1 = GemmSmem<FFN1_STAGES, EPI_FFN1>::TOTAL;
    cudaFuncSetAttribute(qkv_kernel<false>, cudaFuncAttributeMaxDynamicSharedMemorySize, SM_QKV);
    cudaFuncSetAttribute(qkv_kernel<true>, cudaFuncAttributeMaxDynamicSharedMemorySize, SM_QKV0);
    cudaFuncSetAttribute(res_gemm_kernel<8, WO_STAGES>, cudaFuncAttributeMaxDynamicSharedMemorySize, SM_WO);
    cudaFuncSetAttribute(ffn1_kernel, cudaFuncAttributeMaxDynamicSharedMemorySize, SM_FFN1);
    cudaFuncSetAttribute(res_gemm_kernel<28, FFN2_STAGES>, cudaFuncAttributeMaxDynamicSharedMemorySize, SM_FFN2);
    cudaFuncSetAttribute(attn_kernel, cudaFuncAttributeMaxDynamicSharedMemorySize, ATT_SMEM);
    cudaFuncSetAttribute(qkv_kernel<false>, cudaFuncAttributePreferredSharedMemoryCarveout, 100);
    cudaFuncSetAttribute(qkv_kernel<true>, cudaFuncAttributePreferredSharedMemoryCarveout, 100);
    cudaFuncSetAttribute(res_gemm_kernel<8, WO_STAGES>, cudaFuncAttributePreferredSharedMemoryCarveout, 100);
    cudaFuncSetAttribute(ffn1_kernel, cudaFuncAttributePreferredSharedMemoryCarveout, 100);
    cudaFuncSetAttribute(res_gemm_kernel<28, FFN2_STAGES>, cudaFuncAttributePreferredSharedMemoryCarveout, 100);
    cudaFuncSetAttribute(attn_kernel, cudaFuncAttributePreferredSharedMemoryCarveout, 100);

    void *q = sym(g_q), *o = sym(g_o), *x1 = sym(g_x1), *x2 = sym(g_x2), *x3 = sym(g_x3), *h = sym(g_h);
    float2* stats = (float2*)sym(g_stats);
    const void* xs[5] = {x, x1, x2, x3, d_out};

    const CUtensorMapSwizzle SW128 = CU_TENSOR_MAP_SWIZZLE_128B, SW64 = CU_TENSOR_MAP_SWIZZLE_64B;
    const CUtensorMap mWq = map3d32(wq, D_, D_, 64, 2);
    const CUtensorMap mWo = map2d(wo, D_, D_, 64, 64, SW128);
    const CUtensorMap mW1 = map3d32(w1, F_, D_, 64, 7);
    const CUtensorMap mW2 = map2d(w2, D_, F_, 64, 64, SW128);
    const CUtensorMap mQ = map2d(q, D_, S_, 64, 64, SW128);
    const CUtensorMap mQa = map2d(q, D_, S_, 64, 128, SW128), mOs = map2d(o, D_, S_, 64, 128, SW128);
    const CUtensorMap mHst = map2d(h, F_, S_, 32, 16, SW64);
    CUtensorMap mXa[4], mXs[5];
    for (int i = 0; i < 4; i++) {
        mXa[i] = map2d(xs[i], D_, S_, 64, 128, SW128);
    }
    for (int i = 0; i < 5; i++) mXs[i] = map2d(xs[i], D_, S_, 64, 64, SW128);
    const CUtensorMap mOa = map2d(o, D_, S_, 64, 128, SW128);
    const CUtensorMap mHa = map2d(h, F_, S_, 64, 128, SW128);

    for (int layer = 0; layer < 2; layer++) {
        const int xi = layer * 2;
        GemmParams p;
        p.wkv = wk; p.wv = wv;
        p.stats_in = stats + (size_t)xi * 8 * S_; p.stats_out = nullptr;
        if (layer == 0) launch(qkv_kernel<true>, 128, 640, SM_QKV0, 1, false, mXa[xi], mWq, mQ, p);
        else launch(qkv_kernel<false>, 128, 288, SM_QKV, 2, true, mXa[xi], mWq, mQ, p);
        launch(attn_kernel, layer == 0 ? 128 + SIDE_CTAS : 128, 512, ATT_SMEM, 1, true, mQa, mOs, wo, w1, w2);
        p.stats_in = nullptr; p.stats_out = stats + (size_t)(xi + 1) * 8 * S_;
        launch(res_gemm_kernel<8, WO_STAGES>, 128, 288, SM_WO, 2, true, mOa, mWo, mXa[xi], mXs[xi + 1], p);
        p.stats_in = stats + (size_t)(xi + 1) * 8 * S_; p.stats_out = nullptr;
        launch(ffn1_kernel, 128, 288, SM_FFN1, 1, true, mXa[xi + 1], mW1, mHst, p);
        p.stats_in = nullptr; p.stats_out = layer == 0 ? stats + (size_t)2 * 8 * S_ : nullptr;
        launch(res_gemm_kernel<28, FFN2_STAGES>, 128, 288, SM_FFN2, 2, true, mHa, mW2, mXa[xi + 1], mXs[xi + 2], p);
    }
}
```

```cpp
#include <cuda_runtime.h>
#include <cuda_bf16.h>
#include <cuda.h>
#include <stdint.h>

namespace {

constexpr int S_ = 2048, D_ = 512, F_ = 1792;

__device__ __align__(1024) __nv_bfloat16 g_q[S_ * D_];
__device__ __align__(1024) __nv_bfloat16 g_o[S_ * D_];
__device__ __align__(1024) __nv_bfloat16 g_x1[S_ * D_];
__device__ __align__(1024) __nv_bfloat16 g_x2[S_ * D_];
__device__ __align__(1024) __nv_bfloat16 g_x3[S_ * D_];
__device__ __align__(1024) __nv_bfloat16 g_h[S_ * F_];
__device__ __align__(1024) uint8_t g_kimg[S_ * 32];
__device__ __align__(1024) uint8_t g_vimg[(S_ / 16) * 768];
__device__ __align__(1024) float2 g_stats[4][8 * S_];
__device__ __align__(16) float g_cs_q[D_];
__device__ __align__(16) float g_cs_kv[32];
__device__ __align__(16) float g_cs_1[F_];
__device__ __align__(16) float g_kvmax[32];

__device__ __forceinline__ uint32_t smem_u32(const void* p) { return (uint32_t)__cvta_generic_to_shared(p); }
__device__ __forceinline__ void mbar_init(uint32_t bar, uint32_t cnt) {
    asm volatile("mbarrier.init.shared::cta.b64 [%0], %1;" ::"r"(bar), "r"(cnt));
}
__device__ __forceinline__ void mbar_expect_tx(uint32_t bar, uint32_t bytes) {
    asm volatile("mbarrier.arrive.expect_tx.shared::cta.b64 _, [%0], %1;" ::"r"(bar), "r"(bytes) : "memory");
}
__device__ __forceinline__ void mbar_arrive(uint32_t bar) {
    asm volatile("mbarrier.arrive.shared::cta.b64 _, [%0];" ::"r"(bar) : "memory");
}
__device__ __forceinline__ void mbar_wait(uint32_t bar, uint32_t parity) {
    asm volatile("{\n.reg .pred p;\nWAIT_%=:\nmbarrier.try_wait.parity.shared::cta.b64 p, [%0], %1;\n@p bra DONE_%=;\nbra WAIT_%=;\nDONE_%=:\n}" ::"r"(bar), "r"(parity) : "memory");
}
__device__ __forceinline__ void bulk_load(uint32_t dst, const void* src, uint32_t bytes, uint32_t bar) {
    asm volatile("cp.async.bulk.shared::cluster.global.mbarrier::complete_tx::bytes [%0], [%1], %2, [%3];" ::"r"(dst), "l"(src), "r"(bytes), "r"(bar) : "memory");
}
__device__ __forceinline__ void tma2d(uint32_t dst, const CUtensorMap* m, int c0, int c1, uint32_t bar) {
    asm volatile("cp.async.bulk.tensor.2d.shared::cluster.global.mbarrier::complete_tx::bytes [%0], [%1, {%3, %4}], [%2];" ::"r"(dst), "l"(m), "r"(bar), "r"(c0), "r"(c1) : "memory");
}
__device__ __forceinline__ void tma3d(uint32_t dst, const CUtensorMap* m, int c0, int c1, int c2, uint32_t bar) {
    asm volatile("cp.async.bulk.tensor.3d.shared::cluster.global.mbarrier::complete_tx::bytes [%0], [%1, {%3, %4, %5}], [%2];" ::"r"(dst), "l"(m), "r"(bar), "r"(c0), "r"(c1), "r"(c2) : "memory");
}
__device__ __forceinline__ void tma2d_store(const CUtensorMap* m, uint32_t src, int c0, int c1) {
    asm volatile("cp.async.bulk.tensor.2d.global.shared::cta.bulk_group [%0, {%2, %3}], [%1];" ::"l"(m), "r"(src), "r"(c0), "r"(c1) : "memory");
}
__device__ __forceinline__ void bulk_commit() { asm volatile("cp.async.bulk.commit_group;" ::: "memory"); }
__device__ __forceinline__ void bulk_wait_read() { asm volatile("cp.async.bulk.wait_group.read 0;" ::: "memory"); }
__device__ __forceinline__ void prefetch_tmap(const CUtensorMap* m) { asm volatile("prefetch.tensormap [%0];" ::"l"(m) : "memory"); }
__device__ __forceinline__ void fence_async_smem() { asm volatile("fence.proxy.async.shared::cta;" ::: "memory"); }
__device__ __forceinline__ void fence_mbar_init() { asm volatile("fence.mbarrier_init.release.cluster;" ::: "memory"); }
__device__ __forceinline__ void pdl_wait() { asm volatile("griddepcontrol.wait;" ::: "memory"); }
__device__ __forceinline__ void pdl_launch() { asm volatile("griddepcontrol.launch_dependents;" ::: "memory"); }
__device__ __forceinline__ bool elect_one() {
    uint32_t p;
    asm volatile("{\n.reg .pred p;\nelect.sync _|p, 0xffffffff;\nselp.b32 %0, 1, 0, p;\n}" : "=r"(p));
    return p != 0;
}
__device__ __forceinline__ void named_bar(int id, int n) { asm volatile("bar.sync %0, %1;" ::"r"(id), "r"(n) : "memory"); }

__device__ __forceinline__ void wg_fence() { asm volatile("wgmma.fence.sync.aligned;" ::: "memory"); }
__device__ __forceinline__ void wg_commit() { asm volatile("wgmma.commit_group.sync.aligned;" ::: "memory"); }
template <int N> __device__ __forceinline__ void wg_wait() { asm volatile("wgmma.wait_group.sync.aligned %0;" ::"n"(N) : "memory"); }
template <int N> __device__ __forceinline__ void fence_regs(float (&d)[N]) {
#pragma unroll
    for (int i = 0; i < N; i++) asm volatile("" : "+f"(d[i])::"memory");
}
__device__ __forceinline__ uint64_t mkdesc(uint32_t addr, uint32_t lbo, uint32_t sbo, uint32_t swz) {
    uint64_t d = 0;
    d |= (uint64_t)((addr & 0x3FFFF) >> 4);
    d |= (uint64_t)((lbo & 0x3FFFF) >> 4) << 16;
    d |= (uint64_t)((sbo & 0x3FFFF) >> 4) << 32;
    d |= (uint64_t)swz << 62;
    return d;
}
__device__ __forceinline__ void ldsm_x4(uint32_t& r0, uint32_t& r1, uint32_t& r2, uint32_t& r3, uint32_t addr) {
    asm volatile("ldmatrix.sync.aligned.m8n8.x4.shared.b16 {%0,%1,%2,%3}, [%4];" : "=r"(r0), "=r"(r1), "=r"(r2), "=r"(r3) : "r"(addr) : "memory");
}
__device__ __forceinline__ void stsm_x4(uint32_t addr, uint32_t r0, uint32_t r1, uint32_t r2, uint32_t r3) {
    asm volatile("stmatrix.sync.aligned.m8n8.x4.shared.b16 [%0], {%1,%2,%3,%4};" ::"r"(addr), "r"(r0), "r"(r1), "r"(r2), "r"(r3) : "memory");
}
__device__ __forceinline__ uint32_t pack_bf16(float lo, float hi) {
    uint32_t r;
    asm("cvt.rn.bf16x2.f32 %0, %1, %2;" : "=r"(r) : "f"(hi), "f"(lo));
    return r;
}
__device__ __forceinline__ float bf_lo(uint32_t v) { return __uint_as_float(v << 16); }
__device__ __forceinline__ float bf_hi(uint32_t v) { return __uint_as_float(v & 0xFFFF0000u); }

#define WG_REGS_4(o) "+f"(d[o]), "+f"(d[o + 1]), "+f"(d[o + 2]), "+f"(d[o + 3])
#define WG_REGS_8(o) WG_REGS_4(o), WG_REGS_4(o + 4)
#define WG_REGS_16(o) WG_REGS_8(o), WG_REGS_8(o + 8)
#define WG_REGS_32(o) WG_REGS_16(o), WG_REGS_16(o + 16)

__device__ __forceinline__ void wgmma_ss_n80_tb(float (&d)[40], uint64_t dA, uint64_t dB, int sc) {
    asm volatile("{\n.reg .pred p;\nsetp.ne.b32 p, %42, 0;\n"
                 "wgmma.mma_async.sync.aligned.m64n80k16.f32.bf16.bf16 "
                 "{%0,%1,%2,%3,%4,%5,%6,%7,%8,%9,%10,%11,%12,%13,%14,%15,%16,%17,%18,%19,%20,%21,%22,%23,%24,%25,%26,%27,%28,%29,%30,%31,"
                 "%32,%33,%34,%35,%36,%37,%38,%39}, %40, %41, p, 1, 1, 0, 1;\n}\n"
                 : WG_REGS_32(0), WG_REGS_8(32) : "l"(dA), "l"(dB), "r"(sc));
}
__device__ __forceinline__ void wgmma_ss_n64_tb(float (&d)[32], uint64_t dA, uint64_t dB, int sc) {
    asm volatile("{\n.reg .pred p;\nsetp.ne.b32 p, %34, 0;\n"
                 "wgmma.mma_async.sync.aligned.m64n64k16.f32.bf16.bf16 "
                 "{%0,%1,%2,%3,%4,%5,%6,%7,%8,%9,%10,%11,%12,%13,%14,%15,%16,%17,%18,%19,%20,%21,%22,%23,%24,%25,%26,%27,%28,%29,%30,%31}, "
                 "%32, %33, p, 1, 1, 0, 1;\n}\n"
                 : WG_REGS_32(0) : "l"(dA), "l"(dB), "r"(sc));
}
__device__ __forceinline__ void wgmma_ss_n224_tb(float (&d)[112], uint64_t dA, uint64_t dB, int sc) {
    asm volatile("{\n.reg .pred p;\nsetp.ne.b32 p, %114, 0;\n"
                 "wgmma.mma_async.sync.aligned.m64n224k16.f32.bf16.bf16 "
                 "{%0,%1,%2,%3,%4,%5,%6,%7,%8,%9,%10,%11,%12,%13,%14,%15,%16,%17,%18,%19,%20,%21,%22,%23,%24,%25,%26,%27,%28,%29,%30,%31,"
                 "%32,%33,%34,%35,%36,%37,%38,%39,%40,%41,%42,%43,%44,%45,%46,%47,%48,%49,%50,%51,%52,%53,%54,%55,%56,%57,%58,%59,%60,%61,%62,%63,"
                 "%64,%65,%66,%67,%68,%69,%70,%71,%72,%73,%74,%75,%76,%77,%78,%79,%80,%81,%82,%83,%84,%85,%86,%87,%88,%89,%90,%91,%92,%93,%94,%95,"
                 "%96,%97,%98,%99,%100,%101,%102,%103,%104,%105,%106,%107,%108,%109,%110,%111}, "
                 "%112, %113, p, 1, 1, 0, 1;\n}\n"
                 : WG_REGS_32(0), WG_REGS_32(32), WG_REGS_32(64), WG_REGS_16(96) : "l"(dA), "l"(dB), "r"(sc));
}
template <int BN> __device__ __forceinline__ void wgmma_ss_tb(float (&d)[BN / 2], uint64_t dA, uint64_t dB, int sc) {
    if constexpr (BN == 64) wgmma_ss_n64_tb(d, dA, dB, sc);
    else if constexpr (BN == 80) wgmma_ss_n80_tb(d, dA, dB, sc);
    else wgmma_ss_n224_tb(d, dA, dB, sc);
}
__device__ __forceinline__ void wgmma_rs_n64_tb(float (&d)[32], uint32_t a, uint64_t dB, int sc) {
    asm volatile("{\n.reg .pred p;\nsetp.ne.b32 p, %34, 0;\n"
                 "wgmma.mma_async.sync.aligned.m64n64k16.f32.bf16.bf16 "
                 "{%0,%1,%2,%3,%4,%5,%6,%7,%8,%9,%10,%11,%12,%13,%14,%15,%16,%17,%18,%19,%20,%21,%22,%23,%24,%25,%26,%27,%28,%29,%30,%31}, "
                 "{%32,%32,%32,%32}, %33, p, 1, 1, 1;\n}\n"
                 : WG_REGS_32(0) : "r"(a), "l"(dB), "r"(sc));
}
__device__ __forceinline__ void wgmma_rs_n80_tb(float (&d)[40], uint32_t a, uint64_t dB, int sc) {
    asm volatile("{\n.reg .pred p;\nsetp.ne.b32 p, %42, 0;\n"
                 "wgmma.mma_async.sync.aligned.m64n80k16.f32.bf16.bf16 "
                 "{%0,%1,%2,%3,%4,%5,%6,%7,%8,%9,%10,%11,%12,%13,%14,%15,%16,%17,%18,%19,%20,%21,%22,%23,%24,%25,%26,%27,%28,%29,%30,%31,"
                 "%32,%33,%34,%35,%36,%37,%38,%39}, {%40,%40,%40,%40}, %41, p, 1, 1, 1;\n}\n"
                 : WG_REGS_32(0), WG_REGS_8(32) : "r"(a), "l"(dB), "r"(sc));
}
template <int BN> __device__ __forceinline__ void wgmma_rs_ones(float (&d)[BN / 2], uint64_t dB, int sc) {
    if constexpr (BN == 80) wgmma_rs_n80_tb(d, 0x3F803F80u, dB, sc);
    else if constexpr (BN == 64) wgmma_rs_n64_tb(d, 0x3F803F80u, dB, sc);
}
__device__ __forceinline__ void wgmma_rs_n64_z(float (&d)[32], uint32_t a0, uint32_t a1, uint32_t a2, uint32_t a3, uint64_t dB) {
    asm volatile("{\n.reg .pred p;\nsetp.ne.b32 p, 0, 0;\n"
                 "wgmma.mma_async.sync.aligned.m64n64k16.f32.bf16.bf16 "
                 "{%0,%1,%2,%3,%4,%5,%6,%7,%8,%9,%10,%11,%12,%13,%14,%15,%16,%17,%18,%19,%20,%21,%22,%23,%24,%25,%26,%27,%28,%29,%30,%31}, "
                 "{%32,%33,%34,%35}, %36, p, 1, 1, 0;\n}\n"
                 : "=f"(d[0]), "=f"(d[1]), "=f"(d[2]), "=f"(d[3]), "=f"(d[4]), "=f"(d[5]), "=f"(d[6]), "=f"(d[7]),
                   "=f"(d[8]), "=f"(d[9]), "=f"(d[10]), "=f"(d[11]), "=f"(d[12]), "=f"(d[13]), "=f"(d[14]), "=f"(d[15]),
                   "=f"(d[16]), "=f"(d[17]), "=f"(d[18]), "=f"(d[19]), "=f"(d[20]), "=f"(d[21]), "=f"(d[22]), "=f"(d[23]),
                   "=f"(d[24]), "=f"(d[25]), "=f"(d[26]), "=f"(d[27]), "=f"(d[28]), "=f"(d[29]), "=f"(d[30]), "=f"(d[31])
                 : "r"(a0), "r"(a1), "r"(a2), "r"(a3), "l"(dB));
}
__device__ __forceinline__ void wgmma_rs_n24_tb(float (&d)[12], uint32_t a0, uint32_t a1, uint32_t a2, uint32_t a3, uint64_t dB) {
    asm volatile("{\n.reg .pred p;\nsetp.eq.b32 p, 0, 0;\n"
                 "wgmma.mma_async.sync.aligned.m64n24k16.f32.bf16.bf16 "
                 "{%0,%1,%2,%3,%4,%5,%6,%7,%8,%9,%10,%11}, {%12,%13,%14,%15}, %16, p, 1, 1, 1;\n}\n"
                 : WG_REGS_8(0), WG_REGS_4(8) : "r"(a0), "r"(a1), "r"(a2), "r"(a3), "l"(dB));
}

constexpr int SIDE_CTAS = 4;
__device__ __forceinline__ void side_job(int cta, float* red  , const __nv_bfloat16* __restrict__ wo,
                                         const __nv_bfloat16* __restrict__ w1, const __nv_bfloat16* __restrict__ w2) {
    const int tid = threadIdx.x, warp = tid >> 5, lane = tid & 31;
    for (int line = cta * 512 + tid; line < 18432; line += SIDE_CTAS * 512) {
        const char* p = line < 4096 ? (const char*)wo + (size_t)line * 128 : (const char*)w2 + (size_t)(line - 4096) * 128;
        asm volatile("prefetch.global.L2 [%0];" ::"l"(p));
    }
    const int rg = lane >> 3, c8 = lane & 7;
    for (int slab = cta; slab < F_ / 64; slab += SIDE_CTAS) {
        const __nv_bfloat16* base = w1 + slab * 64 + c8 * 8;
        uint4 v[8];
#pragma unroll
        for (int i = 0; i < 8; i++) v[i] = __ldg((const uint4*)(base + (size_t)(warp * 32 + rg + 4 * i) * F_));
        float acc[8];
#pragma unroll
        for (int i = 0; i < 8; i++) acc[i] = 0.f;
#pragma unroll
        for (int i = 0; i < 8; i++) {
            acc[0] += bf_lo(v[i].x); acc[1] += bf_hi(v[i].x); acc[2] += bf_lo(v[i].y); acc[3] += bf_hi(v[i].y);
            acc[4] += bf_lo(v[i].z); acc[5] += bf_hi(v[i].z); acc[6] += bf_lo(v[i].w); acc[7] += bf_hi(v[i].w);
        }
#pragma unroll
        for (int i = 0; i < 8; i++) {
            acc[i] += __shfl_xor_sync(0xffffffffu, acc[i], 8);
            acc[i] += __shfl_xor_sync(0xffffffffu, acc[i], 16);
        }
        if (rg == 0) {
#pragma unroll
            for (int i = 0; i < 8; i++) red[warp * 64 + c8 * 8 + i] = acc[i];
        }
        __syncthreads();
        if (tid < 64) {
            float s = 0.f;
#pragma unroll
            for (int i = 0; i < 16; i++) s += red[i * 64 + tid];
            g_cs_1[slab * 64 + tid] = s;
        }
        __syncthreads();
    }
}

enum { EPI_QKV = 0, EPI_RES = 1, EPI_FFN1 = 2 };

struct GemmParams {
    const float2* stats_in;
    float2* stats_out;
    const __nv_bfloat16* wkv;
    const __nv_bfloat16* wv;
};

template <int BK_, int NBLK> struct Geo {
    static constexpr int BK = BK_, A_BYTES = 128 * BK * 2, A_SWZ = BK == 64 ? 1 : 2, A_SBO = BK * 16;
    static constexpr int BLK = BK * 64;
    static constexpr int B_BYTES = NBLK * BLK, B_SWZ = 2, B_LBO = BLK, B_SBO = 512, B_KSTEP = 1024;
};
template <> struct Geo<64, 0> {
    static constexpr int BK = 64, A_BYTES = 128 * 128, A_SWZ = 1, A_SBO = 1024, BLK = 8192;
    static constexpr int B_BYTES = 64 * 128, B_SWZ = 1, B_LBO = 8192, B_SBO = 1024, B_KSTEP = 2048;
};
template <int EPI> struct EpiGeo;
template <> struct EpiGeo<EPI_QKV> { using G = Geo<64, 3>; };
template <> struct EpiGeo<EPI_RES> { using G = Geo<64, 0>; };
template <> struct EpiGeo<EPI_FFN1> { using G = Geo<64, 7>; };

template <int STAGES, int EPI> struct GemmSmem {
    using G = typename EpiGeo<EPI>::G;
    static constexpr int STAGE = G::A_BYTES + G::B_BYTES;
    static constexpr int AUX_OFF = STAGES * STAGE;
    static constexpr int TOTAL = AUX_OFF + 1152;
    static constexpr int TOTAL_SELF = AUX_OFF + 704 + 1024;
};

struct RowStatRaw { float2 a0, a1, b0, b1; };
__device__ __forceinline__ RowStatRaw load_row_stats(const float2* __restrict__ st, int row0, int c) {
    RowStatRaw r;
    r.a0 = st[(2 * c) * S_ + row0]; r.a1 = st[(2 * c + 1) * S_ + row0];
    r.b0 = st[(2 * c) * S_ + row0 + 8]; r.b1 = st[(2 * c + 1) * S_ + row0 + 8];
    return r;
}
__device__ __forceinline__ void finish_row_stats(const RowStatRaw& r, float& mean0, float& rstd0, float& mean1, float& rstd1) {
    float sa = r.a0.x + r.a1.x, sb = r.b0.x + r.b1.x;
    sa += __shfl_xor_sync(0xffffffffu, sa, 1); sa += __shfl_xor_sync(0xffffffffu, sa, 2);
    sb += __shfl_xor_sync(0xffffffffu, sb, 1); sb += __shfl_xor_sync(0xffffffffu, sb, 2);
    mean0 = sa * 0.125f; mean1 = sb * 0.125f;
    float ma = r.a0.y + r.a1.y + 64.f * ((r.a0.x - mean0) * (r.a0.x - mean0) + (r.a1.x - mean0) * (r.a1.x - mean0));
    float mb = r.b0.y + r.b1.y + 64.f * ((r.b0.x - mean1) * (r.b0.x - mean1) + (r.b1.x - mean1) * (r.b1.x - mean1));
    ma += __shfl_xor_sync(0xffffffffu, ma, 1); ma += __shfl_xor_sync(0xffffffffu, ma, 2);
    mb += __shfl_xor_sync(0xffffffffu, mb, 1); mb += __shfl_xor_sync(0xffffffffu, mb, 2);
    rstd0 = 1.0f / sqrtf(ma * (1.f / 512.f) + 1e-5f);
    rstd1 = 1.0f / sqrtf(mb * (1.f / 512.f) + 1e-5f);
}

template <int BN, int KB, int STAGES, int EPI, bool SELF = false>
__device__ __forceinline__ void gemm_body(const CUtensorMap* mapA, const CUtensorMap* mapB, const CUtensorMap* mapR,
                                          const CUtensorMap* mapC, const GemmParams& prm, int tile_m, int tile_n, uint8_t* smem_raw) {
    using SM = GemmSmem<STAGES, EPI>;
    using G = typename SM::G;
    constexpr bool XKV = BN == 80;
    constexpr int TN = EPI == EPI_QKV ? 64 : BN;
    pdl_launch();
    const uint32_t sbase = smem_u32(smem_raw);
    if (sbase & 1023) __trap();
    uint8_t* sgen = smem_raw;
    const uint32_t bar_full = sbase + SM::AUX_OFF, bar_empty = bar_full + 8 * STAGES;
    float* s_cs = (float*)(sgen + SM::AUX_OFF + 256);
    float* s_row = (float*)(sgen + SM::AUX_OFF + 704);
    float* s_red = (float*)(sgen + SM::AUX_OFF + 640);
    const int tid = threadIdx.x, lane = tid & 31;
    const int warp = __shfl_sync(0xffffffffu, tid >> 5, 0);

    if (warp == 8 && elect_one()) {
#pragma unroll
        for (int s = 0; s < STAGES; s++) { mbar_init(bar_full + 8 * s, 1); mbar_init(bar_empty + 8 * s, 2); }
        fence_mbar_init();
    }
    if (warp == 1 && elect_one()) { prefetch_tmap(mapB); prefetch_tmap(mapA); prefetch_tmap(mapC); }
    __syncthreads();

    const int m0 = tile_m * 128, n0 = tile_n * TN;
    constexpr uint32_t STAGE_TX = G::A_BYTES + (EPI == EPI_QKV ? 2 * G::BLK : G::B_BYTES);
    auto loadB = [&](int kb, int s) {
        const uint32_t dst = sbase + s * SM::STAGE + G::A_BYTES, bar = bar_full + 8 * s;
        if constexpr (EPI == EPI_RES) {
            tma2d(dst, mapB, n0, kb * 64, bar);
        } else if constexpr (EPI == EPI_QKV) {
            tma3d(dst, mapB, 0, kb * G::BK, tile_n * 2, bar);
        } else {
            tma3d(dst, mapB, 0, kb * G::BK, tile_n * 7, bar);
        }
    };
    auto loadA = [&](int kb, int s) {
        const uint32_t dst = sbase + s * SM::STAGE, bar = bar_full + 8 * s;
        tma2d(dst, mapA, kb * G::BK, m0, bar);
    };
    constexpr int PRE = STAGES < KB ? STAGES : KB;
    constexpr int PRE_B = 1;
    auto prologue_loads = [&]() {
        if (elect_one()) {
#pragma unroll
            for (int kb = 0; kb < PRE; kb++) mbar_expect_tx(bar_full + 8 * kb, STAGE_TX);
        }
        if (elect_one()) {
#pragma unroll
            for (int kb = 0; kb < PRE_B; kb++) loadB(kb, kb);
        }
        if (!SELF) pdl_wait();
        if (elect_one()) {
#pragma unroll
            for (int kb = 0; kb < PRE; kb++) {
                loadA(kb, kb);
                if (kb + PRE_B < PRE) loadB(kb + PRE_B, kb + PRE_B);
            }
            if constexpr (EPI == EPI_RES && KB < STAGES) {
                mbar_expect_tx(bar_full + 8 * KB, 16384);
                tma2d(sbase + KB * SM::STAGE, mapR, n0, m0, bar_full + 8 * KB);
            }
        }
    };
    if (SELF && warp >= 8) {
        if (warp == 8) prologue_loads();
        static_assert(!SELF || (STAGES >= KB && EPI == EPI_QKV), "SELF needs every k block resident");
        if ((warp >> 2) == 3) {
            float csum[BN / 2];
            const uint64_t dB0 = mkdesc(sbase + G::A_BYTES, G::B_LBO, G::B_SBO, G::B_SWZ);
            if constexpr (XKV) named_bar(6, 384);
#pragma unroll 1
            for (int kb = 0; kb < KB; kb++) {
                mbar_wait(bar_full + 8 * kb, 0);
                const uint64_t dB = dB0 + (uint64_t)(kb * (SM::STAGE >> 4));
                wg_fence();
#pragma unroll
                for (int k = 0; k < G::BK / 16; k++) {
                    if constexpr (SELF) wgmma_rs_ones<BN>(csum, dB + (uint64_t)(k * (G::B_KSTEP >> 4)), (kb | k) != 0);
                }
                wg_commit();
            }
            wg_wait<0>();
            fence_regs(csum);
            if (warp == 12 && lane < 4) {
#pragma unroll
                for (int j = 0; j < BN / 8; j++) {
                    const float2 v = make_float2(csum[4 * j], csum[4 * j + 1]);
                    *(float2*)(s_cs + 8 * j + 2 * lane) = v;
                    if (tile_m == 0) {
                        if (j < 8) *(float2*)(g_cs_q + n0 + 8 * j + 2 * lane) = v;
                        else *(float2*)(g_cs_kv + tile_n * 16 + 8 * (j - 8) + 2 * lane) = v;
                    }
                }
            }
        } else {
            const int t = (warp < 12 ? warp - 8 : warp - 12) * 32 + lane;
            float ss[4] = {0.f, 0.f, 0.f, 0.f}, sq[4] = {0.f, 0.f, 0.f, 0.f};
#pragma unroll 1
            for (int kb = 0; kb < KB; kb++) {
                mbar_wait(bar_full + 8 * kb, 0);
                const uint32_t arow = sbase + kb * SM::STAGE + (t >> 1) * 128;
                uint32_t w[4][4];
#pragma unroll
                for (int j = 0; j < 4; j++)
                    asm volatile("ld.shared.v4.u32 {%0,%1,%2,%3}, [%4];" : "=r"(w[j][0]), "=r"(w[j][1]), "=r"(w[j][2]), "=r"(w[j][3])
                                 : "r"(arow + (((2 * j + (t & 1) + 2 * ((t >> 1) & 3)) & 7) << 4)));
#pragma unroll
                for (int j = 0; j < 4; j++)
#pragma unroll
                    for (int i = 0; i < 4; i++) {
                        const float lo = bf_lo(w[j][i]), hi = bf_hi(w[j][i]);
                        ss[i] += lo + hi;
                        sq[i] = fmaf(lo, lo, fmaf(hi, hi, sq[i]));
                    }
            }
            float tsum = (ss[0] + ss[1]) + (ss[2] + ss[3]), tsq = (sq[0] + sq[1]) + (sq[2] + sq[3]);
            tsum += __shfl_xor_sync(0xffffffffu, tsum, 1);
            tsq += __shfl_xor_sync(0xffffffffu, tsq, 1);
            if ((t & 1) == 0) {
                const float md = tsum * (1.f / 512.f);
                const float var = fmaxf(tsq * (1.f / 512.f) - md * md, 0.f);
                *(float2*)(s_row + t) = make_float2(md, 1.0f / sqrtf(var + 1e-5f));
            }
        }
        named_bar(4, 640);
    } else if (warp == 8) {
        prologue_loads();
        int s = PRE % STAGES, ph = (PRE / STAGES) & 1;
#pragma unroll 1
        for (int kb = PRE; kb < KB; kb++) {
            mbar_wait(bar_empty + 8 * s, ph ^ 1);
            if (elect_one()) {
                mbar_expect_tx(bar_full + 8 * s, STAGE_TX);
                loadB(kb, s);
                loadA(kb, s);
            }
            if (++s == STAGES) { s = 0; ph ^= 1; }
        }
        if constexpr (EPI == EPI_RES && KB >= STAGES) {
            mbar_wait(bar_empty + 8 * s, ph ^ 1);
            if (elect_one()) {
                mbar_expect_tx(bar_full + 8 * s, 16384);
                tma2d(sbase + s * SM::STAGE, mapR, n0, m0, bar_full + 8 * s);
            }
        }
    } else {
        const int wg = warp >> 2, g = lane >> 2, c = lane & 3;
        const int rloc = wg * 64 + (warp & 3) * 16 + g;
        const int row0 = m0 + rloc;
        float mean0 = 0.f, rstd0 = 1.f, mean1 = 0.f, rstd1 = 1.f;
        if constexpr (XKV) {
            static_assert(!XKV || STAGES >= KB, "the K / V weight block must stay resident");
            const __nv_bfloat16* wsrc = tile_n == 0 ? prm.wkv : prm.wv;
            uint4 v[4];
#pragma unroll
            for (int i = 0; i < 4; i++) v[i] = __ldg((const uint4*)wsrc + tid + 256 * i);
#pragma unroll
            for (int i = 0; i < 4; i++) {
                const int idx = tid + 256 * i, k = idx >> 1, kr = k & 63;
                const uint32_t dst = sbase + (k >> 6) * SM::STAGE + G::A_BYTES + 2 * G::BLK + kr * 64 + (((idx & 1) ^ ((kr >> 1) & 3)) << 4);
                asm volatile("st.shared.v4.u32 [%0], {%1,%2,%3,%4};" ::"r"(dst), "r"(v[i].x), "r"(v[i].y), "r"(v[i].z), "r"(v[i].w) : "memory");
            }
            fence_async_smem();
            if constexpr (SELF) named_bar(6, 384); else named_bar(6, 256);
        }
        RowStatRaw raw;
        float csv = 0.f;
        float2 cskv[2] = {make_float2(0.f, 0.f), make_float2(0.f, 0.f)};
        auto ln_inputs = [&]() {
            pdl_wait();
            if constexpr (EPI != EPI_RES) {
                raw = load_row_stats(prm.stats_in, row0, c);
                const float* cs = EPI == EPI_FFN1 ? g_cs_1 + n0 : g_cs_q + n0;
                if (tid < TN) csv = cs[tid];
                if constexpr (XKV) {
                    cskv[0] = *(const float2*)(g_cs_kv + tile_n * 16 + 2 * c);
                    cskv[1] = *(const float2*)(g_cs_kv + tile_n * 16 + 8 + 2 * c);
                }
            }
        };
        if (!SELF) ln_inputs();
        float acc[BN / 2];
        const uint64_t dA0 = mkdesc(sbase + wg * (G::A_BYTES / 2), 16, G::A_SBO, G::A_SWZ);
        const uint64_t dB0 = mkdesc(sbase + G::A_BYTES, G::B_LBO, G::B_SBO, G::B_SWZ);
        int s = 0, ph = 0;
#pragma unroll 1
        for (int kb = 0; kb < KB; kb++) {
            mbar_wait(bar_full + 8 * s, ph);
            const uint64_t dA = dA0 + (uint64_t)(s * (SM::STAGE >> 4)), dB = dB0 + (uint64_t)(s * (SM::STAGE >> 4));
            wg_fence();
#pragma unroll
            for (int k = 0; k < G::BK / 16; k++) wgmma_ss_tb<BN>(acc, dA + (uint64_t)(k * 2), dB + (uint64_t)(k * (G::B_KSTEP >> 4)), (kb | k) != 0);
            wg_commit();
            if (kb > 0) {
                wg_wait<1>();
                const int sp = s == 0 ? STAGES - 1 : s - 1;
                if ((warp & 3) == 0 && elect_one()) mbar_arrive(bar_empty + 8 * sp);
            }
            if (++s == STAGES) { s = 0; ph ^= 1; }
        }
        if constexpr (SELF) {
            named_bar(4, 640);
            const float2 r0 = *(const float2*)(s_row + 2 * rloc), r1 = *(const float2*)(s_row + 2 * rloc + 16);
            mean0 = r0.x; rstd0 = r0.y; mean1 = r1.x; rstd1 = r1.y;
        } else if constexpr (EPI != EPI_RES) {
            finish_row_stats(raw, mean0, rstd0, mean1, rstd1);
            if (tid < TN) s_cs[tid] = csv;
        }
        wg_wait<0>();
        fence_regs(acc);
        if constexpr (EPI != EPI_RES) named_bar(1, 256);

        if constexpr (EPI != EPI_FFN1) {
            const uint32_t stile = sbase + (EPI == EPI_RES ? s * SM::STAGE : 0);
            const int mrow = wg * 64 + (warp & 3) * 16 + (lane & 7) + ((lane >> 3) & 1) * 8;
            const uint32_t rbase = stile + mrow * 128;
            if constexpr (EPI == EPI_RES) {
                mbar_wait(bar_full + 8 * s, ph);
                float s0 = 0.f, s1 = 0.f;
#pragma unroll
                for (int jj = 0; jj < 4; jj++) {
                    uint32_t r0, r1, r2, r3;
                    const uint32_t addr = rbase + (((2 * jj + (lane >> 4)) ^ (mrow & 7)) << 4);
                    ldsm_x4(r0, r1, r2, r3, addr);
                    const uint32_t u0 = pack_bf16(acc[8 * jj] + bf_lo(r0), acc[8 * jj + 1] + bf_hi(r0));
                    const uint32_t u1 = pack_bf16(acc[8 * jj + 2] + bf_lo(r1), acc[8 * jj + 3] + bf_hi(r1));
                    const uint32_t u2 = pack_bf16(acc[8 * jj + 4] + bf_lo(r2), acc[8 * jj + 5] + bf_hi(r2));
                    const uint32_t u3 = pack_bf16(acc[8 * jj + 6] + bf_lo(r3), acc[8 * jj + 7] + bf_hi(r3));
                    stsm_x4(addr, u0, u1, u2, u3);
                    acc[8 * jj] = bf_lo(u0); acc[8 * jj + 1] = bf_hi(u0); acc[8 * jj + 4] = bf_lo(u2); acc[8 * jj + 5] = bf_hi(u2);
                    acc[8 * jj + 2] = bf_lo(u1); acc[8 * jj + 3] = bf_hi(u1); acc[8 * jj + 6] = bf_lo(u3); acc[8 * jj + 7] = bf_hi(u3);
                    s0 += (acc[8 * jj] + acc[8 * jj + 1]) + (acc[8 * jj + 4] + acc[8 * jj + 5]);
                    s1 += (acc[8 * jj + 2] + acc[8 * jj + 3]) + (acc[8 * jj + 6] + acc[8 * jj + 7]);
                }
                fence_async_smem();
                named_bar(2 + wg, 128);
                if ((warp & 3) == 0 && elect_one()) { tma2d_store(mapC, stile + wg * 8192, n0, m0 + wg * 64); bulk_commit(); }
                if (prm.stats_out) {
                    s0 += __shfl_xor_sync(0xffffffffu, s0, 1); s0 += __shfl_xor_sync(0xffffffffu, s0, 2);
                    s1 += __shfl_xor_sync(0xffffffffu, s1, 1); s1 += __shfl_xor_sync(0xffffffffu, s1, 2);
                    const float mu0 = s0 * (1.f / 64.f), mu1 = s1 * (1.f / 64.f);
                    float q0 = 0.f, q1 = 0.f;
#pragma unroll
                    for (int j = 0; j < 8; j++) {
                        float d;
                        d = acc[4 * j] - mu0; q0 += d * d; d = acc[4 * j + 1] - mu0; q0 += d * d;
                        d = acc[4 * j + 2] - mu1; q1 += d * d; d = acc[4 * j + 3] - mu1; q1 += d * d;
                    }
                    q0 += __shfl_xor_sync(0xffffffffu, q0, 1); q0 += __shfl_xor_sync(0xffffffffu, q0, 2);
                    q1 += __shfl_xor_sync(0xffffffffu, q1, 1); q1 += __shfl_xor_sync(0xffffffffu, q1, 2);
                    if (c == 0) {
                        prm.stats_out[tile_n * S_ + row0] = make_float2(mu0, q0);
                        prm.stats_out[tile_n * S_ + row0 + 8] = make_float2(mu1, q1);
                    }
                }
            } else {
                const float sc = 0.25f * 1.4426950408889634f;
                const float a0 = rstd0 * sc, a1 = rstd1 * sc, rm0 = a0 * mean0, rm1 = a1 * mean1;
#pragma unroll
                for (int jj = 0; jj < 4; jj++) {
                    const float2 ca = *(const float2*)(s_cs + 16 * jj + 2 * c), cb = *(const float2*)(s_cs + 16 * jj + 8 + 2 * c);
                    const uint32_t u0 = pack_bf16(acc[8 * jj] * a0 - rm0 * ca.x, acc[8 * jj + 1] * a0 - rm0 * ca.y);
                    const uint32_t u1 = pack_bf16(acc[8 * jj + 2] * a1 - rm1 * ca.x, acc[8 * jj + 3] * a1 - rm1 * ca.y);
                    const uint32_t u2 = pack_bf16(acc[8 * jj + 4] * a0 - rm0 * cb.x, acc[8 * jj + 5] * a0 - rm0 * cb.y);
                    const uint32_t u3 = pack_bf16(acc[8 * jj + 6] * a1 - rm1 * cb.x, acc[8 * jj + 7] * a1 - rm1 * cb.y);
                    stsm_x4(rbase + (((2 * jj + (lane >> 4)) ^ (mrow & 7)) << 4), u0, u1, u2, u3);
                }
                fence_async_smem();
                named_bar(2 + wg, 128);
                if ((warp & 3) == 0 && elect_one()) { tma2d_store(mapC, stile + wg * 8192, n0, m0 + wg * 64); bulk_commit(); }
            }
            if constexpr (XKV) {
                {
                    const float* acx = &acc[32];
                    const float rm0 = rstd0 * mean0, rm1 = rstd1 * mean1;
                    float n0s = 0.f, n1s = 0.f, vmax = 0.f;
#pragma unroll
                    for (int j = 0; j < 2; j++) {
                        const float2 cs2 = SELF ? *(const float2*)(s_cs + 64 + 8 * j + 2 * c) : cskv[j];
                        const uint32_t u0 = pack_bf16(acx[4 * j] * rstd0 - rm0 * cs2.x, acx[4 * j + 1] * rstd0 - rm0 * cs2.y);
                        const uint32_t u1 = pack_bf16(acx[4 * j + 2] * rstd1 - rm1 * cs2.x, acx[4 * j + 3] * rstd1 - rm1 * cs2.y);
                        n0s += bf_lo(u0) * bf_lo(u0) + bf_hi(u0) * bf_hi(u0);
                        n1s += bf_lo(u1) * bf_lo(u1) + bf_hi(u1) * bf_hi(u1);
                        vmax = fmaxf(vmax, fmaxf(fmaxf(fabsf(bf_lo(u0)), fabsf(bf_hi(u0))), fmaxf(fabsf(bf_lo(u1)), fabsf(bf_hi(u1)))));
                        if (tile_n == 0) {
                            *(uint32_t*)(g_kimg + (row0 >> 3) * 256 + j * 128 + g * 16 + c * 4) = u0;
                            *(uint32_t*)(g_kimg + ((row0 + 8) >> 3) * 256 + j * 128 + g * 16 + c * 4) = u1;
                        } else {
                            uint8_t* vb = g_vimg + (row0 >> 4) * 768 + j * 256 + g * 16 + c * 4;
                            *(uint32_t*)(vb) = u0;
                            *(uint32_t*)(vb + 128) = u1;
                        }
                    }
                    if (tile_n == 1) {
                        uint8_t* vb = g_vimg + (row0 >> 4) * 768 + 512 + g * 16 + c * 4;
                        const uint32_t one = c == 0 ? 0x00003F80u : 0u;
                        *(uint32_t*)(vb) = one;
                        *(uint32_t*)(vb + 128) = one;
                    }
                    n0s += __shfl_xor_sync(0xffffffffu, n0s, 1); n0s += __shfl_xor_sync(0xffffffffu, n0s, 2);
                    n1s += __shfl_xor_sync(0xffffffffu, n1s, 1); n1s += __shfl_xor_sync(0xffffffffu, n1s, 2);
                    float km = tile_n == 0 ? fmaxf(n0s, n1s) : vmax;
                    if (!(n0s + n1s < INFINITY)) km = INFINITY;
#pragma unroll
                    for (int o = 1; o < 32; o <<= 1) km = fmaxf(km, __shfl_xor_sync(0xffffffffu, km, o));
                    if (lane == 0) s_red[warp] = km;
                    named_bar(1, 256);
                    if (tid == 0) {
                        float a = 0.f;
                        for (int i = 0; i < 8; i++) a = fmaxf(a, s_red[i]);
                        g_kvmax[tile_n * 16 + tile_m] = a;
                    }
                }
            }
            if ((warp & 3) == 0) bulk_wait_read();
        } else {
            const uint32_t stile = sbase + wg * (7 * 4096);
            const int mrow = (warp & 3) * 16 + (lane & 7) + ((lane >> 3) & 1) * 8;
            const float a0 = 0.5f * rstd0, a1 = 0.5f * rstd1, rm0 = a0 * mean0, rm1 = a1 * mean1;
#pragma unroll
            for (int jj = 0; jj < 14; jj++) {
                const float2 ca = *(const float2*)(s_cs + 16 * jj + 2 * c), cb = *(const float2*)(s_cs + 16 * jj + 8 + 2 * c);
                float y[8] = {acc[8 * jj] * a0 - rm0 * ca.x,     acc[8 * jj + 1] * a0 - rm0 * ca.y,
                              acc[8 * jj + 2] * a1 - rm1 * ca.x, acc[8 * jj + 3] * a1 - rm1 * ca.y,
                              acc[8 * jj + 4] * a0 - rm0 * cb.x, acc[8 * jj + 5] * a0 - rm0 * cb.y,
                              acc[8 * jj + 6] * a1 - rm1 * cb.x, acc[8 * jj + 7] * a1 - rm1 * cb.y};
#pragma unroll
                for (int i = 0; i < 8; i++) {
                    float t;
                    asm("tanh.approx.f32 %0, %1;" : "=f"(t) : "f"(y[i]));
                    y[i] = fmaf(y[i], t, y[i]);
                }
                const int chunk = (2 * jj + (lane >> 4)) & 3, blk = jj >> 1;
                stsm_x4(stile + blk * 4096 + mrow * 64 + ((chunk ^ ((mrow >> 1) & 3)) << 4),
                        pack_bf16(y[0], y[1]), pack_bf16(y[2], y[3]), pack_bf16(y[4], y[5]), pack_bf16(y[6], y[7]));
                if (jj & 1) {
                    fence_async_smem();
                    __syncwarp();
                    if (elect_one()) {
                        tma2d_store(mapC, stile + blk * 4096 + (warp & 3) * 1024, n0 + blk * 32, m0 + wg * 64 + (warp & 3) * 16);
                        bulk_commit();
                    }
                }
            }
            bulk_wait_read();
        }
    }
}

#define WO_ST 9
#define F2_ST 7
#define F1_ST 4
#define QKV_ST 8
constexpr int QKV_STAGES = QKV_ST, WO_STAGES = WO_ST, FFN2_STAGES = F2_ST, FFN1_STAGES = F1_ST;
template <bool SELF>
__global__ void __launch_bounds__(SELF ? 640 : 288) qkv_kernel(const __grid_constant__ CUtensorMap mapA, const __grid_constant__ CUtensorMap mapWq,
                                                  const __grid_constant__ CUtensorMap mapQ, const GemmParams prm) {
    extern __shared__ __align__(1024) uint8_t smem_raw[];
    const int tn = blockIdx.x & 7;
    if (tn < 2) gemm_body<80, 8, QKV_STAGES, EPI_QKV, SELF>(&mapA, &mapWq, &mapA, &mapQ, prm, blockIdx.x >> 3, tn, smem_raw);
    else gemm_body<64, 8, QKV_STAGES, EPI_QKV, SELF>(&mapA, &mapWq, &mapA, &mapQ, prm, blockIdx.x >> 3, tn, smem_raw);
}
template <int KB, int STAGES>
__global__ void __launch_bounds__(288) res_gemm_kernel(const __grid_constant__ CUtensorMap mapA, const __grid_constant__ CUtensorMap mapW,
                                                       const __grid_constant__ CUtensorMap mapR, const __grid_constant__ CUtensorMap mapC, const GemmParams prm) {
    extern __shared__ __align__(1024) uint8_t smem_raw[];
    gemm_body<64, KB, STAGES, EPI_RES>(&mapA, &mapW, &mapR, &mapC, prm, blockIdx.x >> 3, blockIdx.x & 7, smem_raw);
}
__global__ void __launch_bounds__(288) ffn1_kernel(const __grid_constant__ CUtensorMap mapA, const __grid_constant__ CUtensorMap mapW,
                                                   const __grid_constant__ CUtensorMap mapH, const GemmParams prm) {
    extern __shared__ __align__(1024) uint8_t smem_raw[];
    gemm_body<224, 8, FFN1_STAGES, EPI_FFN1>(&mapA, &mapW, &mapA, &mapH, prm, blockIdx.x >> 3, blockIdx.x & 7, smem_raw);
}

#define ATT_NPOLY 11
constexpr int NPOLY = ATT_NPOLY;
__host__ __device__ constexpr bool is_mufu(int i) { return (i * (16 - NPOLY)) % 16 < 16 - NPOLY; }

__device__ __forceinline__ float ex2(float x) { float r; asm("ex2.approx.ftz.f32 %0, %1;" : "=f"(r) : "f"(x)); return r; }
__device__ __forceinline__ uint32_t exp_pair_mufu(float a, float b) { return pack_bf16(ex2(a), ex2(b)); }
__device__ __forceinline__ uint32_t exp_pair_fma(float a, float b, uint32_t c3f) {
    constexpr float MAGIC = 98430.4140625f;
    const float ta = a + MAGIC, tb = b + (MAGIC - 143.5f);
    uint32_t y, m, r;
    asm("mad.lo.u32 %0, %1, 65536, %2;" : "=r"(y) : "r"(__float_as_uint(tb)), "r"(__float_as_uint(ta)));
    asm("lop3.b32 %0, %1, 0x007F007F, %2, 0xEA;" : "=r"(m) : "r"(y), "r"(c3f));
    const uint32_t e = y & 0xFF80FF80u;
    asm("fma.rn.bf16x2 %0, %1, %2, %3;" : "=r"(r) : "r"(y), "r"(m), "r"(e));
    return r;
}

constexpr int KCH = 256, NCH = S_ / KCH;
constexpr int K_BYTES = S_ * 32, V_BYTES = (S_ / 16) * 768;
constexpr int QO_BYTES = 128 * 128;
constexpr int ATT_SMEM = K_BYTES + V_BYTES + QO_BYTES;

__global__ void __launch_bounds__(512, 1) attn_kernel(const __grid_constant__ CUtensorMap mapQ, const __grid_constant__ CUtensorMap mapO,
                                                       const __nv_bfloat16* __restrict__ wo, const __nv_bfloat16* __restrict__ w1,
                                                       const __nv_bfloat16* __restrict__ w2) {
    extern __shared__ __align__(1024) uint8_t smem[];
    __shared__ uint64_t bars[NCH + 1];
    const int tid = threadIdx.x, wg = tid >> 7, warp = (tid >> 5) & 3, lane = tid & 31;
    const uint32_t sK = smem_u32(smem), sV = sK + K_BYTES, sQ = sV + V_BYTES;
    if (blockIdx.x >= 128) {
        pdl_launch();
        pdl_wait();
        side_job(blockIdx.x - 128, (float*)smem, wo, w1, w2);
        return;
    }
    if (tid == 0) {
#pragma unroll
        for (int i = 0; i <= NCH; i++) mbar_init(smem_u32(&bars[i]), 1);
        fence_mbar_init();
    }
    if (tid == 32) { prefetch_tmap(&mapQ); prefetch_tmap(&mapO); }
    __syncthreads();
    pdl_launch();
    pdl_wait();
    const int wu = __shfl_sync(0xffffffffu, tid >> 5, 0);
    auto fetch_chunk = [&](int w) {
        if (elect_one()) {
            const uint32_t bar = smem_u32(&bars[w]);
            mbar_expect_tx(bar, KCH * 32 + (KCH / 16) * 768);
            bulk_load(sK + w * KCH * 32, g_kimg + w * KCH * 32, KCH * 32, bar);
            bulk_load(sV + w * (KCH / 16) * 768, g_vimg + w * (KCH / 16) * 768, (KCH / 16) * 768, bar);
        }
    };
    const int tb = blockIdx.x >> 3, hg = blockIdx.x & 7;
    if (wu == 1 && elect_one()) {
        mbar_expect_tx(smem_u32(&bars[NCH]), QO_BYTES);
        tma2d(sQ, &mapQ, hg * 64, tb * 128, smem_u32(&bars[NCH]));
    }
    if (wu == 0) fetch_chunk(0);
    float kvm = g_kvmax[lane];
    const int lrow = warp * 16 + (lane & 7) + ((lane >> 3) & 1) * 8;
    const uint32_t qoff = lrow * 128 + (((2 * wg + (lane >> 4)) ^ (lrow & 7)) << 4);
    uint32_t qa[2][4];
    mbar_wait(smem_u32(&bars[NCH]), 0);
    ldsm_x4(qa[0][0], qa[0][1], qa[0][2], qa[0][3], sQ + qoff);
    ldsm_x4(qa[1][0], qa[1][1], qa[1][2], qa[1][3], sQ + 8192 + qoff);
    if (wu >= 1 && wu < NCH) fetch_chunk(wu);
    float qn = 0.f;
#pragma unroll
    for (int m = 0; m < 2; m++) {
        float n0 = bf_lo(qa[m][0]) * bf_lo(qa[m][0]) + bf_hi(qa[m][0]) * bf_hi(qa[m][0]) + bf_lo(qa[m][2]) * bf_lo(qa[m][2]) + bf_hi(qa[m][2]) * bf_hi(qa[m][2]);
        float n1 = bf_lo(qa[m][1]) * bf_lo(qa[m][1]) + bf_hi(qa[m][1]) * bf_hi(qa[m][1]) + bf_lo(qa[m][3]) * bf_lo(qa[m][3]) + bf_hi(qa[m][3]) * bf_hi(qa[m][3]);
        n0 += __shfl_xor_sync(0xffffffffu, n0, 1); n0 += __shfl_xor_sync(0xffffffffu, n0, 2);
        n1 += __shfl_xor_sync(0xffffffffu, n1, 1); n1 += __shfl_xor_sync(0xffffffffu, n1, 2);
        if (!(n0 == n0) || !(n1 == n1)) n0 = INFINITY;
        qn = fmaxf(qn, fmaxf(n0, n1));
    }
    float oacc[2][12];
#pragma unroll
    for (int m = 0; m < 2; m++)
#pragma unroll
        for (int i = 0; i < 12; i++) oacc[m][i] = 0.f;

    const uint64_t dK0 = mkdesc(sK, 128, 256, 0);
    const uint64_t dV0 = mkdesc(sV, 128, 256, 0);
    uint32_t c3f;
    asm volatile("mov.b32 %0, 0x3F003F00;" : "=r"(c3f));
    {
        uint64_t dK = dK0, dV = dV0;
        float s[32];
        fence_regs(oacc[0]); fence_regs(oacc[1]);
        mbar_wait(smem_u32(&bars[0]), 0);
        wg_fence();
        wgmma_rs_n64_z(s, qa[0][0], qa[0][1], qa[0][2], qa[0][3], dK);
        wg_commit();
#pragma unroll 1
        for (int ch = 0; ch < NCH; ch++) {
#pragma unroll
            for (int tt = 0; tt < KCH / 64; tt++) {
#pragma unroll
                for (int m = 0; m < 2; m++) {
                    wg_wait<0>();
                    fence_regs(s);
                    uint32_t p[16];
#pragma unroll
                    for (int i = 0; i < 16; i++) p[i] = is_mufu(i) ? exp_pair_mufu(s[2 * i], s[2 * i + 1]) : exp_pair_fma(s[2 * i], s[2 * i + 1], c3f);
                    if (m == 1 && tt == KCH / 64 - 1) mbar_wait(smem_u32(&bars[ch + 1 < NCH ? ch + 1 : ch]), 0);
                    wg_fence();
#pragma unroll
                    for (int kk = 0; kk < 4; kk++)
                        wgmma_rs_n24_tb(oacc[m], p[4 * kk], p[4 * kk + 1], p[4 * kk + 2], p[4 * kk + 3], dV + (uint64_t)((tt * 4 + kk) * (768 / 16)));
                    wgmma_rs_n64_z(s, qa[1 - m][0], qa[1 - m][1], qa[1 - m][2], qa[1 - m][3], dK + (uint64_t)((tt + m) * (64 * 32 / 16)));
                    wg_commit();
                }
            }
            dK += KCH * 32 / 16;
            dV += (KCH / 16) * (768 / 16);
        }
        wg_wait<0>();
        fence_regs(s);
    }
#pragma unroll
    for (int o = 1; o < 16; o <<= 1) kvm = fmaxf(kvm, __shfl_xor_sync(0xffffffffu, kvm, o));
    const float km = __shfl_sync(0xffffffffu, kvm, 0), vm = __shfl_sync(0xffffffffu, kvm, 16);
    if (__syncthreads_or(!((qn * km <= 10000.f) && (vm <= 16384.f)))) {
        fence_regs(oacc[0]); fence_regs(oacc[1]);
#pragma unroll
        for (int m = 0; m < 2; m++)
#pragma unroll
            for (int i = 0; i < 12; i++) oacc[m][i] = 0.f;
        fence_regs(oacc[0]); fence_regs(oacc[1]);
        float mx[2][2] = {{-INFINITY, -INFINITY}, {-INFINITY, -INFINITY}};
#pragma unroll 1
        for (int t = 0; t < S_ / 64; t++) {
            const uint64_t dK = dK0 + (uint64_t)(t * 64 * 32 / 16);
            const uint64_t dV = dV0 + (uint64_t)(t * 4 * 768 / 16);
#pragma unroll
            for (int m = 0; m < 2; m++) {
                float s[32];
                wg_fence();
                wgmma_rs_n64_z(s, qa[m][0], qa[m][1], qa[m][2], qa[m][3], dK);
                wg_commit();
                wg_wait<0>();
                fence_regs(s);
                fence_regs(oacc[m]);
                float r0 = mx[m][0], r1 = mx[m][1];
#pragma unroll
                for (int j = 0; j < 8; j++) {
                    r0 = fmaxf(r0, fmaxf(s[4 * j], s[4 * j + 1]));
                    r1 = fmaxf(r1, fmaxf(s[4 * j + 2], s[4 * j + 3]));
                }
                r0 = fmaxf(r0, __shfl_xor_sync(0xffffffffu, r0, 1)); r0 = fmaxf(r0, __shfl_xor_sync(0xffffffffu, r0, 2));
                r1 = fmaxf(r1, __shfl_xor_sync(0xffffffffu, r1, 1)); r1 = fmaxf(r1, __shfl_xor_sync(0xffffffffu, r1, 2));
                const float al0 = ex2(mx[m][0] - r0), al1 = ex2(mx[m][1] - r1);
                mx[m][0] = r0; mx[m][1] = r1;
#pragma unroll
                for (int j = 0; j < 3; j++) {
                    oacc[m][4 * j] *= al0; oacc[m][4 * j + 1] *= al0;
                    oacc[m][4 * j + 2] *= al1; oacc[m][4 * j + 3] *= al1;
                }
                uint32_t p[16];
#pragma unroll
                for (int j = 0; j < 8; j++) {
                    p[2 * j] = pack_bf16(ex2(s[4 * j] - r0), ex2(s[4 * j + 1] - r0));
                    p[2 * j + 1] = pack_bf16(ex2(s[4 * j + 2] - r1), ex2(s[4 * j + 3] - r1));
                }
                fence_regs(oacc[m]);
                wg_fence();
#pragma unroll
                for (int kk = 0; kk < 4; kk++)
                    wgmma_rs_n24_tb(oacc[m], p[4 * kk], p[4 * kk + 1], p[4 * kk + 2], p[4 * kk + 3], dV + (uint64_t)(kk * 768 / 16));
                wg_commit();
                wg_wait<0>();
            }
        }
    }
    fence_regs(oacc[0]); fence_regs(oacc[1]);
#pragma unroll
    for (int m = 0; m < 2; m++) {
        const float l0 = __shfl_sync(0xffffffffu, oacc[m][8], lane & ~3);
        const float l1 = __shfl_sync(0xffffffffu, oacc[m][10], lane & ~3);
        const float r0 = __fdividef(1.0f, l0), r1 = __fdividef(1.0f, l1);
        stsm_x4(sQ + m * 8192 + qoff, pack_bf16(oacc[m][0] * r0, oacc[m][1] * r0), pack_bf16(oacc[m][2] * r1, oacc[m][3] * r1),
                pack_bf16(oacc[m][4] * r0, oacc[m][5] * r0), pack_bf16(oacc[m][6] * r1, oacc[m][7] * r1));
    }
    fence_async_smem();
    __syncthreads();
    if (wu == 0 && elect_one()) {
        tma2d_store(&mapO, sQ, hg * 64, tb * 128);
        bulk_commit();
        bulk_wait_read();
    }
}

typedef CUresult (*EncodeFn)(CUtensorMap*, CUtensorMapDataType, cuuint32_t, void*, const cuuint64_t*, const cuuint64_t*, const cuuint32_t*,
                             const cuuint32_t*, CUtensorMapInterleave, CUtensorMapSwizzle, CUtensorMapL2promotion, CUtensorMapFloatOOBfill);

EncodeFn get_encode() {
    static EncodeFn fn = nullptr;
    if (!fn) {
        void* p = nullptr;
        cudaDriverEntryPointQueryResult qr;
        cudaGetDriverEntryPoint("cuTensorMapEncodeTiled", &p, cudaEnableDefault, &qr);
        fn = (EncodeFn)p;
    }
    return fn;
}
CUtensorMap map2d(const void* ptr, uint64_t cols, uint64_t rows, uint32_t bc, uint32_t br, CUtensorMapSwizzle sw) {
    CUtensorMap m;
    cuuint64_t gd[2] = {cols, rows}, gs[1] = {cols * 2};
    cuuint32_t bx[2] = {bc, br}, es[2] = {1, 1};
    get_encode()(&m, CU_TENSOR_MAP_DATA_TYPE_BFLOAT16, 2, (void*)ptr, gd, gs, bx, es, CU_TENSOR_MAP_INTERLEAVE_NONE, sw,
                 CU_TENSOR_MAP_L2_PROMOTION_L2_128B, CU_TENSOR_MAP_FLOAT_OOB_FILL_NONE);
    return m;
}
CUtensorMap map3d32(const void* ptr, uint64_t cols, uint64_t rows, uint32_t br, uint32_t nb) {
    CUtensorMap m;
    cuuint64_t gd[3] = {32, rows, cols / 32}, gs[2] = {cols * 2, 64};
    cuuint32_t bx[3] = {32, br, nb}, es[3] = {1, 1, 1};
    get_encode()(&m, CU_TENSOR_MAP_DATA_TYPE_BFLOAT16, 3, (void*)ptr, gd, gs, bx, es, CU_TENSOR_MAP_INTERLEAVE_NONE, CU_TENSOR_MAP_SWIZZLE_64B,
                 CU_TENSOR_MAP_L2_PROMOTION_L2_128B, CU_TENSOR_MAP_FLOAT_OOB_FILL_NONE);
    return m;
}

template <typename... KArgs, typename... Args>
void launch(void (*kern)(KArgs...), int grid, int block, int smem, int cluster, bool pdl, Args... args) {
    cudaLaunchConfig_t cfg = {};
    cfg.gridDim = dim3(grid);
    cfg.blockDim = dim3(block);
    cfg.dynamicSmemBytes = smem;
    cfg.stream = cudaStreamPerThread;
    cudaLaunchAttribute at[2];
    int n = 0;
    if (cluster > 1) { at[n].id = cudaLaunchAttributeClusterDimension; at[n].val.clusterDim.x = cluster; at[n].val.clusterDim.y = 1; at[n].val.clusterDim.z = 1; n++; }
    if (pdl) { at[n].id = cudaLaunchAttributeProgrammaticStreamSerialization; at[n].val.programmaticStreamSerializationAllowed = 1; n++; }
    cfg.attrs = at;
    cfg.numAttrs = n;
    cudaLaunchKernelEx(&cfg, kern, KArgs(args)...);
}

template <typename T> void* sym(const T& s) { void* p = nullptr; cudaGetSymbolAddress(&p, s); return p; }

}

extern "C" void kernel_launch(void* const* d_in, const int* in_sizes, int n_in, void* d_out, int out_size) {
    const __nv_bfloat16* x = (const __nv_bfloat16*)d_in[0];
    const __nv_bfloat16* wq = (const __nv_bfloat16*)d_in[1];
    const __nv_bfloat16* wk = (const __nv_bfloat16*)d_in[2];
    const __nv_bfloat16* wv = (const __nv_bfloat16*)d_in[3];
    const __nv_bfloat16* wo = (const __nv_bfloat16*)d_in[4];
    const __nv_bfloat16* w1 = (const __nv_bfloat16*)d_in[6];
    const __nv_bfloat16* w2 = (const __nv_bfloat16*)d_in[7];

    constexpr int SM_QKV = GemmSmem<QKV_STAGES, EPI_QKV>::TOTAL, SM_QKV0 = GemmSmem<QKV_STAGES, EPI_QKV>::TOTAL_SELF;
    static_assert(SM_QKV0 <= 232448, "shared memory");
    constexpr int SM_WO = GemmSmem<WO_STAGES, EPI_RES>::TOTAL, SM_FFN2 = GemmSmem<FFN2_STAGES, EPI_RES>::TOTAL;
    static_assert(SM_WO > 116736 && SM_FFN2 > 116736, "one CTA per SM");
    constexpr int SM_FFN1 = GemmSmem<FFN1_STAGES, EPI_FFN1>::TOTAL;
    cudaFuncSetAttribute(qkv_kernel<false>, cudaFuncAttributeMaxDynamicSharedMemorySize, SM_QKV);
    cudaFuncSetAttribute(qkv_kernel<true>, cudaFuncAttributeMaxDynamicSharedMemorySize, SM_QKV0);
    cudaFuncSetAttribute(res_gemm_kernel<8, WO_STAGES>, cudaFuncAttributeMaxDynamicSharedMemorySize, SM_WO);
    cudaFuncSetAttribute(ffn1_kernel, cudaFuncAttributeMaxDynamicSharedMemorySize, SM_FFN1);
    cudaFuncSetAttribute(res_gemm_kernel<28, FFN2_STAGES>, cudaFuncAttributeMaxDynamicSharedMemorySize, SM_FFN2);
    cudaFuncSetAttribute(attn_kernel, cudaFuncAttributeMaxDynamicSharedMemorySize, ATT_SMEM);
    cudaFuncSetAttribute(qkv_kernel<false>, cudaFuncAttributePreferredSharedMemoryCarveout, 100);
    cudaFuncSetAttribute(qkv_kernel<true>, cudaFuncAttributePreferredSharedMemoryCarveout, 100);
    cudaFuncSetAttribute(res_gemm_kernel<8, WO_STAGES>, cudaFuncAttributePreferredSharedMemoryCarveout, 100);
    cudaFuncSetAttribute(ffn1_kernel, cudaFuncAttributePreferredSharedMemoryCarveout, 100);
    cudaFuncSetAttribute(res_gemm_kernel<28, FFN2_STAGES>, cudaFuncAttributePreferredSharedMemoryCarveout, 100);
    cudaFuncSetAttribute(attn_kernel, cudaFuncAttributePreferredSharedMemoryCarveout, 100);

    void *q = sym(g_q), *o = sym(g_o), *x1 = sym(g_x1), *x2 = sym(g_x2), *x3 = sym(g_x3), *h = sym(g_h);
    float2* stats = (float2*)sym(g_stats);
    const void* xs[5] = {x, x1, x2, x3, d_out};

    const CUtensorMapSwizzle SW128 = CU_TENSOR_MAP_SWIZZLE_128B, SW64 = CU_TENSOR_MAP_SWIZZLE_64B;
    const CUtensorMap mWq = map3d32(wq, D_, D_, 64, 2);
    const CUtensorMap mWo = map2d(wo, D_, D_, 64, 64, SW128);
    const CUtensorMap mW1 = map3d32(w1, F_, D_, 64, 7);
    const CUtensorMap mW2 = map2d(w2, D_, F_, 64, 64, SW128);
    const CUtensorMap mQ = map2d(q, D_, S_, 64, 64, SW128);
    const CUtensorMap mQa = map2d(q, D_, S_, 64, 128, SW128), mOs = map2d(o, D_, S_, 64, 128, SW128);
    const CUtensorMap mHst = map2d(h, F_, S_, 32, 16, SW64);
    CUtensorMap mXa[4], mXs[5];
    for (int i = 0; i < 4; i++) {
        mXa[i] = map2d(xs[i], D_, S_, 64, 128, SW128);
    }
    for (int i = 0; i < 5; i++) mXs[i] = map2d(xs[i], D_, S_, 64, 64, SW128);
    const CUtensorMap mOa = map2d(o, D_, S_, 64, 128, SW128);
    const CUtensorMap mHa = map2d(h, F_, S_, 64, 128, SW128);

    for (int layer = 0; layer < 2; layer++) {
        const int xi = layer * 2;
        GemmParams p;
        p.wkv = wk; p.wv = wv;
        p.stats_in = stats + (size_t)xi * 8 * S_; p.stats_out = nullptr;
        if (layer == 0) launch(qkv_kernel<true>, 128, 640, SM_QKV0, 1, false, mXa[xi], mWq, mQ, p);
        else launch(qkv_kernel<false>, 128, 288, SM_QKV, 2, true, mXa[xi], mWq, mQ, p);
        launch(attn_kernel, layer == 0 ? 128 + SIDE_CTAS : 128, 512, ATT_SMEM, 1, true, mQa, mOs, wo, w1, w2);
        p.stats_in = nullptr; p.stats_out = stats + (size_t)(xi + 1) * 8 * S_;
        launch(res_gemm_kernel<8, WO_STAGES>, 128, 288, SM_WO, 2, true, mOa, mWo, mXa[xi], mXs[xi + 1], p);
        p.stats_in = stats + (size_t)(xi + 1) * 8 * S_; p.stats_out = nullptr;
        launch(ffn1_kernel, 128, 288, SM_FFN1, 1, true, mXa[xi + 1], mW1, mHst, p);
        p.stats_in = nullptr; p.stats_out = layer == 0 ? stats + (size_t)2 * 8 * S_ : nullptr;
        launch(res_gemm_kernel<28, FFN2_STAGES>, 128, 288, SM_FFN2, 2, true, mHa, mW2, mXa[xi + 1], mXs[xi + 2], p);
    }
}
```
